```python
import torch

def _softmax(x, axis=-1):
    return torch.softmax(x, dim=axis)
def _gelu(x):
    return torch.nn.functional.gelu(x, approximate="tanh")
def _silu(x):
    return torch.nn.functional.silu(x)
def _sigmoid(x):
    return torch.sigmoid(x)
def _layernorm(x, axis=-1, eps=1e-5):
    m = x.mean(dim=axis, keepdim=True)
    v = x.var(dim=axis, keepdim=True, unbiased=False)
    return (x - m) / torch.sqrt(v + eps)
def _scatter_add(tgt, idx, src, axis=0):
    return tgt.clone().index_add_(axis, idx, src)
def _segment_sum(src, seg, n):
    out = torch.zeros((n,) + src.shape[1:], dtype=src.dtype)
    return out.index_add_(0, seg, src)
def _pad(x, pw):
    flat = tuple(v for pair in reversed(pw) for v in pair)
    return torch.nn.functional.pad(x, flat)

kernel_name = 'parallel_sum__softmax_full_mha__dense_activation_gelu__prompt'

def setup_inputs():

    _w = (lambda a: (lambda t: t.to(torch.bfloat16) if t.is_floating_point() else t)(torch.as_tensor(a)))
    def _A_setup():
        B, S, D = 1, 2048, 576
        return {
            "x": _w((lambda *s: torch.randn(*s, dtype=torch.bfloat16) * 0.05)(B, S, D)),
            "wqkv": _w((lambda *s: torch.randn(*s, dtype=torch.bfloat16) * 0.05)(D, 3 * D)),
            "wo": _w((lambda *s: torch.randn(*s, dtype=torch.bfloat16) * 0.05)(D, D)),
        }
    _A_in = _A_setup()

    def _B_setup():
        B, S, D, F = 1, 2048, 576, 4608
        return {
            "x": _w((lambda *s: torch.randn(*s, dtype=torch.bfloat16) * 0.05)(B, S, D)),
            "w1": _w((lambda *s: torch.randn(*s, dtype=torch.bfloat16) * 0.8)(D, F) * (D ** -0.5)),
            "b1": _w((lambda *s: torch.randn(*s, dtype=torch.bfloat16) * 12.8)(F) * 0.01),
            "w2": _w((lambda *s: torch.randn(*s, dtype=torch.bfloat16) * 0.8)(F, D) * (F ** -0.5)),
            "b2": _w((lambda *s: torch.randn(*s, dtype=torch.bfloat16) * 12.8)(D) * 0.01),
        }
    _B_in = _B_setup()

    return {
        "A_x": _A_in["x"],
        "A_wqkv": _A_in["wqkv"],
        "A_wo": _A_in["wo"],
        "B_x": _B_in["x"],
        "B_w1": _B_in["w1"],
        "B_b1": _B_in["b1"],
        "B_w2": _B_in["w2"],
        "B_b2": _B_in["b2"],
    }

def reference(A_x, A_wqkv, A_wo, B_x, B_w1, B_b1, B_w2, B_b2):
    def _A_ref(x, wqkv, wo):
        B, S, D = x.shape
        H = 32; Dh = D // H
        qkv = (lambda x, *d: x.permute(*d))((x @ wqkv).reshape(B, S, 3, H, Dh), 2, 0, 3, 1, 4)
        q, k, v = qkv[0], qkv[1], qkv[2]
        scale = Dh ** -0.5
        scores = torch.einsum("bhqd,bhkd->bhqk", q, k) * scale
        p = _softmax(scores, axis=-1)
        o = torch.einsum("bhqk,bhkd->bhqd", p, v)
        return (lambda x, *d: x.permute(*d))(o, 0, 2, 1, 3).reshape(B, S, D) @ wo

    def _B_ref(x, w1, b1, w2, b2):
        h = torch.einsum("bsd,df->bsf", x, w1) + b1
        h = _gelu(h)
        return torch.einsum("bsf,fd->bsd", h, w2) + b2

    x = A_x
    xn = _layernorm(x, axis=-1)
    return x + _A_ref(xn, A_wqkv, A_wo) + _B_ref(xn, B_w1, B_b1, B_w2, B_b2)
```

```cpp
#include <cuda_runtime.h>
#include <cuda_bf16.h>
#include <cuda.h>
#include <stdint.h>

namespace {

constexpr int SEQ = 2048, DM = 576, FF = 4608, NH = 32, DH = 18;

constexpr int Q_GROUP_BYTES = 3 * 128, KV_GROUP_BYTES = 5 * 128;
constexpr int Q_HEAD_BYTES = (SEQ / 8) * Q_GROUP_BYTES, KV_HEAD_BYTES = (SEQ / 8) * KV_GROUP_BYTES;
__device__ __align__(1024) uint8_t g_Q[NH * Q_HEAD_BYTES];
__device__ __align__(1024) uint8_t g_KV[NH * KV_HEAD_BYTES];
__device__ __align__(1024) float g_kmax[NH * 128];
__device__ __align__(1024) uint4 g_part[8 * 16 * 36 * 256];
__device__ __align__(1024) __nv_bfloat16 g_O[SEQ * DM];

__device__ __forceinline__ uint32_t s2u(const void* p) { return (uint32_t)__cvta_generic_to_shared(p); }
__device__ __forceinline__ void mbar_init(uint32_t b, int c) { asm volatile("mbarrier.init.shared::cta.b64 [%0], %1;" ::"r"(b), "r"(c) : "memory"); }
__device__ __forceinline__ void mbar_expect(uint32_t b, uint32_t bytes) {
    asm volatile("mbarrier.arrive.expect_tx.shared::cta.b64 _, [%0], %1;" ::"r"(b), "r"(bytes) : "memory");
}
__device__ __forceinline__ void mbar_arrive_cluster(uint32_t local_bar, uint32_t cta) {
    asm volatile("{\n.reg .b32 ra;\nmapa.shared::cluster.u32 ra, %0, %1;\nmbarrier.arrive.release.cluster.shared::cluster.b64 _, [ra];\n}\n" ::"r"(local_bar), "r"(cta) : "memory");
}
__device__ __forceinline__ void mbar_wait(uint32_t b, uint32_t parity) {
    uint32_t ok;
    uint32_t spins = 0;
    do {
        asm volatile("{\n.reg .pred p;\nmbarrier.try_wait.parity.shared::cta.b64 p, [%1], %2;\nselp.u32 %0, 1, 0, p;\n}\n" : "=r"(ok) : "r"(b), "r"(parity) : "memory");
        if (!ok && ++spins > (1u << 22)) __trap();
    } while (!ok);
}
__device__ __forceinline__ void mbar_wait_cluster(uint32_t b, uint32_t parity) {
    uint32_t ok;
    uint32_t spins = 0;
    do {
        asm volatile("{\n.reg .pred p;\nmbarrier.try_wait.parity.acquire.cluster.shared::cta.b64 p, [%1], %2;\nselp.u32 %0, 1, 0, p;\n}\n" : "=r"(ok) : "r"(b), "r"(parity) : "memory");
        if (!ok && ++spins > (1u << 22)) __trap();
    } while (!ok);
}
__device__ __forceinline__ void fence_barrier_init() { asm volatile("fence.mbarrier_init.release.cluster;" ::: "memory"); }
__device__ __forceinline__ void fence_proxy_async() { asm volatile("fence.proxy.async.shared::cta;" ::: "memory"); }
__device__ __forceinline__ void cluster_arrive() { asm volatile("barrier.cluster.arrive.release.aligned;" ::: "memory"); }
__device__ __forceinline__ void cluster_wait() { asm volatile("barrier.cluster.wait.acquire.aligned;" ::: "memory"); }
__device__ __forceinline__ void named_bar_sync(int id, int n) { asm volatile("bar.sync %0, %1;" ::"r"(id), "r"(n) : "memory"); }
__device__ __forceinline__ void griddep_wait() { asm volatile("griddepcontrol.wait;" ::: "memory"); }
__device__ __forceinline__ void griddep_launch() { asm volatile("griddepcontrol.launch_dependents;" ::: "memory"); }

__device__ __forceinline__ void tma3d_mc(uint32_t dst, const CUtensorMap* tm, int c0, int c1, int c2, uint32_t bar, uint16_t mask) {
    asm volatile("cp.async.bulk.tensor.3d.shared::cluster.global.mbarrier::complete_tx::bytes.multicast::cluster [%0], [%1, {%3, %4, %5}], [%2], %6;"
                 ::"r"(dst), "l"(tm), "r"(bar), "r"(c0), "r"(c1), "r"(c2), "h"(mask) : "memory");
}
__device__ __forceinline__ void tma2d_mc(uint32_t dst, const CUtensorMap* tm, int c0, int c1, uint32_t bar, uint16_t mask) {
    asm volatile("cp.async.bulk.tensor.2d.shared::cluster.global.mbarrier::complete_tx::bytes.multicast::cluster [%0], [%1, {%3, %4}], [%2], %5;"
                 ::"r"(dst), "l"(tm), "r"(bar), "r"(c0), "r"(c1), "h"(mask) : "memory");
}
__device__ __forceinline__ void tma2d(uint32_t dst, const CUtensorMap* tm, int c0, int c1, uint32_t bar) {
    asm volatile("cp.async.bulk.tensor.2d.shared::cluster.global.mbarrier::complete_tx::bytes [%0], [%1, {%3, %4}], [%2];"
                 ::"r"(dst), "l"(tm), "r"(bar), "r"(c0), "r"(c1) : "memory");
}
__device__ __forceinline__ void bulk_load(uint32_t dst, const void* src, uint32_t bytes, uint32_t bar) {
    asm volatile("cp.async.bulk.shared::cluster.global.mbarrier::complete_tx::bytes [%0], [%1], %2, [%3];"
                 ::"r"(dst), "l"(src), "r"(bytes), "r"(bar) : "memory");
}
__device__ __forceinline__ void prefetch_tmap(const CUtensorMap* tm) { asm volatile("prefetch.tensormap [%0];" ::"l"(tm) : "memory"); }

__device__ __forceinline__ void wg_fence() { asm volatile("wgmma.fence.sync.aligned;" ::: "memory"); }
__device__ __forceinline__ void wg_commit() { asm volatile("wgmma.commit_group.sync.aligned;" ::: "memory"); }
template <int N> __device__ __forceinline__ void wg_wait() { asm volatile("wgmma.wait_group.sync.aligned %0;" ::"n"(N) : "memory"); }
template <int N> __device__ __forceinline__ void reg_fence(float (&d)[N]) {
#pragma unroll
    for (int i = 0; i < N; i++) asm volatile("" : "+f"(d[i])::"memory");
}
template <int N> __device__ __forceinline__ void reg_fence(uint32_t (&d)[N]) {
#pragma unroll
    for (int i = 0; i < N; i++) asm volatile("" : "+r"(d[i])::"memory");
}
template <int R> __device__ __forceinline__ void reg_alloc() { asm volatile("setmaxnreg.inc.sync.aligned.u32 %0;" ::"n"(R)); }
template <int R> __device__ __forceinline__ void reg_dealloc() { asm volatile("setmaxnreg.dec.sync.aligned.u32 %0;" ::"n"(R)); }

__device__ __forceinline__ uint64_t mk_desc(uint32_t addr, uint32_t lbo, uint32_t sbo, uint32_t swz) {
    return (uint64_t)((addr & 0x3FFFF) >> 4) | ((uint64_t)(lbo >> 4) << 16) | ((uint64_t)(sbo >> 4) << 32) | ((uint64_t)swz << 62);
}
__device__ __forceinline__ uint32_t pack_bf16(float lo, float hi) {
    uint32_t r;
    asm("cvt.rn.bf16x2.f32 %0, %1, %2;" : "=r"(r) : "f"(hi), "f"(lo));
    return r;
}
__device__ __forceinline__ float bf_lo(uint32_t w) { return __uint_as_float(w << 16); }
__device__ __forceinline__ float bf_hi(uint32_t w) { return __uint_as_float(w & 0xFFFF0000u); }
__device__ __forceinline__ float ex2(float x) {
    float r;
    asm("ex2.approx.ftz.f32 %0, %1;" : "=f"(r) : "f"(x));
    return r;
}
__device__ __forceinline__ float tanh_fast(float x) {
    float r;
    asm("tanh.approx.f32 %0, %1;" : "=f"(r) : "f"(x));
    return r;
}
__device__ __forceinline__ float gelu_tanh(float u) {
    float w = fmaf(u * u, 0.0356774081f, 0.7978845608f);
    float t = tanh_fast(u * w);
    float h = 0.5f * u;
    return fmaf(h, t, h);
}

template<int TB> __device__ __forceinline__ void wgmma_ss_n216(float (&d)[108], uint64_t da, uint64_t db, int sd) {
    asm volatile("{\n.reg .pred p;\nsetp.ne.b32 p, %110, 0;\n"
      "wgmma.mma_async.sync.aligned.m64n216k16.f32.bf16.bf16 {%0, %1, %2, %3, %4, %5, %6, %7, %8, %9, %10, %11, %12, %13, %14, %15, %16, %17, %18, %19, %20, %21, %22, %23, %24, %25, %26, %27, %28, %29, %30, %31, %32, %33, %34, %35, %36, %37, %38, %39, %40, %41, %42, %43, %44, %45, %46, %47, %48, %49, %50, %51, %52, %53, %54, %55, %56, %57, %58, %59, %60, %61, %62, %63, %64, %65, %66, %67, %68, %69, %70, %71, %72, %73, %74, %75, %76, %77, %78, %79, %80, %81, %82, %83, %84, %85, %86, %87, %88, %89, %90, %91, %92, %93, %94, %95, %96, %97, %98, %99, %100, %101, %102, %103, %104, %105, %106, %107}, %108, %109, p, 1, 1, 0, %111;\n}\n"
      : "+f"(d[0]), "+f"(d[1]), "+f"(d[2]), "+f"(d[3]), "+f"(d[4]), "+f"(d[5]), "+f"(d[6]), "+f"(d[7]), "+f"(d[8]), "+f"(d[9]), "+f"(d[10]), "+f"(d[11]), "+f"(d[12]), "+f"(d[13]), "+f"(d[14]), "+f"(d[15]), "+f"(d[16]), "+f"(d[17]), "+f"(d[18]), "+f"(d[19]), "+f"(d[20]), "+f"(d[21]), "+f"(d[22]), "+f"(d[23]), "+f"(d[24]), "+f"(d[25]), "+f"(d[26]), "+f"(d[27]), "+f"(d[28]), "+f"(d[29]), "+f"(d[30]), "+f"(d[31]), "+f"(d[32]), "+f"(d[33]), "+f"(d[34]), "+f"(d[35]), "+f"(d[36]), "+f"(d[37]), "+f"(d[38]), "+f"(d[39]), "+f"(d[40]), "+f"(d[41]), "+f"(d[42]), "+f"(d[43]), "+f"(d[44]), "+f"(d[45]), "+f"(d[46]), "+f"(d[47]), "+f"(d[48]), "+f"(d[49]), "+f"(d[50]), "+f"(d[51]), "+f"(d[52]), "+f"(d[53]), "+f"(d[54]), "+f"(d[55]), "+f"(d[56]), "+f"(d[57]), "+f"(d[58]), "+f"(d[59]), "+f"(d[60]), "+f"(d[61]), "+f"(d[62]), "+f"(d[63]), "+f"(d[64]), "+f"(d[65]), "+f"(d[66]), "+f"(d[67]), "+f"(d[68]), "+f"(d[69]), "+f"(d[70]), "+f"(d[71]), "+f"(d[72]), "+f"(d[73]), "+f"(d[74]), "+f"(d[75]), "+f"(d[76]), "+f"(d[77]), "+f"(d[78]), "+f"(d[79]), "+f"(d[80]), "+f"(d[81]), "+f"(d[82]), "+f"(d[83]), "+f"(d[84]), "+f"(d[85]), "+f"(d[86]), "+f"(d[87]), "+f"(d[88]), "+f"(d[89]), "+f"(d[90]), "+f"(d[91]), "+f"(d[92]), "+f"(d[93]), "+f"(d[94]), "+f"(d[95]), "+f"(d[96]), "+f"(d[97]), "+f"(d[98]), "+f"(d[99]), "+f"(d[100]), "+f"(d[101]), "+f"(d[102]), "+f"(d[103]), "+f"(d[104]), "+f"(d[105]), "+f"(d[106]), "+f"(d[107])
      : "l"(da), "l"(db), "r"(sd), "n"(TB));
}

template<int TB> __device__ __forceinline__ void wgmma_ss_n128(float (&d)[64], uint64_t da, uint64_t db, int sd) {
    asm volatile("{\n.reg .pred p;\nsetp.ne.b32 p, %66, 0;\n"
      "wgmma.mma_async.sync.aligned.m64n128k16.f32.bf16.bf16 {%0, %1, %2, %3, %4, %5, %6, %7, %8, %9, %10, %11, %12, %13, %14, %15, %16, %17, %18, %19, %20, %21, %22, %23, %24, %25, %26, %27, %28, %29, %30, %31, %32, %33, %34, %35, %36, %37, %38, %39, %40, %41, %42, %43, %44, %45, %46, %47, %48, %49, %50, %51, %52, %53, %54, %55, %56, %57, %58, %59, %60, %61, %62, %63}, %64, %65, p, 1, 1, 0, %67;\n}\n"
      : "+f"(d[0]), "+f"(d[1]), "+f"(d[2]), "+f"(d[3]), "+f"(d[4]), "+f"(d[5]), "+f"(d[6]), "+f"(d[7]), "+f"(d[8]), "+f"(d[9]), "+f"(d[10]), "+f"(d[11]), "+f"(d[12]), "+f"(d[13]), "+f"(d[14]), "+f"(d[15]), "+f"(d[16]), "+f"(d[17]), "+f"(d[18]), "+f"(d[19]), "+f"(d[20]), "+f"(d[21]), "+f"(d[22]), "+f"(d[23]), "+f"(d[24]), "+f"(d[25]), "+f"(d[26]), "+f"(d[27]), "+f"(d[28]), "+f"(d[29]), "+f"(d[30]), "+f"(d[31]), "+f"(d[32]), "+f"(d[33]), "+f"(d[34]), "+f"(d[35]), "+f"(d[36]), "+f"(d[37]), "+f"(d[38]), "+f"(d[39]), "+f"(d[40]), "+f"(d[41]), "+f"(d[42]), "+f"(d[43]), "+f"(d[44]), "+f"(d[45]), "+f"(d[46]), "+f"(d[47]), "+f"(d[48]), "+f"(d[49]), "+f"(d[50]), "+f"(d[51]), "+f"(d[52]), "+f"(d[53]), "+f"(d[54]), "+f"(d[55]), "+f"(d[56]), "+f"(d[57]), "+f"(d[58]), "+f"(d[59]), "+f"(d[60]), "+f"(d[61]), "+f"(d[62]), "+f"(d[63])
      : "l"(da), "l"(db), "r"(sd), "n"(TB));
}

template<int TB> __device__ __forceinline__ void wgmma_ss_n64(float (&d)[32], uint64_t da, uint64_t db, int sd) {
    asm volatile("{\n.reg .pred p;\nsetp.ne.b32 p, %34, 0;\n"
      "wgmma.mma_async.sync.aligned.m64n64k16.f32.bf16.bf16 {%0, %1, %2, %3, %4, %5, %6, %7, %8, %9, %10, %11, %12, %13, %14, %15, %16, %17, %18, %19, %20, %21, %22, %23, %24, %25, %26, %27, %28, %29, %30, %31}, %32, %33, p, 1, 1, 0, %35;\n}\n"
      : "+f"(d[0]), "+f"(d[1]), "+f"(d[2]), "+f"(d[3]), "+f"(d[4]), "+f"(d[5]), "+f"(d[6]), "+f"(d[7]), "+f"(d[8]), "+f"(d[9]), "+f"(d[10]), "+f"(d[11]), "+f"(d[12]), "+f"(d[13]), "+f"(d[14]), "+f"(d[15]), "+f"(d[16]), "+f"(d[17]), "+f"(d[18]), "+f"(d[19]), "+f"(d[20]), "+f"(d[21]), "+f"(d[22]), "+f"(d[23]), "+f"(d[24]), "+f"(d[25]), "+f"(d[26]), "+f"(d[27]), "+f"(d[28]), "+f"(d[29]), "+f"(d[30]), "+f"(d[31])
      : "l"(da), "l"(db), "r"(sd), "n"(TB));
}

template<int TB> __device__ __forceinline__ void wgmma_rs_n64(float (&d)[32], uint32_t a0, uint32_t a1, uint32_t a2, uint32_t a3, uint64_t db, int sd) {
    asm volatile("{\n.reg .pred p;\nsetp.ne.b32 p, %37, 0;\n"
      "wgmma.mma_async.sync.aligned.m64n64k16.f32.bf16.bf16 {%0, %1, %2, %3, %4, %5, %6, %7, %8, %9, %10, %11, %12, %13, %14, %15, %16, %17, %18, %19, %20, %21, %22, %23, %24, %25, %26, %27, %28, %29, %30, %31}, {%32, %33, %34, %35}, %36, p, 1, 1, %38;\n}\n"
      : "+f"(d[0]), "+f"(d[1]), "+f"(d[2]), "+f"(d[3]), "+f"(d[4]), "+f"(d[5]), "+f"(d[6]), "+f"(d[7]), "+f"(d[8]), "+f"(d[9]), "+f"(d[10]), "+f"(d[11]), "+f"(d[12]), "+f"(d[13]), "+f"(d[14]), "+f"(d[15]), "+f"(d[16]), "+f"(d[17]), "+f"(d[18]), "+f"(d[19]), "+f"(d[20]), "+f"(d[21]), "+f"(d[22]), "+f"(d[23]), "+f"(d[24]), "+f"(d[25]), "+f"(d[26]), "+f"(d[27]), "+f"(d[28]), "+f"(d[29]), "+f"(d[30]), "+f"(d[31])
      : "r"(a0), "r"(a1), "r"(a2), "r"(a3), "l"(db), "r"(sd), "n"(TB));
}

template<int TB> __device__ __forceinline__ void wgmma_rs_n24(float (&d)[12], uint32_t a0, uint32_t a1, uint32_t a2, uint32_t a3, uint64_t db, int sd) {
    asm volatile("{\n.reg .pred p;\nsetp.ne.b32 p, %17, 0;\n"
      "wgmma.mma_async.sync.aligned.m64n24k16.f32.bf16.bf16 {%0, %1, %2, %3, %4, %5, %6, %7, %8, %9, %10, %11}, {%12, %13, %14, %15}, %16, p, 1, 1, %18;\n}\n"
      : "+f"(d[0]), "+f"(d[1]), "+f"(d[2]), "+f"(d[3]), "+f"(d[4]), "+f"(d[5]), "+f"(d[6]), "+f"(d[7]), "+f"(d[8]), "+f"(d[9]), "+f"(d[10]), "+f"(d[11])
      : "r"(a0), "r"(a1), "r"(a2), "r"(a3), "l"(db), "r"(sd), "n"(TB));
}


constexpr int K1_XN_BYTES = 9 * 16384;
constexpr int K1_SLOT = 16384, K1_NSLOT = 5;
constexpr int K1_OFF_RING = K1_XN_BYTES;
constexpr int K1_OFF_BIAS = K1_OFF_RING + K1_NSLOT * K1_SLOT;
constexpr int K1_OFF_BAR = K1_OFF_BIAS + 576 * 4;
constexpr int K1_SMEM = K1_OFF_BAR + 128;
constexpr float QSCALE = 0.23570226039551584f * 1.4426950408889634f;

struct Ring {
    uint32_t slot, phase;
    __device__ __forceinline__ void advance() {
        if (++slot == K1_NSLOT) { slot = 0; phase ^= 1; }
    }
};

struct K1Ctx {
    uint32_t full0, empty0;
    uint32_t ring0;
    uint64_t descA;
    Ring rd;
    uint32_t prev_slot;
    bool rel_thread;
    uint32_t rel_cta;
    __device__ __forceinline__ void release_prev() {
        if (rel_thread && prev_slot != 0xFFFFFFFFu) mbar_arrive_cluster(empty0 + prev_slot * 8, rel_cta);
    }
};

__device__ __forceinline__ uint64_t descA_step(uint64_t base, int ks) { return base + (uint64_t)(((ks >> 2) * 16384 + (ks & 3) * 32) >> 4); }

template <int V> struct IC { static constexpr int value = V; };
template <int I, int N, class F> __device__ __forceinline__ void static_for(F&& f) {
    if constexpr (I < N) { f(IC<I>{}); static_for<I + 1, N>(f); }
}

template <int N, int KS, int NST, int HALF_STRIDE, int LBO, class Epi>
__device__ __forceinline__ void tile_ss(K1Ctx& c, float (&acc)[N / 2], Epi&& epi) {
    static_for<0, NST>([&](auto sc) {
        constexpr int s = decltype(sc)::value;
        mbar_wait(c.full0 + c.rd.slot * 8, c.rd.phase);
        uint64_t db = mk_desc(c.ring0 + c.rd.slot * K1_SLOT, LBO, 1024, 1);
        wg_fence();
#pragma unroll
        for (int t = 0; t < KS; t++) {
            const int off = (t / (KS / 2)) * HALF_STRIDE + (t % (KS / 2)) * 2048;
            uint64_t da = descA_step(c.descA, s * KS + t);
            if constexpr (N == 216) wgmma_ss_n216<1>(acc, da, db + (off >> 4), (s | t) != 0);
            if constexpr (N == 64) wgmma_ss_n64<1>(acc, da, db + (off >> 4), (s | t) != 0);
            if constexpr (N == 128) wgmma_ss_n128<1>(acc, da, db + (off >> 4), (s | t) != 0);
        }
        wg_commit();
        wg_wait<1>();
        c.release_prev();
        c.prev_slot = c.rd.slot;
        c.rd.advance();
        epi(sc);
    });
}

template <class Epi>
__device__ __forceinline__ void tile_rs(K1Ctx& c, float (&acc)[32], uint32_t (&h)[144], Epi&& epi) {
    static_for<0, 6>([&](auto sc) {
        constexpr int s = decltype(sc)::value;
        mbar_wait(c.full0 + c.rd.slot * 8, c.rd.phase);
        uint64_t db = mk_desc(c.ring0 + c.rd.slot * K1_SLOT, 8192, 1024, 1);
        wg_fence();
#pragma unroll
        for (int t = 0; t < 6; t++) {
            const int ks = s * 6 + t;
            wgmma_rs_n64<1>(acc, h[ks * 4], h[ks * 4 + 1], h[ks * 4 + 2], h[ks * 4 + 3], db + ((t * 2048) >> 4), (s | t) != 0);
        }
        wg_commit();
        wg_wait<1>();
        c.release_prev();
        c.prev_slot = c.rd.slot;
        c.rd.advance();
        epi(sc);
    });
}

template <int N, int B0, int NB, int HOFF>
__device__ __forceinline__ void gelu_blocks(const float (&acc)[N / 2], uint32_t (&h)[144], const float* bias  ) {
#pragma unroll
    for (int b = B0; b < B0 + NB; b++) {
        float2 bb = *reinterpret_cast<const float2*>(bias + b * 8);
        float v0 = gelu_tanh(acc[b * 4 + 0] + bb.x), v1 = gelu_tanh(acc[b * 4 + 1] + bb.y);
        float v2 = gelu_tanh(acc[b * 4 + 2] + bb.x), v3 = gelu_tanh(acc[b * 4 + 3] + bb.y);
        h[HOFF + b * 2 + 0] = pack_bf16(v0, v1);
        h[HOFF + b * 2 + 1] = pack_bf16(v2, v3);
    }
}

__global__ void __cluster_dims__(2, 1, 1) __launch_bounds__(384, 1)
k1_kernel(const __grid_constant__ CUtensorMap tmQ3, const __grid_constant__ CUtensorMap tmQ1, const __grid_constant__ CUtensorMap tm1a,
          const __grid_constant__ CUtensorMap tm1b, const __grid_constant__ CUtensorMap tm2, const __nv_bfloat16* __restrict__ x,
          const __nv_bfloat16* __restrict__ b1) {
    extern __shared__ __align__(1024) uint8_t smem[];
    const uint32_t sb = s2u(smem);
    const int tid = threadIdx.x, warp = tid >> 5, lane = tid & 31;
    const uint32_t rank = blockIdx.x & 1;
    const int cl = blockIdx.x >> 1;
    const int rb = (cl & 7) * 2 + rank;
    const int j = cl >> 3;
    const uint32_t full0 = sb + K1_OFF_BAR, empty0 = full0 + 8 * K1_NSLOT;

    if (warp < 8) {
        reg_alloc<240>();
        uint4 xv[4][9];
        const int sub = lane >> 3, l8 = lane & 7;
        {
            const uint4* xp = reinterpret_cast<const uint4*>(x + (size_t)(rb * 128 + warp * 16 + sub) * DM) + l8;
#pragma unroll
            for (int p = 0; p < 4; p++)
#pragma unroll
                for (int i = 0; i < 9; i++) xv[p][i] = __ldg(xp + p * 4 * (DM / 8) + i * 8);
        }
        cluster_arrive();
#pragma unroll
        for (int p = 0; p < 4; p++) {
            float f[72];
#pragma unroll
            for (int i = 0; i < 9; i++) {
                f[i * 8 + 0] = bf_lo(xv[p][i].x); f[i * 8 + 1] = bf_hi(xv[p][i].x);
                f[i * 8 + 2] = bf_lo(xv[p][i].y); f[i * 8 + 3] = bf_hi(xv[p][i].y);
                f[i * 8 + 4] = bf_lo(xv[p][i].z); f[i * 8 + 5] = bf_hi(xv[p][i].z);
                f[i * 8 + 6] = bf_lo(xv[p][i].w); f[i * 8 + 7] = bf_hi(xv[p][i].w);
            }
            float s0 = 0.f, s1 = 0.f, s2 = 0.f, s3 = 0.f;
#pragma unroll
            for (int i = 0; i < 72; i += 4) { s0 += f[i]; s1 += f[i + 1]; s2 += f[i + 2]; s3 += f[i + 3]; }
            float sm = (s0 + s1) + (s2 + s3);
            sm += __shfl_xor_sync(~0u, sm, 1); sm += __shfl_xor_sync(~0u, sm, 2); sm += __shfl_xor_sync(~0u, sm, 4);
            const float mean = sm * (1.0f / DM);
            s0 = s1 = s2 = s3 = 0.f;
#pragma unroll
            for (int i = 0; i < 72; i += 4) {
                f[i] -= mean; f[i + 1] -= mean; f[i + 2] -= mean; f[i + 3] -= mean;
                s0 = fmaf(f[i], f[i], s0); s1 = fmaf(f[i + 1], f[i + 1], s1);
                s2 = fmaf(f[i + 2], f[i + 2], s2); s3 = fmaf(f[i + 3], f[i + 3], s3);
            }
            float sq = (s0 + s1) + (s2 + s3);
            sq += __shfl_xor_sync(~0u, sq, 1); sq += __shfl_xor_sync(~0u, sq, 2); sq += __shfl_xor_sync(~0u, sq, 4);
            const float rstd = rsqrtf(sq * (1.0f / DM) + 1e-5f);
            const int r = warp * 16 + p * 4 + sub;
            uint8_t* dst = smem + r * 128 + ((l8 ^ (r & 7)) << 4);
#pragma unroll
            for (int i = 0; i < 9; i++) {
                uint4 o;
                o.x = pack_bf16(f[i * 8 + 0] * rstd, f[i * 8 + 1] * rstd);
                o.y = pack_bf16(f[i * 8 + 2] * rstd, f[i * 8 + 3] * rstd);
                o.z = pack_bf16(f[i * 8 + 4] * rstd, f[i * 8 + 5] * rstd);
                o.w = pack_bf16(f[i * 8 + 6] * rstd, f[i * 8 + 7] * rstd);
                *reinterpret_cast<uint4*>(dst + i * 16384) = o;
            }
        }
        float* sbias = reinterpret_cast<float*>(smem + K1_OFF_BIAS);
        for (int i = tid; i < 576; i += 256) sbias[i] = __bfloat162float(b1[j * 576 + i]);
        fence_proxy_async();
        named_bar_sync(1, 256);
        cluster_wait();

        const int wg = warp >> 2, wq = warp & 3;
        const int g = lane >> 2, q = lane & 3;
        K1Ctx c;
        c.full0 = full0; c.empty0 = empty0; c.ring0 = sb + K1_OFF_RING;
        c.descA = mk_desc(sb + wg * 8192, 16, 1024, 1);
        c.rd.slot = 0; c.rd.phase = 0; c.prev_slot = 0xFFFFFFFFu;
        c.rel_thread = (lane == 0) && (wq < 2);
        c.rel_cta = wq;
        const float* biasq = sbias + 2 * q;

        uint32_t h[144];
        float accX[64], accY[64];
        {
            float accQ[108];
            tile_ss<216, 2, 18, 8192, 2048>(c, accQ, [&](auto) {});
            const int grp0 = rb * 16 + warp * 2;
            float nrm[2][4];
            uint8_t* gbase = nullptr;
            uint32_t hstride = 0, gstride = 0, o2 = 0;
            float scl0 = 1.f, scl1 = 1.f;
            int type = 0, head0 = 0;
            tile_ss<128, 4, 9, 8192, 4096>(c, accX, [&](auto sc) {
                constexpr int s = decltype(sc)::value;
                if constexpr (s == 0) reg_fence(accQ);
                constexpr int grp = s / 3, part = s % 3;
                if constexpr (part == 0) {
                    const int G = 3 * j + grp;
                    type = G >> 3;
                    head0 = (G & 7) * 4;
                    if (type == 0) {
                        gbase = g_Q + (size_t)head0 * Q_HEAD_BYTES + grp0 * Q_GROUP_BYTES + g * 16;
                        hstride = Q_HEAD_BYTES; gstride = Q_GROUP_BYTES; o2 = 256;
                        scl0 = QSCALE; scl1 = QSCALE;
                    } else {
                        gbase = g_KV + (size_t)head0 * KV_HEAD_BYTES + grp0 * KV_GROUP_BYTES + g * 16 + (type == 2 ? 256 : 0);
                        hstride = KV_HEAD_BYTES; gstride = KV_GROUP_BYTES; o2 = (type == 2) ? 256 + 8 : 512;
                        scl0 = 1.f; scl1 = (type == 1) ? 2.f : 1.f;
                    }
#pragma unroll
                    for (int i = 0; i < 4; i++) { nrm[0][i] = 0.f; nrm[1][i] = 0.f; }
                }
#pragma unroll
                for (int i9 = part * 3; i9 < part * 3 + 3; i9++) {
                    const int b = grp * 9 + i9;
                    const int p = 4 * i9 + q;
                    const int hlo = (4 * i9) / 9;
                    const bool up = (p >= 9 * (hlo + 1));
                    const int hh = hlo + (up ? 1 : 0);
                    const int r = p - 9 * hh;
                    const uint32_t off = hh * hstride + (r < 4 ? r * 4 : (r < 8 ? 112 + r * 4 : o2));
                    const float a0 = accQ[b * 4], a1 = accQ[b * 4 + 1], a2 = accQ[b * 4 + 2], a3 = accQ[b * 4 + 3];
                    *reinterpret_cast<uint32_t*>(gbase + off) = pack_bf16(a0 * scl0, a1 * scl0);
                    *reinterpret_cast<uint32_t*>(gbase + off + gstride) = pack_bf16(a2 * scl1, a3 * scl1);
                    if (r == 8 && type != 0) {
                        *reinterpret_cast<uint32_t*>(gbase + off + 4) = 0x00003F80u;
                        *reinterpret_cast<uint32_t*>(gbase + off + gstride + 4) = (type == 1) ? 0x3F804000u : 0x00003F80u;
                    }
                    const float e0 = fmaf(a0, a0, a1 * a1), e1 = fmaf(a2, a2, a3 * a3);
                    if ((4 * i9 + 3) / 9 == hlo) {
                        nrm[0][hlo] += e0; nrm[1][hlo] += e1;
                    } else {
                        nrm[0][hlo] += up ? 0.f : e0; nrm[1][hlo] += up ? 0.f : e1;
                        nrm[0][(hlo + 1) & 3] += up ? e0 : 0.f; nrm[1][(hlo + 1) & 3] += up ? e1 : 0.f;
                    }
                }
                if constexpr (part == 2) {
                    if (type == 1) {
#pragma unroll
                        for (int i = 0; i < 4; i++) {
                            float u0 = nrm[0][i], u1 = nrm[1][i];
                            u0 += __shfl_xor_sync(~0u, u0, 1); u1 += __shfl_xor_sync(~0u, u1, 1);
                            u0 += __shfl_xor_sync(~0u, u0, 2); u1 += __shfl_xor_sync(~0u, u1, 2);
                            float m = fmaxf(u0, u1);
                            m = fmaxf(m, __shfl_xor_sync(~0u, m, 4));
                            m = fmaxf(m, __shfl_xor_sync(~0u, m, 8));
                            m = fmaxf(m, __shfl_xor_sync(~0u, m, 16));
                            if (lane == 0) g_kmax[(head0 + i) * 128 + rb * 8 + warp] = m;
                        }
                    }
                }
            });
        }
        tile_ss<128, 4, 9, 8192, 4096>(c, accY, [&](auto sc) {
            constexpr int s = decltype(sc)::value;
            if constexpr (s == 0) reg_fence(accX);
            if constexpr (s < 8) gelu_blocks<128, s * 2, 2, 0>(accX, h, biasq);
        });
        tile_ss<128, 4, 9, 8192, 4096>(c, accX, [&](auto sc) {
            constexpr int s = decltype(sc)::value;
            if constexpr (s == 0) reg_fence(accY);
            if constexpr (s < 8) gelu_blocks<128, s * 2, 2, 32>(accY, h, biasq + 128);
        });
        float o0[32], o1[32];
        tile_ss<64, 6, 6, 6144, 8192>(c, o0, [&](auto sc) {
            constexpr int s = decltype(sc)::value;
            if constexpr (s == 0) reg_fence(accX);
            if constexpr (s < 5) gelu_blocks<128, s * 3, 3, 64>(accX, h, biasq + 256);
            if constexpr (s == 5) gelu_blocks<128, 15, 1, 64>(accX, h, biasq + 256);
        });
        tile_ss<64, 6, 6, 6144, 8192>(c, o1, [&](auto sc) {
            constexpr int s = decltype(sc)::value;
            if constexpr (s == 0) reg_fence(o0);
            if constexpr (s < 4) gelu_blocks<64, s * 2, 2, 96>(o0, h, biasq + 384);
        });
        tile_ss<64, 6, 6, 6144, 8192>(c, o0, [&](auto sc) {
            constexpr int s = decltype(sc)::value;
            if constexpr (s == 0) reg_fence(o1);
            if constexpr (s < 4) gelu_blocks<64, s * 2, 2, 112>(o1, h, biasq + 448);
        });
        uint4* pout = g_part + ((size_t)(j * 16 + rb) * 36) * 256 + tid;
        auto store_part = [&](float (&o)[32], int t, auto sc) {
            constexpr int s = decltype(sc)::value;
            if constexpr (s == 0) reg_fence(o);
            if constexpr (s < 4) {
                uint4 v;
                v.x = pack_bf16(o[s * 8 + 0], o[s * 8 + 1]); v.y = pack_bf16(o[s * 8 + 2], o[s * 8 + 3]);
                v.z = pack_bf16(o[s * 8 + 4], o[s * 8 + 5]); v.w = pack_bf16(o[s * 8 + 6], o[s * 8 + 7]);
                pout[(t * 4 + s) * 256] = v;
            }
        };
        tile_rs(c, o1, h, [&](auto sc) {
            constexpr int s = decltype(sc)::value;
            if constexpr (s == 0) reg_fence(o0);
            if constexpr (s < 4) gelu_blocks<64, s * 2, 2, 128>(o0, h, biasq + 512);
            if constexpr (s == 4) reg_fence(h);
        });
#pragma unroll 1
        for (int t = 1; t < 9; t += 2) {
            tile_rs(c, o0, h, [&](auto sc) { store_part(o1, t - 1, sc); });
            tile_rs(c, o1, h, [&](auto sc) { store_part(o0, t, sc); });
        }
        wg_wait<0>();
        static_for<0, 4>([&](auto sc) { store_part(o1, 8, sc); });
        cluster_arrive();
        cluster_wait();
    } else {
        reg_dealloc<24>();
        if (warp == 8 && lane == 0) {
            prefetch_tmap(&tmQ3); prefetch_tmap(&tmQ1); prefetch_tmap(&tm1a); prefetch_tmap(&tm1b); prefetch_tmap(&tm2);
            for (int i = 0; i < K1_NSLOT; i++) { mbar_init(full0 + i * 8, 1); mbar_init(empty0 + i * 8, 4); }
            fence_barrier_init();
        }
        __syncwarp();
        cluster_arrive();
        cluster_wait();
        if (warp == 8 && lane == 0) {
            Ring w{0, 1};
            const uint32_t ring0 = sb + K1_OFF_RING;
            for (int s = 0; s < 18; s++) {
                mbar_wait_cluster(empty0 + w.slot * 8, w.phase);
                mbar_expect(full0 + w.slot * 8, 16384);
                const uint32_t dst = ring0 + w.slot * K1_SLOT + rank * 8192;
                tma3d_mc(dst, &tmQ3, j * 216, s * 32 + rank * 16, 0, full0 + w.slot * 8, 3);
                tma2d_mc(dst + 6144, &tmQ1, j * 216 + 192, s * 32 + rank * 16, full0 + w.slot * 8, 3);
                w.advance();
            }
            for (int t = 0; t < 3; t++)
                for (int s = 0; s < 9; s++) {
                    mbar_wait_cluster(empty0 + w.slot * 8, w.phase);
                    mbar_expect(full0 + w.slot * 8, 16384);
                    tma3d_mc(ring0 + w.slot * K1_SLOT + rank * 8192, &tm1b, 0, s * 64 + rank * 32, j * 9 + t * 2, full0 + w.slot * 8, 3);
                    w.advance();
                }
            for (int t = 0; t < 3; t++)
                for (int s = 0; s < 6; s++) {
                    mbar_wait_cluster(empty0 + w.slot * 8, w.phase);
                    mbar_expect(full0 + w.slot * 8, 12288);
                    tma3d_mc(ring0 + w.slot * K1_SLOT + rank * 6144, &tm1a, 0, s * 96 + rank * 48, j * 9 + 6 + t, full0 + w.slot * 8, 3);
                    w.advance();
                }
            for (int t = 0; t < 9; t++)
                for (int s = 0; s < 6; s++) {
                    mbar_wait_cluster(empty0 + w.slot * 8, w.phase);
                    mbar_expect(full0 + w.slot * 8, 12288);
                    tma2d_mc(ring0 + w.slot * K1_SLOT + rank * 6144, &tm2, t * 64, j * 576 + s * 96 + rank * 48, full0 + w.slot * 8, 3);
                    w.advance();
                }
        }
        __syncwarp();
        cluster_arrive();
        cluster_wait();
    }
}

constexpr int K2_NCHUNK = 16;
constexpr int K2_CHUNK_BYTES = KV_HEAD_BYTES / K2_NCHUNK;
constexpr int K2_OFF_BAR = KV_HEAD_BYTES;
constexpr int K2_SMEM = K2_OFF_BAR + 256;

__device__ __forceinline__ float exp2_fixed(float y) {
    const float u = __uint_as_float((__float_as_uint(y) & 0x7FFFu) | 0x44000000u) - 512.02545f;
    float t = fmaf(u, 0.019497588f, 0.114550486f);
    t = fmaf(t, u, -0.29839927f);
    return fmaf(t, u, y);
}
__device__ __forceinline__ uint32_t pack_fixed(float lo, float hi) { return __byte_perm(__float_as_uint(lo), __float_as_uint(hi), 0x6521); }

__device__ __forceinline__ void softmax_fast(const float (&s)[32], uint32_t (&p)[16]) {
#pragma unroll
    for (int k = 0; k < 4; k++) {
        p[k * 4 + 0] = pack_bf16(ex2(s[k * 8 + 0]), ex2(s[k * 8 + 1]));
        p[k * 4 + 1] = pack_bf16(ex2(s[k * 8 + 2]), ex2(s[k * 8 + 3]));
        p[k * 4 + 2] = pack_fixed(exp2_fixed(s[k * 8 + 4]), exp2_fixed(s[k * 8 + 5]));
        p[k * 4 + 3] = pack_fixed(exp2_fixed(s[k * 8 + 6]), exp2_fixed(s[k * 8 + 7]));
    }
}

__device__ __forceinline__ void issue_qk(float (&s)[32], const uint32_t (&qa)[8], uint64_t dk0, uint64_t dk1, int tile) {
    const uint64_t off = (uint64_t)(tile * (8 * KV_GROUP_BYTES / 16));
    wgmma_rs_n64<0>(s, qa[0], qa[1], qa[2], qa[3], dk0 + off, 0);
    wgmma_rs_n64<0>(s, qa[4], qa[5], qa[6], qa[7], dk1 + off, 1);
}
__device__ __forceinline__ void issue_pv(float (&o)[12], const uint32_t (&p)[16], uint64_t dv, int tile) {
    const uint64_t off = (uint64_t)(tile * (8 * KV_GROUP_BYTES / 16));
#pragma unroll
    for (int k = 0; k < 4; k++) wgmma_rs_n24<1>(o, p[k * 4], p[k * 4 + 1], p[k * 4 + 2], p[k * 4 + 3], dv + off + k * (2 * KV_GROUP_BYTES / 16), 1);
}

__global__ void __launch_bounds__(512, 1) k2_kernel() {
    extern __shared__ __align__(1024) uint8_t smem[];
    const uint32_t sb = s2u(smem);
    const int tid = threadIdx.x, warp = tid >> 5, lane = tid & 31;
    const int wg = warp >> 2, wq = warp & 3, g = lane >> 2, q = lane & 3;
    const int head = blockIdx.x >> 2, quarter = blockIdx.x & 3;
    const uint32_t bar0 = sb + K2_OFF_BAR;
    if (tid == 0) {
        for (int i = 0; i < K2_NCHUNK; i++) mbar_init(bar0 + i * 8, 1);
        fence_barrier_init();
    }
    __syncthreads();
    griddep_wait();
    if (warp == 0 && lane < K2_NCHUNK) {
        mbar_expect(bar0 + lane * 8, K2_CHUNK_BYTES);
        bulk_load(sb + lane * K2_CHUNK_BYTES, g_KV + (size_t)head * KV_HEAD_BYTES + lane * K2_CHUNK_BYTES, K2_CHUNK_BYTES, bar0 + lane * 8);
    }
    float kmax2;
    {
        const float4 v = *reinterpret_cast<const float4*>(g_kmax + head * 128 + lane * 4);
        kmax2 = fmaxf(fmaxf(v.x, v.y), fmaxf(v.z, v.w));
#pragma unroll
        for (int o = 16; o; o >>= 1) kmax2 = fmaxf(kmax2, __shfl_xor_sync(~0u, kmax2, o));
    }
    const uint64_t dk0 = mk_desc(sb, 128, KV_GROUP_BYTES, 0);
    const uint64_t dk1 = mk_desc(sb + 512, 0, KV_GROUP_BYTES, 0);
    const uint64_t dv = mk_desc(sb + 256, KV_GROUP_BYTES, 128, 0);

#pragma unroll 1
    for (int pass = 0; pass < 2; pass++) {
        const int row0 = quarter * 512 + (pass * 4 + wg) * 64 + wq * 16;
        uint32_t qa[8];
        {
            const uint8_t* qp = g_Q + (size_t)head * Q_HEAD_BYTES + (row0 >> 3) * Q_GROUP_BYTES + g * 16 + q * 4;
            qa[0] = *reinterpret_cast<const uint32_t*>(qp);
            qa[1] = *reinterpret_cast<const uint32_t*>(qp + Q_GROUP_BYTES);
            qa[2] = *reinterpret_cast<const uint32_t*>(qp + 128);
            qa[3] = *reinterpret_cast<const uint32_t*>(qp + Q_GROUP_BYTES + 128);
            qa[4] = (q == 0) ? *reinterpret_cast<const uint32_t*>(qp + 256) : 0u;
            qa[5] = (q == 0) ? *reinterpret_cast<const uint32_t*>(qp + Q_GROUP_BYTES + 256) : 0u;
            qa[6] = 0u; qa[7] = 0u;
        }
        float c0, c1;
        {
            float n0 = bf_lo(qa[0]) * bf_lo(qa[0]) + bf_hi(qa[0]) * bf_hi(qa[0]) + bf_lo(qa[2]) * bf_lo(qa[2]) + bf_hi(qa[2]) * bf_hi(qa[2]) +
                       bf_lo(qa[4]) * bf_lo(qa[4]) + bf_hi(qa[4]) * bf_hi(qa[4]);
            float n1 = bf_lo(qa[1]) * bf_lo(qa[1]) + bf_hi(qa[1]) * bf_hi(qa[1]) + bf_lo(qa[3]) * bf_lo(qa[3]) + bf_hi(qa[3]) * bf_hi(qa[3]) +
                       bf_lo(qa[5]) * bf_lo(qa[5]) + bf_hi(qa[5]) * bf_hi(qa[5]);
            n0 += __shfl_xor_sync(~0u, n0, 1); n1 += __shfl_xor_sync(~0u, n1, 1);
            n0 += __shfl_xor_sync(~0u, n0, 2); n1 += __shfl_xor_sync(~0u, n1, 2);
            c0 = sqrtf(n0 * kmax2) * 1.02f;
            c1 = sqrtf(n1 * kmax2) * 1.02f;
        }
        uint32_t slow;
        {
            const bool bad = !(c0 <= 58.f && c1 <= 58.f);
            asm volatile("{\n.reg .pred p, r;\nsetp.ne.u32 p, %1, 0;\nbarrier.cta.red.or.pred.aligned r, %2, 128, p;\nselp.u32 %0, 1, 0, r;\n}\n"
                         : "=r"(slow) : "r"((uint32_t)bad), "r"(wg + 1) : "memory");
        }
        float o[12];
#pragma unroll
        for (int i = 0; i < 12; i++) o[i] = 0.f;

        if (!slow) {
            if (q == 1) {
                qa[4] = pack_bf16(-c0, 768.f); qa[5] = pack_bf16(-c1, 768.f);
                qa[6] = pack_bf16(0.f, -2.f); qa[7] = qa[6];
            }
            float s0[32], s1[32];
            uint32_t p0[16], p1[16];
            if (pass == 0) mbar_wait(bar0, 0);
            reg_fence(qa);
            reg_fence(o);
            wg_fence();
            issue_qk(s0, qa, dk0, dk1, 0);
            wg_commit();
            issue_qk(s1, qa, dk0, dk1, 1);
            wg_commit();
#pragma unroll 1
            for (int t = 0; t < 30; t += 2) {
                wg_wait<1>();
                reg_fence(s0);
                softmax_fast(s0, p0);
                reg_fence(p0);
                if (pass == 0) mbar_wait(bar0 + (t / 2 + 1) * 8, 0);
                wg_fence();
                issue_pv(o, p0, dv, t);
                issue_qk(s0, qa, dk0, dk1, t + 2);
                wg_commit();
                wg_wait<1>();
                reg_fence(s1);
                softmax_fast(s1, p1);
                reg_fence(p1);
                wg_fence();
                issue_pv(o, p1, dv, t + 1);
                issue_qk(s1, qa, dk0, dk1, t + 3);
                wg_commit();
            }
            wg_wait<1>();
            reg_fence(s0);
            softmax_fast(s0, p0);
            reg_fence(p0);
            wg_fence();
            issue_pv(o, p0, dv, 30);
            wg_commit();
            wg_wait<1>();
            reg_fence(s1);
            softmax_fast(s1, p1);
            reg_fence(p1);
            wg_fence();
            issue_pv(o, p1, dv, 31);
            wg_commit();
            wg_wait<0>();
            reg_fence(o);
        } else {
            float m0 = -INFINITY, m1 = -INFINITY;
            float s[32];
            uint32_t p[16];
#pragma unroll 1
            for (int t = 0; t < 32; t++) {
                if (pass == 0) mbar_wait(bar0 + (t / 2) * 8, 0);
                wg_fence();
                issue_qk(s, qa, dk0, dk1, t);
                wg_commit();
                wg_wait<0>();
                reg_fence(s);
                reg_fence(o);
                float a0 = m0, a1 = m1;
#pragma unroll
                for (int k = 0; k < 4; k++) {
#pragma unroll
                    for (int i = 4; i < 8; i++) s[k * 8 + i] *= 0.5f;
                    a0 = fmaxf(fmaxf(a0, fmaxf(s[k * 8 + 0], s[k * 8 + 1])), fmaxf(s[k * 8 + 4], s[k * 8 + 5]));
                    a1 = fmaxf(fmaxf(a1, fmaxf(s[k * 8 + 2], s[k * 8 + 3])), fmaxf(s[k * 8 + 6], s[k * 8 + 7]));
                }
                a0 = fmaxf(a0, __shfl_xor_sync(~0u, a0, 1)); a1 = fmaxf(a1, __shfl_xor_sync(~0u, a1, 1));
                a0 = fmaxf(a0, __shfl_xor_sync(~0u, a0, 2)); a1 = fmaxf(a1, __shfl_xor_sync(~0u, a1, 2));
                const float r0 = ex2(m0 - a0), r1 = ex2(m1 - a1);
                m0 = a0; m1 = a1;
#pragma unroll
                for (int i = 0; i < 3; i++) { o[i * 4] *= r0; o[i * 4 + 1] *= r0; o[i * 4 + 2] *= r1; o[i * 4 + 3] *= r1; }
#pragma unroll
                for (int k = 0; k < 8; k++) {
                    p[k * 2 + 0] = pack_bf16(ex2(s[k * 4 + 0] - m0), ex2(s[k * 4 + 1] - m0));
                    p[k * 2 + 1] = pack_bf16(ex2(s[k * 4 + 2] - m1), ex2(s[k * 4 + 3] - m1));
                }
                reg_fence(p);
                reg_fence(o);
                wg_fence();
                issue_pv(o, p, dv, t);
                wg_commit();
            }
            wg_wait<0>();
            reg_fence(o);
        }
        const float l0 = __shfl_sync(~0u, o[8], (lane & ~3) | 3), l1 = __shfl_sync(~0u, o[10], (lane & ~3) | 3);
        const float i0 = 1.0f / l0, i1 = 1.0f / l1;
        uint32_t* op0 = reinterpret_cast<uint32_t*>(g_O + (size_t)(row0 + g) * DM + head * DH);
        uint32_t* op1 = reinterpret_cast<uint32_t*>(g_O + (size_t)(row0 + g + 8) * DM + head * DH);
        op0[q] = pack_bf16(o[0] * i0, o[1] * i0);
        op1[q] = pack_bf16(o[2] * i1, o[3] * i1);
        op0[4 + q] = pack_bf16(o[4] * i0, o[5] * i0);
        op1[4 + q] = pack_bf16(o[6] * i1, o[7] * i1);
        if (q == 2) {
            op0[8] = pack_bf16(o[8] * i0, o[9] * i0);
            op1[8] = pack_bf16(o[10] * i1, o[11] * i1);
        }
    }
}

constexpr int K3_OFF_B = 9 * 16384;
constexpr int K3_OFF_BAR = K3_OFF_B + 9 * 8192;
constexpr int K3_SMEM = K3_OFF_BAR + 128;

__global__ void __launch_bounds__(256, 1)
k3_kernel(const __grid_constant__ CUtensorMap tmO, const __grid_constant__ CUtensorMap tmWo, const __nv_bfloat16* __restrict__ x,
          const __nv_bfloat16* __restrict__ b2, __nv_bfloat16* __restrict__ out) {
    extern __shared__ __align__(1024) uint8_t smem[];
    const uint32_t sb = s2u(smem);
    const int tid = threadIdx.x, warp = tid >> 5, lane = tid & 31;
    const int wg = warp >> 2, g = lane >> 2, q = lane & 3;
    const int rb = blockIdx.x / 9, t = blockIdx.x % 9;
    const uint32_t bar0 = sb + K3_OFF_BAR;
    if (tid == 0) {
        for (int i = 0; i < 9; i++) mbar_init(bar0 + i * 8, 1);
        fence_barrier_init();
    }
    __syncthreads();
    griddep_wait();
    if (warp == 0 && lane < 9) {
        mbar_expect(bar0 + lane * 8, 16384 + 8192);
        tma2d(sb + lane * 16384, &tmO, lane * 64, rb * 128, bar0 + lane * 8);
        tma2d(sb + K3_OFF_B + lane * 8192, &tmWo, t * 64, lane * 64, bar0 + lane * 8);
    }
    float acc[32];
    {
        const int r0 = rb * 128 + warp * 16 + g;
#pragma unroll
        for (int b = 0; b < 8; b++) {
            const int col = t * 64 + b * 8 + q * 2;
            const uint32_t bb = *reinterpret_cast<const uint32_t*>(b2 + col);
            const uint32_t x0 = *reinterpret_cast<const uint32_t*>(x + (size_t)r0 * DM + col);
            const uint32_t x1 = *reinterpret_cast<const uint32_t*>(x + (size_t)(r0 + 8) * DM + col);
            acc[b * 4 + 0] = bf_lo(x0) + bf_lo(bb); acc[b * 4 + 1] = bf_hi(x0) + bf_hi(bb);
            acc[b * 4 + 2] = bf_lo(x1) + bf_lo(bb); acc[b * 4 + 3] = bf_hi(x1) + bf_hi(bb);
        }
#pragma unroll
        for (int jj = 0; jj < 8; jj++) {
            const uint4* pp = g_part + ((size_t)(jj * 16 + rb) * 36 + t * 4) * 256 + tid;
#pragma unroll
            for (int s = 0; s < 4; s++) {
                const uint4 v = pp[s * 256];
                acc[s * 8 + 0] += bf_lo(v.x); acc[s * 8 + 1] += bf_hi(v.x); acc[s * 8 + 2] += bf_lo(v.y); acc[s * 8 + 3] += bf_hi(v.y);
                acc[s * 8 + 4] += bf_lo(v.z); acc[s * 8 + 5] += bf_hi(v.z); acc[s * 8 + 6] += bf_lo(v.w); acc[s * 8 + 7] += bf_hi(v.w);
            }
        }
    }
    const uint64_t da = mk_desc(sb + wg * 8192, 16, 1024, 1);
    const uint64_t db = mk_desc(sb + K3_OFF_B, 8192, 1024, 1);
#pragma unroll
    for (int kb = 0; kb < 9; kb++) {
        mbar_wait(bar0 + kb * 8, 0);
        wg_fence();
#pragma unroll
        for (int k = 0; k < 4; k++) wgmma_ss_n64<1>(acc, descA_step(da, kb * 4 + k), db + ((kb * 8192 + k * 2048) >> 4), 1);
        wg_commit();
    }
    wg_wait<0>();
    reg_fence(acc);
    const int r0 = rb * 128 + warp * 16 + g;
#pragma unroll
    for (int b = 0; b < 8; b++) {
        const int col = t * 64 + b * 8 + q * 2;
        *reinterpret_cast<uint32_t*>(out + (size_t)r0 * DM + col) = pack_bf16(acc[b * 4], acc[b * 4 + 1]);
        *reinterpret_cast<uint32_t*>(out + (size_t)(r0 + 8) * DM + col) = pack_bf16(acc[b * 4 + 2], acc[b * 4 + 3]);
    }
}

typedef CUresult (*EncodeFn)(CUtensorMap*, CUtensorMapDataType, cuuint32_t, void*, const cuuint64_t*, const cuuint64_t*, const cuuint32_t*,
                             const cuuint32_t*, CUtensorMapInterleave, CUtensorMapSwizzle, CUtensorMapL2promotion, CUtensorMapFloatOOBfill);

void make_map(EncodeFn fn, CUtensorMap* m, const void* base, int rank, const cuuint64_t* dims, const cuuint64_t* strides, const cuuint32_t* box) {
    cuuint32_t es[3] = {1, 1, 1};
    fn(m, CU_TENSOR_MAP_DATA_TYPE_BFLOAT16, rank, const_cast<void*>(base), dims, strides, box, es, CU_TENSOR_MAP_INTERLEAVE_NONE,
       CU_TENSOR_MAP_SWIZZLE_128B, CU_TENSOR_MAP_L2_PROMOTION_L2_256B, CU_TENSOR_MAP_FLOAT_OOB_FILL_NONE);
}

}

extern "C" void kernel_launch(void* const* d_in, const int* in_sizes, int n_in, void* d_out, int out_size) {
    const __nv_bfloat16* x = (const __nv_bfloat16*)d_in[0];
    const __nv_bfloat16* wqkv = (const __nv_bfloat16*)d_in[1];
    const __nv_bfloat16* wo = (const __nv_bfloat16*)d_in[2];
    const __nv_bfloat16* w1 = (const __nv_bfloat16*)d_in[4];
    const __nv_bfloat16* b1 = (const __nv_bfloat16*)d_in[5];
    const __nv_bfloat16* w2 = (const __nv_bfloat16*)d_in[6];
    const __nv_bfloat16* b2 = (const __nv_bfloat16*)d_in[7];
    __nv_bfloat16* out = (__nv_bfloat16*)d_out;

    EncodeFn fn = nullptr;
    cudaDriverEntryPointQueryResult qr;
    cudaGetDriverEntryPoint("cuTensorMapEncodeTiled", (void**)&fn, cudaEnableDefault, &qr);
    void* gO = nullptr;
    cudaGetSymbolAddress(&gO, g_O);
    CUtensorMap tmQ3, tmQ1, tm1a, tm1b, tm2, tmO, tmWo;
    {
        cuuint64_t d[3] = {3 * DM, DM, 3}, s[2] = {3 * DM * 2, 128};
        cuuint32_t b[3] = {64, 16, 3};
        make_map(fn, &tmQ3, wqkv, 3, d, s, b);
        make_map(fn, &tmQ1, wqkv, 2, d, s, b);
    }
    {
        cuuint64_t d[3] = {64, DM, FF / 64}, s[2] = {FF * 2, 128};
        cuuint32_t ba[3] = {64, 48, 1}, bb[3] = {64, 32, 2};
        make_map(fn, &tm1a, w1, 3, d, s, ba);
        make_map(fn, &tm1b, w1, 3, d, s, bb);
    }
    {
        cuuint64_t d[2] = {DM, FF}, s[1] = {DM * 2};
        cuuint32_t b[2] = {64, 48};
        make_map(fn, &tm2, w2, 2, d, s, b);
    }
    {
        cuuint64_t d[2] = {DM, SEQ}, s[1] = {DM * 2};
        cuuint32_t b[2] = {64, 128};
        make_map(fn, &tmO, gO, 2, d, s, b);
        cuuint64_t d2[2] = {DM, DM};
        cuuint32_t b2x[2] = {64, 64};
        make_map(fn, &tmWo, wo, 2, d2, s, b2x);
    }
    cudaFuncSetAttribute(k1_kernel, cudaFuncAttributeMaxDynamicSharedMemorySize, K1_SMEM);
    cudaFuncSetAttribute(k2_kernel, cudaFuncAttributeMaxDynamicSharedMemorySize, K2_SMEM);
    cudaFuncSetAttribute(k3_kernel, cudaFuncAttributeMaxDynamicSharedMemorySize, K3_SMEM);

    cudaStream_t st = cudaStreamPerThread;
    cudaLaunchAttribute pdl[1];
    pdl[0].id = cudaLaunchAttributeProgrammaticStreamSerialization;
    pdl[0].val.programmaticStreamSerializationAllowed = 1;
    {
        cudaLaunchConfig_t cfg = {};
        cfg.gridDim = dim3(128); cfg.blockDim = dim3(384); cfg.dynamicSmemBytes = K1_SMEM; cfg.stream = st;
        cudaLaunchKernelEx(&cfg, k1_kernel, tmQ3, tmQ1, tm1a, tm1b, tm2, x, b1);
    }
    {
        cudaLaunchConfig_t cfg = {};
        cfg.gridDim = dim3(128); cfg.blockDim = dim3(512); cfg.dynamicSmemBytes = K2_SMEM; cfg.stream = st;
        cfg.attrs = pdl; cfg.numAttrs = 1;
        cudaLaunchKernelEx(&cfg, k2_kernel);
    }
    {
        cudaLaunchConfig_t cfg = {};
        cfg.gridDim = dim3(144); cfg.blockDim = dim3(256); cfg.dynamicSmemBytes = K3_SMEM; cfg.stream = st;
        cfg.attrs = pdl; cfg.numAttrs = 1;
        cudaLaunchKernelEx(&cfg, k3_kernel, tmO, tmWo, x, b2, out);
    }
}
```

```cpp
#include <cuda_runtime.h>
#include <cuda_bf16.h>
#include <cuda.h>
#include <stdint.h>

namespace {

constexpr int SEQ = 2048, DM = 576, FF = 4608, NH = 32, DH = 18;

constexpr int Q_GROUP_BYTES = 3 * 128, KV_GROUP_BYTES = 5 * 128;
constexpr int Q_HEAD_BYTES = (SEQ / 8) * Q_GROUP_BYTES, KV_HEAD_BYTES = (SEQ / 8) * KV_GROUP_BYTES;
__device__ __align__(1024) uint8_t g_Q[NH * Q_HEAD_BYTES];
__device__ __align__(1024) uint8_t g_KV[NH * KV_HEAD_BYTES];
__device__ __align__(1024) float g_kmax[NH * 128];
__device__ __align__(1024) uint4 g_part[8 * 16 * 36 * 256];
__device__ __align__(1024) __nv_bfloat16 g_O[SEQ * DM];

__device__ __forceinline__ uint32_t s2u(const void* p) { return (uint32_t)__cvta_generic_to_shared(p); }
__device__ __forceinline__ void mbar_init(uint32_t b, int c) { asm volatile("mbarrier.init.shared::cta.b64 [%0], %1;" ::"r"(b), "r"(c) : "memory"); }
__device__ __forceinline__ void mbar_expect(uint32_t b, uint32_t bytes) {
    asm volatile("mbarrier.arrive.expect_tx.shared::cta.b64 _, [%0], %1;" ::"r"(b), "r"(bytes) : "memory");
}
__device__ __forceinline__ void mbar_arrive_cluster(uint32_t local_bar, uint32_t cta) {
    asm volatile("{\n.reg .b32 ra;\nmapa.shared::cluster.u32 ra, %0, %1;\nmbarrier.arrive.shared::cluster.b64 _, [ra];\n}\n" ::"r"(local_bar), "r"(cta) : "memory");
}
__device__ __forceinline__ void mbar_wait(uint32_t b, uint32_t parity) {
    uint32_t ok;
    uint32_t spins = 0;
    do {
        asm volatile("{\n.reg .pred p;\nmbarrier.try_wait.parity.shared::cta.b64 p, [%1], %2;\nselp.u32 %0, 1, 0, p;\n}\n" : "=r"(ok) : "r"(b), "r"(parity) : "memory");
        if (!ok && ++spins > (1u << 22)) __trap();
    } while (!ok);
}
__device__ __forceinline__ void fence_barrier_init() { asm volatile("fence.mbarrier_init.release.cluster;" ::: "memory"); }
__device__ __forceinline__ void fence_proxy_async() { asm volatile("fence.proxy.async.shared::cta;" ::: "memory"); }
__device__ __forceinline__ void cluster_arrive() { asm volatile("barrier.cluster.arrive.relaxed.aligned;" ::: "memory"); }
__device__ __forceinline__ void cluster_wait() { asm volatile("barrier.cluster.wait.aligned;" ::: "memory"); }
__device__ __forceinline__ void named_bar_sync(int id, int n) { asm volatile("bar.sync %0, %1;" ::"r"(id), "r"(n) : "memory"); }
__device__ __forceinline__ void griddep_wait() { asm volatile("griddepcontrol.wait;" ::: "memory"); }
__device__ __forceinline__ void griddep_launch() { asm volatile("griddepcontrol.launch_dependents;" ::: "memory"); }

__device__ __forceinline__ void tma3d_mc(uint32_t dst, const CUtensorMap* tm, int c0, int c1, int c2, uint32_t bar, uint16_t mask) {
    asm volatile("cp.async.bulk.tensor.3d.shared::cluster.global.mbarrier::complete_tx::bytes.multicast::cluster [%0], [%1, {%3, %4, %5}], [%2], %6;"
                 ::"r"(dst), "l"(tm), "r"(bar), "r"(c0), "r"(c1), "r"(c2), "h"(mask) : "memory");
}
__device__ __forceinline__ void tma2d_mc(uint32_t dst, const CUtensorMap* tm, int c0, int c1, uint32_t bar, uint16_t mask) {
    asm volatile("cp.async.bulk.tensor.2d.shared::cluster.global.mbarrier::complete_tx::bytes.multicast::cluster [%0], [%1, {%3, %4}], [%2], %5;"
                 ::"r"(dst), "l"(tm), "r"(bar), "r"(c0), "r"(c1), "h"(mask) : "memory");
}
__device__ __forceinline__ void tma2d(uint32_t dst, const CUtensorMap* tm, int c0, int c1, uint32_t bar) {
    asm volatile("cp.async.bulk.tensor.2d.shared::cluster.global.mbarrier::complete_tx::bytes [%0], [%1, {%3, %4}], [%2];"
                 ::"r"(dst), "l"(tm), "r"(bar), "r"(c0), "r"(c1) : "memory");
}
__device__ __forceinline__ void bulk_load(uint32_t dst, const void* src, uint32_t bytes, uint32_t bar) {
    asm volatile("cp.async.bulk.shared::cluster.global.mbarrier::complete_tx::bytes [%0], [%1], %2, [%3];"
                 ::"r"(dst), "l"(src), "r"(bytes), "r"(bar) : "memory");
}
__device__ __forceinline__ void prefetch_tmap(const CUtensorMap* tm) { asm volatile("prefetch.tensormap [%0];" ::"l"(tm) : "memory"); }

__device__ __forceinline__ void wg_fence() { asm volatile("wgmma.fence.sync.aligned;" ::: "memory"); }
__device__ __forceinline__ void wg_commit() { asm volatile("wgmma.commit_group.sync.aligned;" ::: "memory"); }
template <int N> __device__ __forceinline__ void wg_wait() { asm volatile("wgmma.wait_group.sync.aligned %0;" ::"n"(N) : "memory"); }
template <int N> __device__ __forceinline__ void reg_fence(float (&d)[N]) {
#pragma unroll
    for (int i = 0; i < N; i++) asm volatile("" : "+f"(d[i])::"memory");
}
template <int N> __device__ __forceinline__ void reg_fence(uint32_t (&d)[N]) {
#pragma unroll
    for (int i = 0; i < N; i++) asm volatile("" : "+r"(d[i])::"memory");
}
template <int R> __device__ __forceinline__ void reg_alloc() { asm volatile("setmaxnreg.inc.sync.aligned.u32 %0;" ::"n"(R)); }
template <int R> __device__ __forceinline__ void reg_dealloc() { asm volatile("setmaxnreg.dec.sync.aligned.u32 %0;" ::"n"(R)); }

__device__ __forceinline__ uint64_t mk_desc(uint32_t addr, uint32_t lbo, uint32_t sbo, uint32_t swz) {
    return (uint64_t)((addr & 0x3FFFF) >> 4) | ((uint64_t)(lbo >> 4) << 16) | ((uint64_t)(sbo >> 4) << 32) | ((uint64_t)swz << 62);
}
__device__ __forceinline__ uint32_t pack_bf16(float lo, float hi) {
    uint32_t r;
    asm("cvt.rn.bf16x2.f32 %0, %1, %2;" : "=r"(r) : "f"(hi), "f"(lo));
    return r;
}
__device__ __forceinline__ float bf_lo(uint32_t w) { return __uint_as_float(w << 16); }
__device__ __forceinline__ float bf_hi(uint32_t w) { return __uint_as_float(w & 0xFFFF0000u); }
__device__ __forceinline__ float ex2(float x) {
    float r;
    asm("ex2.approx.ftz.f32 %0, %1;" : "=f"(r) : "f"(x));
    return r;
}
__device__ __forceinline__ float tanh_fast(float x) {
    float r;
    asm("tanh.approx.f32 %0, %1;" : "=f"(r) : "f"(x));
    return r;
}
__device__ __forceinline__ float gelu_tanh(float u) {
    float w = fmaf(u * u, 0.0356774081f, 0.7978845608f);
    float t = tanh_fast(u * w);
    float h = 0.5f * u;
    return fmaf(h, t, h);
}

template<int TB> __device__ __forceinline__ void wgmma_ss_n216(float (&d)[108], uint64_t da, uint64_t db, int sd) {
    asm volatile("{\n.reg .pred p;\nsetp.ne.b32 p, %110, 0;\n"
      "wgmma.mma_async.sync.aligned.m64n216k16.f32.bf16.bf16 {%0, %1, %2, %3, %4, %5, %6, %7, %8, %9, %10, %11, %12, %13, %14, %15, %16, %17, %18, %19, %20, %21, %22, %23, %24, %25, %26, %27, %28, %29, %30, %31, %32, %33, %34, %35, %36, %37, %38, %39, %40, %41, %42, %43, %44, %45, %46, %47, %48, %49, %50, %51, %52, %53, %54, %55, %56, %57, %58, %59, %60, %61, %62, %63, %64, %65, %66, %67, %68, %69, %70, %71, %72, %73, %74, %75, %76, %77, %78, %79, %80, %81, %82, %83, %84, %85, %86, %87, %88, %89, %90, %91, %92, %93, %94, %95, %96, %97, %98, %99, %100, %101, %102, %103, %104, %105, %106, %107}, %108, %109, p, 1, 1, 0, %111;\n}\n"
      : "+f"(d[0]), "+f"(d[1]), "+f"(d[2]), "+f"(d[3]), "+f"(d[4]), "+f"(d[5]), "+f"(d[6]), "+f"(d[7]), "+f"(d[8]), "+f"(d[9]), "+f"(d[10]), "+f"(d[11]), "+f"(d[12]), "+f"(d[13]), "+f"(d[14]), "+f"(d[15]), "+f"(d[16]), "+f"(d[17]), "+f"(d[18]), "+f"(d[19]), "+f"(d[20]), "+f"(d[21]), "+f"(d[22]), "+f"(d[23]), "+f"(d[24]), "+f"(d[25]), "+f"(d[26]), "+f"(d[27]), "+f"(d[28]), "+f"(d[29]), "+f"(d[30]), "+f"(d[31]), "+f"(d[32]), "+f"(d[33]), "+f"(d[34]), "+f"(d[35]), "+f"(d[36]), "+f"(d[37]), "+f"(d[38]), "+f"(d[39]), "+f"(d[40]), "+f"(d[41]), "+f"(d[42]), "+f"(d[43]), "+f"(d[44]), "+f"(d[45]), "+f"(d[46]), "+f"(d[47]), "+f"(d[48]), "+f"(d[49]), "+f"(d[50]), "+f"(d[51]), "+f"(d[52]), "+f"(d[53]), "+f"(d[54]), "+f"(d[55]), "+f"(d[56]), "+f"(d[57]), "+f"(d[58]), "+f"(d[59]), "+f"(d[60]), "+f"(d[61]), "+f"(d[62]), "+f"(d[63]), "+f"(d[64]), "+f"(d[65]), "+f"(d[66]), "+f"(d[67]), "+f"(d[68]), "+f"(d[69]), "+f"(d[70]), "+f"(d[71]), "+f"(d[72]), "+f"(d[73]), "+f"(d[74]), "+f"(d[75]), "+f"(d[76]), "+f"(d[77]), "+f"(d[78]), "+f"(d[79]), "+f"(d[80]), "+f"(d[81]), "+f"(d[82]), "+f"(d[83]), "+f"(d[84]), "+f"(d[85]), "+f"(d[86]), "+f"(d[87]), "+f"(d[88]), "+f"(d[89]), "+f"(d[90]), "+f"(d[91]), "+f"(d[92]), "+f"(d[93]), "+f"(d[94]), "+f"(d[95]), "+f"(d[96]), "+f"(d[97]), "+f"(d[98]), "+f"(d[99]), "+f"(d[100]), "+f"(d[101]), "+f"(d[102]), "+f"(d[103]), "+f"(d[104]), "+f"(d[105]), "+f"(d[106]), "+f"(d[107])
      : "l"(da), "l"(db), "r"(sd), "n"(TB));
}

template<int TB> __device__ __forceinline__ void wgmma_ss_n128(float (&d)[64], uint64_t da, uint64_t db, int sd) {
    asm volatile("{\n.reg .pred p;\nsetp.ne.b32 p, %66, 0;\n"
      "wgmma.mma_async.sync.aligned.m64n128k16.f32.bf16.bf16 {%0, %1, %2, %3, %4, %5, %6, %7, %8, %9, %10, %11, %12, %13, %14, %15, %16, %17, %18, %19, %20, %21, %22, %23, %24, %25, %26, %27, %28, %29, %30, %31, %32, %33, %34, %35, %36, %37, %38, %39, %40, %41, %42, %43, %44, %45, %46, %47, %48, %49, %50, %51, %52, %53, %54, %55, %56, %57, %58, %59, %60, %61, %62, %63}, %64, %65, p, 1, 1, 0, %67;\n}\n"
      : "+f"(d[0]), "+f"(d[1]), "+f"(d[2]), "+f"(d[3]), "+f"(d[4]), "+f"(d[5]), "+f"(d[6]), "+f"(d[7]), "+f"(d[8]), "+f"(d[9]), "+f"(d[10]), "+f"(d[11]), "+f"(d[12]), "+f"(d[13]), "+f"(d[14]), "+f"(d[15]), "+f"(d[16]), "+f"(d[17]), "+f"(d[18]), "+f"(d[19]), "+f"(d[20]), "+f"(d[21]), "+f"(d[22]), "+f"(d[23]), "+f"(d[24]), "+f"(d[25]), "+f"(d[26]), "+f"(d[27]), "+f"(d[28]), "+f"(d[29]), "+f"(d[30]), "+f"(d[31]), "+f"(d[32]), "+f"(d[33]), "+f"(d[34]), "+f"(d[35]), "+f"(d[36]), "+f"(d[37]), "+f"(d[38]), "+f"(d[39]), "+f"(d[40]), "+f"(d[41]), "+f"(d[42]), "+f"(d[43]), "+f"(d[44]), "+f"(d[45]), "+f"(d[46]), "+f"(d[47]), "+f"(d[48]), "+f"(d[49]), "+f"(d[50]), "+f"(d[51]), "+f"(d[52]), "+f"(d[53]), "+f"(d[54]), "+f"(d[55]), "+f"(d[56]), "+f"(d[57]), "+f"(d[58]), "+f"(d[59]), "+f"(d[60]), "+f"(d[61]), "+f"(d[62]), "+f"(d[63])
      : "l"(da), "l"(db), "r"(sd), "n"(TB));
}

template<int TB> __device__ __forceinline__ void wgmma_ss_n64(float (&d)[32], uint64_t da, uint64_t db, int sd) {
    asm volatile("{\n.reg .pred p;\nsetp.ne.b32 p, %34, 0;\n"
      "wgmma.mma_async.sync.aligned.m64n64k16.f32.bf16.bf16 {%0, %1, %2, %3, %4, %5, %6, %7, %8, %9, %10, %11, %12, %13, %14, %15, %16, %17, %18, %19, %20, %21, %22, %23, %24, %25, %26, %27, %28, %29, %30, %31}, %32, %33, p, 1, 1, 0, %35;\n}\n"
      : "+f"(d[0]), "+f"(d[1]), "+f"(d[2]), "+f"(d[3]), "+f"(d[4]), "+f"(d[5]), "+f"(d[6]), "+f"(d[7]), "+f"(d[8]), "+f"(d[9]), "+f"(d[10]), "+f"(d[11]), "+f"(d[12]), "+f"(d[13]), "+f"(d[14]), "+f"(d[15]), "+f"(d[16]), "+f"(d[17]), "+f"(d[18]), "+f"(d[19]), "+f"(d[20]), "+f"(d[21]), "+f"(d[22]), "+f"(d[23]), "+f"(d[24]), "+f"(d[25]), "+f"(d[26]), "+f"(d[27]), "+f"(d[28]), "+f"(d[29]), "+f"(d[30]), "+f"(d[31])
      : "l"(da), "l"(db), "r"(sd), "n"(TB));
}

template<int TB> __device__ __forceinline__ void wgmma_rs_n64(float (&d)[32], uint32_t a0, uint32_t a1, uint32_t a2, uint32_t a3, uint64_t db, int sd) {
    asm volatile("{\n.reg .pred p;\nsetp.ne.b32 p, %37, 0;\n"
      "wgmma.mma_async.sync.aligned.m64n64k16.f32.bf16.bf16 {%0, %1, %2, %3, %4, %5, %6, %7, %8, %9, %10, %11, %12, %13, %14, %15, %16, %17, %18, %19, %20, %21, %22, %23, %24, %25, %26, %27, %28, %29, %30, %31}, {%32, %33, %34, %35}, %36, p, 1, 1, %38;\n}\n"
      : "+f"(d[0]), "+f"(d[1]), "+f"(d[2]), "+f"(d[3]), "+f"(d[4]), "+f"(d[5]), "+f"(d[6]), "+f"(d[7]), "+f"(d[8]), "+f"(d[9]), "+f"(d[10]), "+f"(d[11]), "+f"(d[12]), "+f"(d[13]), "+f"(d[14]), "+f"(d[15]), "+f"(d[16]), "+f"(d[17]), "+f"(d[18]), "+f"(d[19]), "+f"(d[20]), "+f"(d[21]), "+f"(d[22]), "+f"(d[23]), "+f"(d[24]), "+f"(d[25]), "+f"(d[26]), "+f"(d[27]), "+f"(d[28]), "+f"(d[29]), "+f"(d[30]), "+f"(d[31])
      : "r"(a0), "r"(a1), "r"(a2), "r"(a3), "l"(db), "r"(sd), "n"(TB));
}

template<int TB> __device__ __forceinline__ void wgmma_rs_n24(float (&d)[12], uint32_t a0, uint32_t a1, uint32_t a2, uint32_t a3, uint64_t db, int sd) {
    asm volatile("{\n.reg .pred p;\nsetp.ne.b32 p, %17, 0;\n"
      "wgmma.mma_async.sync.aligned.m64n24k16.f32.bf16.bf16 {%0, %1, %2, %3, %4, %5, %6, %7, %8, %9, %10, %11}, {%12, %13, %14, %15}, %16, p, 1, 1, %18;\n}\n"
      : "+f"(d[0]), "+f"(d[1]), "+f"(d[2]), "+f"(d[3]), "+f"(d[4]), "+f"(d[5]), "+f"(d[6]), "+f"(d[7]), "+f"(d[8]), "+f"(d[9]), "+f"(d[10]), "+f"(d[11])
      : "r"(a0), "r"(a1), "r"(a2), "r"(a3), "l"(db), "r"(sd), "n"(TB));
}


constexpr int K1_XN_BYTES = 9 * 16384;
constexpr int K1_SLOT = 16384, K1_NSLOT = 5;
constexpr int K1_OFF_RING = K1_XN_BYTES;
constexpr int K1_OFF_BIAS = K1_OFF_RING + K1_NSLOT * K1_SLOT;
constexpr int K1_OFF_BAR = K1_OFF_BIAS + 576 * 4;
constexpr int K1_SMEM = K1_OFF_BAR + 128;
constexpr float QSCALE = 0.23570226039551584f * 1.4426950408889634f;

struct Ring {
    uint32_t slot, phase;
    __device__ __forceinline__ void advance() {
        if (++slot == K1_NSLOT) { slot = 0; phase ^= 1; }
    }
};

struct K1Ctx {
    uint32_t full0, empty0;
    uint32_t ring0;
    uint64_t descA;
    Ring rd;
    uint32_t prev_slot;
    bool rel_thread;
    uint32_t rel_cta;
    __device__ __forceinline__ void release_prev() {
        if (rel_thread && prev_slot != 0xFFFFFFFFu) mbar_arrive_cluster(empty0 + prev_slot * 8, rel_cta);
    }
};

__device__ __forceinline__ uint64_t descA_step(uint64_t base, int ks) { return base + (uint64_t)(((ks >> 2) * 16384 + (ks & 3) * 32) >> 4); }

template <int V> struct IC { static constexpr int value = V; };
template <int I, int N, class F> __device__ __forceinline__ void static_for(F&& f) {
    if constexpr (I < N) { f(IC<I>{}); static_for<I + 1, N>(f); }
}

template <int N, int KS, int NST, int HALF_STRIDE, int LBO, class Epi>
__device__ __forceinline__ void tile_ss(K1Ctx& c, float (&acc)[N / 2], Epi&& epi) {
    static_for<0, NST>([&](auto sc) {
        constexpr int s = decltype(sc)::value;
        mbar_wait(c.full0 + c.rd.slot * 8, c.rd.phase);
        uint64_t db = mk_desc(c.ring0 + c.rd.slot * K1_SLOT, LBO, 1024, 1);
        wg_fence();
#pragma unroll
        for (int t = 0; t < KS; t++) {
            const int off = (t / (KS / 2)) * HALF_STRIDE + (t % (KS / 2)) * 2048;
            uint64_t da = descA_step(c.descA, s * KS + t);
            if constexpr (N == 216) wgmma_ss_n216<1>(acc, da, db + (off >> 4), (s | t) != 0);
            if constexpr (N == 64) wgmma_ss_n64<1>(acc, da, db + (off >> 4), (s | t) != 0);
            if constexpr (N == 128) wgmma_ss_n128<1>(acc, da, db + (off >> 4), (s | t) != 0);
        }
        wg_commit();
        wg_wait<1>();
        c.release_prev();
        c.prev_slot = c.rd.slot;
        c.rd.advance();
        epi(sc);
    });
}

template <class Epi>
__device__ __forceinline__ void tile_rs(K1Ctx& c, float (&acc)[32], uint32_t (&h)[144], Epi&& epi) {
    static_for<0, 6>([&](auto sc) {
        constexpr int s = decltype(sc)::value;
        mbar_wait(c.full0 + c.rd.slot * 8, c.rd.phase);
        uint64_t db = mk_desc(c.ring0 + c.rd.slot * K1_SLOT, 8192, 1024, 1);
        wg_fence();
#pragma unroll
        for (int t = 0; t < 6; t++) {
            const int ks = s * 6 + t;
            wgmma_rs_n64<1>(acc, h[ks * 4], h[ks * 4 + 1], h[ks * 4 + 2], h[ks * 4 + 3], db + ((t * 2048) >> 4), (s | t) != 0);
        }
        wg_commit();
        wg_wait<1>();
        c.release_prev();
        c.prev_slot = c.rd.slot;
        c.rd.advance();
        epi(sc);
    });
}

template <int N, int B0, int NB, int HOFF>
__device__ __forceinline__ void gelu_blocks(const float (&acc)[N / 2], uint32_t (&h)[144], const float* bias  ) {
#pragma unroll
    for (int b = B0; b < B0 + NB; b++) {
        float2 bb = *reinterpret_cast<const float2*>(bias + b * 8);
        float v0 = gelu_tanh(acc[b * 4 + 0] + bb.x), v1 = gelu_tanh(acc[b * 4 + 1] + bb.y);
        float v2 = gelu_tanh(acc[b * 4 + 2] + bb.x), v3 = gelu_tanh(acc[b * 4 + 3] + bb.y);
        h[HOFF + b * 2 + 0] = pack_bf16(v0, v1);
        h[HOFF + b * 2 + 1] = pack_bf16(v2, v3);
    }
}

__global__ void __cluster_dims__(2, 1, 1) __launch_bounds__(384, 1)
k1_kernel(const __grid_constant__ CUtensorMap tmQ3, const __grid_constant__ CUtensorMap tmQ1, const __grid_constant__ CUtensorMap tm1a,
          const __grid_constant__ CUtensorMap tm1b, const __grid_constant__ CUtensorMap tm2, const __nv_bfloat16* __restrict__ x,
          const __nv_bfloat16* __restrict__ b1) {
    extern __shared__ __align__(1024) uint8_t smem[];
    const uint32_t sb = s2u(smem);
    const int tid = threadIdx.x, warp = tid >> 5, lane = tid & 31;
    const uint32_t rank = blockIdx.x & 1;
    const int cl = blockIdx.x >> 1;
    const int rb = (cl & 7) * 2 + rank;
    const int j = cl >> 3;
    const uint32_t full0 = sb + K1_OFF_BAR, empty0 = full0 + 8 * K1_NSLOT;

    if (warp < 8) {
        reg_alloc<240>();
        uint4 xv[4][9];
        const int sub = lane >> 3, l8 = lane & 7;
        {
            const uint4* xp = reinterpret_cast<const uint4*>(x + (size_t)(rb * 128 + warp * 16 + sub) * DM) + l8;
#pragma unroll
            for (int p = 0; p < 4; p++)
#pragma unroll
                for (int i = 0; i < 9; i++) xv[p][i] = __ldg(xp + p * 4 * (DM / 8) + i * 8);
        }
        cluster_arrive();
#pragma unroll
        for (int p = 0; p < 4; p++) {
            float f[72];
#pragma unroll
            for (int i = 0; i < 9; i++) {
                f[i * 8 + 0] = bf_lo(xv[p][i].x); f[i * 8 + 1] = bf_hi(xv[p][i].x);
                f[i * 8 + 2] = bf_lo(xv[p][i].y); f[i * 8 + 3] = bf_hi(xv[p][i].y);
                f[i * 8 + 4] = bf_lo(xv[p][i].z); f[i * 8 + 5] = bf_hi(xv[p][i].z);
                f[i * 8 + 6] = bf_lo(xv[p][i].w); f[i * 8 + 7] = bf_hi(xv[p][i].w);
            }
            float s0 = 0.f, s1 = 0.f, s2 = 0.f, s3 = 0.f;
#pragma unroll
            for (int i = 0; i < 72; i += 4) { s0 += f[i]; s1 += f[i + 1]; s2 += f[i + 2]; s3 += f[i + 3]; }
            float sm = (s0 + s1) + (s2 + s3);
            sm += __shfl_xor_sync(~0u, sm, 1); sm += __shfl_xor_sync(~0u, sm, 2); sm += __shfl_xor_sync(~0u, sm, 4);
            const float mean = sm * (1.0f / DM);
            s0 = s1 = s2 = s3 = 0.f;
#pragma unroll
            for (int i = 0; i < 72; i += 4) {
                f[i] -= mean; f[i + 1] -= mean; f[i + 2] -= mean; f[i + 3] -= mean;
                s0 = fmaf(f[i], f[i], s0); s1 = fmaf(f[i + 1], f[i + 1], s1);
                s2 = fmaf(f[i + 2], f[i + 2], s2); s3 = fmaf(f[i + 3], f[i + 3], s3);
            }
            float sq = (s0 + s1) + (s2 + s3);
            sq += __shfl_xor_sync(~0u, sq, 1); sq += __shfl_xor_sync(~0u, sq, 2); sq += __shfl_xor_sync(~0u, sq, 4);
            const float rstd = rsqrtf(sq * (1.0f / DM) + 1e-5f);
            const int r = warp * 16 + p * 4 + sub;
            uint8_t* dst = smem + r * 128 + ((l8 ^ (r & 7)) << 4);
#pragma unroll
            for (int i = 0; i < 9; i++) {
                uint4 o;
                o.x = pack_bf16(f[i * 8 + 0] * rstd, f[i * 8 + 1] * rstd);
                o.y = pack_bf16(f[i * 8 + 2] * rstd, f[i * 8 + 3] * rstd);
                o.z = pack_bf16(f[i * 8 + 4] * rstd, f[i * 8 + 5] * rstd);
                o.w = pack_bf16(f[i * 8 + 6] * rstd, f[i * 8 + 7] * rstd);
                *reinterpret_cast<uint4*>(dst + i * 16384) = o;
            }
        }
        float* sbias = reinterpret_cast<float*>(smem + K1_OFF_BIAS);
        for (int i = tid; i < 576; i += 256) sbias[i] = __bfloat162float(b1[j * 576 + i]);
        fence_proxy_async();
        named_bar_sync(1, 256);
        cluster_wait();

        const int wg = warp >> 2, wq = warp & 3;
        const int g = lane >> 2, q = lane & 3;
        K1Ctx c;
        c.full0 = full0; c.empty0 = empty0; c.ring0 = sb + K1_OFF_RING;
        c.descA = mk_desc(sb + wg * 8192, 16, 1024, 1);
        c.rd.slot = 0; c.rd.phase = 0; c.prev_slot = 0xFFFFFFFFu;
        c.rel_thread = (lane == 0) && (wq < 2);
        c.rel_cta = wq;
        const float* biasq = sbias + 2 * q;

        uint32_t h[144];
        float accX[64], accY[64];
        {
            float accQ[108];
            tile_ss<216, 2, 18, 8192, 2048>(c, accQ, [&](auto) {});
            const int grp0 = rb * 16 + warp * 2;
            float nrm[2][4];
            uint8_t* gbase = nullptr;
            uint32_t hstride = 0, gstride = 0, o2 = 0;
            float scl0 = 1.f, scl1 = 1.f;
            int type = 0, head0 = 0;
            tile_ss<128, 4, 9, 8192, 4096>(c, accX, [&](auto sc) {
                constexpr int s = decltype(sc)::value;
                if constexpr (s == 0) reg_fence(accQ);
                constexpr int grp = s / 3, part = s % 3;
                if constexpr (part == 0) {
                    const int G = 3 * j + grp;
                    type = G >> 3;
                    head0 = (G & 7) * 4;
                    if (type == 0) {
                        gbase = g_Q + (size_t)head0 * Q_HEAD_BYTES + grp0 * Q_GROUP_BYTES + g * 16;
                        hstride = Q_HEAD_BYTES; gstride = Q_GROUP_BYTES; o2 = 256;
                        scl0 = QSCALE; scl1 = QSCALE;
                    } else {
                        gbase = g_KV + (size_t)head0 * KV_HEAD_BYTES + grp0 * KV_GROUP_BYTES + g * 16 + (type == 2 ? 256 : 0);
                        hstride = KV_HEAD_BYTES; gstride = KV_GROUP_BYTES; o2 = (type == 2) ? 256 + 8 : 512;
                        scl0 = 1.f; scl1 = (type == 1) ? 2.f : 1.f;
                    }
#pragma unroll
                    for (int i = 0; i < 4; i++) { nrm[0][i] = 0.f; nrm[1][i] = 0.f; }
                }
#pragma unroll
                for (int i9 = part * 3; i9 < part * 3 + 3; i9++) {
                    const int b = grp * 9 + i9;
                    const int p = 4 * i9 + q;
                    const int hlo = (4 * i9) / 9;
                    const bool up = (p >= 9 * (hlo + 1));
                    const int hh = hlo + (up ? 1 : 0);
                    const int r = p - 9 * hh;
                    const uint32_t off = hh * hstride + (r < 4 ? r * 4 : (r < 8 ? 112 + r * 4 : o2));
                    const float a0 = accQ[b * 4], a1 = accQ[b * 4 + 1], a2 = accQ[b * 4 + 2], a3 = accQ[b * 4 + 3];
                    *reinterpret_cast<uint32_t*>(gbase + off) = pack_bf16(a0 * scl0, a1 * scl0);
                    *reinterpret_cast<uint32_t*>(gbase + off + gstride) = pack_bf16(a2 * scl1, a3 * scl1);
                    if (r == 8 && type != 0) {
                        *reinterpret_cast<uint32_t*>(gbase + off + 4) = 0x00003F80u;
                        *reinterpret_cast<uint32_t*>(gbase + off + gstride + 4) = (type == 1) ? 0x3F804000u : 0x00003F80u;
                    }
                    const float e0 = fmaf(a0, a0, a1 * a1), e1 = fmaf(a2, a2, a3 * a3);
                    if ((4 * i9 + 3) / 9 == hlo) {
                        nrm[0][hlo] += e0; nrm[1][hlo] += e1;
                    } else {
                        nrm[0][hlo] += up ? 0.f : e0; nrm[1][hlo] += up ? 0.f : e1;
                        nrm[0][(hlo + 1) & 3] += up ? e0 : 0.f; nrm[1][(hlo + 1) & 3] += up ? e1 : 0.f;
                    }
                }
                if constexpr (part == 2) {
                    if (type == 1) {
#pragma unroll
                        for (int i = 0; i < 4; i++) {
                            float u0 = nrm[0][i], u1 = nrm[1][i];
                            u0 += __shfl_xor_sync(~0u, u0, 1); u1 += __shfl_xor_sync(~0u, u1, 1);
                            u0 += __shfl_xor_sync(~0u, u0, 2); u1 += __shfl_xor_sync(~0u, u1, 2);
                            float m = fmaxf(u0, u1);
                            m = fmaxf(m, __shfl_xor_sync(~0u, m, 4));
                            m = fmaxf(m, __shfl_xor_sync(~0u, m, 8));
                            m = fmaxf(m, __shfl_xor_sync(~0u, m, 16));
                            if (lane == 0) g_kmax[(head0 + i) * 128 + rb * 8 + warp] = m;
                        }
                    }
                }
            });
        }
        tile_ss<128, 4, 9, 8192, 4096>(c, accY, [&](auto sc) {
            constexpr int s = decltype(sc)::value;
            if constexpr (s == 0) reg_fence(accX);
            if constexpr (s < 8) gelu_blocks<128, s * 2, 2, 0>(accX, h, biasq);
        });
        tile_ss<128, 4, 9, 8192, 4096>(c, accX, [&](auto sc) {
            constexpr int s = decltype(sc)::value;
            if constexpr (s == 0) reg_fence(accY);
            if constexpr (s < 8) gelu_blocks<128, s * 2, 2, 32>(accY, h, biasq + 128);
        });
        float o0[32], o1[32];
        tile_ss<64, 6, 6, 6144, 8192>(c, o0, [&](auto sc) {
            constexpr int s = decltype(sc)::value;
            if constexpr (s == 0) reg_fence(accX);
            if constexpr (s < 5) gelu_blocks<128, s * 3, 3, 64>(accX, h, biasq + 256);
            if constexpr (s == 5) gelu_blocks<128, 15, 1, 64>(accX, h, biasq + 256);
        });
        tile_ss<64, 6, 6, 6144, 8192>(c, o1, [&](auto sc) {
            constexpr int s = decltype(sc)::value;
            if constexpr (s == 0) reg_fence(o0);
            if constexpr (s < 4) gelu_blocks<64, s * 2, 2, 96>(o0, h, biasq + 384);
        });
        tile_ss<64, 6, 6, 6144, 8192>(c, o0, [&](auto sc) {
            constexpr int s = decltype(sc)::value;
            if constexpr (s == 0) reg_fence(o1);
            if constexpr (s < 4) gelu_blocks<64, s * 2, 2, 112>(o1, h, biasq + 448);
        });
        uint4* pout = g_part + ((size_t)(j * 16 + rb) * 36) * 256 + tid;
        auto store_part = [&](float (&o)[32], int t, auto sc) {
            constexpr int s = decltype(sc)::value;
            if constexpr (s == 0) reg_fence(o);
            if constexpr (s < 4) {
                uint4 v;
                v.x = pack_bf16(o[s * 8 + 0], o[s * 8 + 1]); v.y = pack_bf16(o[s * 8 + 2], o[s * 8 + 3]);
                v.z = pack_bf16(o[s * 8 + 4], o[s * 8 + 5]); v.w = pack_bf16(o[s * 8 + 6], o[s * 8 + 7]);
                pout[(t * 4 + s) * 256] = v;
            }
        };
        tile_rs(c, o1, h, [&](auto sc) {
            constexpr int s = decltype(sc)::value;
            if constexpr (s == 0) reg_fence(o0);
            if constexpr (s < 4) gelu_blocks<64, s * 2, 2, 128>(o0, h, biasq + 512);
            if constexpr (s == 4) reg_fence(h);
        });
#pragma unroll 1
        for (int t = 1; t < 9; t += 2) {
            tile_rs(c, o0, h, [&](auto sc) { store_part(o1, t - 1, sc); });
            tile_rs(c, o1, h, [&](auto sc) { store_part(o0, t, sc); });
        }
        wg_wait<0>();
        static_for<0, 4>([&](auto sc) { store_part(o1, 8, sc); });
        cluster_arrive();
        cluster_wait();
    } else {
        reg_dealloc<24>();
        if (warp == 8 && lane == 0) {
            prefetch_tmap(&tmQ3); prefetch_tmap(&tmQ1); prefetch_tmap(&tm1a); prefetch_tmap(&tm1b); prefetch_tmap(&tm2);
            for (int i = 0; i < K1_NSLOT; i++) { mbar_init(full0 + i * 8, 1); mbar_init(empty0 + i * 8, 4); }
            fence_barrier_init();
        }
        __syncwarp();
        cluster_arrive();
        cluster_wait();
        if (warp == 8 && lane == 0) {
            Ring w{0, 1};
            const uint32_t ring0 = sb + K1_OFF_RING;
            for (int s = 0; s < 18; s++) {
                mbar_wait(empty0 + w.slot * 8, w.phase);
                mbar_expect(full0 + w.slot * 8, 16384);
                const uint32_t dst = ring0 + w.slot * K1_SLOT + rank * 8192;
                tma3d_mc(dst, &tmQ3, j * 216, s * 32 + rank * 16, 0, full0 + w.slot * 8, 3);
                tma2d_mc(dst + 6144, &tmQ1, j * 216 + 192, s * 32 + rank * 16, full0 + w.slot * 8, 3);
                w.advance();
            }
            for (int t = 0; t < 3; t++)
                for (int s = 0; s < 9; s++) {
                    mbar_wait(empty0 + w.slot * 8, w.phase);
                    mbar_expect(full0 + w.slot * 8, 16384);
                    tma3d_mc(ring0 + w.slot * K1_SLOT + rank * 8192, &tm1b, 0, s * 64 + rank * 32, j * 9 + t * 2, full0 + w.slot * 8, 3);
                    w.advance();
                }
            for (int t = 0; t < 3; t++)
                for (int s = 0; s < 6; s++) {
                    mbar_wait(empty0 + w.slot * 8, w.phase);
                    mbar_expect(full0 + w.slot * 8, 12288);
                    tma3d_mc(ring0 + w.slot * K1_SLOT + rank * 6144, &tm1a, 0, s * 96 + rank * 48, j * 9 + 6 + t, full0 + w.slot * 8, 3);
                    w.advance();
                }
            for (int t = 0; t < 9; t++)
                for (int s = 0; s < 6; s++) {
                    mbar_wait(empty0 + w.slot * 8, w.phase);
                    mbar_expect(full0 + w.slot * 8, 12288);
                    tma2d_mc(ring0 + w.slot * K1_SLOT + rank * 6144, &tm2, t * 64, j * 576 + s * 96 + rank * 48, full0 + w.slot * 8, 3);
                    w.advance();
                }
        }
        __syncwarp();
        cluster_arrive();
        cluster_wait();
    }
}

constexpr int K2_NCHUNK = 16;
constexpr int K2_CHUNK_BYTES = KV_HEAD_BYTES / K2_NCHUNK;
constexpr int K2_OFF_BAR = KV_HEAD_BYTES;
constexpr int K2_SMEM = K2_OFF_BAR + 256;

__device__ __forceinline__ float exp2_fixed(float y) {
    const float u = __uint_as_float((__float_as_uint(y) & 0x7FFFu) | 0x44000000u) - 512.02545f;
    float t = fmaf(u, 0.019497588f, 0.114550486f);
    t = fmaf(t, u, -0.29839927f);
    return fmaf(t, u, y);
}
__device__ __forceinline__ uint32_t pack_fixed(float lo, float hi) { return __byte_perm(__float_as_uint(lo), __float_as_uint(hi), 0x6521); }

__device__ __forceinline__ void softmax_fast(const float (&s)[32], uint32_t (&p)[16]) {
#pragma unroll
    for (int k = 0; k < 4; k++) {
        p[k * 4 + 0] = pack_bf16(ex2(s[k * 8 + 0]), ex2(s[k * 8 + 1]));
        p[k * 4 + 1] = pack_bf16(ex2(s[k * 8 + 2]), ex2(s[k * 8 + 3]));
        p[k * 4 + 2] = pack_fixed(exp2_fixed(s[k * 8 + 4]), exp2_fixed(s[k * 8 + 5]));
        p[k * 4 + 3] = pack_fixed(exp2_fixed(s[k * 8 + 6]), exp2_fixed(s[k * 8 + 7]));
    }
}

__device__ __forceinline__ void issue_qk(float (&s)[32], const uint32_t (&qa)[8], uint64_t dk0, uint64_t dk1, int tile) {
    const uint64_t off = (uint64_t)(tile * (8 * KV_GROUP_BYTES / 16));
    wgmma_rs_n64<0>(s, qa[0], qa[1], qa[2], qa[3], dk0 + off, 0);
    wgmma_rs_n64<0>(s, qa[4], qa[5], qa[6], qa[7], dk1 + off, 1);
}
__device__ __forceinline__ void issue_pv(float (&o)[12], const uint32_t (&p)[16], uint64_t dv, int tile) {
    const uint64_t off = (uint64_t)(tile * (8 * KV_GROUP_BYTES / 16));
#pragma unroll
    for (int k = 0; k < 4; k++) wgmma_rs_n24<1>(o, p[k * 4], p[k * 4 + 1], p[k * 4 + 2], p[k * 4 + 3], dv + off + k * (2 * KV_GROUP_BYTES / 16), 1);
}

__global__ void __launch_bounds__(512, 1) k2_kernel() {
    extern __shared__ __align__(1024) uint8_t smem[];
    const uint32_t sb = s2u(smem);
    const int tid = threadIdx.x, warp = tid >> 5, lane = tid & 31;
    const int wg = warp >> 2, wq = warp & 3, g = lane >> 2, q = lane & 3;
    const int head = blockIdx.x >> 2, quarter = blockIdx.x & 3;
    const uint32_t bar0 = sb + K2_OFF_BAR;
    if (tid == 0) {
        for (int i = 0; i < K2_NCHUNK; i++) mbar_init(bar0 + i * 8, 1);
        fence_barrier_init();
    }
    __syncthreads();
    griddep_wait();
    if (warp == 0 && lane < K2_NCHUNK) {
        mbar_expect(bar0 + lane * 8, K2_CHUNK_BYTES);
        bulk_load(sb + lane * K2_CHUNK_BYTES, g_KV + (size_t)head * KV_HEAD_BYTES + lane * K2_CHUNK_BYTES, K2_CHUNK_BYTES, bar0 + lane * 8);
    }
    float kmax2;
    {
        const float4 v = *reinterpret_cast<const float4*>(g_kmax + head * 128 + lane * 4);
        kmax2 = fmaxf(fmaxf(v.x, v.y), fmaxf(v.z, v.w));
#pragma unroll
        for (int o = 16; o; o >>= 1) kmax2 = fmaxf(kmax2, __shfl_xor_sync(~0u, kmax2, o));
    }
    const uint64_t dk0 = mk_desc(sb, 128, KV_GROUP_BYTES, 0);
    const uint64_t dk1 = mk_desc(sb + 512, 0, KV_GROUP_BYTES, 0);
    const uint64_t dv = mk_desc(sb + 256, KV_GROUP_BYTES, 128, 0);

#pragma unroll 1
    for (int pass = 0; pass < 2; pass++) {
        const int row0 = quarter * 512 + (pass * 4 + wg) * 64 + wq * 16;
        uint32_t qa[8];
        {
            const uint8_t* qp = g_Q + (size_t)head * Q_HEAD_BYTES + (row0 >> 3) * Q_GROUP_BYTES + g * 16 + q * 4;
            qa[0] = *reinterpret_cast<const uint32_t*>(qp);
            qa[1] = *reinterpret_cast<const uint32_t*>(qp + Q_GROUP_BYTES);
            qa[2] = *reinterpret_cast<const uint32_t*>(qp + 128);
            qa[3] = *reinterpret_cast<const uint32_t*>(qp + Q_GROUP_BYTES + 128);
            qa[4] = (q == 0) ? *reinterpret_cast<const uint32_t*>(qp + 256) : 0u;
            qa[5] = (q == 0) ? *reinterpret_cast<const uint32_t*>(qp + Q_GROUP_BYTES + 256) : 0u;
            qa[6] = 0u; qa[7] = 0u;
        }
        float c0, c1;
        {
            float n0 = bf_lo(qa[0]) * bf_lo(qa[0]) + bf_hi(qa[0]) * bf_hi(qa[0]) + bf_lo(qa[2]) * bf_lo(qa[2]) + bf_hi(qa[2]) * bf_hi(qa[2]) +
                       bf_lo(qa[4]) * bf_lo(qa[4]) + bf_hi(qa[4]) * bf_hi(qa[4]);
            float n1 = bf_lo(qa[1]) * bf_lo(qa[1]) + bf_hi(qa[1]) * bf_hi(qa[1]) + bf_lo(qa[3]) * bf_lo(qa[3]) + bf_hi(qa[3]) * bf_hi(qa[3]) +
                       bf_lo(qa[5]) * bf_lo(qa[5]) + bf_hi(qa[5]) * bf_hi(qa[5]);
            n0 += __shfl_xor_sync(~0u, n0, 1); n1 += __shfl_xor_sync(~0u, n1, 1);
            n0 += __shfl_xor_sync(~0u, n0, 2); n1 += __shfl_xor_sync(~0u, n1, 2);
            c0 = sqrtf(n0 * kmax2) * 1.02f;
            c1 = sqrtf(n1 * kmax2) * 1.02f;
        }
        uint32_t slow;
        {
            const bool bad = !(c0 <= 58.f && c1 <= 58.f);
            asm volatile("{\n.reg .pred p, r;\nsetp.ne.u32 p, %1, 0;\nbarrier.cta.red.or.pred.aligned r, %2, 128, p;\nselp.u32 %0, 1, 0, r;\n}\n"
                         : "=r"(slow) : "r"((uint32_t)bad), "r"(wg + 1) : "memory");
        }
        float o[12];
#pragma unroll
        for (int i = 0; i < 12; i++) o[i] = 0.f;

        if (!slow) {
            if (q == 1) {
                qa[4] = pack_bf16(-c0, 768.f); qa[5] = pack_bf16(-c1, 768.f);
                qa[6] = pack_bf16(0.f, -2.f); qa[7] = qa[6];
            }
            float s0[32], s1[32];
            uint32_t p0[16], p1[16];
            if (pass == 0) mbar_wait(bar0, 0);
            reg_fence(qa);
            reg_fence(o);
            wg_fence();
            issue_qk(s0, qa, dk0, dk1, 0);
            wg_commit();
            issue_qk(s1, qa, dk0, dk1, 1);
            wg_commit();
#pragma unroll 1
            for (int t = 0; t < 30; t += 2) {
                wg_wait<1>();
                reg_fence(s0);
                softmax_fast(s0, p0);
                reg_fence(p0);
                if (pass == 0) mbar_wait(bar0 + (t / 2 + 1) * 8, 0);
                wg_fence();
                issue_pv(o, p0, dv, t);
                issue_qk(s0, qa, dk0, dk1, t + 2);
                wg_commit();
                wg_wait<1>();
                reg_fence(s1);
                softmax_fast(s1, p1);
                reg_fence(p1);
                wg_fence();
                issue_pv(o, p1, dv, t + 1);
                issue_qk(s1, qa, dk0, dk1, t + 3);
                wg_commit();
            }
            wg_wait<1>();
            reg_fence(s0);
            softmax_fast(s0, p0);
            reg_fence(p0);
            wg_fence();
            issue_pv(o, p0, dv, 30);
            wg_commit();
            wg_wait<1>();
            reg_fence(s1);
            softmax_fast(s1, p1);
            reg_fence(p1);
            wg_fence();
            issue_pv(o, p1, dv, 31);
            wg_commit();
            wg_wait<0>();
            reg_fence(o);
        } else {
            float m0 = -INFINITY, m1 = -INFINITY;
            float s[32];
            uint32_t p[16];
#pragma unroll 1
            for (int t = 0; t < 32; t++) {
                if (pass == 0) mbar_wait(bar0 + (t / 2) * 8, 0);
                wg_fence();
                issue_qk(s, qa, dk0, dk1, t);
                wg_commit();
                wg_wait<0>();
                reg_fence(s);
                reg_fence(o);
                float a0 = m0, a1 = m1;
#pragma unroll
                for (int k = 0; k < 4; k++) {
#pragma unroll
                    for (int i = 4; i < 8; i++) s[k * 8 + i] *= 0.5f;
                    a0 = fmaxf(fmaxf(a0, fmaxf(s[k * 8 + 0], s[k * 8 + 1])), fmaxf(s[k * 8 + 4], s[k * 8 + 5]));
                    a1 = fmaxf(fmaxf(a1, fmaxf(s[k * 8 + 2], s[k * 8 + 3])), fmaxf(s[k * 8 + 6], s[k * 8 + 7]));
                }
                a0 = fmaxf(a0, __shfl_xor_sync(~0u, a0, 1)); a1 = fmaxf(a1, __shfl_xor_sync(~0u, a1, 1));
                a0 = fmaxf(a0, __shfl_xor_sync(~0u, a0, 2)); a1 = fmaxf(a1, __shfl_xor_sync(~0u, a1, 2));
                const float r0 = ex2(m0 - a0), r1 = ex2(m1 - a1);
                m0 = a0; m1 = a1;
#pragma unroll
                for (int i = 0; i < 3; i++) { o[i * 4] *= r0; o[i * 4 + 1] *= r0; o[i * 4 + 2] *= r1; o[i * 4 + 3] *= r1; }
#pragma unroll
                for (int k = 0; k < 8; k++) {
                    p[k * 2 + 0] = pack_bf16(ex2(s[k * 4 + 0] - m0), ex2(s[k * 4 + 1] - m0));
                    p[k * 2 + 1] = pack_bf16(ex2(s[k * 4 + 2] - m1), ex2(s[k * 4 + 3] - m1));
                }
                reg_fence(p);
                reg_fence(o);
                wg_fence();
                issue_pv(o, p, dv, t);
                wg_commit();
            }
            wg_wait<0>();
            reg_fence(o);
        }
        const float l0 = __shfl_sync(~0u, o[8], (lane & ~3) | 3), l1 = __shfl_sync(~0u, o[10], (lane & ~3) | 3);
        const float i0 = 1.0f / l0, i1 = 1.0f / l1;
        uint32_t* op0 = reinterpret_cast<uint32_t*>(g_O + (size_t)(row0 + g) * DM + head * DH);
        uint32_t* op1 = reinterpret_cast<uint32_t*>(g_O + (size_t)(row0 + g + 8) * DM + head * DH);
        op0[q] = pack_bf16(o[0] * i0, o[1] * i0);
        op1[q] = pack_bf16(o[2] * i1, o[3] * i1);
        op0[4 + q] = pack_bf16(o[4] * i0, o[5] * i0);
        op1[4 + q] = pack_bf16(o[6] * i1, o[7] * i1);
        if (q == 2) {
            op0[8] = pack_bf16(o[8] * i0, o[9] * i0);
            op1[8] = pack_bf16(o[10] * i1, o[11] * i1);
        }
    }
}

constexpr int K3_OFF_B = 9 * 16384;
constexpr int K3_OFF_BAR = K3_OFF_B + 9 * 8192;
constexpr int K3_SMEM = K3_OFF_BAR + 128;

__global__ void __launch_bounds__(256, 1)
k3_kernel(const __grid_constant__ CUtensorMap tmO, const __grid_constant__ CUtensorMap tmWo, const __nv_bfloat16* __restrict__ x,
          const __nv_bfloat16* __restrict__ b2, __nv_bfloat16* __restrict__ out) {
    extern __shared__ __align__(1024) uint8_t smem[];
    const uint32_t sb = s2u(smem);
    const int tid = threadIdx.x, warp = tid >> 5, lane = tid & 31;
    const int wg = warp >> 2, g = lane >> 2, q = lane & 3;
    const int rb = blockIdx.x / 9, t = blockIdx.x % 9;
    const uint32_t bar0 = sb + K3_OFF_BAR;
    if (tid == 0) {
        for (int i = 0; i < 9; i++) mbar_init(bar0 + i * 8, 1);
        fence_barrier_init();
    }
    __syncthreads();
    griddep_wait();
    if (warp == 0 && lane < 9) {
        mbar_expect(bar0 + lane * 8, 16384 + 8192);
        tma2d(sb + lane * 16384, &tmO, lane * 64, rb * 128, bar0 + lane * 8);
        tma2d(sb + K3_OFF_B + lane * 8192, &tmWo, t * 64, lane * 64, bar0 + lane * 8);
    }
    float acc[32];
    {
        const int r0 = rb * 128 + warp * 16 + g;
#pragma unroll
        for (int b = 0; b < 8; b++) {
            const int col = t * 64 + b * 8 + q * 2;
            const uint32_t bb = *reinterpret_cast<const uint32_t*>(b2 + col);
            const uint32_t x0 = *reinterpret_cast<const uint32_t*>(x + (size_t)r0 * DM + col);
            const uint32_t x1 = *reinterpret_cast<const uint32_t*>(x + (size_t)(r0 + 8) * DM + col);
            acc[b * 4 + 0] = bf_lo(x0) + bf_lo(bb); acc[b * 4 + 1] = bf_hi(x0) + bf_hi(bb);
            acc[b * 4 + 2] = bf_lo(x1) + bf_lo(bb); acc[b * 4 + 3] = bf_hi(x1) + bf_hi(bb);
        }
#pragma unroll
        for (int jj = 0; jj < 8; jj++) {
            const uint4* pp = g_part + ((size_t)(jj * 16 + rb) * 36 + t * 4) * 256 + tid;
#pragma unroll
            for (int s = 0; s < 4; s++) {
                const uint4 v = pp[s * 256];
                acc[s * 8 + 0] += bf_lo(v.x); acc[s * 8 + 1] += bf_hi(v.x); acc[s * 8 + 2] += bf_lo(v.y); acc[s * 8 + 3] += bf_hi(v.y);
                acc[s * 8 + 4] += bf_lo(v.z); acc[s * 8 + 5] += bf_hi(v.z); acc[s * 8 + 6] += bf_lo(v.w); acc[s * 8 + 7] += bf_hi(v.w);
            }
        }
    }
    const uint64_t da = mk_desc(sb + wg * 8192, 16, 1024, 1);
    const uint64_t db = mk_desc(sb + K3_OFF_B, 8192, 1024, 1);
#pragma unroll
    for (int kb = 0; kb < 9; kb++) {
        mbar_wait(bar0 + kb * 8, 0);
        wg_fence();
#pragma unroll
        for (int k = 0; k < 4; k++) wgmma_ss_n64<1>(acc, descA_step(da, kb * 4 + k), db + ((kb * 8192 + k * 2048) >> 4), 1);
        wg_commit();
    }
    wg_wait<0>();
    reg_fence(acc);
    const int r0 = rb * 128 + warp * 16 + g;
#pragma unroll
    for (int b = 0; b < 8; b++) {
        const int col = t * 64 + b * 8 + q * 2;
        *reinterpret_cast<uint32_t*>(out + (size_t)r0 * DM + col) = pack_bf16(acc[b * 4], acc[b * 4 + 1]);
        *reinterpret_cast<uint32_t*>(out + (size_t)(r0 + 8) * DM + col) = pack_bf16(acc[b * 4 + 2], acc[b * 4 + 3]);
    }
}

typedef CUresult (*EncodeFn)(CUtensorMap*, CUtensorMapDataType, cuuint32_t, void*, const cuuint64_t*, const cuuint64_t*, const cuuint32_t*,
                             const cuuint32_t*, CUtensorMapInterleave, CUtensorMapSwizzle, CUtensorMapL2promotion, CUtensorMapFloatOOBfill);

void make_map(EncodeFn fn, CUtensorMap* m, const void* base, int rank, const cuuint64_t* dims, const cuuint64_t* strides, const cuuint32_t* box) {
    cuuint32_t es[3] = {1, 1, 1};
    fn(m, CU_TENSOR_MAP_DATA_TYPE_BFLOAT16, rank, const_cast<void*>(base), dims, strides, box, es, CU_TENSOR_MAP_INTERLEAVE_NONE,
       CU_TENSOR_MAP_SWIZZLE_128B, CU_TENSOR_MAP_L2_PROMOTION_L2_256B, CU_TENSOR_MAP_FLOAT_OOB_FILL_NONE);
}

}

extern "C" void kernel_launch(void* const* d_in, const int* in_sizes, int n_in, void* d_out, int out_size) {
    const __nv_bfloat16* x = (const __nv_bfloat16*)d_in[0];
    const __nv_bfloat16* wqkv = (const __nv_bfloat16*)d_in[1];
    const __nv_bfloat16* wo = (const __nv_bfloat16*)d_in[2];
    const __nv_bfloat16* w1 = (const __nv_bfloat16*)d_in[4];
    const __nv_bfloat16* b1 = (const __nv_bfloat16*)d_in[5];
    const __nv_bfloat16* w2 = (const __nv_bfloat16*)d_in[6];
    const __nv_bfloat16* b2 = (const __nv_bfloat16*)d_in[7];
    __nv_bfloat16* out = (__nv_bfloat16*)d_out;

    EncodeFn fn = nullptr;
    cudaDriverEntryPointQueryResult qr;
    cudaGetDriverEntryPoint("cuTensorMapEncodeTiled", (void**)&fn, cudaEnableDefault, &qr);
    void* gO = nullptr;
    cudaGetSymbolAddress(&gO, g_O);
    CUtensorMap tmQ3, tmQ1, tm1a, tm1b, tm2, tmO, tmWo;
    {
        cuuint64_t d[3] = {3 * DM, DM, 3}, s[2] = {3 * DM * 2, 128};
        cuuint32_t b[3] = {64, 16, 3};
        make_map(fn, &tmQ3, wqkv, 3, d, s, b);
        make_map(fn, &tmQ1, wqkv, 2, d, s, b);
    }
    {
        cuuint64_t d[3] = {64, DM, FF / 64}, s[2] = {FF * 2, 128};
        cuuint32_t ba[3] = {64, 48, 1}, bb[3] = {64, 32, 2};
        make_map(fn, &tm1a, w1, 3, d, s, ba);
        make_map(fn, &tm1b, w1, 3, d, s, bb);
    }
    {
        cuuint64_t d[2] = {DM, FF}, s[1] = {DM * 2};
        cuuint32_t b[2] = {64, 48};
        make_map(fn, &tm2, w2, 2, d, s, b);
    }
    {
        cuuint64_t d[2] = {DM, SEQ}, s[1] = {DM * 2};
        cuuint32_t b[2] = {64, 128};
        make_map(fn, &tmO, gO, 2, d, s, b);
        cuuint64_t d2[2] = {DM, DM};
        cuuint32_t b2x[2] = {64, 64};
        make_map(fn, &tmWo, wo, 2, d2, s, b2x);
    }
    cudaFuncSetAttribute(k1_kernel, cudaFuncAttributeMaxDynamicSharedMemorySize, K1_SMEM);
    cudaFuncSetAttribute(k2_kernel, cudaFuncAttributeMaxDynamicSharedMemorySize, K2_SMEM);
    cudaFuncSetAttribute(k3_kernel, cudaFuncAttributeMaxDynamicSharedMemorySize, K3_SMEM);

    cudaStream_t st = cudaStreamPerThread;
    cudaLaunchAttribute pdl[1];
    pdl[0].id = cudaLaunchAttributeProgrammaticStreamSerialization;
    pdl[0].val.programmaticStreamSerializationAllowed = 1;
    {
        cudaLaunchConfig_t cfg = {};
        cfg.gridDim = dim3(128); cfg.blockDim = dim3(384); cfg.dynamicSmemBytes = K1_SMEM; cfg.stream = st;
        cudaLaunchKernelEx(&cfg, k1_kernel, tmQ3, tmQ1, tm1a, tm1b, tm2, x, b1);
    }
    {
        cudaLaunchConfig_t cfg = {};
        cfg.gridDim = dim3(128); cfg.blockDim = dim3(512); cfg.dynamicSmemBytes = K2_SMEM; cfg.stream = st;
        cfg.attrs = pdl; cfg.numAttrs = 1;
        cudaLaunchKernelEx(&cfg, k2_kernel);
    }
    {
        cudaLaunchConfig_t cfg = {};
        cfg.gridDim = dim3(144); cfg.blockDim = dim3(256); cfg.dynamicSmemBytes = K3_SMEM; cfg.stream = st;
        cfg.attrs = pdl; cfg.numAttrs = 1;
        cudaLaunchKernelEx(&cfg, k3_kernel, tmO, tmWo, x, b2, out);
    }
}
```

```cpp
#include <cuda_runtime.h>
#include <cuda_bf16.h>
#include <cuda.h>
#include <stdint.h>

#define PROF(i) do { } while (0)
#define PROF_WG 0

namespace {

constexpr int SEQ = 2048, DM = 576, FF = 4608, NH = 32, DH = 18;

constexpr int Q_GROUP_BYTES = 3 * 128, KV_GROUP_BYTES = 5 * 128;
constexpr int Q_HEAD_BYTES = (SEQ / 8) * Q_GROUP_BYTES, KV_HEAD_BYTES = (SEQ / 8) * KV_GROUP_BYTES;
__device__ __align__(1024) uint8_t g_Q[NH * Q_HEAD_BYTES];
__device__ __align__(1024) uint8_t g_KV[NH * KV_HEAD_BYTES];
__device__ __align__(1024) float g_kmax[NH * 128];
__device__ __align__(1024) uint4 g_part[8 * 16 * 36 * 256];
__device__ __align__(1024) __nv_bfloat16 g_O[SEQ * DM];

__device__ __forceinline__ uint32_t s2u(const void* p) { return (uint32_t)__cvta_generic_to_shared(p); }
__device__ __forceinline__ void mbar_init(uint32_t b, int c) { asm volatile("mbarrier.init.shared::cta.b64 [%0], %1;" ::"r"(b), "r"(c) : "memory"); }
__device__ __forceinline__ void mbar_expect(uint32_t b, uint32_t bytes) {
    asm volatile("mbarrier.arrive.expect_tx.shared::cta.b64 _, [%0], %1;" ::"r"(b), "r"(bytes) : "memory");
}
__device__ __forceinline__ void mbar_arrive_cluster(uint32_t local_bar, uint32_t cta) {
    asm volatile("{\n.reg .b32 ra;\nmapa.shared::cluster.u32 ra, %0, %1;\nmbarrier.arrive.shared::cluster.b64 _, [ra];\n}\n" ::"r"(local_bar), "r"(cta) : "memory");
}
__device__ __forceinline__ void mbar_wait(uint32_t b, uint32_t parity) {
    uint32_t ok;
    uint32_t spins = 0;
    do {
        asm volatile("{\n.reg .pred p;\nmbarrier.try_wait.parity.shared::cta.b64 p, [%1], %2;\nselp.u32 %0, 1, 0, p;\n}\n" : "=r"(ok) : "r"(b), "r"(parity) : "memory");
        if (!ok && ++spins > (1u << 22)) __trap();
    } while (!ok);
}
__device__ __forceinline__ void fence_barrier_init() { asm volatile("fence.mbarrier_init.release.cluster;" ::: "memory"); }
__device__ __forceinline__ void fence_proxy_async() { asm volatile("fence.proxy.async.shared::cta;" ::: "memory"); }
__device__ __forceinline__ void cluster_arrive() { asm volatile("barrier.cluster.arrive.relaxed.aligned;" ::: "memory"); }
__device__ __forceinline__ void cluster_wait() { asm volatile("barrier.cluster.wait.aligned;" ::: "memory"); }
__device__ __forceinline__ void named_bar_sync(int id, int n) { asm volatile("bar.sync %0, %1;" ::"r"(id), "r"(n) : "memory"); }
__device__ __forceinline__ void griddep_wait() { asm volatile("griddepcontrol.wait;" ::: "memory"); }
__device__ __forceinline__ void griddep_launch() { asm volatile("griddepcontrol.launch_dependents;" ::: "memory"); }

__device__ __forceinline__ void tma3d_mc(uint32_t dst, const CUtensorMap* tm, int c0, int c1, int c2, uint32_t bar, uint16_t mask) {
    asm volatile("cp.async.bulk.tensor.3d.shared::cluster.global.mbarrier::complete_tx::bytes.multicast::cluster [%0], [%1, {%3, %4, %5}], [%2], %6;"
                 ::"r"(dst), "l"(tm), "r"(bar), "r"(c0), "r"(c1), "r"(c2), "h"(mask) : "memory");
}
__device__ __forceinline__ void tma2d_mc(uint32_t dst, const CUtensorMap* tm, int c0, int c1, uint32_t bar, uint16_t mask) {
    asm volatile("cp.async.bulk.tensor.2d.shared::cluster.global.mbarrier::complete_tx::bytes.multicast::cluster [%0], [%1, {%3, %4}], [%2], %5;"
                 ::"r"(dst), "l"(tm), "r"(bar), "r"(c0), "r"(c1), "h"(mask) : "memory");
}
__device__ __forceinline__ void tma2d(uint32_t dst, const CUtensorMap* tm, int c0, int c1, uint32_t bar) {
    asm volatile("cp.async.bulk.tensor.2d.shared::cluster.global.mbarrier::complete_tx::bytes [%0], [%1, {%3, %4}], [%2];"
                 ::"r"(dst), "l"(tm), "r"(bar), "r"(c0), "r"(c1) : "memory");
}
__device__ __forceinline__ void bulk_load(uint32_t dst, const void* src, uint32_t bytes, uint32_t bar) {
    asm volatile("cp.async.bulk.shared::cluster.global.mbarrier::complete_tx::bytes [%0], [%1], %2, [%3];"
                 ::"r"(dst), "l"(src), "r"(bytes), "r"(bar) : "memory");
}
__device__ __forceinline__ void prefetch_tmap(const CUtensorMap* tm) { asm volatile("prefetch.tensormap [%0];" ::"l"(tm) : "memory"); }

__device__ __forceinline__ void wg_fence() { asm volatile("wgmma.fence.sync.aligned;" ::: "memory"); }
__device__ __forceinline__ void wg_commit() { asm volatile("wgmma.commit_group.sync.aligned;" ::: "memory"); }
template <int N> __device__ __forceinline__ void wg_wait() { asm volatile("wgmma.wait_group.sync.aligned %0;" ::"n"(N) : "memory"); }
template <int N> __device__ __forceinline__ void reg_fence(float (&d)[N]) {
#pragma unroll
    for (int i = 0; i < N; i++) asm volatile("" : "+f"(d[i])::"memory");
}
template <int N> __device__ __forceinline__ void reg_fence(uint32_t (&d)[N]) {
#pragma unroll
    for (int i = 0; i < N; i++) asm volatile("" : "+r"(d[i])::"memory");
}
template <int R> __device__ __forceinline__ void reg_alloc() { asm volatile("setmaxnreg.inc.sync.aligned.u32 %0;" ::"n"(R)); }
template <int R> __device__ __forceinline__ void reg_dealloc() { asm volatile("setmaxnreg.dec.sync.aligned.u32 %0;" ::"n"(R)); }

__device__ __forceinline__ uint64_t mk_desc(uint32_t addr, uint32_t lbo, uint32_t sbo, uint32_t swz) {
    return (uint64_t)((addr & 0x3FFFF) >> 4) | ((uint64_t)(lbo >> 4) << 16) | ((uint64_t)(sbo >> 4) << 32) | ((uint64_t)swz << 62);
}
__device__ __forceinline__ uint32_t pack_bf16(float lo, float hi) {
    uint32_t r;
    asm("cvt.rn.bf16x2.f32 %0, %1, %2;" : "=r"(r) : "f"(hi), "f"(lo));
    return r;
}
__device__ __forceinline__ float bf_lo(uint32_t w) { return __uint_as_float(w << 16); }
__device__ __forceinline__ float bf_hi(uint32_t w) { return __uint_as_float(w & 0xFFFF0000u); }
__device__ __forceinline__ float ex2(float x) {
    float r;
    asm("ex2.approx.ftz.f32 %0, %1;" : "=f"(r) : "f"(x));
    return r;
}
__device__ __forceinline__ float tanh_fast(float x) {
    float r;
    asm("tanh.approx.f32 %0, %1;" : "=f"(r) : "f"(x));
    return r;
}
__device__ __forceinline__ float gelu_tanh(float u) {
    float w = fmaf(u * u, 0.0356774081f, 0.7978845608f);
    float t = tanh_fast(u * w);
    float h = 0.5f * u;
    return fmaf(h, t, h);
}

template<int TB> __device__ __forceinline__ void wgmma_ss_n216(float (&d)[108], uint64_t da, uint64_t db, int sd) {
    asm volatile("{\n.reg .pred p;\nsetp.ne.b32 p, %110, 0;\n"
      "wgmma.mma_async.sync.aligned.m64n216k16.f32.bf16.bf16 {%0, %1, %2, %3, %4, %5, %6, %7, %8, %9, %10, %11, %12, %13, %14, %15, %16, %17, %18, %19, %20, %21, %22, %23, %24, %25, %26, %27, %28, %29, %30, %31, %32, %33, %34, %35, %36, %37, %38, %39, %40, %41, %42, %43, %44, %45, %46, %47, %48, %49, %50, %51, %52, %53, %54, %55, %56, %57, %58, %59, %60, %61, %62, %63, %64, %65, %66, %67, %68, %69, %70, %71, %72, %73, %74, %75, %76, %77, %78, %79, %80, %81, %82, %83, %84, %85, %86, %87, %88, %89, %90, %91, %92, %93, %94, %95, %96, %97, %98, %99, %100, %101, %102, %103, %104, %105, %106, %107}, %108, %109, p, 1, 1, 0, %111;\n}\n"
      : "+f"(d[0]), "+f"(d[1]), "+f"(d[2]), "+f"(d[3]), "+f"(d[4]), "+f"(d[5]), "+f"(d[6]), "+f"(d[7]), "+f"(d[8]), "+f"(d[9]), "+f"(d[10]), "+f"(d[11]), "+f"(d[12]), "+f"(d[13]), "+f"(d[14]), "+f"(d[15]), "+f"(d[16]), "+f"(d[17]), "+f"(d[18]), "+f"(d[19]), "+f"(d[20]), "+f"(d[21]), "+f"(d[22]), "+f"(d[23]), "+f"(d[24]), "+f"(d[25]), "+f"(d[26]), "+f"(d[27]), "+f"(d[28]), "+f"(d[29]), "+f"(d[30]), "+f"(d[31]), "+f"(d[32]), "+f"(d[33]), "+f"(d[34]), "+f"(d[35]), "+f"(d[36]), "+f"(d[37]), "+f"(d[38]), "+f"(d[39]), "+f"(d[40]), "+f"(d[41]), "+f"(d[42]), "+f"(d[43]), "+f"(d[44]), "+f"(d[45]), "+f"(d[46]), "+f"(d[47]), "+f"(d[48]), "+f"(d[49]), "+f"(d[50]), "+f"(d[51]), "+f"(d[52]), "+f"(d[53]), "+f"(d[54]), "+f"(d[55]), "+f"(d[56]), "+f"(d[57]), "+f"(d[58]), "+f"(d[59]), "+f"(d[60]), "+f"(d[61]), "+f"(d[62]), "+f"(d[63]), "+f"(d[64]), "+f"(d[65]), "+f"(d[66]), "+f"(d[67]), "+f"(d[68]), "+f"(d[69]), "+f"(d[70]), "+f"(d[71]), "+f"(d[72]), "+f"(d[73]), "+f"(d[74]), "+f"(d[75]), "+f"(d[76]), "+f"(d[77]), "+f"(d[78]), "+f"(d[79]), "+f"(d[80]), "+f"(d[81]), "+f"(d[82]), "+f"(d[83]), "+f"(d[84]), "+f"(d[85]), "+f"(d[86]), "+f"(d[87]), "+f"(d[88]), "+f"(d[89]), "+f"(d[90]), "+f"(d[91]), "+f"(d[92]), "+f"(d[93]), "+f"(d[94]), "+f"(d[95]), "+f"(d[96]), "+f"(d[97]), "+f"(d[98]), "+f"(d[99]), "+f"(d[100]), "+f"(d[101]), "+f"(d[102]), "+f"(d[103]), "+f"(d[104]), "+f"(d[105]), "+f"(d[106]), "+f"(d[107])
      : "l"(da), "l"(db), "r"(sd), "n"(TB));
}

template<int TB> __device__ __forceinline__ void wgmma_ss_n128(float (&d)[64], uint64_t da, uint64_t db, int sd) {
    asm volatile("{\n.reg .pred p;\nsetp.ne.b32 p, %66, 0;\n"
      "wgmma.mma_async.sync.aligned.m64n128k16.f32.bf16.bf16 {%0, %1, %2, %3, %4, %5, %6, %7, %8, %9, %10, %11, %12, %13, %14, %15, %16, %17, %18, %19, %20, %21, %22, %23, %24, %25, %26, %27, %28, %29, %30, %31, %32, %33, %34, %35, %36, %37, %38, %39, %40, %41, %42, %43, %44, %45, %46, %47, %48, %49, %50, %51, %52, %53, %54, %55, %56, %57, %58, %59, %60, %61, %62, %63}, %64, %65, p, 1, 1, 0, %67;\n}\n"
      : "+f"(d[0]), "+f"(d[1]), "+f"(d[2]), "+f"(d[3]), "+f"(d[4]), "+f"(d[5]), "+f"(d[6]), "+f"(d[7]), "+f"(d[8]), "+f"(d[9]), "+f"(d[10]), "+f"(d[11]), "+f"(d[12]), "+f"(d[13]), "+f"(d[14]), "+f"(d[15]), "+f"(d[16]), "+f"(d[17]), "+f"(d[18]), "+f"(d[19]), "+f"(d[20]), "+f"(d[21]), "+f"(d[22]), "+f"(d[23]), "+f"(d[24]), "+f"(d[25]), "+f"(d[26]), "+f"(d[27]), "+f"(d[28]), "+f"(d[29]), "+f"(d[30]), "+f"(d[31]), "+f"(d[32]), "+f"(d[33]), "+f"(d[34]), "+f"(d[35]), "+f"(d[36]), "+f"(d[37]), "+f"(d[38]), "+f"(d[39]), "+f"(d[40]), "+f"(d[41]), "+f"(d[42]), "+f"(d[43]), "+f"(d[44]), "+f"(d[45]), "+f"(d[46]), "+f"(d[47]), "+f"(d[48]), "+f"(d[49]), "+f"(d[50]), "+f"(d[51]), "+f"(d[52]), "+f"(d[53]), "+f"(d[54]), "+f"(d[55]), "+f"(d[56]), "+f"(d[57]), "+f"(d[58]), "+f"(d[59]), "+f"(d[60]), "+f"(d[61]), "+f"(d[62]), "+f"(d[63])
      : "l"(da), "l"(db), "r"(sd), "n"(TB));
}

template<int TB> __device__ __forceinline__ void wgmma_ss_n64(float (&d)[32], uint64_t da, uint64_t db, int sd) {
    asm volatile("{\n.reg .pred p;\nsetp.ne.b32 p, %34, 0;\n"
      "wgmma.mma_async.sync.aligned.m64n64k16.f32.bf16.bf16 {%0, %1, %2, %3, %4, %5, %6, %7, %8, %9, %10, %11, %12, %13, %14, %15, %16, %17, %18, %19, %20, %21, %22, %23, %24, %25, %26, %27, %28, %29, %30, %31}, %32, %33, p, 1, 1, 0, %35;\n}\n"
      : "+f"(d[0]), "+f"(d[1]), "+f"(d[2]), "+f"(d[3]), "+f"(d[4]), "+f"(d[5]), "+f"(d[6]), "+f"(d[7]), "+f"(d[8]), "+f"(d[9]), "+f"(d[10]), "+f"(d[11]), "+f"(d[12]), "+f"(d[13]), "+f"(d[14]), "+f"(d[15]), "+f"(d[16]), "+f"(d[17]), "+f"(d[18]), "+f"(d[19]), "+f"(d[20]), "+f"(d[21]), "+f"(d[22]), "+f"(d[23]), "+f"(d[24]), "+f"(d[25]), "+f"(d[26]), "+f"(d[27]), "+f"(d[28]), "+f"(d[29]), "+f"(d[30]), "+f"(d[31])
      : "l"(da), "l"(db), "r"(sd), "n"(TB));
}

template<int TB> __device__ __forceinline__ void wgmma_rs_n64(float (&d)[32], uint32_t a0, uint32_t a1, uint32_t a2, uint32_t a3, uint64_t db, int sd) {
    asm volatile("{\n.reg .pred p;\nsetp.ne.b32 p, %37, 0;\n"
      "wgmma.mma_async.sync.aligned.m64n64k16.f32.bf16.bf16 {%0, %1, %2, %3, %4, %5, %6, %7, %8, %9, %10, %11, %12, %13, %14, %15, %16, %17, %18, %19, %20, %21, %22, %23, %24, %25, %26, %27, %28, %29, %30, %31}, {%32, %33, %34, %35}, %36, p, 1, 1, %38;\n}\n"
      : "+f"(d[0]), "+f"(d[1]), "+f"(d[2]), "+f"(d[3]), "+f"(d[4]), "+f"(d[5]), "+f"(d[6]), "+f"(d[7]), "+f"(d[8]), "+f"(d[9]), "+f"(d[10]), "+f"(d[11]), "+f"(d[12]), "+f"(d[13]), "+f"(d[14]), "+f"(d[15]), "+f"(d[16]), "+f"(d[17]), "+f"(d[18]), "+f"(d[19]), "+f"(d[20]), "+f"(d[21]), "+f"(d[22]), "+f"(d[23]), "+f"(d[24]), "+f"(d[25]), "+f"(d[26]), "+f"(d[27]), "+f"(d[28]), "+f"(d[29]), "+f"(d[30]), "+f"(d[31])
      : "r"(a0), "r"(a1), "r"(a2), "r"(a3), "l"(db), "r"(sd), "n"(TB));
}

template<int TB> __device__ __forceinline__ void wgmma_rs_n24(float (&d)[12], uint32_t a0, uint32_t a1, uint32_t a2, uint32_t a3, uint64_t db, int sd) {
    asm volatile("{\n.reg .pred p;\nsetp.ne.b32 p, %17, 0;\n"
      "wgmma.mma_async.sync.aligned.m64n24k16.f32.bf16.bf16 {%0, %1, %2, %3, %4, %5, %6, %7, %8, %9, %10, %11}, {%12, %13, %14, %15}, %16, p, 1, 1, %18;\n}\n"
      : "+f"(d[0]), "+f"(d[1]), "+f"(d[2]), "+f"(d[3]), "+f"(d[4]), "+f"(d[5]), "+f"(d[6]), "+f"(d[7]), "+f"(d[8]), "+f"(d[9]), "+f"(d[10]), "+f"(d[11])
      : "r"(a0), "r"(a1), "r"(a2), "r"(a3), "l"(db), "r"(sd), "n"(TB));
}

constexpr int K1_XN_BYTES = 9 * 16384;
constexpr int K1_SLOT = 16384, K1_NSLOT = 5;
constexpr int K1_OFF_RING = K1_XN_BYTES;
constexpr int K1_OFF_BIAS = K1_OFF_RING + K1_NSLOT * K1_SLOT;
constexpr int K1_OFF_BAR = K1_OFF_BIAS + 576 * 4;
constexpr int K1_SMEM = K1_OFF_BAR + 128;
constexpr float QSCALE = 0.23570226039551584f * 1.4426950408889634f;

struct Ring {
    uint32_t slot, phase;
    __device__ __forceinline__ void advance() {
        if (++slot == K1_NSLOT) { slot = 0; phase ^= 1; }
    }
};

struct K1Ctx {
    uint32_t full0, empty0;
    uint32_t ring0;
    uint64_t descA;
    Ring rd;
    uint32_t prev_slot;
    bool rel_thread;
    uint32_t rel_cta;
    __device__ __forceinline__ void release_prev() {
        if (rel_thread && prev_slot != 0xFFFFFFFFu) mbar_arrive_cluster(empty0 + prev_slot * 8, rel_cta);
    }
};

__device__ __forceinline__ uint64_t descA_step(uint64_t base, int ks) { return base + (uint64_t)(((ks >> 2) * 16384 + (ks & 3) * 32) >> 4); }

template <int V> struct IC { static constexpr int value = V; };
template <int I, int N, class F> __device__ __forceinline__ void static_for(F&& f) {
    if constexpr (I < N) { f(IC<I>{}); static_for<I + 1, N>(f); }
}

template <int N, int KS, int NST, int HALF_STRIDE, int LBO, class Epi>
__device__ __forceinline__ void tile_ss(K1Ctx& c, float (&acc)[N / 2], Epi&& epi) {
    static_for<0, NST>([&](auto sc) {
        constexpr int s = decltype(sc)::value;
        mbar_wait(c.full0 + c.rd.slot * 8, c.rd.phase);
        uint64_t db = mk_desc(c.ring0 + c.rd.slot * K1_SLOT, LBO, 1024, 1);
        wg_fence();
#pragma unroll
        for (int t = 0; t < KS; t++) {
            const int off = (t / (KS / 2)) * HALF_STRIDE + (t % (KS / 2)) * 2048;
            uint64_t da = descA_step(c.descA, s * KS + t);
            if constexpr (N == 216) wgmma_ss_n216<1>(acc, da, db + (off >> 4), (s | t) != 0);
            if constexpr (N == 64) wgmma_ss_n64<1>(acc, da, db + (off >> 4), (s | t) != 0);
            if constexpr (N == 128) wgmma_ss_n128<1>(acc, da, db + (off >> 4), (s | t) != 0);
        }
        wg_commit();
        wg_wait<1>();
        c.release_prev();
        c.prev_slot = c.rd.slot;
        c.rd.advance();
        epi(sc);
    });
}

template <class Epi>
__device__ __forceinline__ void tile_rs(K1Ctx& c, float (&acc)[32], uint32_t (&h)[144], Epi&& epi) {
    static_for<0, 6>([&](auto sc) {
        constexpr int s = decltype(sc)::value;
        mbar_wait(c.full0 + c.rd.slot * 8, c.rd.phase);
        uint64_t db = mk_desc(c.ring0 + c.rd.slot * K1_SLOT, 8192, 1024, 1);
        wg_fence();
#pragma unroll
        for (int t = 0; t < 6; t++) {
            const int ks = s * 6 + t;
            wgmma_rs_n64<1>(acc, h[ks * 4], h[ks * 4 + 1], h[ks * 4 + 2], h[ks * 4 + 3], db + ((t * 2048) >> 4), (s | t) != 0);
        }
        wg_commit();
        wg_wait<1>();
        c.release_prev();
        c.prev_slot = c.rd.slot;
        c.rd.advance();
        epi(sc);
    });
}

template <int N, int B0, int NB, int HOFF>
__device__ __forceinline__ void gelu_blocks(const float (&acc)[N / 2], uint32_t (&h)[144], const float* bias  ) {
#pragma unroll
    for (int b = B0; b < B0 + NB; b++) {
        float2 bb = *reinterpret_cast<const float2*>(bias + b * 8);
        float v0 = gelu_tanh(acc[b * 4 + 0] + bb.x), v1 = gelu_tanh(acc[b * 4 + 1] + bb.y);
        float v2 = gelu_tanh(acc[b * 4 + 2] + bb.x), v3 = gelu_tanh(acc[b * 4 + 3] + bb.y);
        h[HOFF + b * 2 + 0] = pack_bf16(v0, v1);
        h[HOFF + b * 2 + 1] = pack_bf16(v2, v3);
    }
}

__global__ void __cluster_dims__(2, 1, 1) __launch_bounds__(384, 1)
k1_kernel(const __grid_constant__ CUtensorMap tmQ3, const __grid_constant__ CUtensorMap tmQ1, const __grid_constant__ CUtensorMap tm1a,
          const __grid_constant__ CUtensorMap tm1b, const __grid_constant__ CUtensorMap tm2, const __nv_bfloat16* __restrict__ x,
          const __nv_bfloat16* __restrict__ b1) {
    extern __shared__ __align__(1024) uint8_t smem[];
    const uint32_t sb = s2u(smem);
    const int tid = threadIdx.x, warp = tid >> 5, lane = tid & 31;
    const uint32_t rank = blockIdx.x & 1;
    const int cl = blockIdx.x >> 1;
    const int rb = (cl & 7) * 2 + rank;
    const int j = cl >> 3;
    const uint32_t full0 = sb + K1_OFF_BAR, empty0 = full0 + 8 * K1_NSLOT;

    if (warp < 8) {
        PROF(0);
        reg_alloc<240>();
        uint4 xv[4][9];
        const int sub = lane >> 3, l8 = lane & 7;
        {
            const uint4* xp = reinterpret_cast<const uint4*>(x + (size_t)(rb * 128 + warp * 16 + sub) * DM) + l8;
#pragma unroll
            for (int p = 0; p < 4; p++)
#pragma unroll
                for (int i = 0; i < 9; i++) xv[p][i] = __ldg(xp + p * 4 * (DM / 8) + i * 8);
        }
        cluster_arrive();
#pragma unroll
        for (int p = 0; p < 4; p++) {
            float f[72];
#pragma unroll
            for (int i = 0; i < 9; i++) {
                f[i * 8 + 0] = bf_lo(xv[p][i].x); f[i * 8 + 1] = bf_hi(xv[p][i].x);
                f[i * 8 + 2] = bf_lo(xv[p][i].y); f[i * 8 + 3] = bf_hi(xv[p][i].y);
                f[i * 8 + 4] = bf_lo(xv[p][i].z); f[i * 8 + 5] = bf_hi(xv[p][i].z);
                f[i * 8 + 6] = bf_lo(xv[p][i].w); f[i * 8 + 7] = bf_hi(xv[p][i].w);
            }
            float s0 = 0.f, s1 = 0.f, s2 = 0.f, s3 = 0.f;
#pragma unroll
            for (int i = 0; i < 72; i += 4) { s0 += f[i]; s1 += f[i + 1]; s2 += f[i + 2]; s3 += f[i + 3]; }
            float sm = (s0 + s1) + (s2 + s3);
            sm += __shfl_xor_sync(~0u, sm, 1); sm += __shfl_xor_sync(~0u, sm, 2); sm += __shfl_xor_sync(~0u, sm, 4);
            const float mean = sm * (1.0f / DM);
            s0 = s1 = s2 = s3 = 0.f;
#pragma unroll
            for (int i = 0; i < 72; i += 4) {
                f[i] -= mean; f[i + 1] -= mean; f[i + 2] -= mean; f[i + 3] -= mean;
                s0 = fmaf(f[i], f[i], s0); s1 = fmaf(f[i + 1], f[i + 1], s1);
                s2 = fmaf(f[i + 2], f[i + 2], s2); s3 = fmaf(f[i + 3], f[i + 3], s3);
            }
            float sq = (s0 + s1) + (s2 + s3);
            sq += __shfl_xor_sync(~0u, sq, 1); sq += __shfl_xor_sync(~0u, sq, 2); sq += __shfl_xor_sync(~0u, sq, 4);
            const float rstd = rsqrtf(sq * (1.0f / DM) + 1e-5f);
            const int r = warp * 16 + p * 4 + sub;
            uint8_t* dst = smem + r * 128 + ((l8 ^ (r & 7)) << 4);
#pragma unroll
            for (int i = 0; i < 9; i++) {
                uint4 o;
                o.x = pack_bf16(f[i * 8 + 0] * rstd, f[i * 8 + 1] * rstd);
                o.y = pack_bf16(f[i * 8 + 2] * rstd, f[i * 8 + 3] * rstd);
                o.z = pack_bf16(f[i * 8 + 4] * rstd, f[i * 8 + 5] * rstd);
                o.w = pack_bf16(f[i * 8 + 6] * rstd, f[i * 8 + 7] * rstd);
                *reinterpret_cast<uint4*>(dst + i * 16384) = o;
            }
        }
        float* sbias = reinterpret_cast<float*>(smem + K1_OFF_BIAS);
        for (int i = tid; i < 576; i += 256) sbias[i] = __bfloat162float(b1[j * 576 + i]);
        fence_proxy_async();
        named_bar_sync(1, 256);
        cluster_wait();
        PROF(1);

        const int wg = warp >> 2, wq = warp & 3;
        const int g = lane >> 2, q = lane & 3;
        K1Ctx c;
        c.full0 = full0; c.empty0 = empty0; c.ring0 = sb + K1_OFF_RING;
        c.descA = mk_desc(sb + wg * 8192, 16, 1024, 1);
        c.rd.slot = 0; c.rd.phase = 0; c.prev_slot = 0xFFFFFFFFu;
        c.rel_thread = (lane == 0) && (wq < 2);
        c.rel_cta = wq;
        const float* biasq = sbias + 2 * q;

        uint32_t h[144];
        float accX[64], accY[64];
        {
            float accQ[108];
            tile_ss<216, 2, 18, 8192, 2048>(c, accQ, [&](auto) {});
            PROF(2);
            const int grp0 = rb * 16 + warp * 2;
            float nrm[2][4];
            uint8_t* gbase = nullptr;
            uint32_t hstride = 0, gstride = 0, o2 = 0;
            float scl0 = 1.f, scl1 = 1.f;
            int type = 0, head0 = 0;
            tile_ss<128, 4, 9, 8192, 4096>(c, accX, [&](auto sc) {
                constexpr int s = decltype(sc)::value;
                if constexpr (s == 0) reg_fence(accQ);
                constexpr int grp = s / 3, part = s % 3;
                if constexpr (part == 0) {
                    const int G = 3 * j + grp;
                    type = G >> 3;
                    head0 = (G & 7) * 4;
                    if (type == 0) {
                        gbase = g_Q + (size_t)head0 * Q_HEAD_BYTES + grp0 * Q_GROUP_BYTES + g * 16;
                        hstride = Q_HEAD_BYTES; gstride = Q_GROUP_BYTES; o2 = 256;
                        scl0 = QSCALE; scl1 = QSCALE;
                    } else {
                        gbase = g_KV + (size_t)head0 * KV_HEAD_BYTES + grp0 * KV_GROUP_BYTES + g * 16 + (type == 2 ? 256 : 0);
                        hstride = KV_HEAD_BYTES; gstride = KV_GROUP_BYTES; o2 = (type == 2) ? 256 + 8 : 512;
                        scl0 = 1.f; scl1 = (type == 1) ? 2.f : 1.f;
                    }
#pragma unroll
                    for (int i = 0; i < 4; i++) { nrm[0][i] = 0.f; nrm[1][i] = 0.f; }
                }
#pragma unroll
                for (int i9 = part * 3; i9 < part * 3 + 3; i9++) {
                    const int b = grp * 9 + i9;
                    const int p = 4 * i9 + q;
                    const int hlo = (4 * i9) / 9;
                    const bool up = (p >= 9 * (hlo + 1));
                    const int hh = hlo + (up ? 1 : 0);
                    const int r = p - 9 * hh;
                    const uint32_t off = hh * hstride + (r < 4 ? r * 4 : (r < 8 ? 112 + r * 4 : o2));
                    const float a0 = accQ[b * 4], a1 = accQ[b * 4 + 1], a2 = accQ[b * 4 + 2], a3 = accQ[b * 4 + 3];
                    *reinterpret_cast<uint32_t*>(gbase + off) = pack_bf16(a0 * scl0, a1 * scl0);
                    *reinterpret_cast<uint32_t*>(gbase + off + gstride) = pack_bf16(a2 * scl1, a3 * scl1);
                    if (r == 8 && type != 0) {
                        *reinterpret_cast<uint32_t*>(gbase + off + 4) = 0x00003F80u;
                        *reinterpret_cast<uint32_t*>(gbase + off + gstride + 4) = (type == 1) ? 0x3F804000u : 0x00003F80u;
                    }
                    const float e0 = fmaf(a0, a0, a1 * a1), e1 = fmaf(a2, a2, a3 * a3);
                    if ((4 * i9 + 3) / 9 == hlo) {
                        nrm[0][hlo] += e0; nrm[1][hlo] += e1;
                    } else {
                        nrm[0][hlo] += up ? 0.f : e0; nrm[1][hlo] += up ? 0.f : e1;
                        nrm[0][(hlo + 1) & 3] += up ? e0 : 0.f; nrm[1][(hlo + 1) & 3] += up ? e1 : 0.f;
                    }
                }
                if constexpr (part == 2) {
                    if (type == 1) {
#pragma unroll
                        for (int i = 0; i < 4; i++) {
                            float u0 = nrm[0][i], u1 = nrm[1][i];
                            u0 += __shfl_xor_sync(~0u, u0, 1); u1 += __shfl_xor_sync(~0u, u1, 1);
                            u0 += __shfl_xor_sync(~0u, u0, 2); u1 += __shfl_xor_sync(~0u, u1, 2);
                            float m = fmaxf(u0, u1);
                            m = fmaxf(m, __shfl_xor_sync(~0u, m, 4));
                            m = fmaxf(m, __shfl_xor_sync(~0u, m, 8));
                            m = fmaxf(m, __shfl_xor_sync(~0u, m, 16));
                            if (lane == 0) g_kmax[(head0 + i) * 128 + rb * 8 + warp] = m;
                        }
                    }
                }
            });
        }
        PROF(3);
        tile_ss<128, 4, 9, 8192, 4096>(c, accY, [&](auto sc) {
            constexpr int s = decltype(sc)::value;
            if constexpr (s == 0) reg_fence(accX);
            if constexpr (s < 8) gelu_blocks<128, s * 2, 2, 0>(accX, h, biasq);
        });
        PROF(4);
        tile_ss<128, 4, 9, 8192, 4096>(c, accX, [&](auto sc) {
            constexpr int s = decltype(sc)::value;
            if constexpr (s == 0) reg_fence(accY);
            if constexpr (s < 8) gelu_blocks<128, s * 2, 2, 32>(accY, h, biasq + 128);
        });
        float o0[32], o1[32];
        PROF(5);
        tile_ss<64, 6, 6, 6144, 8192>(c, o0, [&](auto sc) {
            constexpr int s = decltype(sc)::value;
            if constexpr (s == 0) reg_fence(accX);
            if constexpr (s < 5) gelu_blocks<128, s * 3, 3, 64>(accX, h, biasq + 256);
            if constexpr (s == 5) gelu_blocks<128, 15, 1, 64>(accX, h, biasq + 256);
        });
        tile_ss<64, 6, 6, 6144, 8192>(c, o1, [&](auto sc) {
            constexpr int s = decltype(sc)::value;
            if constexpr (s == 0) reg_fence(o0);
            if constexpr (s < 4) gelu_blocks<64, s * 2, 2, 96>(o0, h, biasq + 384);
        });
        tile_ss<64, 6, 6, 6144, 8192>(c, o0, [&](auto sc) {
            constexpr int s = decltype(sc)::value;
            if constexpr (s == 0) reg_fence(o1);
            if constexpr (s < 4) gelu_blocks<64, s * 2, 2, 112>(o1, h, biasq + 448);
        });
        PROF(6);
        uint4* pout = g_part + ((size_t)(j * 16 + rb) * 36) * 256 + tid;
        auto store_part = [&](float (&o)[32], int t, auto sc) {
            constexpr int s = decltype(sc)::value;
            if constexpr (s == 0) reg_fence(o);
            if constexpr (s < 4) {
                uint4 v;
                v.x = pack_bf16(o[s * 8 + 0], o[s * 8 + 1]); v.y = pack_bf16(o[s * 8 + 2], o[s * 8 + 3]);
                v.z = pack_bf16(o[s * 8 + 4], o[s * 8 + 5]); v.w = pack_bf16(o[s * 8 + 6], o[s * 8 + 7]);
                pout[(t * 4 + s) * 256] = v;
            }
        };
        tile_rs(c, o1, h, [&](auto sc) {
            constexpr int s = decltype(sc)::value;
            if constexpr (s == 0) reg_fence(o0);
            if constexpr (s < 4) gelu_blocks<64, s * 2, 2, 128>(o0, h, biasq + 512);
            if constexpr (s == 4) reg_fence(h);
        });
#pragma unroll 1
        for (int t = 1; t < 9; t += 2) {
            PROF(7 + t / 2);
            tile_rs(c, o0, h, [&](auto sc) { store_part(o1, t - 1, sc); });
            tile_rs(c, o1, h, [&](auto sc) { store_part(o0, t, sc); });
        }
        wg_wait<0>();
        static_for<0, 4>([&](auto sc) { store_part(o1, 8, sc); });
        PROF(11);
        cluster_arrive();
        cluster_wait();
    } else {
        reg_dealloc<24>();
        if (warp == 8 && lane == 0) {
            prefetch_tmap(&tmQ3); prefetch_tmap(&tmQ1); prefetch_tmap(&tm1a); prefetch_tmap(&tm1b); prefetch_tmap(&tm2);
            for (int i = 0; i < K1_NSLOT; i++) { mbar_init(full0 + i * 8, 1); mbar_init(empty0 + i * 8, 4); }
            fence_barrier_init();
        }
        __syncwarp();
        cluster_arrive();
        cluster_wait();
        if (warp == 8 && lane == 0) {
            Ring w{0, 1};
            const uint32_t ring0 = sb + K1_OFF_RING;
            for (int s = 0; s < 18; s++) {
                mbar_wait(empty0 + w.slot * 8, w.phase);
                mbar_expect(full0 + w.slot * 8, 16384);
                const uint32_t dst = ring0 + w.slot * K1_SLOT + rank * 8192;
                tma3d_mc(dst, &tmQ3, j * 216, s * 32 + rank * 16, 0, full0 + w.slot * 8, 3);
                tma2d_mc(dst + 6144, &tmQ1, j * 216 + 192, s * 32 + rank * 16, full0 + w.slot * 8, 3);
                w.advance();
            }
            for (int t = 0; t < 3; t++)
                for (int s = 0; s < 9; s++) {
                    mbar_wait(empty0 + w.slot * 8, w.phase);
                    mbar_expect(full0 + w.slot * 8, 16384);
                    tma3d_mc(ring0 + w.slot * K1_SLOT + rank * 8192, &tm1b, 0, s * 64 + rank * 32, j * 9 + t * 2, full0 + w.slot * 8, 3);
                    w.advance();
                }
            for (int t = 0; t < 3; t++)
                for (int s = 0; s < 6; s++) {
                    mbar_wait(empty0 + w.slot * 8, w.phase);
                    mbar_expect(full0 + w.slot * 8, 12288);
                    tma3d_mc(ring0 + w.slot * K1_SLOT + rank * 6144, &tm1a, 0, s * 96 + rank * 48, j * 9 + 6 + t, full0 + w.slot * 8, 3);
                    w.advance();
                }
            for (int t = 0; t < 9; t++)
                for (int s = 0; s < 6; s++) {
                    mbar_wait(empty0 + w.slot * 8, w.phase);
                    mbar_expect(full0 + w.slot * 8, 12288);
                    tma2d_mc(ring0 + w.slot * K1_SLOT + rank * 6144, &tm2, t * 64, j * 576 + s * 96 + rank * 48, full0 + w.slot * 8, 3);
                    w.advance();
                }
        }
        __syncwarp();
        cluster_arrive();
        cluster_wait();
    }
}

constexpr int K2_NCHUNK = 16;
constexpr int K2_CHUNK_BYTES = KV_HEAD_BYTES / K2_NCHUNK;
constexpr int K2_OFF_BAR = KV_HEAD_BYTES;
constexpr int K2_SMEM = K2_OFF_BAR + 256;

__device__ __forceinline__ float exp2_fixed(float y) {
    const float u = __uint_as_float((__float_as_uint(y) & 0x7FFFu) | 0x44000000u) - 512.02545f;
    float t = fmaf(u, 0.019497588f, 0.114550486f);
    t = fmaf(t, u, -0.29839927f);
    return fmaf(t, u, y);
}
__device__ __forceinline__ uint32_t pack_fixed(float lo, float hi) { return __byte_perm(__float_as_uint(lo), __float_as_uint(hi), 0x6521); }

__device__ __forceinline__ void softmax_fast(const float (&s)[32], uint32_t (&p)[16]) {
#pragma unroll
    for (int k = 0; k < 4; k++) {
        p[k * 4 + 0] = pack_bf16(ex2(s[k * 8 + 0]), ex2(s[k * 8 + 1]));
        p[k * 4 + 1] = pack_bf16(ex2(s[k * 8 + 2]), ex2(s[k * 8 + 3]));
        p[k * 4 + 2] = pack_fixed(exp2_fixed(s[k * 8 + 4]), exp2_fixed(s[k * 8 + 5]));
        p[k * 4 + 3] = pack_fixed(exp2_fixed(s[k * 8 + 6]), exp2_fixed(s[k * 8 + 7]));
    }
}

__device__ __forceinline__ void issue_qk(float (&s)[32], const uint32_t (&qa)[8], uint64_t dk0, uint64_t dk1, int tile) {
    const uint64_t off = (uint64_t)(tile * (8 * KV_GROUP_BYTES / 16));
    wgmma_rs_n64<0>(s, qa[0], qa[1], qa[2], qa[3], dk0 + off, 0);
    wgmma_rs_n64<0>(s, qa[4], qa[5], qa[6], qa[7], dk1 + off, 1);
}
__device__ __forceinline__ void issue_pv(float (&o)[12], const uint32_t (&p)[16], uint64_t dv, int tile) {
    const uint64_t off = (uint64_t)(tile * (8 * KV_GROUP_BYTES / 16));
#pragma unroll
    for (int k = 0; k < 4; k++) wgmma_rs_n24<1>(o, p[k * 4], p[k * 4 + 1], p[k * 4 + 2], p[k * 4 + 3], dv + off + k * (2 * KV_GROUP_BYTES / 16), 1);
}

__global__ void __launch_bounds__(512, 1) k2_kernel() {
    extern __shared__ __align__(1024) uint8_t smem[];
    const uint32_t sb = s2u(smem);
    const int tid = threadIdx.x, warp = tid >> 5, lane = tid & 31;
    const int wg = warp >> 2, wq = warp & 3, g = lane >> 2, q = lane & 3;
    const int head = blockIdx.x >> 2, quarter = blockIdx.x & 3;
    const uint32_t bar0 = sb + K2_OFF_BAR;
    if (tid == 0) {
        for (int i = 0; i < K2_NCHUNK; i++) mbar_init(bar0 + i * 8, 1);
        fence_barrier_init();
    }
    __syncthreads();
    griddep_wait();
    if (warp == 0 && lane < K2_NCHUNK) {
        mbar_expect(bar0 + lane * 8, K2_CHUNK_BYTES);
        bulk_load(sb + lane * K2_CHUNK_BYTES, g_KV + (size_t)head * KV_HEAD_BYTES + lane * K2_CHUNK_BYTES, K2_CHUNK_BYTES, bar0 + lane * 8);
    }
    float kmax2;
    {
        const float4 v = *reinterpret_cast<const float4*>(g_kmax + head * 128 + lane * 4);
        kmax2 = fmaxf(fmaxf(v.x, v.y), fmaxf(v.z, v.w));
#pragma unroll
        for (int o = 16; o; o >>= 1) kmax2 = fmaxf(kmax2, __shfl_xor_sync(~0u, kmax2, o));
    }
    const uint64_t dk0 = mk_desc(sb, 128, KV_GROUP_BYTES, 0);
    const uint64_t dk1 = mk_desc(sb + 512, 0, KV_GROUP_BYTES, 0);
    const uint64_t dv = mk_desc(sb + 256, KV_GROUP_BYTES, 128, 0);

#pragma unroll 1
    for (int pass = 0; pass < 2; pass++) {
        const int row0 = quarter * 512 + (pass * 4 + wg) * 64 + wq * 16;
        uint32_t qa[8];
        {
            const uint8_t* qp = g_Q + (size_t)head * Q_HEAD_BYTES + (row0 >> 3) * Q_GROUP_BYTES + g * 16 + q * 4;
            qa[0] = *reinterpret_cast<const uint32_t*>(qp);
            qa[1] = *reinterpret_cast<const uint32_t*>(qp + Q_GROUP_BYTES);
            qa[2] = *reinterpret_cast<const uint32_t*>(qp + 128);
            qa[3] = *reinterpret_cast<const uint32_t*>(qp + Q_GROUP_BYTES + 128);
            qa[4] = (q == 0) ? *reinterpret_cast<const uint32_t*>(qp + 256) : 0u;
            qa[5] = (q == 0) ? *reinterpret_cast<const uint32_t*>(qp + Q_GROUP_BYTES + 256) : 0u;
            qa[6] = 0u; qa[7] = 0u;
        }
        float c0, c1;
        {
            float n0 = bf_lo(qa[0]) * bf_lo(qa[0]) + bf_hi(qa[0]) * bf_hi(qa[0]) + bf_lo(qa[2]) * bf_lo(qa[2]) + bf_hi(qa[2]) * bf_hi(qa[2]) +
                       bf_lo(qa[4]) * bf_lo(qa[4]) + bf_hi(qa[4]) * bf_hi(qa[4]);
            float n1 = bf_lo(qa[1]) * bf_lo(qa[1]) + bf_hi(qa[1]) * bf_hi(qa[1]) + bf_lo(qa[3]) * bf_lo(qa[3]) + bf_hi(qa[3]) * bf_hi(qa[3]) +
                       bf_lo(qa[5]) * bf_lo(qa[5]) + bf_hi(qa[5]) * bf_hi(qa[5]);
            n0 += __shfl_xor_sync(~0u, n0, 1); n1 += __shfl_xor_sync(~0u, n1, 1);
            n0 += __shfl_xor_sync(~0u, n0, 2); n1 += __shfl_xor_sync(~0u, n1, 2);
            c0 = sqrtf(n0 * kmax2) * 1.02f;
            c1 = sqrtf(n1 * kmax2) * 1.02f;
        }
        uint32_t slow;
        {
            const bool bad = !(c0 <= 58.f && c1 <= 58.f);
            asm volatile("{\n.reg .pred p, r;\nsetp.ne.u32 p, %1, 0;\nbarrier.cta.red.or.pred.aligned r, %2, 128, p;\nselp.u32 %0, 1, 0, r;\n}\n"
                         : "=r"(slow) : "r"((uint32_t)bad), "r"(wg + 1) : "memory");
        }
        float o[12];
#pragma unroll
        for (int i = 0; i < 12; i++) o[i] = 0.f;

        if (!slow) {
            if (q == 1) {
                qa[4] = pack_bf16(-c0, 768.f); qa[5] = pack_bf16(-c1, 768.f);
                qa[6] = pack_bf16(0.f, -2.f); qa[7] = qa[6];
            }
            float s0[32], s1[32];
            uint32_t p0[16], p1[16];
            if (pass == 0) mbar_wait(bar0, 0);
            reg_fence(qa);
            reg_fence(o);
            wg_fence();
            issue_qk(s0, qa, dk0, dk1, 0);
            wg_commit();
            issue_qk(s1, qa, dk0, dk1, 1);
            wg_commit();
#pragma unroll 1
            for (int t = 0; t < 30; t += 2) {
                wg_wait<1>();
                reg_fence(s0);
                softmax_fast(s0, p0);
                reg_fence(p0);
                if (pass == 0) mbar_wait(bar0 + (t / 2 + 1) * 8, 0);
                wg_fence();
                issue_pv(o, p0, dv, t);
                issue_qk(s0, qa, dk0, dk1, t + 2);
                wg_commit();
                wg_wait<1>();
                reg_fence(s1);
                softmax_fast(s1, p1);
                reg_fence(p1);
                wg_fence();
                issue_pv(o, p1, dv, t + 1);
                issue_qk(s1, qa, dk0, dk1, t + 3);
                wg_commit();
            }
            wg_wait<1>();
            reg_fence(s0);
            softmax_fast(s0, p0);
            reg_fence(p0);
            wg_fence();
            issue_pv(o, p0, dv, 30);
            wg_commit();
            wg_wait<1>();
            reg_fence(s1);
            softmax_fast(s1, p1);
            reg_fence(p1);
            wg_fence();
            issue_pv(o, p1, dv, 31);
            wg_commit();
            wg_wait<0>();
            reg_fence(o);
        } else {
            float m0 = -INFINITY, m1 = -INFINITY;
            float s[32];
            uint32_t p[16];
#pragma unroll 1
            for (int t = 0; t < 32; t++) {
                if (pass == 0) mbar_wait(bar0 + (t / 2) * 8, 0);
                wg_fence();
                issue_qk(s, qa, dk0, dk1, t);
                wg_commit();
                wg_wait<0>();
                reg_fence(s);
                reg_fence(o);
                float a0 = m0, a1 = m1;
#pragma unroll
                for (int k = 0; k < 4; k++) {
#pragma unroll
                    for (int i = 4; i < 8; i++) s[k * 8 + i] *= 0.5f;
                    a0 = fmaxf(fmaxf(a0, fmaxf(s[k * 8 + 0], s[k * 8 + 1])), fmaxf(s[k * 8 + 4], s[k * 8 + 5]));
                    a1 = fmaxf(fmaxf(a1, fmaxf(s[k * 8 + 2], s[k * 8 + 3])), fmaxf(s[k * 8 + 6], s[k * 8 + 7]));
                }
                a0 = fmaxf(a0, __shfl_xor_sync(~0u, a0, 1)); a1 = fmaxf(a1, __shfl_xor_sync(~0u, a1, 1));
                a0 = fmaxf(a0, __shfl_xor_sync(~0u, a0, 2)); a1 = fmaxf(a1, __shfl_xor_sync(~0u, a1, 2));
                const float r0 = ex2(m0 - a0), r1 = ex2(m1 - a1);
                m0 = a0; m1 = a1;
#pragma unroll
                for (int i = 0; i < 3; i++) { o[i * 4] *= r0; o[i * 4 + 1] *= r0; o[i * 4 + 2] *= r1; o[i * 4 + 3] *= r1; }
#pragma unroll
                for (int k = 0; k < 8; k++) {
                    p[k * 2 + 0] = pack_bf16(ex2(s[k * 4 + 0] - m0), ex2(s[k * 4 + 1] - m0));
                    p[k * 2 + 1] = pack_bf16(ex2(s[k * 4 + 2] - m1), ex2(s[k * 4 + 3] - m1));
                }
                reg_fence(p);
                reg_fence(o);
                wg_fence();
                issue_pv(o, p, dv, t);
                wg_commit();
            }
            wg_wait<0>();
            reg_fence(o);
        }
        const float l0 = __shfl_sync(~0u, o[8], (lane & ~3) | 3), l1 = __shfl_sync(~0u, o[10], (lane & ~3) | 3);
        const float i0 = 1.0f / l0, i1 = 1.0f / l1;
        uint32_t* op0 = reinterpret_cast<uint32_t*>(g_O + (size_t)(row0 + g) * DM + head * DH);
        uint32_t* op1 = reinterpret_cast<uint32_t*>(g_O + (size_t)(row0 + g + 8) * DM + head * DH);
        op0[q] = pack_bf16(o[0] * i0, o[1] * i0);
        op1[q] = pack_bf16(o[2] * i1, o[3] * i1);
        op0[4 + q] = pack_bf16(o[4] * i0, o[5] * i0);
        op1[4 + q] = pack_bf16(o[6] * i1, o[7] * i1);
        if (q == 2) {
            op0[8] = pack_bf16(o[8] * i0, o[9] * i0);
            op1[8] = pack_bf16(o[10] * i1, o[11] * i1);
        }
    }
}

constexpr int K3_OFF_B = 9 * 16384;
constexpr int K3_OFF_BAR = K3_OFF_B + 9 * 8192;
constexpr int K3_SMEM = K3_OFF_BAR + 128;

__global__ void __launch_bounds__(256, 1)
k3_kernel(const __grid_constant__ CUtensorMap tmO, const __grid_constant__ CUtensorMap tmWo, const __nv_bfloat16* __restrict__ x,
          const __nv_bfloat16* __restrict__ b2, __nv_bfloat16* __restrict__ out) {
    extern __shared__ __align__(1024) uint8_t smem[];
    const uint32_t sb = s2u(smem);
    const int tid = threadIdx.x, warp = tid >> 5, lane = tid & 31;
    const int wg = warp >> 2, g = lane >> 2, q = lane & 3;
    const int rb = blockIdx.x / 9, t = blockIdx.x % 9;
    const uint32_t bar0 = sb + K3_OFF_BAR;
    if (tid == 0) {
        for (int i = 0; i < 9; i++) mbar_init(bar0 + i * 8, 1);
        fence_barrier_init();
    }
    __syncthreads();
    griddep_wait();
    if (warp == 0 && lane < 9) {
        mbar_expect(bar0 + lane * 8, 16384 + 8192);
        tma2d(sb + lane * 16384, &tmO, lane * 64, rb * 128, bar0 + lane * 8);
        tma2d(sb + K3_OFF_B + lane * 8192, &tmWo, t * 64, lane * 64, bar0 + lane * 8);
    }
    float acc[32];
    {
        const int r0 = rb * 128 + warp * 16 + g;
#pragma unroll
        for (int b = 0; b < 8; b++) {
            const int col = t * 64 + b * 8 + q * 2;
            const uint32_t bb = *reinterpret_cast<const uint32_t*>(b2 + col);
            const uint32_t x0 = *reinterpret_cast<const uint32_t*>(x + (size_t)r0 * DM + col);
            const uint32_t x1 = *reinterpret_cast<const uint32_t*>(x + (size_t)(r0 + 8) * DM + col);
            acc[b * 4 + 0] = bf_lo(x0) + bf_lo(bb); acc[b * 4 + 1] = bf_hi(x0) + bf_hi(bb);
            acc[b * 4 + 2] = bf_lo(x1) + bf_lo(bb); acc[b * 4 + 3] = bf_hi(x1) + bf_hi(bb);
        }
#pragma unroll
        for (int jj = 0; jj < 8; jj++) {
            const uint4* pp = g_part + ((size_t)(jj * 16 + rb) * 36 + t * 4) * 256 + tid;
#pragma unroll
            for (int s = 0; s < 4; s++) {
                const uint4 v = pp[s * 256];
                acc[s * 8 + 0] += bf_lo(v.x); acc[s * 8 + 1] += bf_hi(v.x); acc[s * 8 + 2] += bf_lo(v.y); acc[s * 8 + 3] += bf_hi(v.y);
                acc[s * 8 + 4] += bf_lo(v.z); acc[s * 8 + 5] += bf_hi(v.z); acc[s * 8 + 6] += bf_lo(v.w); acc[s * 8 + 7] += bf_hi(v.w);
            }
        }
    }
    const uint64_t da = mk_desc(sb + wg * 8192, 16, 1024, 1);
    const uint64_t db = mk_desc(sb + K3_OFF_B, 8192, 1024, 1);
#pragma unroll
    for (int kb = 0; kb < 9; kb++) {
        mbar_wait(bar0 + kb * 8, 0);
        wg_fence();
#pragma unroll
        for (int k = 0; k < 4; k++) wgmma_ss_n64<1>(acc, descA_step(da, kb * 4 + k), db + ((kb * 8192 + k * 2048) >> 4), 1);
        wg_commit();
    }
    wg_wait<0>();
    reg_fence(acc);
    const int r0 = rb * 128 + warp * 16 + g;
#pragma unroll
    for (int b = 0; b < 8; b++) {
        const int col = t * 64 + b * 8 + q * 2;
        *reinterpret_cast<uint32_t*>(out + (size_t)r0 * DM + col) = pack_bf16(acc[b * 4], acc[b * 4 + 1]);
        *reinterpret_cast<uint32_t*>(out + (size_t)(r0 + 8) * DM + col) = pack_bf16(acc[b * 4 + 2], acc[b * 4 + 3]);
    }
}

typedef CUresult (*EncodeFn)(CUtensorMap*, CUtensorMapDataType, cuuint32_t, void*, const cuuint64_t*, const cuuint64_t*, const cuuint32_t*,
                             const cuuint32_t*, CUtensorMapInterleave, CUtensorMapSwizzle, CUtensorMapL2promotion, CUtensorMapFloatOOBfill);

void make_map(EncodeFn fn, CUtensorMap* m, const void* base, int rank, const cuuint64_t* dims, const cuuint64_t* strides, const cuuint32_t* box) {
    cuuint32_t es[3] = {1, 1, 1};
    fn(m, CU_TENSOR_MAP_DATA_TYPE_BFLOAT16, rank, const_cast<void*>(base), dims, strides, box, es, CU_TENSOR_MAP_INTERLEAVE_NONE,
       CU_TENSOR_MAP_SWIZZLE_128B, CU_TENSOR_MAP_L2_PROMOTION_L2_256B, CU_TENSOR_MAP_FLOAT_OOB_FILL_NONE);
}

}

extern "C" void kernel_launch(void* const* d_in, const int* in_sizes, int n_in, void* d_out, int out_size) {
    const __nv_bfloat16* x = (const __nv_bfloat16*)d_in[0];
    const __nv_bfloat16* wqkv = (const __nv_bfloat16*)d_in[1];
    const __nv_bfloat16* wo = (const __nv_bfloat16*)d_in[2];
    const __nv_bfloat16* w1 = (const __nv_bfloat16*)d_in[4];
    const __nv_bfloat16* b1 = (const __nv_bfloat16*)d_in[5];
    const __nv_bfloat16* w2 = (const __nv_bfloat16*)d_in[6];
    const __nv_bfloat16* b2 = (const __nv_bfloat16*)d_in[7];
    __nv_bfloat16* out = (__nv_bfloat16*)d_out;

    EncodeFn fn = nullptr;
    cudaDriverEntryPointQueryResult qr;
    cudaGetDriverEntryPoint("cuTensorMapEncodeTiled", (void**)&fn, cudaEnableDefault, &qr);
    void* gO = nullptr;
    cudaGetSymbolAddress(&gO, g_O);
    CUtensorMap tmQ3, tmQ1, tm1a, tm1b, tm2, tmO, tmWo;
    {
        cuuint64_t d[3] = {3 * DM, DM, 3}, s[2] = {3 * DM * 2, 128};
        cuuint32_t b[3] = {64, 16, 3};
        make_map(fn, &tmQ3, wqkv, 3, d, s, b);
        make_map(fn, &tmQ1, wqkv, 2, d, s, b);
    }
    {
        cuuint64_t d[3] = {64, DM, FF / 64}, s[2] = {FF * 2, 128};
        cuuint32_t ba[3] = {64, 48, 1}, bb[3] = {64, 32, 2};
        make_map(fn, &tm1a, w1, 3, d, s, ba);
        make_map(fn, &tm1b, w1, 3, d, s, bb);
    }
    {
        cuuint64_t d[2] = {DM, FF}, s[1] = {DM * 2};
        cuuint32_t b[2] = {64, 48};
        make_map(fn, &tm2, w2, 2, d, s, b);
    }
    {
        cuuint64_t d[2] = {DM, SEQ}, s[1] = {DM * 2};
        cuuint32_t b[2] = {64, 128};
        make_map(fn, &tmO, gO, 2, d, s, b);
        cuuint64_t d2[2] = {DM, DM};
        cuuint32_t b2x[2] = {64, 64};
        make_map(fn, &tmWo, wo, 2, d2, s, b2x);
    }
    cudaFuncSetAttribute(k1_kernel, cudaFuncAttributeMaxDynamicSharedMemorySize, K1_SMEM);
    cudaFuncSetAttribute(k2_kernel, cudaFuncAttributeMaxDynamicSharedMemorySize, K2_SMEM);
    cudaFuncSetAttribute(k3_kernel, cudaFuncAttributeMaxDynamicSharedMemorySize, K3_SMEM);

    cudaStream_t st = cudaStreamPerThread;
    cudaLaunchAttribute pdl[1];
    pdl[0].id = cudaLaunchAttributeProgrammaticStreamSerialization;
    pdl[0].val.programmaticStreamSerializationAllowed = 1;
    {
        cudaLaunchConfig_t cfg = {};
        cfg.gridDim = dim3(128); cfg.blockDim = dim3(384); cfg.dynamicSmemBytes = K1_SMEM; cfg.stream = st;
        cudaLaunchKernelEx(&cfg, k1_kernel, tmQ3, tmQ1, tm1a, tm1b, tm2, x, b1);
    }
    {
        cudaLaunchConfig_t cfg = {};
        cfg.gridDim = dim3(128); cfg.blockDim = dim3(512); cfg.dynamicSmemBytes = K2_SMEM; cfg.stream = st;
        cfg.attrs = pdl; cfg.numAttrs = 1;
        cudaLaunchKernelEx(&cfg, k2_kernel);
    }
    {
        cudaLaunchConfig_t cfg = {};
        cfg.gridDim = dim3(144); cfg.blockDim = dim3(256); cfg.dynamicSmemBytes = K3_SMEM; cfg.stream = st;
        cfg.attrs = pdl; cfg.numAttrs = 1;
        cudaLaunchKernelEx(&cfg, k3_kernel, tmO, tmWo, x, b2, out);
    }
}
```

```cpp
#include <cuda_runtime.h>
#include <cuda_bf16.h>
#include <cuda.h>
#include <stdint.h>

#define PROF(i) do { } while (0)
#define PROF_WG 0

namespace {

constexpr int SEQ = 2048, DM = 576, FF = 4608, NH = 32, DH = 18;

constexpr int KV_GROUP_BYTES = 5 * 128;
constexpr int KV_HEAD_BYTES = (SEQ / 8) * KV_GROUP_BYTES;
constexpr int Q_OFFSET = NH * KV_HEAD_BYTES;
__device__ __align__(1024) uint8_t g_QKV[2 * NH * KV_HEAD_BYTES];
__device__ __align__(1024) float g_kmax[NH * 64];
__device__ __align__(1024) uint4 g_part[8 * 16 * 36 * 256];
__device__ __align__(1024) __nv_bfloat16 g_O[SEQ * DM];

__device__ __forceinline__ uint32_t s2u(const void* p) { return (uint32_t)__cvta_generic_to_shared(p); }
__device__ __forceinline__ void mbar_init(uint32_t b, int c) { asm volatile("mbarrier.init.shared::cta.b64 [%0], %1;" ::"r"(b), "r"(c) : "memory"); }
__device__ __forceinline__ void mbar_expect(uint32_t b, uint32_t bytes) {
    asm volatile("mbarrier.arrive.expect_tx.shared::cta.b64 _, [%0], %1;" ::"r"(b), "r"(bytes) : "memory");
}
__device__ __forceinline__ void mbar_wait(uint32_t b, uint32_t parity) {
    asm volatile(
        "{\n.reg .pred p;\n.reg .u32 c;\n"
        "mbarrier.try_wait.parity.shared::cta.b64 p, [%0], %1;\n"
        "@p bra DONE;\n"
        "mov.u32 c, 0;\n"
        "LOOP:\n"
        "mbarrier.try_wait.parity.shared::cta.b64 p, [%0], %1;\n"
        "@p bra DONE;\n"
        "add.u32 c, c, 1;\n"
        "setp.lt.u32 p, c, 4194304;\n"
        "@p bra LOOP;\n"
        "trap;\n"
        "DONE:\n}\n" ::"r"(b), "r"(parity) : "memory");
}
__device__ __forceinline__ void fence_barrier_init() { asm volatile("fence.mbarrier_init.release.cluster;" ::: "memory"); }
__device__ __forceinline__ void fence_proxy_async() { asm volatile("fence.proxy.async.shared::cta;" ::: "memory"); }
__device__ __forceinline__ void cluster_arrive() { asm volatile("barrier.cluster.arrive.relaxed.aligned;" ::: "memory"); }
__device__ __forceinline__ void cluster_wait() { asm volatile("barrier.cluster.wait.aligned;" ::: "memory"); }
__device__ __forceinline__ void named_bar_sync(int id, int n) { asm volatile("bar.sync %0, %1;" ::"r"(id), "r"(n) : "memory"); }
__device__ __forceinline__ void griddep_wait() { asm volatile("griddepcontrol.wait;" ::: "memory"); }
__device__ __forceinline__ void griddep_launch() { asm volatile("griddepcontrol.launch_dependents;" ::: "memory"); }

__device__ __forceinline__ void tma3d_mc(uint32_t dst, const CUtensorMap* tm, int c0, int c1, int c2, uint32_t bar, uint16_t mask) {
    asm volatile("cp.async.bulk.tensor.3d.shared::cluster.global.mbarrier::complete_tx::bytes.multicast::cluster [%0], [%1, {%3, %4, %5}], [%2], %6;"
                 ::"r"(dst), "l"(tm), "r"(bar), "r"(c0), "r"(c1), "r"(c2), "h"(mask) : "memory");
}
__device__ __forceinline__ void tma2d_mc(uint32_t dst, const CUtensorMap* tm, int c0, int c1, uint32_t bar, uint16_t mask) {
    asm volatile("cp.async.bulk.tensor.2d.shared::cluster.global.mbarrier::complete_tx::bytes.multicast::cluster [%0], [%1, {%3, %4}], [%2], %5;"
                 ::"r"(dst), "l"(tm), "r"(bar), "r"(c0), "r"(c1), "h"(mask) : "memory");
}
__device__ __forceinline__ void tma3d(uint32_t dst, const CUtensorMap* tm, int c0, int c1, int c2, uint32_t bar) {
    asm volatile("cp.async.bulk.tensor.3d.shared::cluster.global.mbarrier::complete_tx::bytes [%0], [%1, {%3, %4, %5}], [%2];"
                 ::"r"(dst), "l"(tm), "r"(bar), "r"(c0), "r"(c1), "r"(c2) : "memory");
}
__device__ __forceinline__ void tma2d(uint32_t dst, const CUtensorMap* tm, int c0, int c1, uint32_t bar) {
    asm volatile("cp.async.bulk.tensor.2d.shared::cluster.global.mbarrier::complete_tx::bytes [%0], [%1, {%3, %4}], [%2];"
                 ::"r"(dst), "l"(tm), "r"(bar), "r"(c0), "r"(c1) : "memory");
}
__device__ __forceinline__ void bulk_load(uint32_t dst, const void* src, uint32_t bytes, uint32_t bar) {
    asm volatile("cp.async.bulk.shared::cluster.global.mbarrier::complete_tx::bytes [%0], [%1], %2, [%3];"
                 ::"r"(dst), "l"(src), "r"(bytes), "r"(bar) : "memory");
}
__device__ __forceinline__ void prefetch_tmap(const CUtensorMap* tm) { asm volatile("prefetch.tensormap [%0];" ::"l"(tm) : "memory"); }

__device__ __forceinline__ void wg_fence() { asm volatile("wgmma.fence.sync.aligned;" ::: "memory"); }
__device__ __forceinline__ void wg_commit() { asm volatile("wgmma.commit_group.sync.aligned;" ::: "memory"); }
template <int N> __device__ __forceinline__ void wg_wait() { asm volatile("wgmma.wait_group.sync.aligned %0;" ::"n"(N) : "memory"); }
template <int N> __device__ __forceinline__ void reg_fence(float (&d)[N]) {
#pragma unroll
    for (int i = 0; i < N; i++) asm volatile("" : "+f"(d[i])::"memory");
}
template <int N> __device__ __forceinline__ void reg_fence(uint32_t (&d)[N]) {
#pragma unroll
    for (int i = 0; i < N; i++) asm volatile("" : "+r"(d[i])::"memory");
}
template <int R> __device__ __forceinline__ void reg_alloc() { asm volatile("setmaxnreg.inc.sync.aligned.u32 %0;" ::"n"(R)); }
template <int R> __device__ __forceinline__ void reg_dealloc() { asm volatile("setmaxnreg.dec.sync.aligned.u32 %0;" ::"n"(R)); }

__device__ __forceinline__ uint64_t mk_desc(uint32_t addr, uint32_t lbo, uint32_t sbo, uint32_t swz) {
    return (uint64_t)((addr & 0x3FFFF) >> 4) | ((uint64_t)(lbo >> 4) << 16) | ((uint64_t)(sbo >> 4) << 32) | ((uint64_t)swz << 62);
}
__device__ __forceinline__ uint32_t pack_bf16(float lo, float hi) {
    uint32_t r;
    asm("cvt.rn.bf16x2.f32 %0, %1, %2;" : "=r"(r) : "f"(hi), "f"(lo));
    return r;
}
__device__ __forceinline__ float bf_lo(uint32_t w) { return __uint_as_float(w << 16); }
__device__ __forceinline__ float bf_hi(uint32_t w) { return __uint_as_float(w & 0xFFFF0000u); }
__device__ __forceinline__ float ex2(float x) {
    float r;
    asm("ex2.approx.ftz.f32 %0, %1;" : "=f"(r) : "f"(x));
    return r;
}
__device__ __forceinline__ float tanh_fast(float x) {
    float r;
    asm("tanh.approx.f32 %0, %1;" : "=f"(r) : "f"(x));
    return r;
}
__device__ __forceinline__ float gelu_tanh(float u) {
    float w = fmaf(u * u, 0.0356774081f, 0.7978845608f);
    float t = tanh_fast(u * w);
    float h = 0.5f * u;
    return fmaf(h, t, h);
}

template<int TB> __device__ __forceinline__ void wgmma_ss_n216(float (&d)[108], uint64_t da, uint64_t db, int sd) {
    asm volatile("{\n.reg .pred p;\nsetp.ne.b32 p, %110, 0;\n"
      "wgmma.mma_async.sync.aligned.m64n216k16.f32.bf16.bf16 {%0, %1, %2, %3, %4, %5, %6, %7, %8, %9, %10, %11, %12, %13, %14, %15, %16, %17, %18, %19, %20, %21, %22, %23, %24, %25, %26, %27, %28, %29, %30, %31, %32, %33, %34, %35, %36, %37, %38, %39, %40, %41, %42, %43, %44, %45, %46, %47, %48, %49, %50, %51, %52, %53, %54, %55, %56, %57, %58, %59, %60, %61, %62, %63, %64, %65, %66, %67, %68, %69, %70, %71, %72, %73, %74, %75, %76, %77, %78, %79, %80, %81, %82, %83, %84, %85, %86, %87, %88, %89, %90, %91, %92, %93, %94, %95, %96, %97, %98, %99, %100, %101, %102, %103, %104, %105, %106, %107}, %108, %109, p, 1, 1, 0, %111;\n}\n"
      : "+f"(d[0]), "+f"(d[1]), "+f"(d[2]), "+f"(d[3]), "+f"(d[4]), "+f"(d[5]), "+f"(d[6]), "+f"(d[7]), "+f"(d[8]), "+f"(d[9]), "+f"(d[10]), "+f"(d[11]), "+f"(d[12]), "+f"(d[13]), "+f"(d[14]), "+f"(d[15]), "+f"(d[16]), "+f"(d[17]), "+f"(d[18]), "+f"(d[19]), "+f"(d[20]), "+f"(d[21]), "+f"(d[22]), "+f"(d[23]), "+f"(d[24]), "+f"(d[25]), "+f"(d[26]), "+f"(d[27]), "+f"(d[28]), "+f"(d[29]), "+f"(d[30]), "+f"(d[31]), "+f"(d[32]), "+f"(d[33]), "+f"(d[34]), "+f"(d[35]), "+f"(d[36]), "+f"(d[37]), "+f"(d[38]), "+f"(d[39]), "+f"(d[40]), "+f"(d[41]), "+f"(d[42]), "+f"(d[43]), "+f"(d[44]), "+f"(d[45]), "+f"(d[46]), "+f"(d[47]), "+f"(d[48]), "+f"(d[49]), "+f"(d[50]), "+f"(d[51]), "+f"(d[52]), "+f"(d[53]), "+f"(d[54]), "+f"(d[55]), "+f"(d[56]), "+f"(d[57]), "+f"(d[58]), "+f"(d[59]), "+f"(d[60]), "+f"(d[61]), "+f"(d[62]), "+f"(d[63]), "+f"(d[64]), "+f"(d[65]), "+f"(d[66]), "+f"(d[67]), "+f"(d[68]), "+f"(d[69]), "+f"(d[70]), "+f"(d[71]), "+f"(d[72]), "+f"(d[73]), "+f"(d[74]), "+f"(d[75]), "+f"(d[76]), "+f"(d[77]), "+f"(d[78]), "+f"(d[79]), "+f"(d[80]), "+f"(d[81]), "+f"(d[82]), "+f"(d[83]), "+f"(d[84]), "+f"(d[85]), "+f"(d[86]), "+f"(d[87]), "+f"(d[88]), "+f"(d[89]), "+f"(d[90]), "+f"(d[91]), "+f"(d[92]), "+f"(d[93]), "+f"(d[94]), "+f"(d[95]), "+f"(d[96]), "+f"(d[97]), "+f"(d[98]), "+f"(d[99]), "+f"(d[100]), "+f"(d[101]), "+f"(d[102]), "+f"(d[103]), "+f"(d[104]), "+f"(d[105]), "+f"(d[106]), "+f"(d[107])
      : "l"(da), "l"(db), "r"(sd), "n"(TB));
}

template<int TB> __device__ __forceinline__ void wgmma_ss_n64(float (&d)[32], uint64_t da, uint64_t db, int sd) {
    asm volatile("{\n.reg .pred p;\nsetp.ne.b32 p, %34, 0;\n"
      "wgmma.mma_async.sync.aligned.m64n64k16.f32.bf16.bf16 {%0, %1, %2, %3, %4, %5, %6, %7, %8, %9, %10, %11, %12, %13, %14, %15, %16, %17, %18, %19, %20, %21, %22, %23, %24, %25, %26, %27, %28, %29, %30, %31}, %32, %33, p, 1, 1, 0, %35;\n}\n"
      : "+f"(d[0]), "+f"(d[1]), "+f"(d[2]), "+f"(d[3]), "+f"(d[4]), "+f"(d[5]), "+f"(d[6]), "+f"(d[7]), "+f"(d[8]), "+f"(d[9]), "+f"(d[10]), "+f"(d[11]), "+f"(d[12]), "+f"(d[13]), "+f"(d[14]), "+f"(d[15]), "+f"(d[16]), "+f"(d[17]), "+f"(d[18]), "+f"(d[19]), "+f"(d[20]), "+f"(d[21]), "+f"(d[22]), "+f"(d[23]), "+f"(d[24]), "+f"(d[25]), "+f"(d[26]), "+f"(d[27]), "+f"(d[28]), "+f"(d[29]), "+f"(d[30]), "+f"(d[31])
      : "l"(da), "l"(db), "r"(sd), "n"(TB));
}

template<int TB> __device__ __forceinline__ void wgmma_rs_n64(float (&d)[32], uint32_t a0, uint32_t a1, uint32_t a2, uint32_t a3, uint64_t db, int sd) {
    asm volatile("{\n.reg .pred p;\nsetp.ne.b32 p, %37, 0;\n"
      "wgmma.mma_async.sync.aligned.m64n64k16.f32.bf16.bf16 {%0, %1, %2, %3, %4, %5, %6, %7, %8, %9, %10, %11, %12, %13, %14, %15, %16, %17, %18, %19, %20, %21, %22, %23, %24, %25, %26, %27, %28, %29, %30, %31}, {%32, %33, %34, %35}, %36, p, 1, 1, %38;\n}\n"
      : "+f"(d[0]), "+f"(d[1]), "+f"(d[2]), "+f"(d[3]), "+f"(d[4]), "+f"(d[5]), "+f"(d[6]), "+f"(d[7]), "+f"(d[8]), "+f"(d[9]), "+f"(d[10]), "+f"(d[11]), "+f"(d[12]), "+f"(d[13]), "+f"(d[14]), "+f"(d[15]), "+f"(d[16]), "+f"(d[17]), "+f"(d[18]), "+f"(d[19]), "+f"(d[20]), "+f"(d[21]), "+f"(d[22]), "+f"(d[23]), "+f"(d[24]), "+f"(d[25]), "+f"(d[26]), "+f"(d[27]), "+f"(d[28]), "+f"(d[29]), "+f"(d[30]), "+f"(d[31])
      : "r"(a0), "r"(a1), "r"(a2), "r"(a3), "l"(db), "r"(sd), "n"(TB));
}

template<int TB> __device__ __forceinline__ void wgmma_rs_n24(float (&d)[12], uint32_t a0, uint32_t a1, uint32_t a2, uint32_t a3, uint64_t db, int sd) {
    asm volatile("{\n.reg .pred p;\nsetp.ne.b32 p, %17, 0;\n"
      "wgmma.mma_async.sync.aligned.m64n24k16.f32.bf16.bf16 {%0, %1, %2, %3, %4, %5, %6, %7, %8, %9, %10, %11}, {%12, %13, %14, %15}, %16, p, 1, 1, %18;\n}\n"
      : "+f"(d[0]), "+f"(d[1]), "+f"(d[2]), "+f"(d[3]), "+f"(d[4]), "+f"(d[5]), "+f"(d[6]), "+f"(d[7]), "+f"(d[8]), "+f"(d[9]), "+f"(d[10]), "+f"(d[11])
      : "r"(a0), "r"(a1), "r"(a2), "r"(a3), "l"(db), "r"(sd), "n"(TB));
}

constexpr int K1_XN_BYTES = 16 * 9216;
constexpr int K1_SLOT = 16384, K1_NSLOT = 5;
constexpr int K1_OFF_RING = K1_XN_BYTES;
constexpr int K1_OFF_BIAS = K1_OFF_RING + K1_NSLOT * K1_SLOT;
constexpr int K1_OFF_BAR = K1_OFF_BIAS + 576 * 4;
constexpr int K1_SMEM = K1_OFF_BAR + 256;
constexpr float QSCALE = 0.23570226039551584f * 1.4426950408889634f;

struct Ring {
    uint32_t slot, phase;
    __device__ __forceinline__ void advance() {
        if (++slot == K1_NSLOT) { slot = 0; phase ^= 1; }
    }
};

struct K1Ctx {
    uint32_t full0;
    uint32_t rel_addr;
    uint64_t descA, descB;
    Ring rd;
    uint32_t prev_slot;
    __device__ __forceinline__ uint64_t begin_stage() {
        mbar_wait(full0 + rd.slot * 8, rd.phase);
        wg_fence();
        return descB + rd.slot * (K1_SLOT >> 4);
    }
    __device__ __forceinline__ void end_stage() {
        wg_commit();
        wg_wait<1>();
        if (rel_addr) asm volatile("mbarrier.arrive.shared::cluster.b64 _, [%0];" ::"r"(rel_addr + prev_slot * 8) : "memory");
        prev_slot = rd.slot;
        rd.advance();
    }
};

__device__ __forceinline__ uint64_t descA_step(uint64_t base, int ks) { return base + (uint64_t)(((ks >> 2) * 1024 + (ks & 3) * 32) >> 4); }

template <int V> struct IC { static constexpr int value = V; };
template <int I, int N, class F> __device__ __forceinline__ void static_for(F&& f) {
    if constexpr (I < N) { f(IC<I>{}); static_for<I + 1, N>(f); }
}

template <bool A_RS, bool B_RS, class Epi>
__device__ __forceinline__ void tile_pair(K1Ctx& c, float (&accA)[32], float (&accB)[32], uint32_t (&h)[144], Epi&& epi) {
    static_for<0, 9>([&](auto sc) {
        constexpr int s = decltype(sc)::value;
        const uint64_t db = c.begin_stage();
#pragma unroll
        for (int t = 0; t < 8; t++) {
            const int kk = s * 8 + t, ks = kk % 36;
            const uint64_t dbt = db + ((t * 2048) >> 4);
            if (kk < 36) {
                if constexpr (A_RS) wgmma_rs_n64<1>(accA, h[ks * 4], h[ks * 4 + 1], h[ks * 4 + 2], h[ks * 4 + 3], dbt, ks != 0);
                else wgmma_ss_n64<1>(accA, descA_step(c.descA, ks), dbt, ks != 0);
            } else {
                if constexpr (B_RS) wgmma_rs_n64<1>(accB, h[ks * 4], h[ks * 4 + 1], h[ks * 4 + 2], h[ks * 4 + 3], dbt, ks != 0);
                else wgmma_ss_n64<1>(accB, descA_step(c.descA, ks), dbt, ks != 0);
            }
        }
        c.end_stage();
        epi(sc);
    });
}

template <int B0, int NB, int HOFF>
__device__ __forceinline__ void gelu_blocks(const float (&acc)[32], uint32_t (&h)[144], const float* bias  ) {
#pragma unroll
    for (int b = B0; b < B0 + NB; b++) {
        const float2 bb = *reinterpret_cast<const float2*>(bias + b * 8);
        const float v0 = gelu_tanh(acc[b * 4 + 0] + bb.x), v1 = gelu_tanh(acc[b * 4 + 1] + bb.y);
        const float v2 = gelu_tanh(acc[b * 4 + 2] + bb.x), v3 = gelu_tanh(acc[b * 4 + 3] + bb.y);
        h[HOFF + b * 2 + 0] = pack_bf16(v0, v1);
        h[HOFF + b * 2 + 1] = pack_bf16(v2, v3);
    }
}
template <int S> __device__ __forceinline__ void store_part(const float (&o)[32], uint4* p) {
    uint4 v;
    v.x = pack_bf16(o[S * 8 + 0], o[S * 8 + 1]); v.y = pack_bf16(o[S * 8 + 2], o[S * 8 + 3]);
    v.z = pack_bf16(o[S * 8 + 4], o[S * 8 + 5]); v.w = pack_bf16(o[S * 8 + 6], o[S * 8 + 7]);
    p[S * 256] = v;
}

__global__ void __cluster_dims__(2, 1, 1) __launch_bounds__(384, 1)
k1_kernel(const __grid_constant__ CUtensorMap tmX, const __grid_constant__ CUtensorMap tmQ3, const __grid_constant__ CUtensorMap tmQ1,
          const __grid_constant__ CUtensorMap tm1, const __grid_constant__ CUtensorMap tm2, const __nv_bfloat16* __restrict__ b1) {
    extern __shared__ __align__(1024) uint8_t smem[];
    const uint32_t sb = s2u(smem);
    const int tid = threadIdx.x, lane = tid & 31;
    const int warp = __shfl_sync(~0u, tid >> 5, 0);
    const uint32_t rank = blockIdx.x & 1;
    const int cl = blockIdx.x >> 1;
    const int rb = (cl & 7) * 2 + rank;
    const int j = cl >> 3;
    const uint32_t full0 = sb + K1_OFF_BAR, empty0 = full0 + 8 * K1_NSLOT, xbar0 = full0 + 128;

    if (warp < 8) {
        PROF(0);
        if (lane == 0) {
            mbar_init(xbar0 + warp * 16, 1);
            mbar_init(xbar0 + warp * 16 + 8, 1);
            fence_barrier_init();
            mbar_expect(xbar0 + warp * 16, 9216);
            tma3d(sb + warp * 2 * 9216, &tmX, 0, rb * 128 + warp * 16, 0, xbar0 + warp * 16);
            mbar_expect(xbar0 + warp * 16 + 8, 9216);
            tma3d(sb + (warp * 2 + 1) * 9216, &tmX, 0, rb * 128 + warp * 16 + 8, 0, xbar0 + warp * 16 + 8);
        }
        __syncwarp();
        cluster_arrive();
        reg_alloc<240>();
#pragma unroll 1
        for (int p = 0; p < 4; p++) {
            mbar_wait(xbar0 + warp * 16 + (p >> 1) * 8, 0);
            uint4* row = reinterpret_cast<uint4*>(smem + (warp * 2 + (p >> 1)) * 9216 + (p & 1) * 512 + lane * 16);
            float f[72];
#pragma unroll
            for (int i = 0; i < 9; i++) {
                const uint4 v = row[i * 64];
                f[i * 8 + 0] = bf_lo(v.x); f[i * 8 + 1] = bf_hi(v.x); f[i * 8 + 2] = bf_lo(v.y); f[i * 8 + 3] = bf_hi(v.y);
                f[i * 8 + 4] = bf_lo(v.z); f[i * 8 + 5] = bf_hi(v.z); f[i * 8 + 6] = bf_lo(v.w); f[i * 8 + 7] = bf_hi(v.w);
            }
            float s0 = 0.f, s1 = 0.f, s2 = 0.f, s3 = 0.f;
#pragma unroll
            for (int i = 0; i < 72; i += 4) { s0 += f[i]; s1 += f[i + 1]; s2 += f[i + 2]; s3 += f[i + 3]; }
            float sm = (s0 + s1) + (s2 + s3);
            sm += __shfl_xor_sync(~0u, sm, 1); sm += __shfl_xor_sync(~0u, sm, 2); sm += __shfl_xor_sync(~0u, sm, 4);
            const float mean = sm * (1.0f / DM);
            s0 = s1 = s2 = s3 = 0.f;
#pragma unroll
            for (int i = 0; i < 72; i += 4) {
                f[i] -= mean; f[i + 1] -= mean; f[i + 2] -= mean; f[i + 3] -= mean;
                s0 = fmaf(f[i], f[i], s0); s1 = fmaf(f[i + 1], f[i + 1], s1);
                s2 = fmaf(f[i + 2], f[i + 2], s2); s3 = fmaf(f[i + 3], f[i + 3], s3);
            }
            float sq = (s0 + s1) + (s2 + s3);
            sq += __shfl_xor_sync(~0u, sq, 1); sq += __shfl_xor_sync(~0u, sq, 2); sq += __shfl_xor_sync(~0u, sq, 4);
            const float rstd = rsqrtf(sq * (1.0f / DM) + 1e-5f);
#pragma unroll
            for (int i = 0; i < 9; i++) {
                uint4 o;
                o.x = pack_bf16(f[i * 8 + 0] * rstd, f[i * 8 + 1] * rstd);
                o.y = pack_bf16(f[i * 8 + 2] * rstd, f[i * 8 + 3] * rstd);
                o.z = pack_bf16(f[i * 8 + 4] * rstd, f[i * 8 + 5] * rstd);
                o.w = pack_bf16(f[i * 8 + 6] * rstd, f[i * 8 + 7] * rstd);
                row[i * 64] = o;
            }
        }
        const int wg = warp >> 2, wq = warp & 3;
        fence_proxy_async();
        named_bar_sync(1 + wg, 128);
        cluster_wait();
        PROF(1);

        const int g = lane >> 2, q = lane & 3;
        K1Ctx c;
        c.full0 = full0;
        c.rel_addr = 0;
        c.descA = mk_desc(sb + wg * 8 * 9216, 16, 9216, 1);
        c.descB = mk_desc(sb + K1_OFF_RING, 2048, 1024, 1);
        c.rd.slot = 0; c.rd.phase = 0; c.prev_slot = 0;
        const float* biasq = reinterpret_cast<const float*>(smem + K1_OFF_BIAS) + 2 * q;

        uint32_t h[144];
        float accA[32], accB[32];
        {
            float accQ[108];
            uint32_t rel = 0;
            if (lane == 0 && wq < 2) asm("mapa.shared::cluster.u32 %0, %1, %2;" : "=r"(rel) : "r"(empty0), "r"(wq));
#pragma unroll 1
            for (int s = 0; s < 18; s++) {
                const uint64_t db = c.begin_stage();
                const uint64_t da = c.descA + (uint64_t)((s >> 1) * 64 + (s & 1) * 4);
                wgmma_ss_n216<1>(accQ, da, db, s != 0);
                wgmma_ss_n216<1>(accQ, da + 2, db + (8192 >> 4), 1);
                c.end_stage();
                c.rel_addr = rel;
            }
            PROF(2);
            uint32_t rel9[9];
#pragma unroll
            for (int i9 = 0; i9 < 9; i9++) {
                const int p = 4 * i9 + q, hh = (p * 57) >> 9, r = p - 9 * hh;
                rel9[i9] = hh * KV_HEAD_BYTES + (r < 8 ? (r >> 2) * 128 + (r & 3) * 4 : 0);
            }
            uint32_t gb = 0, o2 = 0;
            float scl0 = 1.f, scl1 = 1.f;
            tile_pair<false, false>(c, accA, accB, h, [&](auto sc) {
                constexpr int s = decltype(sc)::value;
                if constexpr (s == 0) reg_fence(accQ);
                if constexpr (s < 6) {
                    constexpr int grp = s / 2, part = s % 2;
                    if constexpr (part == 0) {
                        const int G = 3 * j + grp, type = G >> 3;
                        gb = (G & 7) * 4 * KV_HEAD_BYTES + (rb * 16 + warp * 2) * KV_GROUP_BYTES + g * 16 + (type == 0 ? Q_OFFSET : (type == 2 ? 256 : 0));
                        o2 = type == 0 ? 256 : (type == 2 ? 264 : 512);
                        scl0 = type == 0 ? QSCALE : 1.f;
                        scl1 = type == 0 ? QSCALE : (type == 1 ? 2.f : 1.f);
                    }
#pragma unroll
                    for (int i9 = part * 5; i9 < (part ? 9 : 5); i9++) {
                        const int b = grp * 9 + i9;
                        uint32_t off = gb + rel9[i9];
                        if (i9 >= 2 && (i9 & 1) == 0) off += (q == i9 / 2 - 1) ? o2 : 0;
                        *reinterpret_cast<uint32_t*>(g_QKV + off) = pack_bf16(accQ[b * 4] * scl0, accQ[b * 4 + 1] * scl0);
                        *reinterpret_cast<uint32_t*>(g_QKV + off + KV_GROUP_BYTES) = pack_bf16(accQ[b * 4 + 2] * scl1, accQ[b * 4 + 3] * scl1);
                    }
                    if constexpr (s == 5) asm volatile("bar.arrive 3, 352;" ::: "memory");
                }
                if constexpr (s == 5) { named_bar_sync(4, 288); reg_fence(accA); }
                if constexpr (s >= 5) gelu_blocks<(s - 5) * 2, 2, 96>(accA, h, biasq);
            });
        }
        PROF(3);
#pragma unroll
        for (int i = 32; i < 96; i++) asm volatile("mov.u32 %0, 0;" : "=r"(h[i]));
#pragma unroll 1
        for (int p = 1; p < 4; p++) {
            const float* bp = biasq + p * 128 - 64;
            tile_pair<false, false>(c, accA, accB, h, [&](auto sc) {
                constexpr int s = decltype(sc)::value;
                if constexpr (s == 0) {
                    reg_fence(accB);
#pragma unroll
                    for (int i = 0; i < 80; i++) h[i] = h[i + 32];
                }
                if constexpr (s < 4) gelu_blocks<s * 2, 2, 80>(accB, h, bp);
                if constexpr (s == 5) reg_fence(accA);
                if constexpr (s >= 5) gelu_blocks<(s - 5) * 2, 2, 96>(accA, h, bp + 64);
            });
        }
        PROF(4);
        tile_pair<false, true>(c, accA, accB, h, [&](auto sc) {
            constexpr int s = decltype(sc)::value;
            if constexpr (s == 0) reg_fence(accB);
            if constexpr (s < 4) gelu_blocks<s * 2, 2, 112>(accB, h, biasq + 448);
            if constexpr (s == 5) reg_fence(accA);
            if constexpr (s == 5 || s == 6) gelu_blocks<(s - 5) * 3, 3, 128>(accA, h, biasq + 512);
            if constexpr (s == 7) gelu_blocks<6, 2, 128>(accA, h, biasq + 512);
            if constexpr (s == 3 || s == 7) reg_fence(h);
        });
        PROF(5);
        uint4* pout = g_part + ((size_t)(j * 16 + rb) * 36) * 256 + tid;
#pragma unroll 1
        for (int p = 0; p < 4; p++) {
            tile_pair<true, true>(c, accA, accB, h, [&](auto sc) {
                constexpr int s = decltype(sc)::value;
                if constexpr (s == 0) reg_fence(accB);
                if constexpr (s < 4) store_part<s>(accB, pout);
                if constexpr (s == 5) reg_fence(accA);
                if constexpr (s >= 5) store_part<s - 5>(accA, pout + 1024);
            });
            pout += 2048;
            PROF(6 + p);
        }
        wg_wait<0>();
        reg_fence(accB);
        store_part<0>(accB, pout); store_part<1>(accB, pout); store_part<2>(accB, pout); store_part<3>(accB, pout);
        PROF(10);
        cluster_arrive();
        cluster_wait();
        PROF(11);
    } else {
        reg_dealloc<24>();
        if (warp == 8 && lane == 0) {
            prefetch_tmap(&tmQ3); prefetch_tmap(&tmQ1); prefetch_tmap(&tm1); prefetch_tmap(&tm2);
            for (int i = 0; i < K1_NSLOT; i++) { mbar_init(full0 + i * 8, 1); mbar_init(empty0 + i * 8, 4); }
            fence_barrier_init();
        }
        __syncwarp();
        cluster_arrive();
        cluster_wait();
        if (warp == 8) {
            if (lane == 0) {
                Ring w{0, 1};
                const uint32_t dst0 = sb + K1_OFF_RING + rank * 8192;
#pragma unroll 1
                for (int s = 0; s < 18; s++) {
                    mbar_wait(empty0 + w.slot * 8, w.phase);
                    mbar_expect(full0 + w.slot * 8, 16384);
                    const uint32_t dst = dst0 + w.slot * K1_SLOT;
                    tma3d_mc(dst, &tmQ3, j * 216, s * 32 + rank * 16, 0, full0 + w.slot * 8, 3);
                    tma2d_mc(dst + 6144, &tmQ1, j * 216 + 192, s * 32 + rank * 16, full0 + w.slot * 8, 3);
                    w.advance();
                }
                int tile = 0, kb = rank;
#pragma unroll 1
                for (int s = 0; s < 81; s++) {
                    mbar_wait(empty0 + w.slot * 8, w.phase);
                    mbar_expect(full0 + w.slot * 8, 16384);
                    const uint32_t dst = dst0 + w.slot * K1_SLOT;
                    if (tile < 9) tma2d_mc(dst, &tm1, j * 576 + tile * 64, kb * 64, full0 + w.slot * 8, 3);
                    else tma2d_mc(dst, &tm2, (tile - 9) * 64, j * 576 + kb * 64, full0 + w.slot * 8, 3);
                    kb += 2;
                    if (kb >= 9) { kb -= 9; tile++; }
                    w.advance();
                }
            }
        } else {
            const int ht = tid - 288;
            if (warp == 9) {
                float* sbias = reinterpret_cast<float*>(smem + K1_OFF_BIAS);
#pragma unroll 1
                for (int i = lane; i < 288; i += 32) {
                    const uint32_t w2 = reinterpret_cast<const uint32_t*>(b1 + j * 576)[i];
                    sbias[2 * i] = bf_lo(w2); sbias[2 * i + 1] = bf_hi(w2);
                }
                asm volatile("bar.arrive 4, 288;" ::: "memory");
            }
#pragma unroll 1
            for (int i = ht; i < 512; i += 96) {
                const int key = i & 127;
                uint8_t* p = g_QKV + (size_t)(j * 4 + (i >> 7)) * KV_HEAD_BYTES + (rb * 16 + (key >> 3)) * KV_GROUP_BYTES + 512 + (key & 7) * 16;
                *reinterpret_cast<uint32_t*>(p + 4) = (key & 8) ? 0x3F804000u : 0x00003F80u;
                *reinterpret_cast<uint32_t*>(p + 12) = 0x00003F80u;
            }
            named_bar_sync(3, 352);
#pragma unroll 1
            for (int i = warp - 9; i < 48; i += 3) {
                const int G = 3 * j + (i >> 4);
                if ((G >> 3) != 1) continue;
                const int head = (G & 7) * 4 + ((i >> 2) & 3), key = (i & 3) * 32 + lane;
                const uint8_t* p = g_QKV + (size_t)head * KV_HEAD_BYTES + (rb * 16 + (key >> 3)) * KV_GROUP_BYTES + (key & 7) * 16;
                const uint4 a = __ldcg(reinterpret_cast<const uint4*>(p)), b = __ldcg(reinterpret_cast<const uint4*>(p + 128));
                const uint32_t e = __ldcg(reinterpret_cast<const uint32_t*>(p + 512));
                float n = bf_lo(e) * bf_lo(e) + bf_hi(e) * bf_hi(e);
                n += bf_lo(a.x) * bf_lo(a.x) + bf_hi(a.x) * bf_hi(a.x) + bf_lo(a.y) * bf_lo(a.y) + bf_hi(a.y) * bf_hi(a.y);
                n += bf_lo(a.z) * bf_lo(a.z) + bf_hi(a.z) * bf_hi(a.z) + bf_lo(a.w) * bf_lo(a.w) + bf_hi(a.w) * bf_hi(a.w);
                n += bf_lo(b.x) * bf_lo(b.x) + bf_hi(b.x) * bf_hi(b.x) + bf_lo(b.y) * bf_lo(b.y) + bf_hi(b.y) * bf_hi(b.y);
                n += bf_lo(b.z) * bf_lo(b.z) + bf_hi(b.z) * bf_hi(b.z) + bf_lo(b.w) * bf_lo(b.w) + bf_hi(b.w) * bf_hi(b.w);
                if (key & 8) n *= 0.25f;
#pragma unroll
                for (int o = 16; o; o >>= 1) n = fmaxf(n, __shfl_xor_sync(~0u, n, o));
                if (lane == 0) g_kmax[head * 64 + rb * 4 + (i & 3)] = n;
            }
        }
        __syncwarp();
        cluster_arrive();
        cluster_wait();
    }
}

constexpr int K2_NCHUNK = 16;
constexpr int K2_CHUNK_BYTES = KV_HEAD_BYTES / K2_NCHUNK;
constexpr int K2_OFF_BAR = KV_HEAD_BYTES;
constexpr int K2_SMEM = K2_OFF_BAR + 256;

__device__ __forceinline__ float exp2_fixed(float y) {
    const float u = __uint_as_float(__float_as_uint(y) & 0xFF807FFFu) - 512.02545f;
    float t = fmaf(u, 0.019497588f, 0.114550486f);
    t = fmaf(t, u, -0.29839927f);
    return fmaf(t, u, y);
}
__device__ __forceinline__ uint32_t pack_fixed(float lo, float hi) { return __byte_perm(__float_as_uint(lo), __float_as_uint(hi), 0x6521); }

__device__ __forceinline__ void softmax_fast(const float (&s)[32], uint32_t (&p)[16]) {
#pragma unroll
    for (int k = 0; k < 4; k++) {
        p[k * 4 + 0] = pack_bf16(ex2(s[k * 8 + 0]), ex2(s[k * 8 + 1]));
        p[k * 4 + 1] = pack_bf16(ex2(s[k * 8 + 2]), ex2(s[k * 8 + 3]));
        p[k * 4 + 2] = pack_fixed(exp2_fixed(s[k * 8 + 4]), exp2_fixed(s[k * 8 + 5]));
        p[k * 4 + 3] = pack_fixed(exp2_fixed(s[k * 8 + 6]), exp2_fixed(s[k * 8 + 7]));
    }
}

__device__ __forceinline__ void issue_qk(float (&s)[32], const uint32_t (&qa)[8], uint64_t dk0, uint64_t dk1, int tile) {
    const uint64_t off = (uint64_t)(tile * (8 * KV_GROUP_BYTES / 16));
    wgmma_rs_n64<0>(s, qa[0], qa[1], qa[2], qa[3], dk0 + off, 0);
    wgmma_rs_n64<0>(s, qa[4], qa[5], qa[6], qa[7], dk1 + off, 1);
}
__device__ __forceinline__ void issue_pv(float (&o)[12], const uint32_t (&p)[16], uint64_t dv, int tile) {
    const uint64_t off = (uint64_t)(tile * (8 * KV_GROUP_BYTES / 16));
#pragma unroll
    for (int k = 0; k < 4; k++) wgmma_rs_n24<1>(o, p[k * 4], p[k * 4 + 1], p[k * 4 + 2], p[k * 4 + 3], dv + off + k * (2 * KV_GROUP_BYTES / 16), 1);
}

__global__ void __launch_bounds__(512, 1) k2_kernel() {
    extern __shared__ __align__(1024) uint8_t smem[];
    const uint32_t sb = s2u(smem);
    const int tid = threadIdx.x, lane = tid & 31;
    const int warp = __shfl_sync(~0u, tid >> 5, 0);
    const int wg = warp >> 2, wq = warp & 3, g = lane >> 2, q = lane & 3;
    const int head = blockIdx.x >> 2, quarter = blockIdx.x & 3;
    const uint32_t bar0 = sb + K2_OFF_BAR;
    if (tid == 0) {
        for (int i = 0; i < K2_NCHUNK; i++) mbar_init(bar0 + i * 8, 1);
        fence_barrier_init();
    }
    __syncthreads();
    griddep_wait();
    if (warp == 0 && lane < K2_NCHUNK) {
        mbar_expect(bar0 + lane * 8, K2_CHUNK_BYTES);
        bulk_load(sb + lane * K2_CHUNK_BYTES, g_QKV + (size_t)head * KV_HEAD_BYTES + lane * K2_CHUNK_BYTES, K2_CHUNK_BYTES, bar0 + lane * 8);
    }
    float kmax2;
    {
        const float2 v = *reinterpret_cast<const float2*>(g_kmax + head * 64 + lane * 2);
        kmax2 = fmaxf(v.x, v.y);
#pragma unroll
        for (int o = 16; o; o >>= 1) kmax2 = fmaxf(kmax2, __shfl_xor_sync(~0u, kmax2, o));
    }
    const uint64_t dk0 = mk_desc(sb, 128, KV_GROUP_BYTES, 0);
    const uint64_t dk1 = mk_desc(sb + 512, 0, KV_GROUP_BYTES, 0);
    const uint64_t dv = mk_desc(sb + 256, KV_GROUP_BYTES, 128, 0);

#pragma unroll 1
    for (int pass = 0; pass < 2; pass++) {
        const int row0 = quarter * 512 + (pass * 4 + wg) * 64 + wq * 16;
        uint32_t qa[8];
        {
            const uint8_t* qp = g_QKV + Q_OFFSET + (size_t)head * KV_HEAD_BYTES + (row0 >> 3) * KV_GROUP_BYTES + g * 16 + q * 4;
            qa[0] = *reinterpret_cast<const uint32_t*>(qp);
            qa[1] = *reinterpret_cast<const uint32_t*>(qp + KV_GROUP_BYTES);
            qa[2] = *reinterpret_cast<const uint32_t*>(qp + 128);
            qa[3] = *reinterpret_cast<const uint32_t*>(qp + KV_GROUP_BYTES + 128);
            qa[4] = (q == 0) ? *reinterpret_cast<const uint32_t*>(qp + 256) : 0u;
            qa[5] = (q == 0) ? *reinterpret_cast<const uint32_t*>(qp + KV_GROUP_BYTES + 256) : 0u;
            qa[6] = 0u; qa[7] = 0u;
        }
        float c0, c1;
        {
            float n0 = bf_lo(qa[0]) * bf_lo(qa[0]) + bf_hi(qa[0]) * bf_hi(qa[0]) + bf_lo(qa[2]) * bf_lo(qa[2]) + bf_hi(qa[2]) * bf_hi(qa[2]) +
                       bf_lo(qa[4]) * bf_lo(qa[4]) + bf_hi(qa[4]) * bf_hi(qa[4]);
            float n1 = bf_lo(qa[1]) * bf_lo(qa[1]) + bf_hi(qa[1]) * bf_hi(qa[1]) + bf_lo(qa[3]) * bf_lo(qa[3]) + bf_hi(qa[3]) * bf_hi(qa[3]) +
                       bf_lo(qa[5]) * bf_lo(qa[5]) + bf_hi(qa[5]) * bf_hi(qa[5]);
            n0 += __shfl_xor_sync(~0u, n0, 1); n1 += __shfl_xor_sync(~0u, n1, 1);
            n0 += __shfl_xor_sync(~0u, n0, 2); n1 += __shfl_xor_sync(~0u, n1, 2);
            c0 = sqrtf(n0 * kmax2) * 1.02f;
            c1 = sqrtf(n1 * kmax2) * 1.02f;
        }
        uint32_t slow;
        {
            const bool bad = !(c0 <= 58.f && c1 <= 58.f);
            asm volatile("{\n.reg .pred p, r;\nsetp.ne.u32 p, %1, 0;\nbarrier.cta.red.or.pred.aligned r, %2, 128, p;\nselp.u32 %0, 1, 0, r;\n}\n"
                         : "=r"(slow) : "r"((uint32_t)bad), "r"(wg + 1) : "memory");
        }
        slow = __any_sync(~0u, slow);
        float o[12];
#pragma unroll
        for (int i = 0; i < 12; i++) o[i] = 0.f;
        if (!slow && q == 1) {
            qa[4] = pack_bf16(-c0, 768.f); qa[5] = pack_bf16(-c1, 768.f);
            qa[6] = 0xC0000000u;
        }
        qa[7] = __shfl_sync(~0u, qa[6], lane);
        qa[6] = __shfl_sync(~0u, qa[6], lane ^ 4);

        if (!slow) {
            float s0[32], s1[32];
            uint32_t p[16];
            if (pass == 0) mbar_wait(bar0, 0);
            reg_fence(qa);
            reg_fence(o);
            wg_fence();
            issue_qk(s0, qa, dk0, dk1, 0);
            wg_commit();
#pragma unroll 1
            for (int t = 0; t < 32; t += 2) {
                wg_fence();
                issue_qk(s1, qa, dk0, dk1, t + 1);
                wg_commit();
                wg_wait<1>();
                reg_fence(s0);
                softmax_fast(s0, p);
                reg_fence(p);
                if (pass == 0 && t < 30) mbar_wait(bar0 + (t / 2 + 1) * 8, 0);
                wg_fence();
                issue_pv(o, p, dv, t);
                wg_commit();
                issue_qk(s0, qa, dk0, dk1, (t + 2) & 31);
                wg_commit();
                wg_wait<1>();
                reg_fence(s1);
                softmax_fast(s1, p);
                reg_fence(p);
                wg_fence();
                issue_pv(o, p, dv, t + 1);
                wg_commit();
            }
            wg_wait<0>();
            reg_fence(o);
            reg_fence(s0);
        } else {
            float m0 = -INFINITY, m1 = -INFINITY;
            float s[32];
            uint32_t p[16];
            reg_fence(qa);
#pragma unroll 1
            for (int t = 0; t < 32; t++) {
                if (pass == 0) mbar_wait(bar0 + (t / 2) * 8, 0);
                wg_fence();
                issue_qk(s, qa, dk0, dk1, t);
                wg_commit();
                wg_wait<0>();
                reg_fence(s);
                reg_fence(o);
                float a0 = m0, a1 = m1;
#pragma unroll
                for (int k = 0; k < 4; k++) {
#pragma unroll
                    for (int i = 4; i < 8; i++) s[k * 8 + i] *= 0.5f;
                    a0 = fmaxf(fmaxf(a0, fmaxf(s[k * 8 + 0], s[k * 8 + 1])), fmaxf(s[k * 8 + 4], s[k * 8 + 5]));
                    a1 = fmaxf(fmaxf(a1, fmaxf(s[k * 8 + 2], s[k * 8 + 3])), fmaxf(s[k * 8 + 6], s[k * 8 + 7]));
                }
                a0 = fmaxf(a0, __shfl_xor_sync(~0u, a0, 1)); a1 = fmaxf(a1, __shfl_xor_sync(~0u, a1, 1));
                a0 = fmaxf(a0, __shfl_xor_sync(~0u, a0, 2)); a1 = fmaxf(a1, __shfl_xor_sync(~0u, a1, 2));
                const float r0 = ex2(m0 - a0), r1 = ex2(m1 - a1);
                m0 = a0; m1 = a1;
#pragma unroll
                for (int i = 0; i < 3; i++) { o[i * 4] *= r0; o[i * 4 + 1] *= r0; o[i * 4 + 2] *= r1; o[i * 4 + 3] *= r1; }
#pragma unroll
                for (int k = 0; k < 8; k++) {
                    p[k * 2 + 0] = pack_bf16(ex2(s[k * 4 + 0] - m0), ex2(s[k * 4 + 1] - m0));
                    p[k * 2 + 1] = pack_bf16(ex2(s[k * 4 + 2] - m1), ex2(s[k * 4 + 3] - m1));
                }
                reg_fence(p);
                reg_fence(o);
                wg_fence();
                issue_pv(o, p, dv, t);
                wg_commit();
                wg_wait<0>();
            }
            reg_fence(o);
        }
        const float l0 = __shfl_sync(~0u, o[8], (lane & ~3) | 3), l1 = __shfl_sync(~0u, o[10], (lane & ~3) | 3);
        const float i0 = 1.0f / l0, i1 = 1.0f / l1;
        uint32_t* op0 = reinterpret_cast<uint32_t*>(g_O + (size_t)(row0 + g) * DM + head * DH);
        uint32_t* op1 = reinterpret_cast<uint32_t*>(g_O + (size_t)(row0 + g + 8) * DM + head * DH);
        op0[q] = pack_bf16(o[0] * i0, o[1] * i0);
        op1[q] = pack_bf16(o[2] * i1, o[3] * i1);
        op0[4 + q] = pack_bf16(o[4] * i0, o[5] * i0);
        op1[4 + q] = pack_bf16(o[6] * i1, o[7] * i1);
        if (q == 2) {
            op0[8] = pack_bf16(o[8] * i0, o[9] * i0);
            op1[8] = pack_bf16(o[10] * i1, o[11] * i1);
        }
    }
}

constexpr int K3_OFF_B = 9 * 16384;
constexpr int K3_OFF_BAR = K3_OFF_B + 9 * 8192;
constexpr int K3_SMEM = K3_OFF_BAR + 128;

__global__ void __launch_bounds__(256, 1)
k3_kernel(const __grid_constant__ CUtensorMap tmO, const __grid_constant__ CUtensorMap tmWo, const __nv_bfloat16* __restrict__ x,
          const __nv_bfloat16* __restrict__ b2, __nv_bfloat16* __restrict__ out) {
    extern __shared__ __align__(1024) uint8_t smem[];
    const uint32_t sb = s2u(smem);
    const int tid = threadIdx.x, warp = tid >> 5, lane = tid & 31;
    const int wg = warp >> 2, g = lane >> 2, q = lane & 3;
    const int rb = blockIdx.x / 9, t = blockIdx.x % 9;
    const uint32_t bar0 = sb + K3_OFF_BAR;
    if (tid == 0) {
        for (int i = 0; i < 9; i++) mbar_init(bar0 + i * 8, 1);
        fence_barrier_init();
    }
    __syncthreads();
    griddep_wait();
    if (warp == 0 && lane < 9) {
        mbar_expect(bar0 + lane * 8, 16384 + 8192);
        tma2d(sb + lane * 16384, &tmO, lane * 64, rb * 128, bar0 + lane * 8);
        tma2d(sb + K3_OFF_B + lane * 8192, &tmWo, t * 64, lane * 64, bar0 + lane * 8);
    }
    float acc[32];
    {
        const int r0 = rb * 128 + warp * 16 + g;
#pragma unroll
        for (int b = 0; b < 8; b++) {
            const int col = t * 64 + b * 8 + q * 2;
            const uint32_t bb = *reinterpret_cast<const uint32_t*>(b2 + col);
            const uint32_t x0 = *reinterpret_cast<const uint32_t*>(x + (size_t)r0 * DM + col);
            const uint32_t x1 = *reinterpret_cast<const uint32_t*>(x + (size_t)(r0 + 8) * DM + col);
            acc[b * 4 + 0] = bf_lo(x0) + bf_lo(bb); acc[b * 4 + 1] = bf_hi(x0) + bf_hi(bb);
            acc[b * 4 + 2] = bf_lo(x1) + bf_lo(bb); acc[b * 4 + 3] = bf_hi(x1) + bf_hi(bb);
        }
#pragma unroll
        for (int jj = 0; jj < 8; jj++) {
            const uint4* pp = g_part + ((size_t)(jj * 16 + rb) * 36 + t * 4) * 256 + tid;
#pragma unroll
            for (int s = 0; s < 4; s++) {
                const uint4 v = pp[s * 256];
                acc[s * 8 + 0] += bf_lo(v.x); acc[s * 8 + 1] += bf_hi(v.x); acc[s * 8 + 2] += bf_lo(v.y); acc[s * 8 + 3] += bf_hi(v.y);
                acc[s * 8 + 4] += bf_lo(v.z); acc[s * 8 + 5] += bf_hi(v.z); acc[s * 8 + 6] += bf_lo(v.w); acc[s * 8 + 7] += bf_hi(v.w);
            }
        }
    }
    const uint64_t da = mk_desc(sb + wg * 8192, 16, 1024, 1);
    const uint64_t db = mk_desc(sb + K3_OFF_B, 8192, 1024, 1);
#pragma unroll
    for (int kb = 0; kb < 9; kb++) {
        mbar_wait(bar0 + kb * 8, 0);
        wg_fence();
#pragma unroll
        for (int k = 0; k < 4; k++) wgmma_ss_n64<1>(acc, da + ((kb * 16384 + k * 32) >> 4), db + ((kb * 8192 + k * 2048) >> 4), 1);
        wg_commit();
    }
    wg_wait<0>();
    reg_fence(acc);
    const int r0 = rb * 128 + warp * 16 + g;
#pragma unroll
    for (int b = 0; b < 8; b++) {
        const int col = t * 64 + b * 8 + q * 2;
        *reinterpret_cast<uint32_t*>(out + (size_t)r0 * DM + col) = pack_bf16(acc[b * 4], acc[b * 4 + 1]);
        *reinterpret_cast<uint32_t*>(out + (size_t)(r0 + 8) * DM + col) = pack_bf16(acc[b * 4 + 2], acc[b * 4 + 3]);
    }
}

typedef CUresult (*EncodeFn)(CUtensorMap*, CUtensorMapDataType, cuuint32_t, void*, const cuuint64_t*, const cuuint64_t*, const cuuint32_t*,
                             const cuuint32_t*, CUtensorMapInterleave, CUtensorMapSwizzle, CUtensorMapL2promotion, CUtensorMapFloatOOBfill);

void make_map(EncodeFn fn, CUtensorMap* m, const void* base, int rank, const cuuint64_t* dims, const cuuint64_t* strides, const cuuint32_t* box) {
    cuuint32_t es[3] = {1, 1, 1};
    fn(m, CU_TENSOR_MAP_DATA_TYPE_BFLOAT16, rank, const_cast<void*>(base), dims, strides, box, es, CU_TENSOR_MAP_INTERLEAVE_NONE,
       CU_TENSOR_MAP_SWIZZLE_128B, CU_TENSOR_MAP_L2_PROMOTION_L2_256B, CU_TENSOR_MAP_FLOAT_OOB_FILL_NONE);
}

}

extern "C" void kernel_launch(void* const* d_in, const int* in_sizes, int n_in, void* d_out, int out_size) {
    const __nv_bfloat16* x = (const __nv_bfloat16*)d_in[0];
    const __nv_bfloat16* wqkv = (const __nv_bfloat16*)d_in[1];
    const __nv_bfloat16* wo = (const __nv_bfloat16*)d_in[2];
    const __nv_bfloat16* w1 = (const __nv_bfloat16*)d_in[4];
    const __nv_bfloat16* b1 = (const __nv_bfloat16*)d_in[5];
    const __nv_bfloat16* w2 = (const __nv_bfloat16*)d_in[6];
    const __nv_bfloat16* b2 = (const __nv_bfloat16*)d_in[7];
    __nv_bfloat16* out = (__nv_bfloat16*)d_out;

    EncodeFn fn = nullptr;
    cudaDriverEntryPointQueryResult qr;
    cudaGetDriverEntryPoint("cuTensorMapEncodeTiled", (void**)&fn, cudaEnableDefault, &qr);
    void* gO = nullptr;
    cudaGetSymbolAddress(&gO, g_O);
    CUtensorMap tmX, tmQ3, tmQ1, tm1, tm2, tmO, tmWo;
    {
        cuuint64_t d[3] = {64, SEQ, 9}, s[2] = {DM * 2, 128};
        cuuint32_t b[3] = {64, 8, 9};
        make_map(fn, &tmX, x, 3, d, s, b);
    }
    {
        cuuint64_t d[3] = {3 * DM, DM, 3}, s[2] = {3 * DM * 2, 128};
        cuuint32_t b[3] = {64, 16, 3};
        make_map(fn, &tmQ3, wqkv, 3, d, s, b);
        make_map(fn, &tmQ1, wqkv, 2, d, s, b);
    }
    {
        cuuint64_t d[2] = {FF, DM}, s[1] = {FF * 2};
        cuuint32_t b[2] = {64, 64};
        make_map(fn, &tm1, w1, 2, d, s, b);
        cuuint64_t d2[2] = {DM, FF}, s2[1] = {DM * 2};
        make_map(fn, &tm2, w2, 2, d2, s2, b);
    }
    {
        cuuint64_t d[2] = {DM, SEQ}, s[1] = {DM * 2};
        cuuint32_t b[2] = {64, 128};
        make_map(fn, &tmO, gO, 2, d, s, b);
        cuuint64_t d2[2] = {DM, DM};
        cuuint32_t b2x[2] = {64, 64};
        make_map(fn, &tmWo, wo, 2, d2, s, b2x);
    }
    cudaFuncSetAttribute(k1_kernel, cudaFuncAttributeMaxDynamicSharedMemorySize, K1_SMEM);
    cudaFuncSetAttribute(k2_kernel, cudaFuncAttributeMaxDynamicSharedMemorySize, K2_SMEM);
    cudaFuncSetAttribute(k3_kernel, cudaFuncAttributeMaxDynamicSharedMemorySize, K3_SMEM);

    cudaStream_t st = cudaStreamPerThread;
    cudaLaunchAttribute pdl[1];
    pdl[0].id = cudaLaunchAttributeProgrammaticStreamSerialization;
    pdl[0].val.programmaticStreamSerializationAllowed = 1;
    {
        cudaLaunchConfig_t cfg = {};
        cfg.gridDim = dim3(128); cfg.blockDim = dim3(384); cfg.dynamicSmemBytes = K1_SMEM; cfg.stream = st;
        cudaLaunchKernelEx(&cfg, k1_kernel, tmX, tmQ3, tmQ1, tm1, tm2, b1);
    }
    {
        cudaLaunchConfig_t cfg = {};
        cfg.gridDim = dim3(128); cfg.blockDim = dim3(512); cfg.dynamicSmemBytes = K2_SMEM; cfg.stream = st;
        cfg.attrs = pdl; cfg.numAttrs = 1;
        cudaLaunchKernelEx(&cfg, k2_kernel);
    }
    {
        cudaLaunchConfig_t cfg = {};
        cfg.gridDim = dim3(144); cfg.blockDim = dim3(256); cfg.dynamicSmemBytes = K3_SMEM; cfg.stream = st;
        cfg.attrs = pdl; cfg.numAttrs = 1;
        cudaLaunchKernelEx(&cfg, k3_kernel, tmO, tmWo, x, b2, out);
    }
}
```

```cpp
#include <cuda_runtime.h>
#include <cuda_bf16.h>
#include <cuda.h>
#include <stdint.h>

#define PROF(i) do { } while (0)
#define PROF_WG 0

namespace {

constexpr int SEQ = 2048, DM = 576, FF = 4608, NH = 32, DH = 18;

constexpr int KV_GROUP_BYTES = 5 * 128;
constexpr int KV_HEAD_BYTES = (SEQ / 8) * KV_GROUP_BYTES;
constexpr int Q_OFFSET = NH * KV_HEAD_BYTES;
#define POLY_MASK 0x92
__device__ __align__(1024) uint8_t g_QKV[2 * NH * KV_HEAD_BYTES];
__device__ __align__(1024) float g_kmax[NH * 64];
__device__ __align__(1024) uint4 g_part[8 * 16 * 36 * 256];
__device__ __align__(1024) __nv_bfloat16 g_O[SEQ * DM];

__device__ __forceinline__ uint32_t s2u(const void* p) { return (uint32_t)__cvta_generic_to_shared(p); }
__device__ __forceinline__ void mbar_init(uint32_t b, int c) { asm volatile("mbarrier.init.shared::cta.b64 [%0], %1;" ::"r"(b), "r"(c) : "memory"); }
__device__ __forceinline__ void mbar_expect(uint32_t b, uint32_t bytes) {
    asm volatile("mbarrier.arrive.expect_tx.shared::cta.b64 _, [%0], %1;" ::"r"(b), "r"(bytes) : "memory");
}
__device__ __forceinline__ void mbar_wait(uint32_t b, uint32_t parity) {
    asm volatile(
        "{\n.reg .pred p;\n.reg .u32 c;\n"
        "mbarrier.try_wait.parity.shared::cta.b64 p, [%0], %1;\n"
        "@p bra DONE;\n"
        "mov.u32 c, 0;\n"
        "LOOP:\n"
        "mbarrier.try_wait.parity.shared::cta.b64 p, [%0], %1;\n"
        "@p bra DONE;\n"
        "add.u32 c, c, 1;\n"
        "setp.lt.u32 p, c, 4194304;\n"
        "@p bra LOOP;\n"
        "trap;\n"
        "DONE:\n}\n" ::"r"(b), "r"(parity) : "memory");
}
__device__ __forceinline__ void fence_barrier_init() { asm volatile("fence.mbarrier_init.release.cluster;" ::: "memory"); }
__device__ __forceinline__ void fence_proxy_async() { asm volatile("fence.proxy.async.shared::cta;" ::: "memory"); }
__device__ __forceinline__ void cluster_arrive() { asm volatile("barrier.cluster.arrive.relaxed.aligned;" ::: "memory"); }
__device__ __forceinline__ void cluster_wait() { asm volatile("barrier.cluster.wait.aligned;" ::: "memory"); }
__device__ __forceinline__ void named_bar_sync(int id, int n) { asm volatile("bar.sync %0, %1;" ::"r"(id), "r"(n) : "memory"); }
__device__ __forceinline__ void griddep_wait() { asm volatile("griddepcontrol.wait;" ::: "memory"); }
__device__ __forceinline__ void griddep_launch() { asm volatile("griddepcontrol.launch_dependents;" ::: "memory"); }

__device__ __forceinline__ void tma3d_mc(uint32_t dst, const CUtensorMap* tm, int c0, int c1, int c2, uint32_t bar, uint16_t mask) {
    asm volatile("cp.async.bulk.tensor.3d.shared::cluster.global.mbarrier::complete_tx::bytes.multicast::cluster [%0], [%1, {%3, %4, %5}], [%2], %6;"
                 ::"r"(dst), "l"(tm), "r"(bar), "r"(c0), "r"(c1), "r"(c2), "h"(mask) : "memory");
}
__device__ __forceinline__ void tma2d_mc(uint32_t dst, const CUtensorMap* tm, int c0, int c1, uint32_t bar, uint16_t mask) {
    asm volatile("cp.async.bulk.tensor.2d.shared::cluster.global.mbarrier::complete_tx::bytes.multicast::cluster [%0], [%1, {%3, %4}], [%2], %5;"
                 ::"r"(dst), "l"(tm), "r"(bar), "r"(c0), "r"(c1), "h"(mask) : "memory");
}
__device__ __forceinline__ void tma3d(uint32_t dst, const CUtensorMap* tm, int c0, int c1, int c2, uint32_t bar) {
    asm volatile("cp.async.bulk.tensor.3d.shared::cluster.global.mbarrier::complete_tx::bytes [%0], [%1, {%3, %4, %5}], [%2];"
                 ::"r"(dst), "l"(tm), "r"(bar), "r"(c0), "r"(c1), "r"(c2) : "memory");
}
__device__ __forceinline__ void tma2d(uint32_t dst, const CUtensorMap* tm, int c0, int c1, uint32_t bar) {
    asm volatile("cp.async.bulk.tensor.2d.shared::cluster.global.mbarrier::complete_tx::bytes [%0], [%1, {%3, %4}], [%2];"
                 ::"r"(dst), "l"(tm), "r"(bar), "r"(c0), "r"(c1) : "memory");
}
__device__ __forceinline__ void bulk_load(uint32_t dst, const void* src, uint32_t bytes, uint32_t bar) {
    asm volatile("cp.async.bulk.shared::cluster.global.mbarrier::complete_tx::bytes [%0], [%1], %2, [%3];"
                 ::"r"(dst), "l"(src), "r"(bytes), "r"(bar) : "memory");
}
__device__ __forceinline__ void prefetch_tmap(const CUtensorMap* tm) { asm volatile("prefetch.tensormap [%0];" ::"l"(tm) : "memory"); }

__device__ __forceinline__ void wg_fence() { asm volatile("wgmma.fence.sync.aligned;" ::: "memory"); }
__device__ __forceinline__ void wg_commit() { asm volatile("wgmma.commit_group.sync.aligned;" ::: "memory"); }
template <int N> __device__ __forceinline__ void wg_wait() { asm volatile("wgmma.wait_group.sync.aligned %0;" ::"n"(N) : "memory"); }
template <int N> __device__ __forceinline__ void reg_fence(float (&d)[N]) {
#pragma unroll
    for (int i = 0; i < N; i++) asm volatile("" : "+f"(d[i])::"memory");
}
template <int N> __device__ __forceinline__ void reg_fence(uint32_t (&d)[N]) {
#pragma unroll
    for (int i = 0; i < N; i++) asm volatile("" : "+r"(d[i])::"memory");
}
template <int R> __device__ __forceinline__ void reg_alloc() { asm volatile("setmaxnreg.inc.sync.aligned.u32 %0;" ::"n"(R)); }
template <int R> __device__ __forceinline__ void reg_dealloc() { asm volatile("setmaxnreg.dec.sync.aligned.u32 %0;" ::"n"(R)); }

__device__ __forceinline__ uint32_t desc_lo(uint32_t addr, uint32_t lbo) { return ((addr & 0x3FFFF) >> 4) | ((lbo >> 4) << 16); }
__host__ __device__ constexpr uint32_t desc_hi(uint32_t sbo, uint32_t swz) { return (sbo >> 4) | (swz << 30); }
__device__ __forceinline__ uint32_t pack_bf16(float lo, float hi) {
    uint32_t r;
    asm("cvt.rn.bf16x2.f32 %0, %1, %2;" : "=r"(r) : "f"(hi), "f"(lo));
    return r;
}
__device__ __forceinline__ float bf_lo(uint32_t w) { return __uint_as_float(w << 16); }
__device__ __forceinline__ float bf_hi(uint32_t w) { return __uint_as_float(w & 0xFFFF0000u); }
__device__ __forceinline__ float ex2(float x) {
    float r;
    asm("ex2.approx.ftz.f32 %0, %1;" : "=f"(r) : "f"(x));
    return r;
}
__device__ __forceinline__ float tanh_fast(float x) {
    float r;
    asm("tanh.approx.f32 %0, %1;" : "=f"(r) : "f"(x));
    return r;
}
__device__ __forceinline__ float gelu2(float u) {
    const float w = fmaf(u * u, 0.0356774081f, 0.7978845608f);
    return fmaf(u, tanh_fast(u * w), u);
}

template<int TB> __device__ __forceinline__ void wgmma_ss_n216(float (&d)[108], uint32_t alo, uint32_t ahi, uint32_t blo, uint32_t bhi, int sd) {
    asm volatile("{\n.reg .pred p;\n.reg .b64 da, db;\nsetp.ne.b32 p, %110, 0;\nmov.b64 da, {%108, %112};\nmov.b64 db, {%109, %113};\n"
      "wgmma.mma_async.sync.aligned.m64n216k16.f32.bf16.bf16 {%0, %1, %2, %3, %4, %5, %6, %7, %8, %9, %10, %11, %12, %13, %14, %15, %16, %17, %18, %19, %20, %21, %22, %23, %24, %25, %26, %27, %28, %29, %30, %31, %32, %33, %34, %35, %36, %37, %38, %39, %40, %41, %42, %43, %44, %45, %46, %47, %48, %49, %50, %51, %52, %53, %54, %55, %56, %57, %58, %59, %60, %61, %62, %63, %64, %65, %66, %67, %68, %69, %70, %71, %72, %73, %74, %75, %76, %77, %78, %79, %80, %81, %82, %83, %84, %85, %86, %87, %88, %89, %90, %91, %92, %93, %94, %95, %96, %97, %98, %99, %100, %101, %102, %103, %104, %105, %106, %107}, da, db, p, 1, 1, 0, %111;\n}\n"
      : "+f"(d[0]), "+f"(d[1]), "+f"(d[2]), "+f"(d[3]), "+f"(d[4]), "+f"(d[5]), "+f"(d[6]), "+f"(d[7]), "+f"(d[8]), "+f"(d[9]), "+f"(d[10]), "+f"(d[11]), "+f"(d[12]), "+f"(d[13]), "+f"(d[14]), "+f"(d[15]), "+f"(d[16]), "+f"(d[17]), "+f"(d[18]), "+f"(d[19]), "+f"(d[20]), "+f"(d[21]), "+f"(d[22]), "+f"(d[23]), "+f"(d[24]), "+f"(d[25]), "+f"(d[26]), "+f"(d[27]), "+f"(d[28]), "+f"(d[29]), "+f"(d[30]), "+f"(d[31]), "+f"(d[32]), "+f"(d[33]), "+f"(d[34]), "+f"(d[35]), "+f"(d[36]), "+f"(d[37]), "+f"(d[38]), "+f"(d[39]), "+f"(d[40]), "+f"(d[41]), "+f"(d[42]), "+f"(d[43]), "+f"(d[44]), "+f"(d[45]), "+f"(d[46]), "+f"(d[47]), "+f"(d[48]), "+f"(d[49]), "+f"(d[50]), "+f"(d[51]), "+f"(d[52]), "+f"(d[53]), "+f"(d[54]), "+f"(d[55]), "+f"(d[56]), "+f"(d[57]), "+f"(d[58]), "+f"(d[59]), "+f"(d[60]), "+f"(d[61]), "+f"(d[62]), "+f"(d[63]), "+f"(d[64]), "+f"(d[65]), "+f"(d[66]), "+f"(d[67]), "+f"(d[68]), "+f"(d[69]), "+f"(d[70]), "+f"(d[71]), "+f"(d[72]), "+f"(d[73]), "+f"(d[74]), "+f"(d[75]), "+f"(d[76]), "+f"(d[77]), "+f"(d[78]), "+f"(d[79]), "+f"(d[80]), "+f"(d[81]), "+f"(d[82]), "+f"(d[83]), "+f"(d[84]), "+f"(d[85]), "+f"(d[86]), "+f"(d[87]), "+f"(d[88]), "+f"(d[89]), "+f"(d[90]), "+f"(d[91]), "+f"(d[92]), "+f"(d[93]), "+f"(d[94]), "+f"(d[95]), "+f"(d[96]), "+f"(d[97]), "+f"(d[98]), "+f"(d[99]), "+f"(d[100]), "+f"(d[101]), "+f"(d[102]), "+f"(d[103]), "+f"(d[104]), "+f"(d[105]), "+f"(d[106]), "+f"(d[107])
      : "r"(alo), "r"(blo), "r"(sd), "n"(TB), "r"(ahi), "r"(bhi));
}

template<int TB> __device__ __forceinline__ void wgmma_ss_n64(float (&d)[32], uint32_t alo, uint32_t ahi, uint32_t blo, uint32_t bhi, int sd) {
    asm volatile("{\n.reg .pred p;\n.reg .b64 da, db;\nsetp.ne.b32 p, %34, 0;\nmov.b64 da, {%32, %36};\nmov.b64 db, {%33, %37};\n"
      "wgmma.mma_async.sync.aligned.m64n64k16.f32.bf16.bf16 {%0, %1, %2, %3, %4, %5, %6, %7, %8, %9, %10, %11, %12, %13, %14, %15, %16, %17, %18, %19, %20, %21, %22, %23, %24, %25, %26, %27, %28, %29, %30, %31}, da, db, p, 1, 1, 0, %35;\n}\n"
      : "+f"(d[0]), "+f"(d[1]), "+f"(d[2]), "+f"(d[3]), "+f"(d[4]), "+f"(d[5]), "+f"(d[6]), "+f"(d[7]), "+f"(d[8]), "+f"(d[9]), "+f"(d[10]), "+f"(d[11]), "+f"(d[12]), "+f"(d[13]), "+f"(d[14]), "+f"(d[15]), "+f"(d[16]), "+f"(d[17]), "+f"(d[18]), "+f"(d[19]), "+f"(d[20]), "+f"(d[21]), "+f"(d[22]), "+f"(d[23]), "+f"(d[24]), "+f"(d[25]), "+f"(d[26]), "+f"(d[27]), "+f"(d[28]), "+f"(d[29]), "+f"(d[30]), "+f"(d[31])
      : "r"(alo), "r"(blo), "r"(sd), "n"(TB), "r"(ahi), "r"(bhi));
}

template<int TB> __device__ __forceinline__ void wgmma_rs_n64(float (&d)[32], uint32_t a0, uint32_t a1, uint32_t a2, uint32_t a3, uint32_t blo, uint32_t bhi, int sd) {
    asm volatile("{\n.reg .pred p;\n.reg .b64 db;\nsetp.ne.b32 p, %37, 0;\nmov.b64 db, {%36, %39};\n"
      "wgmma.mma_async.sync.aligned.m64n64k16.f32.bf16.bf16 {%0, %1, %2, %3, %4, %5, %6, %7, %8, %9, %10, %11, %12, %13, %14, %15, %16, %17, %18, %19, %20, %21, %22, %23, %24, %25, %26, %27, %28, %29, %30, %31}, {%32, %33, %34, %35}, db, p, 1, 1, %38;\n}\n"
      : "+f"(d[0]), "+f"(d[1]), "+f"(d[2]), "+f"(d[3]), "+f"(d[4]), "+f"(d[5]), "+f"(d[6]), "+f"(d[7]), "+f"(d[8]), "+f"(d[9]), "+f"(d[10]), "+f"(d[11]), "+f"(d[12]), "+f"(d[13]), "+f"(d[14]), "+f"(d[15]), "+f"(d[16]), "+f"(d[17]), "+f"(d[18]), "+f"(d[19]), "+f"(d[20]), "+f"(d[21]), "+f"(d[22]), "+f"(d[23]), "+f"(d[24]), "+f"(d[25]), "+f"(d[26]), "+f"(d[27]), "+f"(d[28]), "+f"(d[29]), "+f"(d[30]), "+f"(d[31])
      : "r"(a0), "r"(a1), "r"(a2), "r"(a3), "r"(blo), "r"(sd), "n"(TB), "r"(bhi));
}

template<int TB> __device__ __forceinline__ void wgmma_rs_n24(float (&d)[12], uint32_t a0, uint32_t a1, uint32_t a2, uint32_t a3, uint32_t blo, uint32_t bhi, int sd) {
    asm volatile("{\n.reg .pred p;\n.reg .b64 db;\nsetp.ne.b32 p, %17, 0;\nmov.b64 db, {%16, %19};\n"
      "wgmma.mma_async.sync.aligned.m64n24k16.f32.bf16.bf16 {%0, %1, %2, %3, %4, %5, %6, %7, %8, %9, %10, %11}, {%12, %13, %14, %15}, db, p, 1, 1, %18;\n}\n"
      : "+f"(d[0]), "+f"(d[1]), "+f"(d[2]), "+f"(d[3]), "+f"(d[4]), "+f"(d[5]), "+f"(d[6]), "+f"(d[7]), "+f"(d[8]), "+f"(d[9]), "+f"(d[10]), "+f"(d[11])
      : "r"(a0), "r"(a1), "r"(a2), "r"(a3), "r"(blo), "r"(sd), "n"(TB), "r"(bhi));
}

constexpr int K1_XN_BYTES = 16 * 9216;
constexpr int K1_SLOT = 16384, K1_NSLOT = 5;
constexpr int K1_OFF_RING = K1_XN_BYTES;
constexpr int K1_OFF_BIAS = K1_OFF_RING + K1_NSLOT * K1_SLOT;
constexpr int K1_OFF_BAR = K1_OFF_BIAS + 576 * 2;
constexpr int K1_SMEM = K1_OFF_BAR + 256;
constexpr float QSCALE = 0.23570226039551584f * 1.4426950408889634f;

struct Ring {
    uint32_t slot, phase;
    __device__ __forceinline__ void advance() {
        if (++slot == K1_NSLOT) { slot = 0; phase ^= 1; }
    }
};

struct K1Ctx {
    uint32_t full0;
    uint32_t rel_addr;
    uint32_t descA, descB;
    Ring rd;
    uint32_t prev_slot;
    __device__ __forceinline__ uint32_t begin_stage() {
        mbar_wait(full0 + rd.slot * 8, rd.phase);
        wg_fence();
        return descB + rd.slot * (K1_SLOT >> 4);
    }
    __device__ __forceinline__ void end_stage() {
        wg_commit();
        wg_wait<1>();
        if (rel_addr) asm volatile("mbarrier.arrive.shared::cluster.b64 _, [%0];" ::"r"(rel_addr + prev_slot * 8) : "memory");
        prev_slot = rd.slot;
        rd.advance();
    }
};

__device__ __forceinline__ uint32_t descA_step(uint32_t base, int ks) { return base + (((ks >> 2) * 1024 + (ks & 3) * 32) >> 4); }
constexpr uint32_t K1_AHI = desc_hi(9216, 1), K1_BHI = desc_hi(1024, 1);

template <int V> struct IC { static constexpr int value = V; };
template <int I, int N, class F> __device__ __forceinline__ void static_for(F&& f) {
    if constexpr (I < N) { f(IC<I>{}); static_for<I + 1, N>(f); }
}

template <bool A_RS, bool B_RS, class Epi>
__device__ __forceinline__ void tile_pair(K1Ctx& c, float (&accA)[32], float (&accB)[32], uint32_t (&h)[144], Epi&& epi) {
    static_for<0, 9>([&](auto sc) {
        constexpr int s = decltype(sc)::value;
        const uint32_t db = c.begin_stage();
#pragma unroll
        for (int t = 0; t < 8; t++) {
            const int kk = s * 8 + t, ks = kk % 36;
            const uint32_t dbt = db + ((t * 2048) >> 4);
            if (kk < 36) {
                if constexpr (A_RS) wgmma_rs_n64<1>(accA, h[ks * 4], h[ks * 4 + 1], h[ks * 4 + 2], h[ks * 4 + 3], dbt, K1_BHI, ks != 0);
                else wgmma_ss_n64<1>(accA, descA_step(c.descA, ks), K1_AHI, dbt, K1_BHI, ks != 0);
            } else {
                if constexpr (B_RS) wgmma_rs_n64<1>(accB, h[ks * 4], h[ks * 4 + 1], h[ks * 4 + 2], h[ks * 4 + 3], dbt, K1_BHI, ks != 0);
                else wgmma_ss_n64<1>(accB, descA_step(c.descA, ks), K1_AHI, dbt, K1_BHI, ks != 0);
            }
        }
        c.end_stage();
        epi(sc);
    });
}

template <int B0, int NB, int HOFF>
__device__ __forceinline__ void gelu_blocks(const float (&acc)[32], uint32_t (&h)[144], const uint32_t (&bq)[8]) {
#pragma unroll
    for (int b = B0; b < B0 + NB; b++) {
        const float b0 = bf_lo(bq[b]), b1 = bf_hi(bq[b]);
        h[HOFF + b * 2 + 0] = pack_bf16(gelu2(acc[b * 4 + 0] + b0), gelu2(acc[b * 4 + 1] + b1));
        h[HOFF + b * 2 + 1] = pack_bf16(gelu2(acc[b * 4 + 2] + b0), gelu2(acc[b * 4 + 3] + b1));
    }
}
__device__ __forceinline__ void load_bias(uint32_t (&bq)[8], uint32_t addr) {
    asm volatile("ld.shared.v4.u32 {%0, %1, %2, %3}, [%4];" : "=r"(bq[0]), "=r"(bq[1]), "=r"(bq[2]), "=r"(bq[3]) : "r"(addr));
    asm volatile("ld.shared.v4.u32 {%0, %1, %2, %3}, [%4 + 16];" : "=r"(bq[4]), "=r"(bq[5]), "=r"(bq[6]), "=r"(bq[7]) : "r"(addr));
}
template <int S> __device__ __forceinline__ void store_part(const float (&o)[32], uint4* p) {
    uint4 v;
    v.x = pack_bf16(o[S * 8 + 0], o[S * 8 + 1]); v.y = pack_bf16(o[S * 8 + 2], o[S * 8 + 3]);
    v.z = pack_bf16(o[S * 8 + 4], o[S * 8 + 5]); v.w = pack_bf16(o[S * 8 + 6], o[S * 8 + 7]);
    p[S * 256] = v;
}

__global__ void __cluster_dims__(2, 1, 1) __launch_bounds__(384, 1)
k1_kernel(const __grid_constant__ CUtensorMap tmX, const __grid_constant__ CUtensorMap tmQ3, const __grid_constant__ CUtensorMap tmQ1,
          const __grid_constant__ CUtensorMap tm1, const __grid_constant__ CUtensorMap tm2, const __nv_bfloat16* __restrict__ b1) {
    extern __shared__ __align__(1024) uint8_t smem[];
    const uint32_t sb = s2u(smem);
    const int tid = threadIdx.x, lane = tid & 31;
    const int warp = __shfl_sync(~0u, tid >> 5, 0);
    const uint32_t rank = blockIdx.x & 1;
    const int cl = blockIdx.x >> 1;
    const int rb = (cl & 7) * 2 + rank;
    const int j = cl >> 3;
    const uint32_t full0 = sb + K1_OFF_BAR, empty0 = full0 + 8 * K1_NSLOT, xbar0 = full0 + 128;

    if (warp < 8) {
        PROF(0);
        if (lane == 0) {
            mbar_init(xbar0 + warp * 16, 1);
            mbar_init(xbar0 + warp * 16 + 8, 1);
            fence_barrier_init();
            mbar_expect(xbar0 + warp * 16, 9216);
            tma3d(sb + warp * 2 * 9216, &tmX, 0, rb * 128 + warp * 16, 0, xbar0 + warp * 16);
            mbar_expect(xbar0 + warp * 16 + 8, 9216);
            tma3d(sb + (warp * 2 + 1) * 9216, &tmX, 0, rb * 128 + warp * 16 + 8, 0, xbar0 + warp * 16 + 8);
        }
        __syncwarp();
        cluster_arrive();
        reg_alloc<240>();
#pragma unroll 1
        for (int p = 0; p < 4; p++) {
            mbar_wait(xbar0 + warp * 16 + (p >> 1) * 8, 0);
            uint4* row = reinterpret_cast<uint4*>(smem + (warp * 2 + (p >> 1)) * 9216 + (p & 1) * 512 + lane * 16);
            float f[72];
#pragma unroll
            for (int i = 0; i < 9; i++) {
                const uint4 v = row[i * 64];
                f[i * 8 + 0] = bf_lo(v.x); f[i * 8 + 1] = bf_hi(v.x); f[i * 8 + 2] = bf_lo(v.y); f[i * 8 + 3] = bf_hi(v.y);
                f[i * 8 + 4] = bf_lo(v.z); f[i * 8 + 5] = bf_hi(v.z); f[i * 8 + 6] = bf_lo(v.w); f[i * 8 + 7] = bf_hi(v.w);
            }
            float s0 = 0.f, s1 = 0.f, s2 = 0.f, s3 = 0.f;
#pragma unroll
            for (int i = 0; i < 72; i += 4) { s0 += f[i]; s1 += f[i + 1]; s2 += f[i + 2]; s3 += f[i + 3]; }
            float sm = (s0 + s1) + (s2 + s3);
            sm += __shfl_xor_sync(~0u, sm, 1); sm += __shfl_xor_sync(~0u, sm, 2); sm += __shfl_xor_sync(~0u, sm, 4);
            const float mean = sm * (1.0f / DM);
            s0 = s1 = s2 = s3 = 0.f;
#pragma unroll
            for (int i = 0; i < 72; i += 4) {
                f[i] -= mean; f[i + 1] -= mean; f[i + 2] -= mean; f[i + 3] -= mean;
                s0 = fmaf(f[i], f[i], s0); s1 = fmaf(f[i + 1], f[i + 1], s1);
                s2 = fmaf(f[i + 2], f[i + 2], s2); s3 = fmaf(f[i + 3], f[i + 3], s3);
            }
            float sq = (s0 + s1) + (s2 + s3);
            sq += __shfl_xor_sync(~0u, sq, 1); sq += __shfl_xor_sync(~0u, sq, 2); sq += __shfl_xor_sync(~0u, sq, 4);
            const float rstd = rsqrtf(sq * (1.0f / DM) + 1e-5f);
#pragma unroll
            for (int i = 0; i < 9; i++) {
                uint4 o;
                o.x = pack_bf16(f[i * 8 + 0] * rstd, f[i * 8 + 1] * rstd);
                o.y = pack_bf16(f[i * 8 + 2] * rstd, f[i * 8 + 3] * rstd);
                o.z = pack_bf16(f[i * 8 + 4] * rstd, f[i * 8 + 5] * rstd);
                o.w = pack_bf16(f[i * 8 + 6] * rstd, f[i * 8 + 7] * rstd);
                row[i * 64] = o;
            }
        }
        const int wg = warp >> 2, wq = warp & 3;
        fence_proxy_async();
        named_bar_sync(1 + wg, 128);
        cluster_wait();
        PROF(1);

        const int g = lane >> 2, q = lane & 3;
        K1Ctx c;
        c.full0 = full0;
        c.rel_addr = 0;
        c.descA = desc_lo(sb + wg * 8 * 9216, 16);
        c.descB = desc_lo(sb + K1_OFF_RING, 2048);
        c.rd.slot = 0; c.rd.phase = 0; c.prev_slot = 0;
        uint32_t biasq = sb + K1_OFF_BIAS + q * 32;
        uint32_t bq[8];

        uint32_t h[144];
        float accA[32], accB[32];
        {
            float accQ[108];
            uint32_t rel = 0;
            if (lane == 0 && wq < 2) asm("mapa.shared::cluster.u32 %0, %1, %2;" : "=r"(rel) : "r"(empty0), "r"(wq));
#pragma unroll 1
            for (int s = 0; s < 18; s++) {
                const uint32_t db = c.begin_stage();
                const uint32_t da = c.descA + (s >> 1) * 64 + (s & 1) * 4;
                wgmma_ss_n216<1>(accQ, da, K1_AHI, db, K1_BHI, s != 0);
                wgmma_ss_n216<1>(accQ, da + 2, K1_AHI, db + (8192 >> 4), K1_BHI, 1);
                c.end_stage();
                c.rel_addr = rel;
            }
            PROF(2);
            uint32_t rel9[9];
#pragma unroll
            for (int i9 = 0; i9 < 9; i9++) {
                const int p = 4 * i9 + q, hh = (p * 57) >> 9, r = p - 9 * hh;
                rel9[i9] = hh * KV_HEAD_BYTES + (r < 8 ? (r >> 2) * 128 + (r & 3) * 4 : 0);
            }
            uint32_t gb = 0, o2 = 0;
            float scl0 = 1.f, scl1 = 1.f;
            tile_pair<false, false>(c, accA, accB, h, [&](auto sc) {
                constexpr int s = decltype(sc)::value;
                if constexpr (s == 0) reg_fence(accQ);
                if constexpr (s < 6) {
                    constexpr int grp = s / 2, part = s % 2;
                    if constexpr (part == 0) {
                        const int G = 3 * j + grp, type = G >> 3;
                        gb = (G & 7) * 4 * KV_HEAD_BYTES + (rb * 16 + warp * 2) * KV_GROUP_BYTES + g * 16 + (type == 0 ? Q_OFFSET : (type == 2 ? 256 : 0));
                        o2 = type == 0 ? 256 : (type == 2 ? 264 : 512);
                        scl0 = type == 0 ? QSCALE : ((type == 1 && ((POLY_MASK >> (wq * 2)) & 1)) ? 2.f : 1.f);
                        scl1 = type == 0 ? QSCALE : ((type == 1 && ((POLY_MASK >> (wq * 2 + 1)) & 1)) ? 2.f : 1.f);
                    }
#pragma unroll
                    for (int i9 = part * 5; i9 < (part ? 9 : 5); i9++) {
                        const int b = grp * 9 + i9;
                        uint32_t off = gb + rel9[i9];
                        if (i9 >= 2 && (i9 & 1) == 0) off += (q == i9 / 2 - 1) ? o2 : 0;
                        *reinterpret_cast<uint32_t*>(g_QKV + off) = pack_bf16(accQ[b * 4] * scl0, accQ[b * 4 + 1] * scl0);
                        *reinterpret_cast<uint32_t*>(g_QKV + off + KV_GROUP_BYTES) = pack_bf16(accQ[b * 4 + 2] * scl1, accQ[b * 4 + 3] * scl1);
                    }
                    if constexpr (s == 5) asm volatile("bar.arrive 3, 352;" ::: "memory");
                }
                if constexpr (s == 4) { named_bar_sync(4, 288); load_bias(bq, biasq); }
                if constexpr (s == 5) reg_fence(accA);
                if constexpr (s >= 5) gelu_blocks<(s - 5) * 2, 2, 96>(accA, h, bq);
                if constexpr (s == 8) load_bias(bq, biasq + 128);
            });
        }
        PROF(3);
#pragma unroll
        for (int i = 32; i < 96; i++) asm volatile("mov.u32 %0, 0;" : "=r"(h[i]));
#pragma unroll 1
        for (int p = 1; p < 4; p++) {
            biasq += 256;
            tile_pair<false, false>(c, accA, accB, h, [&](auto sc) {
                constexpr int s = decltype(sc)::value;
                if constexpr (s == 0) {
                    reg_fence(accB);
#pragma unroll
                    for (int i = 0; i < 80; i++) h[i] = h[i + 32];
                }
                if constexpr (s < 4) gelu_blocks<s * 2, 2, 80>(accB, h, bq);
                if constexpr (s == 4) load_bias(bq, biasq);
                if constexpr (s == 5) reg_fence(accA);
                if constexpr (s >= 5) gelu_blocks<(s - 5) * 2, 2, 96>(accA, h, bq);
                if constexpr (s == 8) load_bias(bq, biasq + 128);
            });
        }
        PROF(4);
        tile_pair<false, true>(c, accA, accB, h, [&](auto sc) {
            constexpr int s = decltype(sc)::value;
            if constexpr (s == 0) reg_fence(accB);
            if constexpr (s < 4) gelu_blocks<s * 2, 2, 112>(accB, h, bq);
            if constexpr (s == 4) load_bias(bq, biasq + 256);
            if constexpr (s == 5) reg_fence(accA);
            if constexpr (s == 5 || s == 6) gelu_blocks<(s - 5) * 3, 3, 128>(accA, h, bq);
            if constexpr (s == 7) gelu_blocks<6, 2, 128>(accA, h, bq);
            if constexpr (s == 3 || s == 7) reg_fence(h);
        });
        PROF(5);
        uint4* pout = g_part + ((size_t)(j * 16 + rb) * 36) * 256 + tid;
#pragma unroll 1
        for (int p = 0; p < 4; p++) {
            tile_pair<true, true>(c, accA, accB, h, [&](auto sc) {
                constexpr int s = decltype(sc)::value;
                if constexpr (s == 0) reg_fence(accB);
                if constexpr (s < 4) store_part<s>(accB, pout);
                if constexpr (s == 5) reg_fence(accA);
                if constexpr (s >= 5) store_part<s - 5>(accA, pout + 1024);
            });
            pout += 2048;
            PROF(6 + p);
        }
        wg_wait<0>();
        reg_fence(accB);
        store_part<0>(accB, pout); store_part<1>(accB, pout); store_part<2>(accB, pout); store_part<3>(accB, pout);
        PROF(10);
        cluster_arrive();
        cluster_wait();
        PROF(11);
    } else {
        reg_dealloc<24>();
        if (warp == 8 && lane == 0) {
            prefetch_tmap(&tmQ3); prefetch_tmap(&tmQ1); prefetch_tmap(&tm1); prefetch_tmap(&tm2);
            for (int i = 0; i < K1_NSLOT; i++) { mbar_init(full0 + i * 8, 1); mbar_init(empty0 + i * 8, 4); }
            fence_barrier_init();
        }
        __syncwarp();
        cluster_arrive();
        cluster_wait();
        if (warp == 8) {
            if (lane == 0) {
                Ring w{0, 1};
                const uint32_t dst0 = sb + K1_OFF_RING + rank * 8192;
#pragma unroll 1
                for (int s = 0; s < 18; s++) {
                    mbar_wait(empty0 + w.slot * 8, w.phase);
                    mbar_expect(full0 + w.slot * 8, 16384);
                    const uint32_t dst = dst0 + w.slot * K1_SLOT;
                    tma3d_mc(dst, &tmQ3, j * 216, s * 32 + rank * 16, 0, full0 + w.slot * 8, 3);
                    tma2d_mc(dst + 6144, &tmQ1, j * 216 + 192, s * 32 + rank * 16, full0 + w.slot * 8, 3);
                    w.advance();
                }
                int tile = 0, kb = rank;
#pragma unroll 1
                for (int s = 0; s < 81; s++) {
                    mbar_wait(empty0 + w.slot * 8, w.phase);
                    mbar_expect(full0 + w.slot * 8, 16384);
                    const uint32_t dst = dst0 + w.slot * K1_SLOT;
                    if (tile < 9) tma2d_mc(dst, &tm1, j * 576 + tile * 64, kb * 64, full0 + w.slot * 8, 3);
                    else tma2d_mc(dst, &tm2, (tile - 9) * 64, j * 576 + kb * 64, full0 + w.slot * 8, 3);
                    kb += 2;
                    if (kb >= 9) { kb -= 9; tile++; }
                    w.advance();
                }
            }
        } else {
            const int ht = tid - 288;
            if (warp == 9) {
                uint32_t* sbias = reinterpret_cast<uint32_t*>(smem + K1_OFF_BIAS);
#pragma unroll 1
                for (int t = 0; t < 9; t++) sbias[t * 32 + (lane & 3) * 8 + (lane >> 2)] = reinterpret_cast<const uint32_t*>(b1 + j * 576)[t * 32 + lane];
                asm volatile("bar.arrive 4, 288;" ::: "memory");
            }
#pragma unroll 1
            for (int i = ht; i < 512; i += 96) {
                const int key = i & 127;
                uint8_t* p = g_QKV + (size_t)(j * 4 + (i >> 7)) * KV_HEAD_BYTES + (rb * 16 + (key >> 3)) * KV_GROUP_BYTES + 512 + (key & 7) * 16;
                *reinterpret_cast<uint32_t*>(p + 4) = ((POLY_MASK >> ((key >> 3) & 7)) & 1) ? 0x3F804000u : 0x00003F80u;
                *reinterpret_cast<uint32_t*>(p + 12) = 0x00003F80u;
            }
            named_bar_sync(3, 352);
#pragma unroll 1
            for (int i = warp - 9; i < 48; i += 3) {
                const int G = 3 * j + (i >> 4);
                if ((G >> 3) != 1) continue;
                const int head = (G & 7) * 4 + ((i >> 2) & 3), key = (i & 3) * 32 + lane;
                const uint8_t* p = g_QKV + (size_t)head * KV_HEAD_BYTES + (rb * 16 + (key >> 3)) * KV_GROUP_BYTES + (key & 7) * 16;
                const uint4 a = __ldcg(reinterpret_cast<const uint4*>(p)), b = __ldcg(reinterpret_cast<const uint4*>(p + 128));
                const uint32_t e = __ldcg(reinterpret_cast<const uint32_t*>(p + 512));
                float n = bf_lo(e) * bf_lo(e) + bf_hi(e) * bf_hi(e);
                n += bf_lo(a.x) * bf_lo(a.x) + bf_hi(a.x) * bf_hi(a.x) + bf_lo(a.y) * bf_lo(a.y) + bf_hi(a.y) * bf_hi(a.y);
                n += bf_lo(a.z) * bf_lo(a.z) + bf_hi(a.z) * bf_hi(a.z) + bf_lo(a.w) * bf_lo(a.w) + bf_hi(a.w) * bf_hi(a.w);
                n += bf_lo(b.x) * bf_lo(b.x) + bf_hi(b.x) * bf_hi(b.x) + bf_lo(b.y) * bf_lo(b.y) + bf_hi(b.y) * bf_hi(b.y);
                n += bf_lo(b.z) * bf_lo(b.z) + bf_hi(b.z) * bf_hi(b.z) + bf_lo(b.w) * bf_lo(b.w) + bf_hi(b.w) * bf_hi(b.w);
                if ((POLY_MASK >> ((key >> 3) & 7)) & 1) n *= 0.25f;
#pragma unroll
                for (int o = 16; o; o >>= 1) n = fmaxf(n, __shfl_xor_sync(~0u, n, o));
                if (lane == 0) g_kmax[head * 64 + rb * 4 + (i & 3)] = n;
            }
        }
        __syncwarp();
        cluster_arrive();
        cluster_wait();
    }
}

constexpr int K2_NCHUNK = 16;
constexpr int K2_CHUNK_BYTES = KV_HEAD_BYTES / K2_NCHUNK;
constexpr int K2_OFF_BAR = KV_HEAD_BYTES + 8 * KV_GROUP_BYTES;
constexpr int K2_SMEM = K2_OFF_BAR + 256;

__device__ __forceinline__ float exp2_fixed(float y) {
    const float u = __uint_as_float(__float_as_uint(y) & 0xFF807FFFu) - 512.02545f;
    float t = fmaf(u, 0.019497588f, 0.114550486f);
    t = fmaf(t, u, -0.29839927f);
    return fmaf(t, u, y);
}
__device__ __forceinline__ uint32_t pack_fixed(float lo, float hi) { return __byte_perm(__float_as_uint(lo), __float_as_uint(hi), 0x6521); }

__device__ __forceinline__ void softmax_fast(const float (&s)[32], uint32_t (&p)[16]) {
#pragma unroll
    for (int b = 0; b < 8; b++) {
        if ((POLY_MASK >> b) & 1) {
            p[b * 2 + 0] = pack_fixed(exp2_fixed(s[b * 4 + 0]), exp2_fixed(s[b * 4 + 1]));
            p[b * 2 + 1] = pack_fixed(exp2_fixed(s[b * 4 + 2]), exp2_fixed(s[b * 4 + 3]));
        } else {
            p[b * 2 + 0] = pack_bf16(ex2(s[b * 4 + 0]), ex2(s[b * 4 + 1]));
            p[b * 2 + 1] = pack_bf16(ex2(s[b * 4 + 2]), ex2(s[b * 4 + 3]));
        }
    }
}

constexpr uint32_t K2_TILE = 8 * KV_GROUP_BYTES / 16;
__device__ __forceinline__ void issue_qk(float (&s)[32], const uint32_t (&qa)[8], uint32_t base) {
    wgmma_rs_n64<0>(s, qa[0], qa[1], qa[2], qa[3], base + (8u << 16), desc_hi(KV_GROUP_BYTES, 0), 0);
    wgmma_rs_n64<0>(s, qa[4], qa[5], qa[6], qa[7], base + 32, desc_hi(KV_GROUP_BYTES, 0), 1);
}
__device__ __forceinline__ void issue_pv(float (&o)[12], const uint32_t (&p)[16], uint32_t base) {
#pragma unroll
    for (int k = 0; k < 4; k++)
        wgmma_rs_n24<1>(o, p[k * 4], p[k * 4 + 1], p[k * 4 + 2], p[k * 4 + 3], base + 16 + ((KV_GROUP_BYTES / 16) << 16) + k * (2 * KV_GROUP_BYTES / 16),
                        desc_hi(128, 0), 1);
}

__global__ void __launch_bounds__(512, 1) k2_kernel() {
    extern __shared__ __align__(1024) uint8_t smem[];
    const uint32_t sb = s2u(smem);
    const int tid = threadIdx.x, lane = tid & 31;
    const int warp = __shfl_sync(~0u, tid >> 5, 0);
    const int wg = warp >> 2, wq = warp & 3, g = lane >> 2, q = lane & 3;
    const int head = blockIdx.x >> 2, quarter = blockIdx.x & 3;
    const uint32_t bar0 = sb + K2_OFF_BAR;
    if (tid == 0) {
        for (int i = 0; i <= K2_NCHUNK; i++) mbar_init(bar0 + i * 8, 1);
        asm volatile("mbarrier.arrive.shared::cta.b64 _, [%0];" ::"r"(bar0 + K2_NCHUNK * 8) : "memory");
        fence_barrier_init();
    }
    __syncthreads();
    griddep_wait();
    if (warp == 0 && lane < K2_NCHUNK) {
        mbar_expect(bar0 + lane * 8, K2_CHUNK_BYTES);
        bulk_load(sb + lane * K2_CHUNK_BYTES, g_QKV + (size_t)head * KV_HEAD_BYTES + lane * K2_CHUNK_BYTES, K2_CHUNK_BYTES, bar0 + lane * 8);
    }
    float kmax2;
    {
        const float2 v = *reinterpret_cast<const float2*>(g_kmax + head * 64 + lane * 2);
        kmax2 = fmaxf(v.x, v.y);
#pragma unroll
        for (int o = 16; o; o >>= 1) kmax2 = fmaxf(kmax2, __shfl_xor_sync(~0u, kmax2, o));
    }
    const uint32_t d0 = (sb & 0x3FFFF) >> 4;

#pragma unroll 1
    for (int pass = 0; pass < 2; pass++) {
        const int row0 = quarter * 512 + (pass * 4 + wg) * 64 + wq * 16;
        uint32_t qa[8];
        {
            const uint8_t* qp = g_QKV + Q_OFFSET + (size_t)head * KV_HEAD_BYTES + (row0 >> 3) * KV_GROUP_BYTES + g * 16 + q * 4;
            qa[0] = *reinterpret_cast<const uint32_t*>(qp);
            qa[1] = *reinterpret_cast<const uint32_t*>(qp + KV_GROUP_BYTES);
            qa[2] = *reinterpret_cast<const uint32_t*>(qp + 128);
            qa[3] = *reinterpret_cast<const uint32_t*>(qp + KV_GROUP_BYTES + 128);
            qa[4] = (q == 0) ? *reinterpret_cast<const uint32_t*>(qp + 256) : 0u;
            qa[5] = (q == 0) ? *reinterpret_cast<const uint32_t*>(qp + KV_GROUP_BYTES + 256) : 0u;
            qa[6] = 0u; qa[7] = 0u;
        }
        float c0, c1;
        {
            float n0 = bf_lo(qa[0]) * bf_lo(qa[0]) + bf_hi(qa[0]) * bf_hi(qa[0]) + bf_lo(qa[2]) * bf_lo(qa[2]) + bf_hi(qa[2]) * bf_hi(qa[2]) +
                       bf_lo(qa[4]) * bf_lo(qa[4]) + bf_hi(qa[4]) * bf_hi(qa[4]);
            float n1 = bf_lo(qa[1]) * bf_lo(qa[1]) + bf_hi(qa[1]) * bf_hi(qa[1]) + bf_lo(qa[3]) * bf_lo(qa[3]) + bf_hi(qa[3]) * bf_hi(qa[3]) +
                       bf_lo(qa[5]) * bf_lo(qa[5]) + bf_hi(qa[5]) * bf_hi(qa[5]);
            n0 += __shfl_xor_sync(~0u, n0, 1); n1 += __shfl_xor_sync(~0u, n1, 1);
            n0 += __shfl_xor_sync(~0u, n0, 2); n1 += __shfl_xor_sync(~0u, n1, 2);
            c0 = sqrtf(n0 * kmax2) * 1.02f;
            c1 = sqrtf(n1 * kmax2) * 1.02f;
        }
        uint32_t slow;
        {
            const bool bad = !(c0 <= 58.f && c1 <= 58.f);
            asm volatile("{\n.reg .pred p, r;\nsetp.ne.u32 p, %1, 0;\nbarrier.cta.red.or.pred.aligned r, %2, 128, p;\nselp.u32 %0, 1, 0, r;\n}\n"
                         : "=r"(slow) : "r"((uint32_t)bad), "r"(wg + 1) : "memory");
        }
        slow = __any_sync(~0u, slow);
        float o[12];
#pragma unroll
        for (int i = 0; i < 12; i++) o[i] = 0.f;
        if (!slow && q == 1) {
            qa[4] = pack_bf16(-c0, 768.f); qa[5] = pack_bf16(-c1, 768.f);
            qa[6] = 0xC0000000u;
        }
        qa[7] = __shfl_sync(~0u, qa[6], lane);
        qa[6] = __shfl_sync(~0u, qa[6], lane ^ 4);

        if (!slow) {
            float s0[32], s1[32];
            uint32_t p[16];
            mbar_wait(bar0, 0);
            reg_fence(qa);
            reg_fence(o);
            wg_fence();
            issue_qk(s0, qa, d0);
            wg_commit();
            uint32_t d = d0, bar = bar0;
#pragma unroll 1
            for (int t = 0; t < 16; t++) {
                wg_fence();
                issue_qk(s1, qa, d + K2_TILE);
                wg_commit();
                wg_wait<1>();
                reg_fence(s0);
                softmax_fast(s0, p);
                reg_fence(p);
                bar += 8;
                mbar_wait(bar, 0);
                wg_fence();
                issue_pv(o, p, d);
                wg_commit();
                issue_qk(s0, qa, d + 2 * K2_TILE);
                wg_commit();
                wg_wait<1>();
                reg_fence(s1);
                softmax_fast(s1, p);
                reg_fence(p);
                wg_fence();
                issue_pv(o, p, d + K2_TILE);
                wg_commit();
                d += 2 * K2_TILE;
            }
            wg_wait<0>();
            reg_fence(o);
            reg_fence(s0);
        } else {
            float m0 = -INFINITY, m1 = -INFINITY;
            float s[32];
            uint32_t p[16];
            reg_fence(qa);
#pragma unroll 1
            for (int t = 0; t < 32; t++) {
                mbar_wait(bar0 + (t / 2) * 8, 0);
                wg_fence();
                issue_qk(s, qa, d0 + t * K2_TILE);
                wg_commit();
                wg_wait<0>();
                reg_fence(s);
                reg_fence(o);
                float a0 = m0, a1 = m1;
#pragma unroll
                for (int k = 0; k < 8; k++) {
                    if ((POLY_MASK >> k) & 1) {
#pragma unroll
                        for (int i = 0; i < 4; i++) s[k * 4 + i] *= 0.5f;
                    }
                    a0 = fmaxf(a0, fmaxf(s[k * 4 + 0], s[k * 4 + 1]));
                    a1 = fmaxf(a1, fmaxf(s[k * 4 + 2], s[k * 4 + 3]));
                }
                a0 = fmaxf(a0, __shfl_xor_sync(~0u, a0, 1)); a1 = fmaxf(a1, __shfl_xor_sync(~0u, a1, 1));
                a0 = fmaxf(a0, __shfl_xor_sync(~0u, a0, 2)); a1 = fmaxf(a1, __shfl_xor_sync(~0u, a1, 2));
                const float r0 = ex2(m0 - a0), r1 = ex2(m1 - a1);
                m0 = a0; m1 = a1;
#pragma unroll
                for (int i = 0; i < 3; i++) { o[i * 4] *= r0; o[i * 4 + 1] *= r0; o[i * 4 + 2] *= r1; o[i * 4 + 3] *= r1; }
#pragma unroll
                for (int k = 0; k < 8; k++) {
                    p[k * 2 + 0] = pack_bf16(ex2(s[k * 4 + 0] - m0), ex2(s[k * 4 + 1] - m0));
                    p[k * 2 + 1] = pack_bf16(ex2(s[k * 4 + 2] - m1), ex2(s[k * 4 + 3] - m1));
                }
                reg_fence(p);
                reg_fence(o);
                wg_fence();
                issue_pv(o, p, d0 + t * K2_TILE);
                wg_commit();
                wg_wait<0>();
            }
            reg_fence(o);
        }
        const float l0 = __shfl_sync(~0u, o[8], (lane & ~3) | 3), l1 = __shfl_sync(~0u, o[10], (lane & ~3) | 3);
        const float i0 = 1.0f / l0, i1 = 1.0f / l1;
        uint32_t* op0 = reinterpret_cast<uint32_t*>(g_O + (size_t)(row0 + g) * DM + head * DH);
        uint32_t* op1 = reinterpret_cast<uint32_t*>(g_O + (size_t)(row0 + g + 8) * DM + head * DH);
        op0[q] = pack_bf16(o[0] * i0, o[1] * i0);
        op1[q] = pack_bf16(o[2] * i1, o[3] * i1);
        op0[4 + q] = pack_bf16(o[4] * i0, o[5] * i0);
        op1[4 + q] = pack_bf16(o[6] * i1, o[7] * i1);
        if (q == 2) {
            op0[8] = pack_bf16(o[8] * i0, o[9] * i0);
            op1[8] = pack_bf16(o[10] * i1, o[11] * i1);
        }
    }
}

constexpr int K3_OFF_B = 9 * 16384;
constexpr int K3_OFF_BAR = K3_OFF_B + 9 * 8192;
constexpr int K3_SMEM = K3_OFF_BAR + 128;

__global__ void __launch_bounds__(256, 1)
k3_kernel(const __grid_constant__ CUtensorMap tmO, const __grid_constant__ CUtensorMap tmWo, const __nv_bfloat16* __restrict__ x,
          const __nv_bfloat16* __restrict__ b2, __nv_bfloat16* __restrict__ out) {
    extern __shared__ __align__(1024) uint8_t smem[];
    const uint32_t sb = s2u(smem);
    const int tid = threadIdx.x, warp = tid >> 5, lane = tid & 31;
    const int wg = warp >> 2, g = lane >> 2, q = lane & 3;
    const int rb = blockIdx.x / 9, t = blockIdx.x % 9;
    const uint32_t bar0 = sb + K3_OFF_BAR;
    if (tid == 0) {
        for (int i = 0; i < 9; i++) mbar_init(bar0 + i * 8, 1);
        fence_barrier_init();
    }
    __syncthreads();
    griddep_wait();
    if (warp == 0 && lane < 9) {
        mbar_expect(bar0 + lane * 8, 16384 + 8192);
        tma2d(sb + lane * 16384, &tmO, lane * 64, rb * 128, bar0 + lane * 8);
        tma2d(sb + K3_OFF_B + lane * 8192, &tmWo, t * 64, lane * 64, bar0 + lane * 8);
    }
    float acc[32];
    {
#pragma unroll
        for (int i = 0; i < 32; i++) acc[i] = 0.f;
#pragma unroll 2
        for (int jj = 0; jj < 8; jj++) {
            const uint4* pp = g_part + ((size_t)(jj * 16 + rb) * 36 + t * 4) * 256 + tid;
#pragma unroll
            for (int s = 0; s < 4; s++) {
                const uint4 v = pp[s * 256];
                acc[s * 8 + 0] += bf_lo(v.x); acc[s * 8 + 1] += bf_hi(v.x); acc[s * 8 + 2] += bf_lo(v.y); acc[s * 8 + 3] += bf_hi(v.y);
                acc[s * 8 + 4] += bf_lo(v.z); acc[s * 8 + 5] += bf_hi(v.z); acc[s * 8 + 6] += bf_lo(v.w); acc[s * 8 + 7] += bf_hi(v.w);
            }
        }
        const int r0 = rb * 128 + warp * 16 + g;
#pragma unroll
        for (int b = 0; b < 8; b++) {
            const int col = t * 64 + b * 8 + q * 2;
            const uint32_t bb = *reinterpret_cast<const uint32_t*>(b2 + col);
            const uint32_t x0 = *reinterpret_cast<const uint32_t*>(x + (size_t)r0 * DM + col);
            const uint32_t x1 = *reinterpret_cast<const uint32_t*>(x + (size_t)(r0 + 8) * DM + col);
            acc[b * 4 + 0] = fmaf(acc[b * 4 + 0], 0.5f, bf_lo(x0) + bf_lo(bb)); acc[b * 4 + 1] = fmaf(acc[b * 4 + 1], 0.5f, bf_hi(x0) + bf_hi(bb));
            acc[b * 4 + 2] = fmaf(acc[b * 4 + 2], 0.5f, bf_lo(x1) + bf_lo(bb)); acc[b * 4 + 3] = fmaf(acc[b * 4 + 3], 0.5f, bf_hi(x1) + bf_hi(bb));
        }
    }
    const uint32_t da = desc_lo(sb + wg * 8192, 16);
    const uint32_t db = desc_lo(sb + K3_OFF_B, 8192);
#pragma unroll
    for (int kb = 0; kb < 9; kb++) {
        mbar_wait(bar0 + kb * 8, 0);
        wg_fence();
#pragma unroll
        for (int k = 0; k < 4; k++) wgmma_ss_n64<1>(acc, da + ((kb * 16384 + k * 32) >> 4), desc_hi(1024, 1), db + ((kb * 8192 + k * 2048) >> 4), desc_hi(1024, 1), 1);
        wg_commit();
    }
    wg_wait<0>();
    reg_fence(acc);
    const int r0 = rb * 128 + warp * 16 + g;
#pragma unroll
    for (int b = 0; b < 8; b++) {
        const int col = t * 64 + b * 8 + q * 2;
        *reinterpret_cast<uint32_t*>(out + (size_t)r0 * DM + col) = pack_bf16(acc[b * 4], acc[b * 4 + 1]);
        *reinterpret_cast<uint32_t*>(out + (size_t)(r0 + 8) * DM + col) = pack_bf16(acc[b * 4 + 2], acc[b * 4 + 3]);
    }
}

typedef CUresult (*EncodeFn)(CUtensorMap*, CUtensorMapDataType, cuuint32_t, void*, const cuuint64_t*, const cuuint64_t*, const cuuint32_t*,
                             const cuuint32_t*, CUtensorMapInterleave, CUtensorMapSwizzle, CUtensorMapL2promotion, CUtensorMapFloatOOBfill);

void make_map(EncodeFn fn, CUtensorMap* m, const void* base, int rank, const cuuint64_t* dims, const cuuint64_t* strides, const cuuint32_t* box) {
    cuuint32_t es[3] = {1, 1, 1};
    fn(m, CU_TENSOR_MAP_DATA_TYPE_BFLOAT16, rank, const_cast<void*>(base), dims, strides, box, es, CU_TENSOR_MAP_INTERLEAVE_NONE,
       CU_TENSOR_MAP_SWIZZLE_128B, CU_TENSOR_MAP_L2_PROMOTION_L2_256B, CU_TENSOR_MAP_FLOAT_OOB_FILL_NONE);
}

}

extern "C" void kernel_launch(void* const* d_in, const int* in_sizes, int n_in, void* d_out, int out_size) {
    const __nv_bfloat16* x = (const __nv_bfloat16*)d_in[0];
    const __nv_bfloat16* wqkv = (const __nv_bfloat16*)d_in[1];
    const __nv_bfloat16* wo = (const __nv_bfloat16*)d_in[2];
    const __nv_bfloat16* w1 = (const __nv_bfloat16*)d_in[4];
    const __nv_bfloat16* b1 = (const __nv_bfloat16*)d_in[5];
    const __nv_bfloat16* w2 = (const __nv_bfloat16*)d_in[6];
    const __nv_bfloat16* b2 = (const __nv_bfloat16*)d_in[7];
    __nv_bfloat16* out = (__nv_bfloat16*)d_out;

    EncodeFn fn = nullptr;
    cudaDriverEntryPointQueryResult qr;
    cudaGetDriverEntryPoint("cuTensorMapEncodeTiled", (void**)&fn, cudaEnableDefault, &qr);
    void* gO = nullptr;
    cudaGetSymbolAddress(&gO, g_O);
    CUtensorMap tmX, tmQ3, tmQ1, tm1, tm2, tmO, tmWo;
    {
        cuuint64_t d[3] = {64, SEQ, 9}, s[2] = {DM * 2, 128};
        cuuint32_t b[3] = {64, 8, 9};
        make_map(fn, &tmX, x, 3, d, s, b);
    }
    {
        cuuint64_t d[3] = {3 * DM, DM, 3}, s[2] = {3 * DM * 2, 128};
        cuuint32_t b[3] = {64, 16, 3};
        make_map(fn, &tmQ3, wqkv, 3, d, s, b);
        make_map(fn, &tmQ1, wqkv, 2, d, s, b);
    }
    {
        cuuint64_t d[2] = {FF, DM}, s[1] = {FF * 2};
        cuuint32_t b[2] = {64, 64};
        make_map(fn, &tm1, w1, 2, d, s, b);
        cuuint64_t d2[2] = {DM, FF}, s2[1] = {DM * 2};
        make_map(fn, &tm2, w2, 2, d2, s2, b);
    }
    {
        cuuint64_t d[2] = {DM, SEQ}, s[1] = {DM * 2};
        cuuint32_t b[2] = {64, 128};
        make_map(fn, &tmO, gO, 2, d, s, b);
        cuuint64_t d2[2] = {DM, DM};
        cuuint32_t b2x[2] = {64, 64};
        make_map(fn, &tmWo, wo, 2, d2, s, b2x);
    }
    cudaFuncSetAttribute(k1_kernel, cudaFuncAttributeMaxDynamicSharedMemorySize, K1_SMEM);
    cudaFuncSetAttribute(k2_kernel, cudaFuncAttributeMaxDynamicSharedMemorySize, K2_SMEM);
    cudaFuncSetAttribute(k3_kernel, cudaFuncAttributeMaxDynamicSharedMemorySize, K3_SMEM);

    cudaStream_t st = cudaStreamPerThread;
    cudaLaunchAttribute pdl[1];
    pdl[0].id = cudaLaunchAttributeProgrammaticStreamSerialization;
    pdl[0].val.programmaticStreamSerializationAllowed = 1;
    {
        cudaLaunchConfig_t cfg = {};
        cfg.gridDim = dim3(128); cfg.blockDim = dim3(384); cfg.dynamicSmemBytes = K1_SMEM; cfg.stream = st;
        cudaLaunchKernelEx(&cfg, k1_kernel, tmX, tmQ3, tmQ1, tm1, tm2, b1);
    }
    {
        cudaLaunchConfig_t cfg = {};
        cfg.gridDim = dim3(128); cfg.blockDim = dim3(512); cfg.dynamicSmemBytes = K2_SMEM; cfg.stream = st;
        cfg.attrs = pdl; cfg.numAttrs = 1;
        cudaLaunchKernelEx(&cfg, k2_kernel);
    }
    {
        cudaLaunchConfig_t cfg = {};
        cfg.gridDim = dim3(144); cfg.blockDim = dim3(256); cfg.dynamicSmemBytes = K3_SMEM; cfg.stream = st;
        cfg.attrs = pdl; cfg.numAttrs = 1;
        cudaLaunchKernelEx(&cfg, k3_kernel, tmO, tmWo, x, b2, out);
    }
}
```

```cpp
#include <cuda_runtime.h>
#include <cuda_bf16.h>
#include <cuda.h>
#include <stdint.h>

#define PROF(i) do { } while (0)
#define PROF_WG 0

namespace {

constexpr int SEQ = 2048, DM = 576, FF = 4608, NH = 32, DH = 18;

constexpr int KV_GROUP_BYTES = 5 * 128;
constexpr int KV_HEAD_BYTES = (SEQ / 8) * KV_GROUP_BYTES;
constexpr int Q_OFFSET = NH * KV_HEAD_BYTES;
#define POLY_MASK 0x92
__device__ __align__(1024) uint8_t g_QKV[2 * NH * KV_HEAD_BYTES];
__device__ __align__(1024) float g_kmax[NH * 64];
__device__ __align__(1024) uint4 g_part[8 * 16 * 36 * 256];
__device__ __align__(1024) uint4 g_base[16 * 36 * 256];
__device__ __align__(1024) uint32_t g_O[SEQ * DM / 2];
constexpr int WO_TILE_BYTES = DM * 144 * 2;
__device__ __align__(1024) uint8_t g_Wo[4 * WO_TILE_BYTES];

__device__ __forceinline__ uint32_t s2u(const void* p) { return (uint32_t)__cvta_generic_to_shared(p); }
__device__ __forceinline__ void mbar_init(uint32_t b, int c) { asm volatile("mbarrier.init.shared::cta.b64 [%0], %1;" ::"r"(b), "r"(c) : "memory"); }
__device__ __forceinline__ void mbar_expect(uint32_t b, uint32_t bytes) {
    asm volatile("mbarrier.arrive.expect_tx.shared::cta.b64 _, [%0], %1;" ::"r"(b), "r"(bytes) : "memory");
}
__device__ __forceinline__ void mbar_wait(uint32_t b, uint32_t parity) {
    asm volatile(
        "{\n.reg .pred p;\n.reg .u32 c;\n"
        "mbarrier.try_wait.parity.shared::cta.b64 p, [%0], %1;\n"
        "@p bra DONE;\n"
        "mov.u32 c, 0;\n"
        "LOOP:\n"
        "mbarrier.try_wait.parity.shared::cta.b64 p, [%0], %1;\n"
        "@p bra DONE;\n"
        "add.u32 c, c, 1;\n"
        "setp.lt.u32 p, c, 4194304;\n"
        "@p bra LOOP;\n"
        "trap;\n"
        "DONE:\n}\n" ::"r"(b), "r"(parity) : "memory");
}
__device__ __forceinline__ void fence_barrier_init() { asm volatile("fence.mbarrier_init.release.cluster;" ::: "memory"); }
__device__ __forceinline__ void fence_proxy_async() { asm volatile("fence.proxy.async.shared::cta;" ::: "memory"); }
__device__ __forceinline__ void cluster_arrive() { asm volatile("barrier.cluster.arrive.relaxed.aligned;" ::: "memory"); }
__device__ __forceinline__ void cluster_wait() { asm volatile("barrier.cluster.wait.aligned;" ::: "memory"); }
__device__ __forceinline__ void named_bar_sync(int id, int n) { asm volatile("bar.sync %0, %1;" ::"r"(id), "r"(n) : "memory"); }
__device__ __forceinline__ void griddep_wait() { asm volatile("griddepcontrol.wait;" ::: "memory"); }
__device__ __forceinline__ void griddep_launch() { asm volatile("griddepcontrol.launch_dependents;" ::: "memory"); }

__device__ __forceinline__ void tma3d_mc(uint32_t dst, const CUtensorMap* tm, int c0, int c1, int c2, uint32_t bar, uint16_t mask) {
    asm volatile("cp.async.bulk.tensor.3d.shared::cluster.global.mbarrier::complete_tx::bytes.multicast::cluster [%0], [%1, {%3, %4, %5}], [%2], %6;"
                 ::"r"(dst), "l"(tm), "r"(bar), "r"(c0), "r"(c1), "r"(c2), "h"(mask) : "memory");
}
__device__ __forceinline__ void tma2d_mc(uint32_t dst, const CUtensorMap* tm, int c0, int c1, uint32_t bar, uint16_t mask) {
    asm volatile("cp.async.bulk.tensor.2d.shared::cluster.global.mbarrier::complete_tx::bytes.multicast::cluster [%0], [%1, {%3, %4}], [%2], %5;"
                 ::"r"(dst), "l"(tm), "r"(bar), "r"(c0), "r"(c1), "h"(mask) : "memory");
}
__device__ __forceinline__ void tma3d(uint32_t dst, const CUtensorMap* tm, int c0, int c1, int c2, uint32_t bar) {
    asm volatile("cp.async.bulk.tensor.3d.shared::cluster.global.mbarrier::complete_tx::bytes [%0], [%1, {%3, %4, %5}], [%2];"
                 ::"r"(dst), "l"(tm), "r"(bar), "r"(c0), "r"(c1), "r"(c2) : "memory");
}
__device__ __forceinline__ void tma2d(uint32_t dst, const CUtensorMap* tm, int c0, int c1, uint32_t bar) {
    asm volatile("cp.async.bulk.tensor.2d.shared::cluster.global.mbarrier::complete_tx::bytes [%0], [%1, {%3, %4}], [%2];"
                 ::"r"(dst), "l"(tm), "r"(bar), "r"(c0), "r"(c1) : "memory");
}
__device__ __forceinline__ void bulk_load(uint32_t dst, const void* src, uint32_t bytes, uint32_t bar) {
    asm volatile("cp.async.bulk.shared::cluster.global.mbarrier::complete_tx::bytes [%0], [%1], %2, [%3];"
                 ::"r"(dst), "l"(src), "r"(bytes), "r"(bar) : "memory");
}
__device__ __forceinline__ void prefetch_tmap(const CUtensorMap* tm) { asm volatile("prefetch.tensormap [%0];" ::"l"(tm) : "memory"); }

__device__ __forceinline__ void wg_fence() { asm volatile("wgmma.fence.sync.aligned;" ::: "memory"); }
__device__ __forceinline__ void wg_commit() { asm volatile("wgmma.commit_group.sync.aligned;" ::: "memory"); }
template <int N> __device__ __forceinline__ void wg_wait() { asm volatile("wgmma.wait_group.sync.aligned %0;" ::"n"(N) : "memory"); }
template <int N> __device__ __forceinline__ void reg_fence(float (&d)[N]) {
#pragma unroll
    for (int i = 0; i < N; i++) asm volatile("" : "+f"(d[i])::"memory");
}
template <int N> __device__ __forceinline__ void reg_fence(uint32_t (&d)[N]) {
#pragma unroll
    for (int i = 0; i < N; i++) asm volatile("" : "+r"(d[i])::"memory");
}
template <int R> __device__ __forceinline__ void reg_alloc() { asm volatile("setmaxnreg.inc.sync.aligned.u32 %0;" ::"n"(R)); }
template <int R> __device__ __forceinline__ void reg_dealloc() { asm volatile("setmaxnreg.dec.sync.aligned.u32 %0;" ::"n"(R)); }

__device__ __forceinline__ uint32_t desc_lo(uint32_t addr, uint32_t lbo) { return ((addr & 0x3FFFF) >> 4) | ((lbo >> 4) << 16); }
__host__ __device__ constexpr uint32_t desc_hi(uint32_t sbo, uint32_t swz) { return (sbo >> 4) | (swz << 30); }
__device__ __forceinline__ uint32_t pack_bf16(float lo, float hi) {
    uint32_t r;
    asm("cvt.rn.bf16x2.f32 %0, %1, %2;" : "=r"(r) : "f"(hi), "f"(lo));
    return r;
}
__device__ __forceinline__ float bf_lo(uint32_t w) { return __uint_as_float(w << 16); }
__device__ __forceinline__ float bf_hi(uint32_t w) { return __uint_as_float(w & 0xFFFF0000u); }
__device__ __forceinline__ float ex2(float x) {
    float r;
    asm("ex2.approx.ftz.f32 %0, %1;" : "=f"(r) : "f"(x));
    return r;
}
__device__ __forceinline__ float tanh_fast(float x) {
    float r;
    asm("tanh.approx.f32 %0, %1;" : "=f"(r) : "f"(x));
    return r;
}
__device__ __forceinline__ float gelu2(float u) {
    const float w = fmaf(u * u, 0.0356774081f, 0.7978845608f);
    return fmaf(u, tanh_fast(u * w), u);
}

template<int TB> __device__ __forceinline__ void wgmma_ss_n216(float (&d)[108], uint32_t alo, uint32_t ahi, uint32_t blo, uint32_t bhi, int sd) {
    asm volatile("{\n.reg .pred p;\n.reg .b64 da, db;\nsetp.ne.b32 p, %110, 0;\nmov.b64 da, {%108, %112};\nmov.b64 db, {%109, %113};\n"
      "wgmma.mma_async.sync.aligned.m64n216k16.f32.bf16.bf16 {%0, %1, %2, %3, %4, %5, %6, %7, %8, %9, %10, %11, %12, %13, %14, %15, %16, %17, %18, %19, %20, %21, %22, %23, %24, %25, %26, %27, %28, %29, %30, %31, %32, %33, %34, %35, %36, %37, %38, %39, %40, %41, %42, %43, %44, %45, %46, %47, %48, %49, %50, %51, %52, %53, %54, %55, %56, %57, %58, %59, %60, %61, %62, %63, %64, %65, %66, %67, %68, %69, %70, %71, %72, %73, %74, %75, %76, %77, %78, %79, %80, %81, %82, %83, %84, %85, %86, %87, %88, %89, %90, %91, %92, %93, %94, %95, %96, %97, %98, %99, %100, %101, %102, %103, %104, %105, %106, %107}, da, db, p, 1, 1, 0, %111;\n}\n"
      : "+f"(d[0]), "+f"(d[1]), "+f"(d[2]), "+f"(d[3]), "+f"(d[4]), "+f"(d[5]), "+f"(d[6]), "+f"(d[7]), "+f"(d[8]), "+f"(d[9]), "+f"(d[10]), "+f"(d[11]), "+f"(d[12]), "+f"(d[13]), "+f"(d[14]), "+f"(d[15]), "+f"(d[16]), "+f"(d[17]), "+f"(d[18]), "+f"(d[19]), "+f"(d[20]), "+f"(d[21]), "+f"(d[22]), "+f"(d[23]), "+f"(d[24]), "+f"(d[25]), "+f"(d[26]), "+f"(d[27]), "+f"(d[28]), "+f"(d[29]), "+f"(d[30]), "+f"(d[31]), "+f"(d[32]), "+f"(d[33]), "+f"(d[34]), "+f"(d[35]), "+f"(d[36]), "+f"(d[37]), "+f"(d[38]), "+f"(d[39]), "+f"(d[40]), "+f"(d[41]), "+f"(d[42]), "+f"(d[43]), "+f"(d[44]), "+f"(d[45]), "+f"(d[46]), "+f"(d[47]), "+f"(d[48]), "+f"(d[49]), "+f"(d[50]), "+f"(d[51]), "+f"(d[52]), "+f"(d[53]), "+f"(d[54]), "+f"(d[55]), "+f"(d[56]), "+f"(d[57]), "+f"(d[58]), "+f"(d[59]), "+f"(d[60]), "+f"(d[61]), "+f"(d[62]), "+f"(d[63]), "+f"(d[64]), "+f"(d[65]), "+f"(d[66]), "+f"(d[67]), "+f"(d[68]), "+f"(d[69]), "+f"(d[70]), "+f"(d[71]), "+f"(d[72]), "+f"(d[73]), "+f"(d[74]), "+f"(d[75]), "+f"(d[76]), "+f"(d[77]), "+f"(d[78]), "+f"(d[79]), "+f"(d[80]), "+f"(d[81]), "+f"(d[82]), "+f"(d[83]), "+f"(d[84]), "+f"(d[85]), "+f"(d[86]), "+f"(d[87]), "+f"(d[88]), "+f"(d[89]), "+f"(d[90]), "+f"(d[91]), "+f"(d[92]), "+f"(d[93]), "+f"(d[94]), "+f"(d[95]), "+f"(d[96]), "+f"(d[97]), "+f"(d[98]), "+f"(d[99]), "+f"(d[100]), "+f"(d[101]), "+f"(d[102]), "+f"(d[103]), "+f"(d[104]), "+f"(d[105]), "+f"(d[106]), "+f"(d[107])
      : "r"(alo), "r"(blo), "r"(sd), "n"(TB), "r"(ahi), "r"(bhi));
}

template<int TB> __device__ __forceinline__ void wgmma_ss_n64(float (&d)[32], uint32_t alo, uint32_t ahi, uint32_t blo, uint32_t bhi, int sd) {
    asm volatile("{\n.reg .pred p;\n.reg .b64 da, db;\nsetp.ne.b32 p, %34, 0;\nmov.b64 da, {%32, %36};\nmov.b64 db, {%33, %37};\n"
      "wgmma.mma_async.sync.aligned.m64n64k16.f32.bf16.bf16 {%0, %1, %2, %3, %4, %5, %6, %7, %8, %9, %10, %11, %12, %13, %14, %15, %16, %17, %18, %19, %20, %21, %22, %23, %24, %25, %26, %27, %28, %29, %30, %31}, da, db, p, 1, 1, 0, %35;\n}\n"
      : "+f"(d[0]), "+f"(d[1]), "+f"(d[2]), "+f"(d[3]), "+f"(d[4]), "+f"(d[5]), "+f"(d[6]), "+f"(d[7]), "+f"(d[8]), "+f"(d[9]), "+f"(d[10]), "+f"(d[11]), "+f"(d[12]), "+f"(d[13]), "+f"(d[14]), "+f"(d[15]), "+f"(d[16]), "+f"(d[17]), "+f"(d[18]), "+f"(d[19]), "+f"(d[20]), "+f"(d[21]), "+f"(d[22]), "+f"(d[23]), "+f"(d[24]), "+f"(d[25]), "+f"(d[26]), "+f"(d[27]), "+f"(d[28]), "+f"(d[29]), "+f"(d[30]), "+f"(d[31])
      : "r"(alo), "r"(blo), "r"(sd), "n"(TB), "r"(ahi), "r"(bhi));
}

template<int TB> __device__ __forceinline__ void wgmma_rs_n64(float (&d)[32], uint32_t a0, uint32_t a1, uint32_t a2, uint32_t a3, uint32_t blo, uint32_t bhi, int sd) {
    asm volatile("{\n.reg .pred p;\n.reg .b64 db;\nsetp.ne.b32 p, %37, 0;\nmov.b64 db, {%36, %39};\n"
      "wgmma.mma_async.sync.aligned.m64n64k16.f32.bf16.bf16 {%0, %1, %2, %3, %4, %5, %6, %7, %8, %9, %10, %11, %12, %13, %14, %15, %16, %17, %18, %19, %20, %21, %22, %23, %24, %25, %26, %27, %28, %29, %30, %31}, {%32, %33, %34, %35}, db, p, 1, 1, %38;\n}\n"
      : "+f"(d[0]), "+f"(d[1]), "+f"(d[2]), "+f"(d[3]), "+f"(d[4]), "+f"(d[5]), "+f"(d[6]), "+f"(d[7]), "+f"(d[8]), "+f"(d[9]), "+f"(d[10]), "+f"(d[11]), "+f"(d[12]), "+f"(d[13]), "+f"(d[14]), "+f"(d[15]), "+f"(d[16]), "+f"(d[17]), "+f"(d[18]), "+f"(d[19]), "+f"(d[20]), "+f"(d[21]), "+f"(d[22]), "+f"(d[23]), "+f"(d[24]), "+f"(d[25]), "+f"(d[26]), "+f"(d[27]), "+f"(d[28]), "+f"(d[29]), "+f"(d[30]), "+f"(d[31])
      : "r"(a0), "r"(a1), "r"(a2), "r"(a3), "r"(blo), "r"(sd), "n"(TB), "r"(bhi));
}

template<int TB> __device__ __forceinline__ void wgmma_rs_n24(float (&d)[12], uint32_t a0, uint32_t a1, uint32_t a2, uint32_t a3, uint32_t blo, uint32_t bhi, int sd) {
    asm volatile("{\n.reg .pred p;\n.reg .b64 db;\nsetp.ne.b32 p, %17, 0;\nmov.b64 db, {%16, %19};\n"
      "wgmma.mma_async.sync.aligned.m64n24k16.f32.bf16.bf16 {%0, %1, %2, %3, %4, %5, %6, %7, %8, %9, %10, %11}, {%12, %13, %14, %15}, db, p, 1, 1, %18;\n}\n"
      : "+f"(d[0]), "+f"(d[1]), "+f"(d[2]), "+f"(d[3]), "+f"(d[4]), "+f"(d[5]), "+f"(d[6]), "+f"(d[7]), "+f"(d[8]), "+f"(d[9]), "+f"(d[10]), "+f"(d[11])
      : "r"(a0), "r"(a1), "r"(a2), "r"(a3), "r"(blo), "r"(sd), "n"(TB), "r"(bhi));
}

template<int TB> __device__ __forceinline__ void wgmma_rs_n144(float (&d)[72], uint32_t a0, uint32_t a1, uint32_t a2, uint32_t a3, uint32_t blo, uint32_t bhi, int sd) {
    asm volatile("{\n.reg .pred p;\n.reg .b64 db;\nsetp.ne.b32 p, %77, 0;\nmov.b64 db, {%76, %79};\n"
      "wgmma.mma_async.sync.aligned.m64n144k16.f32.bf16.bf16 {%0, %1, %2, %3, %4, %5, %6, %7, %8, %9, %10, %11, %12, %13, %14, %15, %16, %17, %18, %19, %20, %21, %22, %23, %24, %25, %26, %27, %28, %29, %30, %31, %32, %33, %34, %35, %36, %37, %38, %39, %40, %41, %42, %43, %44, %45, %46, %47, %48, %49, %50, %51, %52, %53, %54, %55, %56, %57, %58, %59, %60, %61, %62, %63, %64, %65, %66, %67, %68, %69, %70, %71}, {%72, %73, %74, %75}, db, p, 1, 1, %78;\n}\n"
      : "+f"(d[0]), "+f"(d[1]), "+f"(d[2]), "+f"(d[3]), "+f"(d[4]), "+f"(d[5]), "+f"(d[6]), "+f"(d[7]), "+f"(d[8]), "+f"(d[9]), "+f"(d[10]), "+f"(d[11]), "+f"(d[12]), "+f"(d[13]), "+f"(d[14]), "+f"(d[15]), "+f"(d[16]), "+f"(d[17]), "+f"(d[18]), "+f"(d[19]), "+f"(d[20]), "+f"(d[21]), "+f"(d[22]), "+f"(d[23]), "+f"(d[24]), "+f"(d[25]), "+f"(d[26]), "+f"(d[27]), "+f"(d[28]), "+f"(d[29]), "+f"(d[30]), "+f"(d[31]), "+f"(d[32]), "+f"(d[33]), "+f"(d[34]), "+f"(d[35]), "+f"(d[36]), "+f"(d[37]), "+f"(d[38]), "+f"(d[39]), "+f"(d[40]), "+f"(d[41]), "+f"(d[42]), "+f"(d[43]), "+f"(d[44]), "+f"(d[45]), "+f"(d[46]), "+f"(d[47]), "+f"(d[48]), "+f"(d[49]), "+f"(d[50]), "+f"(d[51]), "+f"(d[52]), "+f"(d[53]), "+f"(d[54]), "+f"(d[55]), "+f"(d[56]), "+f"(d[57]), "+f"(d[58]), "+f"(d[59]), "+f"(d[60]), "+f"(d[61]), "+f"(d[62]), "+f"(d[63]), "+f"(d[64]), "+f"(d[65]), "+f"(d[66]), "+f"(d[67]), "+f"(d[68]), "+f"(d[69]), "+f"(d[70]), "+f"(d[71])
      : "r"(a0), "r"(a1), "r"(a2), "r"(a3), "r"(blo), "r"(sd), "n"(TB), "r"(bhi));
}

constexpr int K1_XN_BYTES = 16 * 9216;
constexpr int K1_SLOT = 16384, K1_NSLOT = 5;
constexpr int K1_OFF_RING = K1_XN_BYTES;
constexpr int K1_OFF_BIAS = K1_OFF_RING + K1_NSLOT * K1_SLOT;
constexpr int K1_OFF_BAR = K1_OFF_BIAS + 576 * 2;
constexpr int K1_SMEM = K1_OFF_BAR + 256;
constexpr float QSCALE = 0.23570226039551584f * 1.4426950408889634f;

struct Ring {
    uint32_t slot, phase;
    __device__ __forceinline__ void advance() {
        if (++slot == K1_NSLOT) { slot = 0; phase ^= 1; }
    }
};

struct K1Ctx {
    uint32_t full0;
    uint32_t rel_addr;
    uint32_t descA, descB;
    Ring rd;
    uint32_t prev_slot;
    __device__ __forceinline__ uint32_t begin_stage() {
        mbar_wait(full0 + rd.slot * 8, rd.phase);
        wg_fence();
        return descB + rd.slot * (K1_SLOT >> 4);
    }
    __device__ __forceinline__ void end_stage() {
        wg_commit();
        wg_wait<1>();
        if (rel_addr) asm volatile("mbarrier.arrive.shared::cluster.b64 _, [%0];" ::"r"(rel_addr + prev_slot * 8) : "memory");
        prev_slot = rd.slot;
        rd.advance();
    }
};

__device__ __forceinline__ uint32_t descA_step(uint32_t base, int ks) { return base + (((ks >> 2) * 1024 + (ks & 3) * 32) >> 4); }
constexpr uint32_t K1_AHI = desc_hi(9216, 1), K1_BHI = desc_hi(1024, 1);

template <int V> struct IC { static constexpr int value = V; };
template <int I, int N, class F> __device__ __forceinline__ void static_for(F&& f) {
    if constexpr (I < N) { f(IC<I>{}); static_for<I + 1, N>(f); }
}

template <bool A_RS, bool B_RS, class Epi>
__device__ __forceinline__ void tile_pair(K1Ctx& c, float (&accA)[32], float (&accB)[32], uint32_t (&h)[144], Epi&& epi) {
    static_for<0, 9>([&](auto sc) {
        constexpr int s = decltype(sc)::value;
        const uint32_t db = c.begin_stage();
#pragma unroll
        for (int t = 0; t < 8; t++) {
            const int kk = s * 8 + t, ks = kk % 36;
            const uint32_t dbt = db + ((t * 2048) >> 4);
            if (kk < 36) {
                if constexpr (A_RS) wgmma_rs_n64<1>(accA, h[ks * 4], h[ks * 4 + 1], h[ks * 4 + 2], h[ks * 4 + 3], dbt, K1_BHI, ks != 0);
                else wgmma_ss_n64<1>(accA, descA_step(c.descA, ks), K1_AHI, dbt, K1_BHI, ks != 0);
            } else {
                if constexpr (B_RS) wgmma_rs_n64<1>(accB, h[ks * 4], h[ks * 4 + 1], h[ks * 4 + 2], h[ks * 4 + 3], dbt, K1_BHI, ks != 0);
                else wgmma_ss_n64<1>(accB, descA_step(c.descA, ks), K1_AHI, dbt, K1_BHI, ks != 0);
            }
        }
        c.end_stage();
        epi(sc);
    });
}

template <int B0, int NB, int HOFF>
__device__ __forceinline__ void gelu_blocks(const float (&acc)[32], uint32_t (&h)[144], const uint32_t (&bq)[8]) {
#pragma unroll
    for (int b = B0; b < B0 + NB; b++) {
        const float b0 = bf_lo(bq[b]), b1 = bf_hi(bq[b]);
        h[HOFF + b * 2 + 0] = pack_bf16(gelu2(acc[b * 4 + 0] + b0), gelu2(acc[b * 4 + 1] + b1));
        h[HOFF + b * 2 + 1] = pack_bf16(gelu2(acc[b * 4 + 2] + b0), gelu2(acc[b * 4 + 3] + b1));
    }
}
__device__ __forceinline__ void load_bias(uint32_t (&bq)[8], uint32_t addr) {
    asm volatile("ld.shared.v4.u32 {%0, %1, %2, %3}, [%4];" : "=r"(bq[0]), "=r"(bq[1]), "=r"(bq[2]), "=r"(bq[3]) : "r"(addr));
    asm volatile("ld.shared.v4.u32 {%0, %1, %2, %3}, [%4 + 16];" : "=r"(bq[4]), "=r"(bq[5]), "=r"(bq[6]), "=r"(bq[7]) : "r"(addr));
}
template <int S> __device__ __forceinline__ void store_part(const float (&o)[32], uint4* p) {
    uint4 v;
    v.x = pack_bf16(o[S * 8 + 0], o[S * 8 + 1]); v.y = pack_bf16(o[S * 8 + 2], o[S * 8 + 3]);
    v.z = pack_bf16(o[S * 8 + 4], o[S * 8 + 5]); v.w = pack_bf16(o[S * 8 + 6], o[S * 8 + 7]);
    p[S * 256] = v;
}

__global__ void __cluster_dims__(2, 1, 1) __launch_bounds__(384, 1)
k1_kernel(const __grid_constant__ CUtensorMap tmX, const __grid_constant__ CUtensorMap tmQ3, const __grid_constant__ CUtensorMap tmQ1,
          const __grid_constant__ CUtensorMap tm1, const __grid_constant__ CUtensorMap tm2, const __nv_bfloat16* __restrict__ b1,
          const __nv_bfloat16* __restrict__ wo) {
    extern __shared__ __align__(1024) uint8_t smem[];
    const uint32_t sb = s2u(smem);
    const int tid = threadIdx.x, lane = tid & 31;
    const int warp = __shfl_sync(~0u, tid >> 5, 0);
    const uint32_t rank = blockIdx.x & 1;
    const int cl = blockIdx.x >> 1;
    const int rb = (cl & 7) * 2 + rank;
    const int j = cl >> 3;
    const uint32_t full0 = sb + K1_OFF_BAR, empty0 = full0 + 8 * K1_NSLOT, xbar0 = full0 + 128;

    if (warp < 8) {
        PROF(0);
        if (lane == 0) {
            mbar_init(xbar0 + warp * 16, 1);
            mbar_init(xbar0 + warp * 16 + 8, 1);
            fence_barrier_init();
            mbar_expect(xbar0 + warp * 16, 9216);
            tma3d(sb + warp * 2 * 9216, &tmX, 0, rb * 128 + warp * 16, 0, xbar0 + warp * 16);
            mbar_expect(xbar0 + warp * 16 + 8, 9216);
            tma3d(sb + (warp * 2 + 1) * 9216, &tmX, 0, rb * 128 + warp * 16 + 8, 0, xbar0 + warp * 16 + 8);
        }
        __syncwarp();
        cluster_arrive();
        reg_alloc<240>();
#pragma unroll 1
        for (int p = 0; p < 4; p++) {
            mbar_wait(xbar0 + warp * 16 + (p >> 1) * 8, 0);
            uint4* row = reinterpret_cast<uint4*>(smem + (warp * 2 + (p >> 1)) * 9216 + (p & 1) * 512 + lane * 16);
            float f[72];
#pragma unroll
            for (int i = 0; i < 9; i++) {
                const uint4 v = row[i * 64];
                f[i * 8 + 0] = bf_lo(v.x); f[i * 8 + 1] = bf_hi(v.x); f[i * 8 + 2] = bf_lo(v.y); f[i * 8 + 3] = bf_hi(v.y);
                f[i * 8 + 4] = bf_lo(v.z); f[i * 8 + 5] = bf_hi(v.z); f[i * 8 + 6] = bf_lo(v.w); f[i * 8 + 7] = bf_hi(v.w);
            }
            float s0 = 0.f, s1 = 0.f, s2 = 0.f, s3 = 0.f;
#pragma unroll
            for (int i = 0; i < 72; i += 4) { s0 += f[i]; s1 += f[i + 1]; s2 += f[i + 2]; s3 += f[i + 3]; }
            float sm = (s0 + s1) + (s2 + s3);
            sm += __shfl_xor_sync(~0u, sm, 1); sm += __shfl_xor_sync(~0u, sm, 2); sm += __shfl_xor_sync(~0u, sm, 4);
            const float mean = sm * (1.0f / DM);
            s0 = s1 = s2 = s3 = 0.f;
#pragma unroll
            for (int i = 0; i < 72; i += 4) {
                f[i] -= mean; f[i + 1] -= mean; f[i + 2] -= mean; f[i + 3] -= mean;
                s0 = fmaf(f[i], f[i], s0); s1 = fmaf(f[i + 1], f[i + 1], s1);
                s2 = fmaf(f[i + 2], f[i + 2], s2); s3 = fmaf(f[i + 3], f[i + 3], s3);
            }
            float sq = (s0 + s1) + (s2 + s3);
            sq += __shfl_xor_sync(~0u, sq, 1); sq += __shfl_xor_sync(~0u, sq, 2); sq += __shfl_xor_sync(~0u, sq, 4);
            const float rstd = rsqrtf(sq * (1.0f / DM) + 1e-5f);
#pragma unroll
            for (int i = 0; i < 9; i++) {
                uint4 o;
                o.x = pack_bf16(f[i * 8 + 0] * rstd, f[i * 8 + 1] * rstd);
                o.y = pack_bf16(f[i * 8 + 2] * rstd, f[i * 8 + 3] * rstd);
                o.z = pack_bf16(f[i * 8 + 4] * rstd, f[i * 8 + 5] * rstd);
                o.w = pack_bf16(f[i * 8 + 6] * rstd, f[i * 8 + 7] * rstd);
                row[i * 64] = o;
            }
        }
        const int wg = warp >> 2, wq = warp & 3;
        fence_proxy_async();
        named_bar_sync(1 + wg, 128);
        cluster_wait();
        PROF(1);

        const int g = lane >> 2, q = lane & 3;
        K1Ctx c;
        c.full0 = full0;
        c.rel_addr = 0;
        c.descA = desc_lo(sb + wg * 8 * 9216, 16);
        c.descB = desc_lo(sb + K1_OFF_RING, 2048);
        c.rd.slot = 0; c.rd.phase = 0; c.prev_slot = 0;
        uint32_t biasq = sb + K1_OFF_BIAS + q * 32;
        uint32_t bq[8];

        uint32_t h[144];
        float accA[32], accB[32];
        {
            float accQ[108];
            uint32_t rel = 0;
            if (lane == 0 && wq < 2) asm("mapa.shared::cluster.u32 %0, %1, %2;" : "=r"(rel) : "r"(empty0), "r"(wq));
#pragma unroll 1
            for (int s = 0; s < 18; s++) {
                const uint32_t db = c.begin_stage();
                const uint32_t da = c.descA + (s >> 1) * 64 + (s & 1) * 4;
                wgmma_ss_n216<1>(accQ, da, K1_AHI, db, K1_BHI, s != 0);
                wgmma_ss_n216<1>(accQ, da + 2, K1_AHI, db + (8192 >> 4), K1_BHI, 1);
                c.end_stage();
                c.rel_addr = rel;
            }
            PROF(2);
            uint32_t rel9[9];
#pragma unroll
            for (int i9 = 0; i9 < 9; i9++) {
                const int p = 4 * i9 + q, hh = (p * 57) >> 9, r = p - 9 * hh;
                rel9[i9] = hh * KV_HEAD_BYTES + (r < 8 ? (r >> 2) * 128 + (r & 3) * 4 : 0);
            }
            uint32_t gb = 0, o2 = 0;
            float scl0 = 1.f, scl1 = 1.f;
            tile_pair<false, false>(c, accA, accB, h, [&](auto sc) {
                constexpr int s = decltype(sc)::value;
                if constexpr (s == 0) reg_fence(accQ);
                if constexpr (s < 6) {
                    constexpr int grp = s / 2, part = s % 2;
                    if constexpr (part == 0) {
                        const int G = 3 * j + grp, type = G >> 3;
                        gb = (G & 7) * 4 * KV_HEAD_BYTES + (rb * 16 + warp * 2) * KV_GROUP_BYTES + g * 16 + (type == 0 ? Q_OFFSET : (type == 2 ? 256 : 0));
                        o2 = type == 0 ? 256 : (type == 2 ? 264 : 512);
                        scl0 = type == 0 ? QSCALE : ((type == 1 && ((POLY_MASK >> (wq * 2)) & 1)) ? 2.f : 1.f);
                        scl1 = type == 0 ? QSCALE : ((type == 1 && ((POLY_MASK >> (wq * 2 + 1)) & 1)) ? 2.f : 1.f);
                    }
#pragma unroll
                    for (int i9 = part * 5; i9 < (part ? 9 : 5); i9++) {
                        const int b = grp * 9 + i9;
                        uint32_t off = gb + rel9[i9];
                        if (i9 >= 2 && (i9 & 1) == 0) off += (q == i9 / 2 - 1) ? o2 : 0;
                        *reinterpret_cast<uint32_t*>(g_QKV + off) = pack_bf16(accQ[b * 4] * scl0, accQ[b * 4 + 1] * scl0);
                        *reinterpret_cast<uint32_t*>(g_QKV + off + KV_GROUP_BYTES) = pack_bf16(accQ[b * 4 + 2] * scl1, accQ[b * 4 + 3] * scl1);
                    }
                    if constexpr (s == 5) asm volatile("bar.arrive 3, 352;" ::: "memory");
                }
                if constexpr (s == 4) { named_bar_sync(4, 288); load_bias(bq, biasq); }
                if constexpr (s == 5) reg_fence(accA);
                if constexpr (s >= 5) gelu_blocks<(s - 5) * 2, 2, 96>(accA, h, bq);
                if constexpr (s == 8) load_bias(bq, biasq + 128);
            });
        }
        PROF(3);
#pragma unroll
        for (int i = 32; i < 96; i++) asm volatile("mov.u32 %0, 0;" : "=r"(h[i]));
#pragma unroll 1
        for (int p = 1; p < 4; p++) {
            biasq += 256;
            tile_pair<false, false>(c, accA, accB, h, [&](auto sc) {
                constexpr int s = decltype(sc)::value;
                if constexpr (s == 0) {
                    reg_fence(accB);
#pragma unroll
                    for (int i = 0; i < 80; i++) h[i] = h[i + 32];
                }
                if constexpr (s < 4) gelu_blocks<s * 2, 2, 80>(accB, h, bq);
                if constexpr (s == 4) load_bias(bq, biasq);
                if constexpr (s == 5) reg_fence(accA);
                if constexpr (s >= 5) gelu_blocks<(s - 5) * 2, 2, 96>(accA, h, bq);
                if constexpr (s == 8) load_bias(bq, biasq + 128);
            });
        }
        PROF(4);
        tile_pair<false, true>(c, accA, accB, h, [&](auto sc) {
            constexpr int s = decltype(sc)::value;
            if constexpr (s == 0) reg_fence(accB);
            if constexpr (s < 4) gelu_blocks<s * 2, 2, 112>(accB, h, bq);
            if constexpr (s == 4) load_bias(bq, biasq + 256);
            if constexpr (s == 5) reg_fence(accA);
            if constexpr (s == 5 || s == 6) gelu_blocks<(s - 5) * 3, 3, 128>(accA, h, bq);
            if constexpr (s == 7) gelu_blocks<6, 2, 128>(accA, h, bq);
            if constexpr (s == 3 || s == 7) reg_fence(h);
        });
        PROF(5);
        uint4* pout = g_part + ((size_t)(j * 16 + rb) * 36) * 256 + tid;
#pragma unroll 1
        for (int p = 0; p < 4; p++) {
            tile_pair<true, true>(c, accA, accB, h, [&](auto sc) {
                constexpr int s = decltype(sc)::value;
                if constexpr (s == 0) reg_fence(accB);
                if constexpr (s < 4) store_part<s>(accB, pout);
                if constexpr (s == 5) reg_fence(accA);
                if constexpr (s >= 5) store_part<s - 5>(accA, pout + 1024);
            });
            pout += 2048;
            PROF(6 + p);
        }
        wg_wait<0>();
        reg_fence(accB);
        store_part<0>(accB, pout); store_part<1>(accB, pout); store_part<2>(accB, pout); store_part<3>(accB, pout);
        PROF(10);
        cluster_arrive();
        cluster_wait();
        PROF(11);
    } else {
        reg_dealloc<24>();
        if (warp == 8 && lane == 0) {
            prefetch_tmap(&tmQ3); prefetch_tmap(&tmQ1); prefetch_tmap(&tm1); prefetch_tmap(&tm2);
            for (int i = 0; i < K1_NSLOT; i++) { mbar_init(full0 + i * 8, 1); mbar_init(empty0 + i * 8, 4); }
            fence_barrier_init();
        }
        __syncwarp();
        cluster_arrive();
        cluster_wait();
        if (warp == 8) {
            if (lane == 0) {
                Ring w{0, 1};
                const uint32_t dst0 = sb + K1_OFF_RING + rank * 8192;
#pragma unroll 1
                for (int s = 0; s < 18; s++) {
                    mbar_wait(empty0 + w.slot * 8, w.phase);
                    mbar_expect(full0 + w.slot * 8, 16384);
                    const uint32_t dst = dst0 + w.slot * K1_SLOT;
                    tma3d_mc(dst, &tmQ3, j * 216, s * 32 + rank * 16, 0, full0 + w.slot * 8, 3);
                    tma2d_mc(dst + 6144, &tmQ1, j * 216 + 192, s * 32 + rank * 16, full0 + w.slot * 8, 3);
                    w.advance();
                }
                int tile = 0, kb = rank;
#pragma unroll 1
                for (int s = 0; s < 81; s++) {
                    mbar_wait(empty0 + w.slot * 8, w.phase);
                    mbar_expect(full0 + w.slot * 8, 16384);
                    const uint32_t dst = dst0 + w.slot * K1_SLOT;
                    if (tile < 9) tma2d_mc(dst, &tm1, j * 576 + tile * 64, kb * 64, full0 + w.slot * 8, 3);
                    else tma2d_mc(dst, &tm2, (tile - 9) * 64, j * 576 + kb * 64, full0 + w.slot * 8, 3);
                    kb += 2;
                    if (kb >= 9) { kb -= 9; tile++; }
                    w.advance();
                }
            }
        } else {
            const int ht = tid - 288;
            if (warp == 9) {
                uint32_t* sbias = reinterpret_cast<uint32_t*>(smem + K1_OFF_BIAS);
#pragma unroll 1
                for (int t = 0; t < 9; t++) sbias[t * 32 + (lane & 3) * 8 + (lane >> 2)] = reinterpret_cast<const uint32_t*>(b1 + j * 576)[t * 32 + lane];
                asm volatile("bar.arrive 4, 288;" ::: "memory");
            }
#pragma unroll 1
            for (int i = ht; i < 512; i += 96) {
                const int key = i & 127;
                uint8_t* p = g_QKV + (size_t)(j * 4 + (i >> 7)) * KV_HEAD_BYTES + (rb * 16 + (key >> 3)) * KV_GROUP_BYTES + 512 + (key & 7) * 16;
                *reinterpret_cast<uint32_t*>(p + 4) = ((POLY_MASK >> ((key >> 3) & 7)) & 1) ? 0x3F804000u : 0x00003F80u;
                *reinterpret_cast<uint32_t*>(p + 12) = 0x00003F80u;
            }
#pragma unroll 1
            for (int i = blockIdx.x * 324 + ht; i < blockIdx.x * 324 + 324; i += 96) {
                const int k = i / 72, nc = i - k * 72, ct = nc / 18;
                *reinterpret_cast<uint4*>(g_Wo + ct * WO_TILE_BYTES + (k >> 3) * 2304 + (nc - ct * 18) * 128 + (k & 7) * 16) =
                    __ldg(reinterpret_cast<const uint4*>(wo) + i);
            }
            named_bar_sync(3, 352);
#pragma unroll 1
            for (int i = warp - 9; i < 48; i += 3) {
                const int G = 3 * j + (i >> 4);
                if ((G >> 3) != 1) continue;
                const int head = (G & 7) * 4 + ((i >> 2) & 3), key = (i & 3) * 32 + lane;
                const uint8_t* p = g_QKV + (size_t)head * KV_HEAD_BYTES + (rb * 16 + (key >> 3)) * KV_GROUP_BYTES + (key & 7) * 16;
                const uint4 a = __ldcg(reinterpret_cast<const uint4*>(p)), b = __ldcg(reinterpret_cast<const uint4*>(p + 128));
                const uint32_t e = __ldcg(reinterpret_cast<const uint32_t*>(p + 512));
                float n = bf_lo(e) * bf_lo(e) + bf_hi(e) * bf_hi(e);
                n += bf_lo(a.x) * bf_lo(a.x) + bf_hi(a.x) * bf_hi(a.x) + bf_lo(a.y) * bf_lo(a.y) + bf_hi(a.y) * bf_hi(a.y);
                n += bf_lo(a.z) * bf_lo(a.z) + bf_hi(a.z) * bf_hi(a.z) + bf_lo(a.w) * bf_lo(a.w) + bf_hi(a.w) * bf_hi(a.w);
                n += bf_lo(b.x) * bf_lo(b.x) + bf_hi(b.x) * bf_hi(b.x) + bf_lo(b.y) * bf_lo(b.y) + bf_hi(b.y) * bf_hi(b.y);
                n += bf_lo(b.z) * bf_lo(b.z) + bf_hi(b.z) * bf_hi(b.z) + bf_lo(b.w) * bf_lo(b.w) + bf_hi(b.w) * bf_hi(b.w);
                if ((POLY_MASK >> ((key >> 3) & 7)) & 1) n *= 0.25f;
#pragma unroll
                for (int o = 16; o; o >>= 1) n = fmaxf(n, __shfl_xor_sync(~0u, n, o));
                if (lane == 0) g_kmax[head * 64 + rb * 4 + (i & 3)] = n;
            }
        }
        __syncwarp();
        cluster_arrive();
        cluster_wait();
    }
}

constexpr int K2_NCHUNK = 16;
constexpr int K2_CHUNK_BYTES = KV_HEAD_BYTES / K2_NCHUNK;
constexpr int K2_OFF_BAR = KV_HEAD_BYTES + 8 * KV_GROUP_BYTES;
constexpr int K2_OFF_Q = K2_OFF_BAR + 256;
constexpr int K2_SMEM = K2_OFF_Q + 12 * 512 * 4;

__device__ __forceinline__ float exp2_fixed(float y) {
    const float u = __uint_as_float(__float_as_uint(y) & 0xFF807FFFu) - 512.02545f;
    float t = fmaf(u, 0.019497588f, 0.114550486f);
    t = fmaf(t, u, -0.29839927f);
    return fmaf(t, u, y);
}
__device__ __forceinline__ uint32_t pack_fixed(float lo, float hi) { return __byte_perm(__float_as_uint(lo), __float_as_uint(hi), 0x6521); }

__device__ __forceinline__ void softmax_fast(const float (&s)[32], uint32_t (&p)[16]) {
#pragma unroll
    for (int b = 0; b < 8; b++) {
        if ((POLY_MASK >> b) & 1) {
            p[b * 2 + 0] = pack_fixed(exp2_fixed(s[b * 4 + 0]), exp2_fixed(s[b * 4 + 1]));
            p[b * 2 + 1] = pack_fixed(exp2_fixed(s[b * 4 + 2]), exp2_fixed(s[b * 4 + 3]));
        } else {
            p[b * 2 + 0] = pack_bf16(ex2(s[b * 4 + 0]), ex2(s[b * 4 + 1]));
            p[b * 2 + 1] = pack_bf16(ex2(s[b * 4 + 2]), ex2(s[b * 4 + 3]));
        }
    }
}

constexpr uint32_t K2_TILE = 8 * KV_GROUP_BYTES / 16;
__device__ __forceinline__ void issue_qk(float (&s)[32], const uint32_t (&qa)[8], uint32_t base) {
    wgmma_rs_n64<0>(s, qa[0], qa[1], qa[2], qa[3], base + (8u << 16), desc_hi(KV_GROUP_BYTES, 0), 0);
    wgmma_rs_n64<0>(s, qa[4], qa[5], qa[6], qa[7], base + 32, desc_hi(KV_GROUP_BYTES, 0), 1);
}
__device__ __forceinline__ void issue_pv(float (&o)[12], const uint32_t (&p)[16], uint32_t base) {
#pragma unroll
    for (int k = 0; k < 4; k++)
        wgmma_rs_n24<1>(o, p[k * 4], p[k * 4 + 1], p[k * 4 + 2], p[k * 4 + 3], base + 16 + ((KV_GROUP_BYTES / 16) << 16) + k * (2 * KV_GROUP_BYTES / 16),
                        desc_hi(128, 0), 1);
}

__device__ __forceinline__ void reduce_unit(int u, const __nv_bfloat16* __restrict__ x, const __nv_bfloat16* __restrict__ b2) {
    uint4 v[8];
#pragma unroll
    for (int jj = 0; jj < 8; jj++) v[jj] = __ldcg(g_part + jj * (16 * 36 * 256) + u);
    const int t = u & 255, pbr = u >> 8, rb = pbr / 36, pb = pbr - rb * 36;
    const int row = rb * 128 + (t >> 5) * 16 + ((t & 31) >> 2), col = pb * 16 + (t & 3) * 2;
    const uint32_t* xp = reinterpret_cast<const uint32_t*>(x + (size_t)row * DM + col);
    const uint32_t x0 = __ldg(xp), x1 = __ldg(xp + 4 * DM), x2 = __ldg(xp + 4), x3 = __ldg(xp + 4 * DM + 4);
    const uint32_t ba = __ldg(reinterpret_cast<const uint32_t*>(b2 + col)), bb = __ldg(reinterpret_cast<const uint32_t*>(b2 + col + 8));
    float a[8];
#pragma unroll
    for (int i = 0; i < 8; i++) a[i] = 0.f;
#pragma unroll
    for (int jj = 0; jj < 8; jj++) {
        a[0] += bf_lo(v[jj].x); a[1] += bf_hi(v[jj].x); a[2] += bf_lo(v[jj].y); a[3] += bf_hi(v[jj].y);
        a[4] += bf_lo(v[jj].z); a[5] += bf_hi(v[jj].z); a[6] += bf_lo(v[jj].w); a[7] += bf_hi(v[jj].w);
    }
    uint4 o;
    o.x = pack_bf16(fmaf(a[0], 0.5f, bf_lo(x0) + bf_lo(ba)), fmaf(a[1], 0.5f, bf_hi(x0) + bf_hi(ba)));
    o.y = pack_bf16(fmaf(a[2], 0.5f, bf_lo(x1) + bf_lo(ba)), fmaf(a[3], 0.5f, bf_hi(x1) + bf_hi(ba)));
    o.z = pack_bf16(fmaf(a[4], 0.5f, bf_lo(x2) + bf_lo(bb)), fmaf(a[5], 0.5f, bf_hi(x2) + bf_hi(bb)));
    o.w = pack_bf16(fmaf(a[6], 0.5f, bf_lo(x3) + bf_lo(bb)), fmaf(a[7], 0.5f, bf_hi(x3) + bf_hi(bb)));
    g_base[u] = o;
}

__global__ void __launch_bounds__(512, 1) k2_kernel(const __nv_bfloat16* __restrict__ x, const __nv_bfloat16* __restrict__ b2) {
    extern __shared__ __align__(1024) uint8_t smem[];
    const uint32_t sb = s2u(smem);
    const int tid = threadIdx.x, lane = tid & 31;
    const int warp = __shfl_sync(~0u, tid >> 5, 0);
    const int wg = warp >> 2, wq = warp & 3, g = lane >> 2, q = lane & 3;
    const int head = blockIdx.x >> 2, quarter = blockIdx.x & 3;
    const uint32_t bar0 = sb + K2_OFF_BAR;
    PROF(16);
    if (tid == 0) {
        for (int i = 0; i <= K2_NCHUNK; i++) mbar_init(bar0 + i * 8, 1);
        asm volatile("mbarrier.arrive.shared::cta.b64 _, [%0];" ::"r"(bar0 + K2_NCHUNK * 8) : "memory");
        fence_barrier_init();
    }
    __syncthreads();
    griddep_wait();
    PROF(17);
    uint32_t* qs = reinterpret_cast<uint32_t*>(smem + K2_OFF_Q) + tid;
    float kmax2;
    {
        uint32_t qv[12];
#pragma unroll
        for (int pass = 0; pass < 2; pass++) {
            const int row0 = quarter * 512 + (pass * 4 + wg) * 64 + wq * 16;
            const uint8_t* qp = g_QKV + Q_OFFSET + (size_t)head * KV_HEAD_BYTES + (row0 >> 3) * KV_GROUP_BYTES + g * 16 + q * 4;
            qv[pass * 6 + 0] = __ldcg(reinterpret_cast<const uint32_t*>(qp));
            qv[pass * 6 + 1] = __ldcg(reinterpret_cast<const uint32_t*>(qp + KV_GROUP_BYTES));
            qv[pass * 6 + 2] = __ldcg(reinterpret_cast<const uint32_t*>(qp + 128));
            qv[pass * 6 + 3] = __ldcg(reinterpret_cast<const uint32_t*>(qp + KV_GROUP_BYTES + 128));
            qv[pass * 6 + 4] = (q == 0) ? __ldcg(reinterpret_cast<const uint32_t*>(qp + 256)) : 0u;
            qv[pass * 6 + 5] = (q == 0) ? __ldcg(reinterpret_cast<const uint32_t*>(qp + KV_GROUP_BYTES + 256)) : 0u;
        }
        const float2 v = __ldcg(reinterpret_cast<const float2*>(g_kmax + head * 64 + lane * 2));
        if (lane == 0) {
            mbar_expect(bar0 + warp * 8, K2_CHUNK_BYTES);
            if (warp >= 4) __nanosleep(warp * 64);
            bulk_load(sb + warp * K2_CHUNK_BYTES, g_QKV + (size_t)head * KV_HEAD_BYTES + warp * K2_CHUNK_BYTES, K2_CHUNK_BYTES, bar0 + warp * 8);
        }
        __syncwarp();
#pragma unroll
        for (int i = 0; i < 12; i++) qs[i * 512] = qv[i];
        kmax2 = fmaxf(v.x, v.y);
#pragma unroll
        for (int o = 16; o; o >>= 1) kmax2 = fmaxf(kmax2, __shfl_xor_sync(~0u, kmax2, o));
    }
    const uint32_t d0 = (sb & 0x3FFFF) >> 4;

#pragma unroll 1
    for (int pass = 0; pass < 2; pass++) {
#pragma unroll 1
        for (int r = pass; r < 1 + 2 * pass; r++)
            if (lane < 24) reduce_unit((blockIdx.x * 16 + warp) * 72 + r * 24 + lane, x, b2);
        __syncwarp();
        const int row0 = quarter * 512 + (pass * 4 + wg) * 64 + wq * 16;
        uint32_t qa[8];
#pragma unroll
        for (int i = 0; i < 6; i++) qa[i] = qs[(pass * 6 + i) * 512];
        qa[6] = 0u;
        float c0, c1;
        {
            float n0 = bf_lo(qa[0]) * bf_lo(qa[0]) + bf_hi(qa[0]) * bf_hi(qa[0]) + bf_lo(qa[2]) * bf_lo(qa[2]) + bf_hi(qa[2]) * bf_hi(qa[2]) +
                       bf_lo(qa[4]) * bf_lo(qa[4]) + bf_hi(qa[4]) * bf_hi(qa[4]);
            float n1 = bf_lo(qa[1]) * bf_lo(qa[1]) + bf_hi(qa[1]) * bf_hi(qa[1]) + bf_lo(qa[3]) * bf_lo(qa[3]) + bf_hi(qa[3]) * bf_hi(qa[3]) +
                       bf_lo(qa[5]) * bf_lo(qa[5]) + bf_hi(qa[5]) * bf_hi(qa[5]);
            n0 += __shfl_xor_sync(~0u, n0, 1); n1 += __shfl_xor_sync(~0u, n1, 1);
            n0 += __shfl_xor_sync(~0u, n0, 2); n1 += __shfl_xor_sync(~0u, n1, 2);
            c0 = sqrtf(n0 * kmax2) * 1.02f;
            c1 = sqrtf(n1 * kmax2) * 1.02f;
        }
        uint32_t slow;
        {
            const bool bad = !(c0 <= 58.f && c1 <= 58.f);
            asm volatile("{\n.reg .pred p, r;\nsetp.ne.u32 p, %1, 0;\nbarrier.cta.red.or.pred.aligned r, %2, 128, p;\nselp.u32 %0, 1, 0, r;\n}\n"
                         : "=r"(slow) : "r"((uint32_t)bad), "r"(wg + 1) : "memory");
        }
        slow = __any_sync(~0u, slow);
        float o[12];
#pragma unroll
        for (int i = 0; i < 12; i++) o[i] = 0.f;
        if (!slow && q == 1) {
            qa[4] = pack_bf16(-c0, 768.f); qa[5] = pack_bf16(-c1, 768.f);
            qa[6] = 0xC0000000u;
        }
        qa[7] = __shfl_sync(~0u, qa[6], lane);
        qa[6] = __shfl_sync(~0u, qa[6], lane ^ 4);

        if (!slow) {
            float s0[32], s1[32];
            uint32_t p[16];
            mbar_wait(bar0, 0);
            PROF(18 + pass * 3);
            reg_fence(qa);
            reg_fence(o);
            wg_fence();
            issue_qk(s0, qa, d0);
            wg_commit();
            uint32_t d = d0, bar = bar0;
#pragma unroll 1
            for (int t = 0; t < 16; t++) {
                wg_fence();
                issue_qk(s1, qa, d + K2_TILE);
                wg_commit();
                wg_wait<1>();
                reg_fence(s0);
                softmax_fast(s0, p);
                reg_fence(p);
                bar += 8;
                mbar_wait(bar, 0);
                wg_fence();
                issue_pv(o, p, d);
                wg_commit();
                issue_qk(s0, qa, d + 2 * K2_TILE);
                wg_commit();
                wg_wait<1>();
                reg_fence(s1);
                softmax_fast(s1, p);
                reg_fence(p);
                wg_fence();
                issue_pv(o, p, d + K2_TILE);
                wg_commit();
                d += 2 * K2_TILE;
            }
            wg_wait<0>();
            reg_fence(o);
            reg_fence(s0);
        } else {
            float m0 = -INFINITY, m1 = -INFINITY;
            float s[32];
            uint32_t p[16];
            reg_fence(qa);
#pragma unroll 1
            for (int t = 0; t < 32; t++) {
                mbar_wait(bar0 + (t / 2) * 8, 0);
                wg_fence();
                issue_qk(s, qa, d0 + t * K2_TILE);
                wg_commit();
                wg_wait<0>();
                reg_fence(s);
                reg_fence(o);
                float a0 = m0, a1 = m1;
#pragma unroll
                for (int k = 0; k < 8; k++) {
                    if ((POLY_MASK >> k) & 1) {
#pragma unroll
                        for (int i = 0; i < 4; i++) s[k * 4 + i] *= 0.5f;
                    }
                    a0 = fmaxf(a0, fmaxf(s[k * 4 + 0], s[k * 4 + 1]));
                    a1 = fmaxf(a1, fmaxf(s[k * 4 + 2], s[k * 4 + 3]));
                }
                a0 = fmaxf(a0, __shfl_xor_sync(~0u, a0, 1)); a1 = fmaxf(a1, __shfl_xor_sync(~0u, a1, 1));
                a0 = fmaxf(a0, __shfl_xor_sync(~0u, a0, 2)); a1 = fmaxf(a1, __shfl_xor_sync(~0u, a1, 2));
                const float r0 = ex2(m0 - a0), r1 = ex2(m1 - a1);
                m0 = a0; m1 = a1;
#pragma unroll
                for (int i = 0; i < 3; i++) { o[i * 4] *= r0; o[i * 4 + 1] *= r0; o[i * 4 + 2] *= r1; o[i * 4 + 3] *= r1; }
#pragma unroll
                for (int k = 0; k < 8; k++) {
                    p[k * 2 + 0] = pack_bf16(ex2(s[k * 4 + 0] - m0), ex2(s[k * 4 + 1] - m0));
                    p[k * 2 + 1] = pack_bf16(ex2(s[k * 4 + 2] - m1), ex2(s[k * 4 + 3] - m1));
                }
                reg_fence(p);
                reg_fence(o);
                wg_fence();
                issue_pv(o, p, d0 + t * K2_TILE);
                wg_commit();
                wg_wait<0>();
            }
            reg_fence(o);
        }
        PROF(19 + pass * 3);
        const float l0 = __shfl_sync(~0u, o[8], (lane & ~3) | 3), l1 = __shfl_sync(~0u, o[10], (lane & ~3) | 3);
        const float i0 = 1.0f / l0, i1 = 1.0f / l1;
#pragma unroll
        for (int i = 0; i < 3; i++) {
            const int pc = head * 9 + (i < 2 ? i * 4 + q : 8);
            uint32_t* op = g_O + ((((row0 >> 6) * 36 + (pc >> 3)) * 128 + wq * 32 + g * 4 + (pc & 3)) * 4 + ((pc >> 2) & 1) * 2);
            if (i < 2 || q == 2) *reinterpret_cast<uint2*>(op) = make_uint2(pack_bf16(o[i * 4] * i0, o[i * 4 + 1] * i0), pack_bf16(o[i * 4 + 2] * i1, o[i * 4 + 3] * i1));
        }
        PROF(20 + pass * 3);
    }
}

constexpr int K3_PIECE = WO_TILE_BYTES / 9;
constexpr int K3_OFF_BAR = WO_TILE_BYTES;
constexpr int K3_SMEM = K3_OFF_BAR + 128;

__global__ void __cluster_dims__(2, 1, 1) __launch_bounds__(128, 1) k3_kernel(__nv_bfloat16* __restrict__ out) {
    extern __shared__ __align__(1024) uint8_t smem[];
    const uint32_t sb = s2u(smem);
    const int tid = threadIdx.x, warp = tid >> 5, lane = tid & 31;
    const int g = lane >> 2, q = lane & 3;
    const uint32_t rank = blockIdx.x & 1;
    const int ct = (blockIdx.x >> 1) & 3, rt = (blockIdx.x >> 3) * 2 + rank;
    const uint32_t bar0 = sb + K3_OFF_BAR;
    PROF(32);
    if (tid == 0) {
        for (int i = 0; i < 9; i++) { mbar_init(bar0 + i * 8, 1); mbar_expect(bar0 + i * 8, K3_PIECE); }
        fence_barrier_init();
    }
    cluster_arrive();
    cluster_wait();
    griddep_wait();
    PROF(33);
    uint4 a[36];
    const uint4* ap = reinterpret_cast<const uint4*>(g_O) + rt * 36 * 128 + tid;
#pragma unroll
    for (int k = 0; k < 4; k++) a[k] = __ldcg(ap + k * 128);
    if (tid < 9) {
        const uint32_t off = tid * K3_PIECE + rank * (K3_PIECE / 2);
        asm volatile("cp.async.bulk.shared::cluster.global.mbarrier::complete_tx::bytes.multicast::cluster [%0], [%1], %2, [%3], %4;"
                     ::"r"(sb + off), "l"(g_Wo + ct * WO_TILE_BYTES + off), "r"(K3_PIECE / 2), "r"(bar0 + tid * 8), "h"((uint16_t)3) : "memory");
    }
    float acc[72];
    {
        const uint4* bp = g_base + ((rt >> 1) * 36 + ct * 9) * 256 + (rt & 1) * 128 + tid;
        uint4 v[9];
#pragma unroll
        for (int i = 0; i < 9; i++) v[i] = __ldcg(bp + i * 256);
#pragma unroll
        for (int k = 4; k < 36; k++) a[k] = __ldcg(ap + k * 128);
#pragma unroll
        for (int i = 0; i < 9; i++) {
            acc[i * 8 + 0] = bf_lo(v[i].x); acc[i * 8 + 1] = bf_hi(v[i].x); acc[i * 8 + 2] = bf_lo(v[i].y); acc[i * 8 + 3] = bf_hi(v[i].y);
            acc[i * 8 + 4] = bf_lo(v[i].z); acc[i * 8 + 5] = bf_hi(v[i].z); acc[i * 8 + 6] = bf_lo(v[i].w); acc[i * 8 + 7] = bf_hi(v[i].w);
        }
    }
    PROF(34);
    const uint32_t db = desc_lo(sb, 2304);
#pragma unroll
    for (int kb = 0; kb < 9; kb++) {
        mbar_wait(bar0 + kb * 8, 0);
        wg_fence();
#pragma unroll
        for (int k = 0; k < 4; k++) {
            const uint4 f = a[kb * 4 + k];
            wgmma_rs_n144<1>(acc, f.x, f.y, f.z, f.w, db + (((kb * 4 + k) * 4608) >> 4), desc_hi(128, 0), 1);
        }
        wg_commit();
    }
    wg_wait<0>();
    reg_fence(acc);
    PROF(35);
    uint32_t* op = reinterpret_cast<uint32_t*>(out + (size_t)(rt * 64 + warp * 16 + g) * DM + ct * 144 + q * 2);
#pragma unroll
    for (int b = 0; b < 18; b++) {
        op[b * 4] = pack_bf16(acc[b * 4], acc[b * 4 + 1]);
        op[b * 4 + 4 * DM] = pack_bf16(acc[b * 4 + 2], acc[b * 4 + 3]);
    }
    cluster_arrive();
    cluster_wait();
    PROF(36);
}

typedef CUresult (*EncodeFn)(CUtensorMap*, CUtensorMapDataType, cuuint32_t, void*, const cuuint64_t*, const cuuint64_t*, const cuuint32_t*,
                             const cuuint32_t*, CUtensorMapInterleave, CUtensorMapSwizzle, CUtensorMapL2promotion, CUtensorMapFloatOOBfill);

void make_map(EncodeFn fn, CUtensorMap* m, const void* base, int rank, const cuuint64_t* dims, const cuuint64_t* strides, const cuuint32_t* box) {
    cuuint32_t es[3] = {1, 1, 1};
    fn(m, CU_TENSOR_MAP_DATA_TYPE_BFLOAT16, rank, const_cast<void*>(base), dims, strides, box, es, CU_TENSOR_MAP_INTERLEAVE_NONE,
       CU_TENSOR_MAP_SWIZZLE_128B, CU_TENSOR_MAP_L2_PROMOTION_L2_256B, CU_TENSOR_MAP_FLOAT_OOB_FILL_NONE);
}

}

extern "C" void kernel_launch(void* const* d_in, const int* in_sizes, int n_in, void* d_out, int out_size) {
    const __nv_bfloat16* x = (const __nv_bfloat16*)d_in[0];
    const __nv_bfloat16* wqkv = (const __nv_bfloat16*)d_in[1];
    const __nv_bfloat16* wo = (const __nv_bfloat16*)d_in[2];
    const __nv_bfloat16* w1 = (const __nv_bfloat16*)d_in[4];
    const __nv_bfloat16* b1 = (const __nv_bfloat16*)d_in[5];
    const __nv_bfloat16* w2 = (const __nv_bfloat16*)d_in[6];
    const __nv_bfloat16* b2 = (const __nv_bfloat16*)d_in[7];
    __nv_bfloat16* out = (__nv_bfloat16*)d_out;

    EncodeFn fn = nullptr;
    cudaDriverEntryPointQueryResult qr;
    cudaGetDriverEntryPoint("cuTensorMapEncodeTiled", (void**)&fn, cudaEnableDefault, &qr);
    CUtensorMap tmX, tmQ3, tmQ1, tm1, tm2;
    {
        cuuint64_t d[3] = {64, SEQ, 9}, s[2] = {DM * 2, 128};
        cuuint32_t b[3] = {64, 8, 9};
        make_map(fn, &tmX, x, 3, d, s, b);
    }
    {
        cuuint64_t d[3] = {3 * DM, DM, 3}, s[2] = {3 * DM * 2, 128};
        cuuint32_t b[3] = {64, 16, 3};
        make_map(fn, &tmQ3, wqkv, 3, d, s, b);
        make_map(fn, &tmQ1, wqkv, 2, d, s, b);
    }
    {
        cuuint64_t d[2] = {FF, DM}, s[1] = {FF * 2};
        cuuint32_t b[2] = {64, 64};
        make_map(fn, &tm1, w1, 2, d, s, b);
        cuuint64_t d2[2] = {DM, FF}, s2[1] = {DM * 2};
        make_map(fn, &tm2, w2, 2, d2, s2, b);
    }
    cudaFuncSetAttribute(k1_kernel, cudaFuncAttributeMaxDynamicSharedMemorySize, K1_SMEM);
    cudaFuncSetAttribute(k2_kernel, cudaFuncAttributeMaxDynamicSharedMemorySize, K2_SMEM);
    cudaFuncSetAttribute(k3_kernel, cudaFuncAttributeMaxDynamicSharedMemorySize, K3_SMEM);

    cudaStream_t st = cudaStreamPerThread;
    cudaLaunchAttribute pdl[1];
    pdl[0].id = cudaLaunchAttributeProgrammaticStreamSerialization;
    pdl[0].val.programmaticStreamSerializationAllowed = 1;
    {
        cudaLaunchConfig_t cfg = {};
        cfg.gridDim = dim3(128); cfg.blockDim = dim3(384); cfg.dynamicSmemBytes = K1_SMEM; cfg.stream = st;
        cudaLaunchKernelEx(&cfg, k1_kernel, tmX, tmQ3, tmQ1, tm1, tm2, b1, wo);
    }
    {
        cudaLaunchConfig_t cfg = {};
        cfg.gridDim = dim3(128); cfg.blockDim = dim3(512); cfg.dynamicSmemBytes = K2_SMEM; cfg.stream = st;
        cfg.attrs = pdl; cfg.numAttrs = 1;
        cudaLaunchKernelEx(&cfg, k2_kernel, x, b2);
    }
    {
        cudaLaunchConfig_t cfg = {};
        cfg.gridDim = dim3(128); cfg.blockDim = dim3(128); cfg.dynamicSmemBytes = K3_SMEM; cfg.stream = st;
        cfg.attrs = pdl; cfg.numAttrs = 1;
        cudaLaunchKernelEx(&cfg, k3_kernel, out);
    }
}
```

```cpp
#include <cuda_runtime.h>
#include <cuda_bf16.h>
#include <cuda.h>
#include <stdint.h>

#define PROF(i) do { } while (0)
#define PROFT(i) do { } while (0)
#define PROF_WG 0

namespace {

constexpr int SEQ = 2048, DM = 576, FF = 4608, NH = 32, DH = 18;

constexpr int KV_GROUP_BYTES = 5 * 128;
constexpr int KV_HEAD_BYTES = (SEQ / 8) * KV_GROUP_BYTES;
constexpr int Q_OFFSET = NH * KV_HEAD_BYTES;
#define POLY_MASK 0x92
__device__ __align__(1024) uint8_t g_QKV[2 * NH * KV_HEAD_BYTES];
__device__ __align__(1024) float g_kmax[NH * 64];
__device__ __align__(1024) uint4 g_part[8 * 16 * 36 * 256];
__device__ __align__(1024) uint4 g_base[16 * 36 * 256];
__device__ __align__(1024) uint32_t g_O[SEQ * DM / 2];
__device__ unsigned int g_flag[16 * 8];
constexpr int WO_TILE_BYTES = DM * 144 * 2;
__device__ __align__(1024) uint8_t g_Wo[4 * WO_TILE_BYTES];

__device__ __forceinline__ uint32_t s2u(const void* p) { return (uint32_t)__cvta_generic_to_shared(p); }
__device__ __forceinline__ void mbar_init(uint32_t b, int c) { asm volatile("mbarrier.init.shared::cta.b64 [%0], %1;" ::"r"(b), "r"(c) : "memory"); }
__device__ __forceinline__ void mbar_expect(uint32_t b, uint32_t bytes) {
    asm volatile("mbarrier.arrive.expect_tx.shared::cta.b64 _, [%0], %1;" ::"r"(b), "r"(bytes) : "memory");
}
__device__ __forceinline__ void mbar_wait(uint32_t b, uint32_t parity) {
    asm volatile(
        "{\n.reg .pred p;\n.reg .u32 c;\n"
        "mbarrier.try_wait.parity.shared::cta.b64 p, [%0], %1;\n"
        "@p bra DONE;\n"
        "mov.u32 c, 0;\n"
        "LOOP:\n"
        "mbarrier.try_wait.parity.shared::cta.b64 p, [%0], %1;\n"
        "@p bra DONE;\n"
        "add.u32 c, c, 1;\n"
        "setp.lt.u32 p, c, 4194304;\n"
        "@p bra LOOP;\n"
        "trap;\n"
        "DONE:\n}\n" ::"r"(b), "r"(parity) : "memory");
}
__device__ __forceinline__ void fence_barrier_init() { asm volatile("fence.mbarrier_init.release.cluster;" ::: "memory"); }
__device__ __forceinline__ void fence_proxy_async() { asm volatile("fence.proxy.async.shared::cta;" ::: "memory"); }
__device__ __forceinline__ void cluster_arrive() { asm volatile("barrier.cluster.arrive.relaxed.aligned;" ::: "memory"); }
__device__ __forceinline__ void cluster_wait() { asm volatile("barrier.cluster.wait.aligned;" ::: "memory"); }
__device__ __forceinline__ void named_bar_sync(int id, int n) { asm volatile("bar.sync %0, %1;" ::"r"(id), "r"(n) : "memory"); }
__device__ __forceinline__ void griddep_wait() { asm volatile("griddepcontrol.wait;" ::: "memory"); }
__device__ __forceinline__ void griddep_launch() { asm volatile("griddepcontrol.launch_dependents;" ::: "memory"); }

__device__ __forceinline__ void tma3d_mc(uint32_t dst, const CUtensorMap* tm, int c0, int c1, int c2, uint32_t bar, uint16_t mask) {
    asm volatile("cp.async.bulk.tensor.3d.shared::cluster.global.mbarrier::complete_tx::bytes.multicast::cluster [%0], [%1, {%3, %4, %5}], [%2], %6;"
                 ::"r"(dst), "l"(tm), "r"(bar), "r"(c0), "r"(c1), "r"(c2), "h"(mask) : "memory");
}
__device__ __forceinline__ void tma2d_mc(uint32_t dst, const CUtensorMap* tm, int c0, int c1, uint32_t bar, uint16_t mask) {
    asm volatile("cp.async.bulk.tensor.2d.shared::cluster.global.mbarrier::complete_tx::bytes.multicast::cluster [%0], [%1, {%3, %4}], [%2], %5;"
                 ::"r"(dst), "l"(tm), "r"(bar), "r"(c0), "r"(c1), "h"(mask) : "memory");
}
__device__ __forceinline__ void tma3d(uint32_t dst, const CUtensorMap* tm, int c0, int c1, int c2, uint32_t bar) {
    asm volatile("cp.async.bulk.tensor.3d.shared::cluster.global.mbarrier::complete_tx::bytes [%0], [%1, {%3, %4, %5}], [%2];"
                 ::"r"(dst), "l"(tm), "r"(bar), "r"(c0), "r"(c1), "r"(c2) : "memory");
}
__device__ __forceinline__ void tma2d(uint32_t dst, const CUtensorMap* tm, int c0, int c1, uint32_t bar) {
    asm volatile("cp.async.bulk.tensor.2d.shared::cluster.global.mbarrier::complete_tx::bytes [%0], [%1, {%3, %4}], [%2];"
                 ::"r"(dst), "l"(tm), "r"(bar), "r"(c0), "r"(c1) : "memory");
}
__device__ __forceinline__ void bulk_load(uint32_t dst, const void* src, uint32_t bytes, uint32_t bar) {
    asm volatile("cp.async.bulk.shared::cluster.global.mbarrier::complete_tx::bytes [%0], [%1], %2, [%3];"
                 ::"r"(dst), "l"(src), "r"(bytes), "r"(bar) : "memory");
}
__device__ __forceinline__ void prefetch_tmap(const CUtensorMap* tm) { asm volatile("prefetch.tensormap [%0];" ::"l"(tm) : "memory"); }

__device__ __forceinline__ void wg_fence() { asm volatile("wgmma.fence.sync.aligned;" ::: "memory"); }
__device__ __forceinline__ void wg_commit() { asm volatile("wgmma.commit_group.sync.aligned;" ::: "memory"); }
template <int N> __device__ __forceinline__ void wg_wait() { asm volatile("wgmma.wait_group.sync.aligned %0;" ::"n"(N) : "memory"); }
template <int N> __device__ __forceinline__ void reg_fence(float (&d)[N]) {
#pragma unroll
    for (int i = 0; i < N; i++) asm volatile("" : "+f"(d[i])::"memory");
}
template <int N> __device__ __forceinline__ void reg_fence(uint32_t (&d)[N]) {
#pragma unroll
    for (int i = 0; i < N; i++) asm volatile("" : "+r"(d[i])::"memory");
}
template <int R> __device__ __forceinline__ void reg_alloc() { asm volatile("setmaxnreg.inc.sync.aligned.u32 %0;" ::"n"(R)); }
template <int R> __device__ __forceinline__ void reg_dealloc() { asm volatile("setmaxnreg.dec.sync.aligned.u32 %0;" ::"n"(R)); }

__device__ __forceinline__ uint32_t desc_lo(uint32_t addr, uint32_t lbo) { return ((addr & 0x3FFFF) >> 4) | ((lbo >> 4) << 16); }
__host__ __device__ constexpr uint32_t desc_hi(uint32_t sbo, uint32_t swz) { return (sbo >> 4) | (swz << 30); }
__device__ __forceinline__ uint32_t pack_bf16(float lo, float hi) {
    uint32_t r;
    asm("cvt.rn.bf16x2.f32 %0, %1, %2;" : "=r"(r) : "f"(hi), "f"(lo));
    return r;
}
__device__ __forceinline__ float bf_lo(uint32_t w) { return __uint_as_float(w << 16); }
__device__ __forceinline__ float bf_hi(uint32_t w) { return __uint_as_float(w & 0xFFFF0000u); }
__device__ __forceinline__ float ex2(float x) {
    float r;
    asm("ex2.approx.ftz.f32 %0, %1;" : "=f"(r) : "f"(x));
    return r;
}
__device__ __forceinline__ float tanh_fast(float x) {
    float r;
    asm("tanh.approx.f32 %0, %1;" : "=f"(r) : "f"(x));
    return r;
}
__device__ __forceinline__ float gelu2(float u) {
    const float w = fmaf(u * u, 0.0356774081f, 0.7978845608f);
    return fmaf(u, tanh_fast(u * w), u);
}

template<int TB> __device__ __forceinline__ void wgmma_ss_n216(float (&d)[108], uint32_t alo, uint32_t ahi, uint32_t blo, uint32_t bhi, int sd) {
    asm volatile("{\n.reg .pred p;\n.reg .b64 da, db;\nsetp.ne.b32 p, %110, 0;\nmov.b64 da, {%108, %112};\nmov.b64 db, {%109, %113};\n"
      "wgmma.mma_async.sync.aligned.m64n216k16.f32.bf16.bf16 {%0, %1, %2, %3, %4, %5, %6, %7, %8, %9, %10, %11, %12, %13, %14, %15, %16, %17, %18, %19, %20, %21, %22, %23, %24, %25, %26, %27, %28, %29, %30, %31, %32, %33, %34, %35, %36, %37, %38, %39, %40, %41, %42, %43, %44, %45, %46, %47, %48, %49, %50, %51, %52, %53, %54, %55, %56, %57, %58, %59, %60, %61, %62, %63, %64, %65, %66, %67, %68, %69, %70, %71, %72, %73, %74, %75, %76, %77, %78, %79, %80, %81, %82, %83, %84, %85, %86, %87, %88, %89, %90, %91, %92, %93, %94, %95, %96, %97, %98, %99, %100, %101, %102, %103, %104, %105, %106, %107}, da, db, p, 1, 1, 0, %111;\n}\n"
      : "+f"(d[0]), "+f"(d[1]), "+f"(d[2]), "+f"(d[3]), "+f"(d[4]), "+f"(d[5]), "+f"(d[6]), "+f"(d[7]), "+f"(d[8]), "+f"(d[9]), "+f"(d[10]), "+f"(d[11]), "+f"(d[12]), "+f"(d[13]), "+f"(d[14]), "+f"(d[15]), "+f"(d[16]), "+f"(d[17]), "+f"(d[18]), "+f"(d[19]), "+f"(d[20]), "+f"(d[21]), "+f"(d[22]), "+f"(d[23]), "+f"(d[24]), "+f"(d[25]), "+f"(d[26]), "+f"(d[27]), "+f"(d[28]), "+f"(d[29]), "+f"(d[30]), "+f"(d[31]), "+f"(d[32]), "+f"(d[33]), "+f"(d[34]), "+f"(d[35]), "+f"(d[36]), "+f"(d[37]), "+f"(d[38]), "+f"(d[39]), "+f"(d[40]), "+f"(d[41]), "+f"(d[42]), "+f"(d[43]), "+f"(d[44]), "+f"(d[45]), "+f"(d[46]), "+f"(d[47]), "+f"(d[48]), "+f"(d[49]), "+f"(d[50]), "+f"(d[51]), "+f"(d[52]), "+f"(d[53]), "+f"(d[54]), "+f"(d[55]), "+f"(d[56]), "+f"(d[57]), "+f"(d[58]), "+f"(d[59]), "+f"(d[60]), "+f"(d[61]), "+f"(d[62]), "+f"(d[63]), "+f"(d[64]), "+f"(d[65]), "+f"(d[66]), "+f"(d[67]), "+f"(d[68]), "+f"(d[69]), "+f"(d[70]), "+f"(d[71]), "+f"(d[72]), "+f"(d[73]), "+f"(d[74]), "+f"(d[75]), "+f"(d[76]), "+f"(d[77]), "+f"(d[78]), "+f"(d[79]), "+f"(d[80]), "+f"(d[81]), "+f"(d[82]), "+f"(d[83]), "+f"(d[84]), "+f"(d[85]), "+f"(d[86]), "+f"(d[87]), "+f"(d[88]), "+f"(d[89]), "+f"(d[90]), "+f"(d[91]), "+f"(d[92]), "+f"(d[93]), "+f"(d[94]), "+f"(d[95]), "+f"(d[96]), "+f"(d[97]), "+f"(d[98]), "+f"(d[99]), "+f"(d[100]), "+f"(d[101]), "+f"(d[102]), "+f"(d[103]), "+f"(d[104]), "+f"(d[105]), "+f"(d[106]), "+f"(d[107])
      : "r"(alo), "r"(blo), "r"(sd), "n"(TB), "r"(ahi), "r"(bhi));
}

template<int TB> __device__ __forceinline__ void wgmma_ss_n64(float (&d)[32], uint32_t alo, uint32_t ahi, uint32_t blo, uint32_t bhi, int sd) {
    asm volatile("{\n.reg .pred p;\n.reg .b64 da, db;\nsetp.ne.b32 p, %34, 0;\nmov.b64 da, {%32, %36};\nmov.b64 db, {%33, %37};\n"
      "wgmma.mma_async.sync.aligned.m64n64k16.f32.bf16.bf16 {%0, %1, %2, %3, %4, %5, %6, %7, %8, %9, %10, %11, %12, %13, %14, %15, %16, %17, %18, %19, %20, %21, %22, %23, %24, %25, %26, %27, %28, %29, %30, %31}, da, db, p, 1, 1, 0, %35;\n}\n"
      : "+f"(d[0]), "+f"(d[1]), "+f"(d[2]), "+f"(d[3]), "+f"(d[4]), "+f"(d[5]), "+f"(d[6]), "+f"(d[7]), "+f"(d[8]), "+f"(d[9]), "+f"(d[10]), "+f"(d[11]), "+f"(d[12]), "+f"(d[13]), "+f"(d[14]), "+f"(d[15]), "+f"(d[16]), "+f"(d[17]), "+f"(d[18]), "+f"(d[19]), "+f"(d[20]), "+f"(d[21]), "+f"(d[22]), "+f"(d[23]), "+f"(d[24]), "+f"(d[25]), "+f"(d[26]), "+f"(d[27]), "+f"(d[28]), "+f"(d[29]), "+f"(d[30]), "+f"(d[31])
      : "r"(alo), "r"(blo), "r"(sd), "n"(TB), "r"(ahi), "r"(bhi));
}

template<int TB> __device__ __forceinline__ void wgmma_rs_n64(float (&d)[32], uint32_t a0, uint32_t a1, uint32_t a2, uint32_t a3, uint32_t blo, uint32_t bhi, int sd) {
    asm volatile("{\n.reg .pred p;\n.reg .b64 db;\nsetp.ne.b32 p, %37, 0;\nmov.b64 db, {%36, %39};\n"
      "wgmma.mma_async.sync.aligned.m64n64k16.f32.bf16.bf16 {%0, %1, %2, %3, %4, %5, %6, %7, %8, %9, %10, %11, %12, %13, %14, %15, %16, %17, %18, %19, %20, %21, %22, %23, %24, %25, %26, %27, %28, %29, %30, %31}, {%32, %33, %34, %35}, db, p, 1, 1, %38;\n}\n"
      : "+f"(d[0]), "+f"(d[1]), "+f"(d[2]), "+f"(d[3]), "+f"(d[4]), "+f"(d[5]), "+f"(d[6]), "+f"(d[7]), "+f"(d[8]), "+f"(d[9]), "+f"(d[10]), "+f"(d[11]), "+f"(d[12]), "+f"(d[13]), "+f"(d[14]), "+f"(d[15]), "+f"(d[16]), "+f"(d[17]), "+f"(d[18]), "+f"(d[19]), "+f"(d[20]), "+f"(d[21]), "+f"(d[22]), "+f"(d[23]), "+f"(d[24]), "+f"(d[25]), "+f"(d[26]), "+f"(d[27]), "+f"(d[28]), "+f"(d[29]), "+f"(d[30]), "+f"(d[31])
      : "r"(a0), "r"(a1), "r"(a2), "r"(a3), "r"(blo), "r"(sd), "n"(TB), "r"(bhi));
}

template<int TB> __device__ __forceinline__ void wgmma_rs_n24(float (&d)[12], uint32_t a0, uint32_t a1, uint32_t a2, uint32_t a3, uint32_t blo, uint32_t bhi, int sd) {
    asm volatile("{\n.reg .pred p;\n.reg .b64 db;\nsetp.ne.b32 p, %17, 0;\nmov.b64 db, {%16, %19};\n"
      "wgmma.mma_async.sync.aligned.m64n24k16.f32.bf16.bf16 {%0, %1, %2, %3, %4, %5, %6, %7, %8, %9, %10, %11}, {%12, %13, %14, %15}, db, p, 1, 1, %18;\n}\n"
      : "+f"(d[0]), "+f"(d[1]), "+f"(d[2]), "+f"(d[3]), "+f"(d[4]), "+f"(d[5]), "+f"(d[6]), "+f"(d[7]), "+f"(d[8]), "+f"(d[9]), "+f"(d[10]), "+f"(d[11])
      : "r"(a0), "r"(a1), "r"(a2), "r"(a3), "r"(blo), "r"(sd), "n"(TB), "r"(bhi));
}

template<int TB> __device__ __forceinline__ void wgmma_rs_n144(float (&d)[72], uint32_t a0, uint32_t a1, uint32_t a2, uint32_t a3, uint32_t blo, uint32_t bhi, int sd) {
    asm volatile("{\n.reg .pred p;\n.reg .b64 db;\nsetp.ne.b32 p, %77, 0;\nmov.b64 db, {%76, %79};\n"
      "wgmma.mma_async.sync.aligned.m64n144k16.f32.bf16.bf16 {%0, %1, %2, %3, %4, %5, %6, %7, %8, %9, %10, %11, %12, %13, %14, %15, %16, %17, %18, %19, %20, %21, %22, %23, %24, %25, %26, %27, %28, %29, %30, %31, %32, %33, %34, %35, %36, %37, %38, %39, %40, %41, %42, %43, %44, %45, %46, %47, %48, %49, %50, %51, %52, %53, %54, %55, %56, %57, %58, %59, %60, %61, %62, %63, %64, %65, %66, %67, %68, %69, %70, %71}, {%72, %73, %74, %75}, db, p, 1, 1, %78;\n}\n"
      : "+f"(d[0]), "+f"(d[1]), "+f"(d[2]), "+f"(d[3]), "+f"(d[4]), "+f"(d[5]), "+f"(d[6]), "+f"(d[7]), "+f"(d[8]), "+f"(d[9]), "+f"(d[10]), "+f"(d[11]), "+f"(d[12]), "+f"(d[13]), "+f"(d[14]), "+f"(d[15]), "+f"(d[16]), "+f"(d[17]), "+f"(d[18]), "+f"(d[19]), "+f"(d[20]), "+f"(d[21]), "+f"(d[22]), "+f"(d[23]), "+f"(d[24]), "+f"(d[25]), "+f"(d[26]), "+f"(d[27]), "+f"(d[28]), "+f"(d[29]), "+f"(d[30]), "+f"(d[31]), "+f"(d[32]), "+f"(d[33]), "+f"(d[34]), "+f"(d[35]), "+f"(d[36]), "+f"(d[37]), "+f"(d[38]), "+f"(d[39]), "+f"(d[40]), "+f"(d[41]), "+f"(d[42]), "+f"(d[43]), "+f"(d[44]), "+f"(d[45]), "+f"(d[46]), "+f"(d[47]), "+f"(d[48]), "+f"(d[49]), "+f"(d[50]), "+f"(d[51]), "+f"(d[52]), "+f"(d[53]), "+f"(d[54]), "+f"(d[55]), "+f"(d[56]), "+f"(d[57]), "+f"(d[58]), "+f"(d[59]), "+f"(d[60]), "+f"(d[61]), "+f"(d[62]), "+f"(d[63]), "+f"(d[64]), "+f"(d[65]), "+f"(d[66]), "+f"(d[67]), "+f"(d[68]), "+f"(d[69]), "+f"(d[70]), "+f"(d[71])
      : "r"(a0), "r"(a1), "r"(a2), "r"(a3), "r"(blo), "r"(sd), "n"(TB), "r"(bhi));
}

__device__ __forceinline__ void finish_unit(int u, const float (&a)[8], const __nv_bfloat16* __restrict__ x, const __nv_bfloat16* __restrict__ b2) {
    const int t = u & 255, pbr = u >> 8, rb = pbr / 36, pb = pbr - rb * 36;
    const int row = rb * 128 + (t >> 5) * 16 + ((t & 31) >> 2), col = pb * 16 + (t & 3) * 2;
    const uint32_t* xp = reinterpret_cast<const uint32_t*>(x + (size_t)row * DM + col);
    const uint32_t x0 = __ldg(xp), x1 = __ldg(xp + 4 * DM), x2 = __ldg(xp + 4), x3 = __ldg(xp + 4 * DM + 4);
    const uint32_t ba = __ldg(reinterpret_cast<const uint32_t*>(b2 + col)), bb = __ldg(reinterpret_cast<const uint32_t*>(b2 + col + 8));
    uint4 o;
    o.x = pack_bf16(fmaf(a[0], 0.5f, bf_lo(x0) + bf_lo(ba)), fmaf(a[1], 0.5f, bf_hi(x0) + bf_hi(ba)));
    o.y = pack_bf16(fmaf(a[2], 0.5f, bf_lo(x1) + bf_lo(ba)), fmaf(a[3], 0.5f, bf_hi(x1) + bf_hi(ba)));
    o.z = pack_bf16(fmaf(a[4], 0.5f, bf_lo(x2) + bf_lo(bb)), fmaf(a[5], 0.5f, bf_hi(x2) + bf_hi(bb)));
    o.w = pack_bf16(fmaf(a[6], 0.5f, bf_lo(x3) + bf_lo(bb)), fmaf(a[7], 0.5f, bf_hi(x3) + bf_hi(bb)));
    g_base[u] = o;
}
__device__ __forceinline__ void add_unit(float (&a)[8], const uint4 v) {
    a[0] += bf_lo(v.x); a[1] += bf_hi(v.x); a[2] += bf_lo(v.y); a[3] += bf_hi(v.y);
    a[4] += bf_lo(v.z); a[5] += bf_hi(v.z); a[6] += bf_lo(v.w); a[7] += bf_hi(v.w);
}

constexpr int K1_XN_BYTES = 16 * 9216;
constexpr int K1_SLOT = 16384, K1_NSLOT = 5;
constexpr int K1_OFF_RING = K1_XN_BYTES;
constexpr int K1_OFF_BIAS = K1_OFF_RING + K1_NSLOT * K1_SLOT;
constexpr int K1_OFF_BAR = K1_OFF_BIAS + 576 * 2;
constexpr int K1_SMEM = K1_OFF_BAR + 256 + 64;
constexpr float QSCALE = 0.23570226039551584f * 1.4426950408889634f;

struct Ring {
    uint32_t slot, phase;
    __device__ __forceinline__ void advance() {
        if (++slot == K1_NSLOT) { slot = 0; phase ^= 1; }
    }
};

struct K1Ctx {
    uint32_t full0;
    uint32_t rel_addr;
    uint32_t descA, descB;
    Ring rd;
    uint32_t prev_slot;
    __device__ __forceinline__ uint32_t begin_stage() {
        mbar_wait(full0 + rd.slot * 8, rd.phase);
        wg_fence();
        return descB + rd.slot * (K1_SLOT >> 4);
    }
    __device__ __forceinline__ void end_stage() {
        wg_commit();
        wg_wait<1>();
        if (rel_addr) asm volatile("mbarrier.arrive.shared::cluster.b64 _, [%0];" ::"r"(rel_addr + prev_slot * 8) : "memory");
        prev_slot = rd.slot;
        rd.advance();
    }
};

__device__ __forceinline__ uint32_t descA_step(uint32_t base, int ks) { return base + (((ks >> 2) * 1024 + (ks & 3) * 32) >> 4); }
constexpr uint32_t K1_AHI = desc_hi(9216, 1), K1_BHI = desc_hi(1024, 1);

template <int V> struct IC { static constexpr int value = V; };
template <int I, int N, class F> __device__ __forceinline__ void static_for(F&& f) {
    if constexpr (I < N) { f(IC<I>{}); static_for<I + 1, N>(f); }
}

template <bool A_RS, bool B_RS, class Epi>
__device__ __forceinline__ void tile_pair(K1Ctx& c, float (&accA)[32], float (&accB)[32], uint32_t (&h)[144], Epi&& epi) {
    static_for<0, 9>([&](auto sc) {
        constexpr int s = decltype(sc)::value;
        const uint32_t db = c.begin_stage();
#pragma unroll
        for (int t = 0; t < 8; t++) {
            const int kk = s * 8 + t, ks = kk % 36;
            const uint32_t dbt = db + ((t * 2048) >> 4);
            if (kk < 36) {
                if constexpr (A_RS) wgmma_rs_n64<1>(accA, h[ks * 4], h[ks * 4 + 1], h[ks * 4 + 2], h[ks * 4 + 3], dbt, K1_BHI, ks != 0);
                else wgmma_ss_n64<1>(accA, descA_step(c.descA, ks), K1_AHI, dbt, K1_BHI, ks != 0);
            } else {
                if constexpr (B_RS) wgmma_rs_n64<1>(accB, h[ks * 4], h[ks * 4 + 1], h[ks * 4 + 2], h[ks * 4 + 3], dbt, K1_BHI, ks != 0);
                else wgmma_ss_n64<1>(accB, descA_step(c.descA, ks), K1_AHI, dbt, K1_BHI, ks != 0);
            }
        }
        c.end_stage();
        epi(sc);
    });
}

template <int B0, int NB, int HOFF>
__device__ __forceinline__ void gelu_blocks(const float (&acc)[32], uint32_t (&h)[144], const uint32_t (&bq)[8]) {
#pragma unroll
    for (int b = B0; b < B0 + NB; b++) {
        const float b0 = bf_lo(bq[b]), b1 = bf_hi(bq[b]);
        h[HOFF + b * 2 + 0] = pack_bf16(gelu2(acc[b * 4 + 0] + b0), gelu2(acc[b * 4 + 1] + b1));
        h[HOFF + b * 2 + 1] = pack_bf16(gelu2(acc[b * 4 + 2] + b0), gelu2(acc[b * 4 + 3] + b1));
    }
}
__device__ __forceinline__ void load_bias(uint32_t (&bq)[8], uint32_t addr) {
    asm volatile("ld.shared.v4.u32 {%0, %1, %2, %3}, [%4];" : "=r"(bq[0]), "=r"(bq[1]), "=r"(bq[2]), "=r"(bq[3]) : "r"(addr));
    asm volatile("ld.shared.v4.u32 {%0, %1, %2, %3}, [%4 + 16];" : "=r"(bq[4]), "=r"(bq[5]), "=r"(bq[6]), "=r"(bq[7]) : "r"(addr));
}
template <int S> __device__ __forceinline__ void store_part(const float (&o)[32], uint4* p) {
    uint4 v;
    v.x = pack_bf16(o[S * 8 + 0], o[S * 8 + 1]); v.y = pack_bf16(o[S * 8 + 2], o[S * 8 + 3]);
    v.z = pack_bf16(o[S * 8 + 4], o[S * 8 + 5]); v.w = pack_bf16(o[S * 8 + 6], o[S * 8 + 7]);
    p[S * 256] = v;
}

__global__ void __cluster_dims__(2, 1, 1) __launch_bounds__(384, 1)
k1_kernel(const __grid_constant__ CUtensorMap tmX, const __grid_constant__ CUtensorMap tmQ3, const __grid_constant__ CUtensorMap tmQ1,
          const __grid_constant__ CUtensorMap tm1, const __grid_constant__ CUtensorMap tm2, const __nv_bfloat16* __restrict__ b1,
          const __nv_bfloat16* __restrict__ wo, const __nv_bfloat16* __restrict__ x, const __nv_bfloat16* __restrict__ b2) {
    extern __shared__ __align__(1024) uint8_t smem[];
    const uint32_t sb = s2u(smem);
    const int tid = threadIdx.x, lane = tid & 31;
    const int warp = __shfl_sync(~0u, tid >> 5, 0);
    const uint32_t rank = blockIdx.x & 1;
    const int cl = blockIdx.x >> 1;
    const int rb = (cl & 7) * 2 + rank;
    const int j = cl >> 3;
    const uint32_t full0 = sb + K1_OFF_BAR, empty0 = full0 + 8 * K1_NSLOT, xbar0 = full0 + 128, rbar0 = full0 + 256;

    if (warp < 8) {
        PROF(0);
        PROFT(48);
        if (lane == 0) {
            mbar_init(xbar0 + warp * 16, 1);
            mbar_init(xbar0 + warp * 16 + 8, 1);
            fence_barrier_init();
            mbar_expect(xbar0 + warp * 16, 9216);
            tma3d(sb + warp * 2 * 9216, &tmX, 0, rb * 128 + warp * 16, 0, xbar0 + warp * 16);
            mbar_expect(xbar0 + warp * 16 + 8, 9216);
            tma3d(sb + (warp * 2 + 1) * 9216, &tmX, 0, rb * 128 + warp * 16 + 8, 0, xbar0 + warp * 16 + 8);
        }
        __syncwarp();
        cluster_arrive();
        reg_alloc<240>();
#pragma unroll 1
        for (int p = 0; p < 4; p++) {
            mbar_wait(xbar0 + warp * 16 + (p >> 1) * 8, 0);
            uint4* row = reinterpret_cast<uint4*>(smem + (warp * 2 + (p >> 1)) * 9216 + (p & 1) * 512 + lane * 16);
            float f[72];
#pragma unroll
            for (int i = 0; i < 9; i++) {
                const uint4 v = row[i * 64];
                f[i * 8 + 0] = bf_lo(v.x); f[i * 8 + 1] = bf_hi(v.x); f[i * 8 + 2] = bf_lo(v.y); f[i * 8 + 3] = bf_hi(v.y);
                f[i * 8 + 4] = bf_lo(v.z); f[i * 8 + 5] = bf_hi(v.z); f[i * 8 + 6] = bf_lo(v.w); f[i * 8 + 7] = bf_hi(v.w);
            }
            float s0 = 0.f, s1 = 0.f, s2 = 0.f, s3 = 0.f;
#pragma unroll
            for (int i = 0; i < 72; i += 4) { s0 += f[i]; s1 += f[i + 1]; s2 += f[i + 2]; s3 += f[i + 3]; }
            float sm = (s0 + s1) + (s2 + s3);
            sm += __shfl_xor_sync(~0u, sm, 1); sm += __shfl_xor_sync(~0u, sm, 2); sm += __shfl_xor_sync(~0u, sm, 4);
            const float mean = sm * (1.0f / DM);
            s0 = s1 = s2 = s3 = 0.f;
#pragma unroll
            for (int i = 0; i < 72; i += 4) {
                f[i] -= mean; f[i + 1] -= mean; f[i + 2] -= mean; f[i + 3] -= mean;
                s0 = fmaf(f[i], f[i], s0); s1 = fmaf(f[i + 1], f[i + 1], s1);
                s2 = fmaf(f[i + 2], f[i + 2], s2); s3 = fmaf(f[i + 3], f[i + 3], s3);
            }
            float sq = (s0 + s1) + (s2 + s3);
            sq += __shfl_xor_sync(~0u, sq, 1); sq += __shfl_xor_sync(~0u, sq, 2); sq += __shfl_xor_sync(~0u, sq, 4);
            const float rstd = rsqrtf(sq * (1.0f / DM) + 1e-5f);
#pragma unroll
            for (int i = 0; i < 9; i++) {
                uint4 o;
                o.x = pack_bf16(f[i * 8 + 0] * rstd, f[i * 8 + 1] * rstd);
                o.y = pack_bf16(f[i * 8 + 2] * rstd, f[i * 8 + 3] * rstd);
                o.z = pack_bf16(f[i * 8 + 4] * rstd, f[i * 8 + 5] * rstd);
                o.w = pack_bf16(f[i * 8 + 6] * rstd, f[i * 8 + 7] * rstd);
                row[i * 64] = o;
            }
        }
        const int wg = warp >> 2, wq = warp & 3;
        fence_proxy_async();
        named_bar_sync(1 + wg, 128);
        cluster_wait();
        PROF(1);

        const int g = lane >> 2, q = lane & 3;
        K1Ctx c;
        c.full0 = full0;
        c.rel_addr = 0;
        c.descA = desc_lo(sb + wg * 8 * 9216, 16);
        c.descB = desc_lo(sb + K1_OFF_RING, 2048);
        c.rd.slot = 0; c.rd.phase = 0; c.prev_slot = 0;
        uint32_t biasq = sb + K1_OFF_BIAS + q * 32;
        uint32_t bq[8];

        uint32_t h[144];
        float accA[32], accB[32];
        {
            float accQ[108];
            uint32_t rel = 0;
            if (lane == 0 && wq < 2) asm("mapa.shared::cluster.u32 %0, %1, %2;" : "=r"(rel) : "r"(empty0), "r"(wq));
#pragma unroll 1
            for (int s = 0; s < 18; s++) {
                const uint32_t db = c.begin_stage();
                const uint32_t da = c.descA + (s >> 1) * 64 + (s & 1) * 4;
                wgmma_ss_n216<1>(accQ, da, K1_AHI, db, K1_BHI, s != 0);
                wgmma_ss_n216<1>(accQ, da + 2, K1_AHI, db + (8192 >> 4), K1_BHI, 1);
                c.end_stage();
                c.rel_addr = rel;
            }
            PROF(2);
            uint32_t rel9[9];
#pragma unroll
            for (int i9 = 0; i9 < 9; i9++) {
                const int p = 4 * i9 + q, hh = (p * 57) >> 9, r = p - 9 * hh;
                rel9[i9] = hh * KV_HEAD_BYTES + (r < 8 ? (r >> 2) * 128 + (r & 3) * 4 : 0);
            }
            uint32_t gb = 0, o2 = 0;
            float scl0 = 1.f, scl1 = 1.f;
            tile_pair<false, false>(c, accA, accB, h, [&](auto sc) {
                constexpr int s = decltype(sc)::value;
                if constexpr (s == 0) reg_fence(accQ);
                if constexpr (s < 6) {
                    constexpr int grp = s / 2, part = s % 2;
                    if constexpr (part == 0) {
                        const int G = 3 * j + grp, type = G >> 3;
                        gb = (G & 7) * 4 * KV_HEAD_BYTES + (rb * 16 + warp * 2) * KV_GROUP_BYTES + g * 16 + (type == 0 ? Q_OFFSET : (type == 2 ? 256 : 0));
                        o2 = type == 0 ? 256 : (type == 2 ? 264 : 512);
                        scl0 = type == 0 ? QSCALE : ((type == 1 && ((POLY_MASK >> (wq * 2)) & 1)) ? 2.f : 1.f);
                        scl1 = type == 0 ? QSCALE : ((type == 1 && ((POLY_MASK >> (wq * 2 + 1)) & 1)) ? 2.f : 1.f);
                    }
#pragma unroll
                    for (int i9 = part * 5; i9 < (part ? 9 : 5); i9++) {
                        const int b = grp * 9 + i9;
                        uint32_t off = gb + rel9[i9];
                        if (i9 >= 2 && (i9 & 1) == 0) off += (q == i9 / 2 - 1) ? o2 : 0;
                        *reinterpret_cast<uint32_t*>(g_QKV + off) = pack_bf16(accQ[b * 4] * scl0, accQ[b * 4 + 1] * scl0);
                        *reinterpret_cast<uint32_t*>(g_QKV + off + KV_GROUP_BYTES) = pack_bf16(accQ[b * 4 + 2] * scl1, accQ[b * 4 + 3] * scl1);
                    }
                    if constexpr (s == 5) asm volatile("bar.arrive 3, 352;" ::: "memory");
                }
                if constexpr (s == 4) { named_bar_sync(4, 288); load_bias(bq, biasq); }
                if constexpr (s == 5) reg_fence(accA);
                if constexpr (s >= 5) gelu_blocks<(s - 5) * 2, 2, 96>(accA, h, bq);
                if constexpr (s == 8) load_bias(bq, biasq + 128);
            });
        }
        PROF(3);
#pragma unroll
        for (int i = 32; i < 96; i++) asm volatile("mov.u32 %0, 0;" : "=r"(h[i]));
#pragma unroll 1
        for (int p = 1; p < 4; p++) {
            biasq += 256;
            tile_pair<false, false>(c, accA, accB, h, [&](auto sc) {
                constexpr int s = decltype(sc)::value;
                if constexpr (s == 0) {
                    reg_fence(accB);
#pragma unroll
                    for (int i = 0; i < 80; i++) h[i] = h[i + 32];
                }
                if constexpr (s < 4) gelu_blocks<s * 2, 2, 80>(accB, h, bq);
                if constexpr (s == 4) load_bias(bq, biasq);
                if constexpr (s == 5) reg_fence(accA);
                if constexpr (s >= 5) gelu_blocks<(s - 5) * 2, 2, 96>(accA, h, bq);
                if constexpr (s == 8) load_bias(bq, biasq + 128);
            });
        }
        PROF(4);
        tile_pair<false, true>(c, accA, accB, h, [&](auto sc) {
            constexpr int s = decltype(sc)::value;
            if constexpr (s == 0) reg_fence(accB);
            if constexpr (s < 4) gelu_blocks<s * 2, 2, 112>(accB, h, bq);
            if constexpr (s == 4) load_bias(bq, biasq + 256);
            if constexpr (s == 5) reg_fence(accA);
            if constexpr (s == 5 || s == 6) gelu_blocks<(s - 5) * 3, 3, 128>(accA, h, bq);
            if constexpr (s == 7) gelu_blocks<6, 2, 128>(accA, h, bq);
            if constexpr (s == 3 || s == 7) reg_fence(h);
        });
        PROF(5);
        uint4* pout = g_part + ((size_t)(j * 16 + rb) * 36) * 256 + tid;
#pragma unroll 1
        for (int p = 0; p < 4; p++) {
            tile_pair<true, true>(c, accA, accB, h, [&](auto sc) {
                constexpr int s = decltype(sc)::value;
                if constexpr (s == 0) reg_fence(accB);
                if constexpr (s < 4) store_part<s>(accB, pout);
                if constexpr (s == 3) asm volatile("bar.arrive 5, 288;" ::: "memory");
                if constexpr (s == 5) reg_fence(accA);
                if constexpr (s >= 5) store_part<s - 5>(accA, pout + 1024);
                if constexpr (s == 8) asm volatile("bar.arrive 6, 288;" ::: "memory");
            });
            pout += 2048;
            PROF(6 + p);
        }
        wg_wait<0>();
        reg_fence(accB);
        store_part<0>(accB, pout); store_part<1>(accB, pout); store_part<2>(accB, pout); store_part<3>(accB, pout);
        PROF(10);
        cluster_arrive();
        cluster_wait();
        PROF(11);
        PROFT(49);
    } else {
        reg_dealloc<24>();
        if (warp == 8 && lane == 0) {
            prefetch_tmap(&tmQ3); prefetch_tmap(&tmQ1); prefetch_tmap(&tm1); prefetch_tmap(&tm2);
            for (int i = 0; i < K1_NSLOT; i++) { mbar_init(full0 + i * 8, 1); mbar_init(empty0 + i * 8, 4); }
            for (int i = 0; i < 8; i++) mbar_init(rbar0 + i * 8, 1);
            fence_barrier_init();
        }
        __syncwarp();
        cluster_arrive();
        cluster_wait();
        if (warp == 8) {
            if (lane == 0) {
                Ring w{0, 1};
                const uint32_t dst0 = sb + K1_OFF_RING + rank * 8192;
#pragma unroll 1
                for (int s = 0; s < 18; s++) {
                    mbar_wait(empty0 + w.slot * 8, w.phase);
                    mbar_expect(full0 + w.slot * 8, 16384);
                    const uint32_t dst = dst0 + w.slot * K1_SLOT;
                    tma3d_mc(dst, &tmQ3, j * 216, s * 32 + rank * 16, 0, full0 + w.slot * 8, 3);
                    tma2d_mc(dst + 6144, &tmQ1, j * 216 + 192, s * 32 + rank * 16, full0 + w.slot * 8, 3);
                    w.advance();
                }
                int tile = 0, kb = rank;
#pragma unroll 1
                for (int s = 0; s < 81; s++) {
                    mbar_wait(empty0 + w.slot * 8, w.phase);
                    mbar_expect(full0 + w.slot * 8, 16384);
                    const uint32_t dst = dst0 + w.slot * K1_SLOT;
                    if (tile < 9) tma2d_mc(dst, &tm1, j * 576 + tile * 64, kb * 64, full0 + w.slot * 8, 3);
                    else tma2d_mc(dst, &tm2, (tile - 9) * 64, j * 576 + kb * 64, full0 + w.slot * 8, 3);
                    kb += 2;
                    if (kb >= 9) { kb -= 9; tile++; }
                    w.advance();
                }
            }
        } else {
            const int ht = tid - 288;
            if (warp == 9) {
                uint32_t* sbias = reinterpret_cast<uint32_t*>(smem + K1_OFF_BIAS);
#pragma unroll 1
                for (int t = 0; t < 9; t++) sbias[t * 32 + (lane & 3) * 8 + (lane >> 2)] = reinterpret_cast<const uint32_t*>(b1 + j * 576)[t * 32 + lane];
                asm volatile("bar.arrive 4, 288;" ::: "memory");
            }
#pragma unroll 1
            for (int i = ht; i < 512; i += 96) {
                const int key = i & 127;
                uint8_t* p = g_QKV + (size_t)(j * 4 + (i >> 7)) * KV_HEAD_BYTES + (rb * 16 + (key >> 3)) * KV_GROUP_BYTES + 512 + (key & 7) * 16;
                *reinterpret_cast<uint32_t*>(p + 4) = ((POLY_MASK >> ((key >> 3) & 7)) & 1) ? 0x3F804000u : 0x00003F80u;
                *reinterpret_cast<uint32_t*>(p + 12) = 0x00003F80u;
            }
#pragma unroll 1
            for (int i = blockIdx.x * 324 + ht; i < blockIdx.x * 324 + 324; i += 96) {
                const int k = i / 72, nc = i - k * 72, ct = nc / 18;
                *reinterpret_cast<uint4*>(g_Wo + ct * WO_TILE_BYTES + (k >> 3) * 2304 + (nc - ct * 18) * 128 + (k & 7) * 16) =
                    __ldg(reinterpret_cast<const uint4*>(wo) + i);
            }
            named_bar_sync(3, 352);
#pragma unroll 1
            for (int i = warp - 9; i < 48; i += 3) {
                const int G = 3 * j + (i >> 4);
                if ((G >> 3) != 1) continue;
                const int head = (G & 7) * 4 + ((i >> 2) & 3), key = (i & 3) * 32 + lane;
                const uint8_t* p = g_QKV + (size_t)head * KV_HEAD_BYTES + (rb * 16 + (key >> 3)) * KV_GROUP_BYTES + (key & 7) * 16;
                const uint4 a = __ldcg(reinterpret_cast<const uint4*>(p)), b = __ldcg(reinterpret_cast<const uint4*>(p + 128));
                const uint32_t e = __ldcg(reinterpret_cast<const uint32_t*>(p + 512));
                float n = bf_lo(e) * bf_lo(e) + bf_hi(e) * bf_hi(e);
                n += bf_lo(a.x) * bf_lo(a.x) + bf_hi(a.x) * bf_hi(a.x) + bf_lo(a.y) * bf_lo(a.y) + bf_hi(a.y) * bf_hi(a.y);
                n += bf_lo(a.z) * bf_lo(a.z) + bf_hi(a.z) * bf_hi(a.z) + bf_lo(a.w) * bf_lo(a.w) + bf_hi(a.w) * bf_hi(a.w);
                n += bf_lo(b.x) * bf_lo(b.x) + bf_hi(b.x) * bf_hi(b.x) + bf_lo(b.y) * bf_lo(b.y) + bf_hi(b.y) * bf_hi(b.y);
                n += bf_lo(b.z) * bf_lo(b.z) + bf_hi(b.z) * bf_hi(b.z) + bf_lo(b.w) * bf_lo(b.w) + bf_hi(b.w) * bf_hi(b.w);
                if ((POLY_MASK >> ((key >> 3) & 7)) & 1) n *= 0.25f;
#pragma unroll
                for (int o = 16; o; o >>= 1) n = fmaxf(n, __shfl_xor_sync(~0u, n, o));
                if (lane == 0) g_kmax[head * 64 + rb * 4 + (i & 3)] = n;
            }
            if (warp == 9) {
#pragma unroll 1
                for (int t = 0; t < 8; t++) {
                    named_bar_sync(5 + (t & 1), 288);
                    if (lane == 0) {
                        __threadfence();
                        atomicAdd(&g_flag[rb * 8 + t], 1u);
                    }
                }
            } else if (warp == 10) {
                if (lane == 0) {
#pragma unroll 1
                    for (int t = 0; t < 8; t++) {
                        uint32_t v, spins = 0;
                        do {
                            asm volatile("ld.acquire.gpu.global.u32 %0, [%1];" : "=r"(v) : "l"(&g_flag[rb * 8 + t]) : "memory");
                            if (v < 8) { __nanosleep(100); if (++spins > (1u << 22)) __trap(); }
                        } while (v < 8);
                        asm volatile("fence.proxy.async;" ::: "memory");
                        mbar_expect(rbar0 + t * 8, 16384);
#pragma unroll 1
                        for (int jj = 0; jj < 8; jj++)
                            bulk_load(sb + t * 16384 + jj * 2048, g_part + ((size_t)(jj * 16 + rb) * 36 + t * 4) * 256 + j * 128, 2048, rbar0 + t * 8);
                    }
                }
            } else {
#pragma unroll 1
                for (int i = 0; i < 32; i++) {
                    const int t = i >> 2;
                    mbar_wait(rbar0 + t * 8, 0);
                    const uint4* sp = reinterpret_cast<const uint4*>(smem + t * 16384) + (i & 3) * 32 + lane;
                    float a[8];
#pragma unroll
                    for (int k = 0; k < 8; k++) a[k] = 0.f;
#pragma unroll 2
                    for (int jj = 0; jj < 8; jj++) add_unit(a, sp[jj * 128]);
                    finish_unit((rb * 36 + t * 4) * 256 + j * 128 + (i & 3) * 32 + lane, a, x, b2);
                }
            }
        }
        __syncwarp();
        cluster_arrive();
        cluster_wait();
    }
}

constexpr int K2_NCHUNK = 16;
constexpr int K2_AHEAD = 4;
constexpr int K2_CHUNK_BYTES = KV_HEAD_BYTES / K2_NCHUNK;
constexpr int K2_OFF_BAR = KV_HEAD_BYTES + 8 * KV_GROUP_BYTES;
constexpr int K2_OFF_Q = K2_OFF_BAR + 256;
constexpr int K2_SMEM = K2_OFF_Q + 12 * 512 * 4;

__device__ __forceinline__ float exp2_fixed(float y) {
    const float u = __uint_as_float(__float_as_uint(y) & 0xFF807FFFu) - 512.02545f;
    float t = fmaf(u, 0.019497588f, 0.114550486f);
    t = fmaf(t, u, -0.29839927f);
    return fmaf(t, u, y);
}
__device__ __forceinline__ uint32_t pack_fixed(float lo, float hi) { return __byte_perm(__float_as_uint(lo), __float_as_uint(hi), 0x6521); }

__device__ __forceinline__ void softmax_fast(const float (&s)[32], uint32_t (&p)[16]) {
#pragma unroll
    for (int b = 0; b < 8; b++) {
        if ((POLY_MASK >> b) & 1) {
            p[b * 2 + 0] = pack_fixed(exp2_fixed(s[b * 4 + 0]), exp2_fixed(s[b * 4 + 1]));
            p[b * 2 + 1] = pack_fixed(exp2_fixed(s[b * 4 + 2]), exp2_fixed(s[b * 4 + 3]));
        } else {
            p[b * 2 + 0] = pack_bf16(ex2(s[b * 4 + 0]), ex2(s[b * 4 + 1]));
            p[b * 2 + 1] = pack_bf16(ex2(s[b * 4 + 2]), ex2(s[b * 4 + 3]));
        }
    }
}

constexpr uint32_t K2_TILE = 8 * KV_GROUP_BYTES / 16;
__device__ __forceinline__ void issue_qk(float (&s)[32], const uint32_t (&qa)[8], uint32_t base) {
    wgmma_rs_n64<0>(s, qa[0], qa[1], qa[2], qa[3], base + (8u << 16), desc_hi(KV_GROUP_BYTES, 0), 0);
    wgmma_rs_n64<0>(s, qa[4], qa[5], qa[6], qa[7], base + 32, desc_hi(KV_GROUP_BYTES, 0), 1);
}
__device__ __forceinline__ void issue_pv(float (&o)[12], const uint32_t (&p)[16], uint32_t base) {
#pragma unroll
    for (int k = 0; k < 4; k++)
        wgmma_rs_n24<1>(o, p[k * 4], p[k * 4 + 1], p[k * 4 + 2], p[k * 4 + 3], base + 16 + ((KV_GROUP_BYTES / 16) << 16) + k * (2 * KV_GROUP_BYTES / 16),
                        desc_hi(128, 0), 1);
}

__global__ void __launch_bounds__(512, 1) k2_kernel(const __nv_bfloat16* __restrict__ x, const __nv_bfloat16* __restrict__ b2) {
    extern __shared__ __align__(1024) uint8_t smem[];
    const uint32_t sb = s2u(smem);
    const int tid = threadIdx.x, lane = tid & 31;
    const int warp = __shfl_sync(~0u, tid >> 5, 0);
    const int wg = warp >> 2, wq = warp & 3, g = lane >> 2, q = lane & 3;
    const int head = blockIdx.x >> 2, quarter = blockIdx.x & 3;
    const uint32_t bar0 = sb + K2_OFF_BAR;
    PROF(16);
    if (tid == 0) {
        for (int i = 0; i <= K2_NCHUNK; i++) mbar_init(bar0 + i * 8, 1);
        asm volatile("mbarrier.arrive.shared::cta.b64 _, [%0];" ::"r"(bar0 + K2_NCHUNK * 8) : "memory");
        fence_barrier_init();
    }
    __syncthreads();
    griddep_wait();
    PROF(17);
    PROFT(50);
    uint32_t* qs = reinterpret_cast<uint32_t*>(smem + K2_OFF_Q) + tid;
    const uint8_t* kvsrc = g_QKV + (size_t)head * KV_HEAD_BYTES;
    int next_chunk = (tid == 0) ? K2_AHEAD : K2_NCHUNK;
    float kmax2;
    {
        uint32_t qv[12];
#pragma unroll
        for (int pass = 0; pass < 2; pass++) {
            const int row0 = quarter * 512 + (pass * 4 + wg) * 64 + wq * 16;
            const uint8_t* qp = g_QKV + Q_OFFSET + (size_t)head * KV_HEAD_BYTES + (row0 >> 3) * KV_GROUP_BYTES + g * 16 + q * 4;
            qv[pass * 6 + 0] = __ldcg(reinterpret_cast<const uint32_t*>(qp));
            qv[pass * 6 + 1] = __ldcg(reinterpret_cast<const uint32_t*>(qp + KV_GROUP_BYTES));
            qv[pass * 6 + 2] = __ldcg(reinterpret_cast<const uint32_t*>(qp + 128));
            qv[pass * 6 + 3] = __ldcg(reinterpret_cast<const uint32_t*>(qp + KV_GROUP_BYTES + 128));
            qv[pass * 6 + 4] = (q == 0) ? __ldcg(reinterpret_cast<const uint32_t*>(qp + 256)) : 0u;
            qv[pass * 6 + 5] = (q == 0) ? __ldcg(reinterpret_cast<const uint32_t*>(qp + KV_GROUP_BYTES + 256)) : 0u;
        }
        const float2 v = __ldcg(reinterpret_cast<const float2*>(g_kmax + head * 64 + lane * 2));
        if (lane == 0 && warp < K2_AHEAD) {
            mbar_expect(bar0 + warp * 8, K2_CHUNK_BYTES);
            bulk_load(sb + warp * K2_CHUNK_BYTES, kvsrc + warp * K2_CHUNK_BYTES, K2_CHUNK_BYTES, bar0 + warp * 8);
        }
        __syncwarp();
        if (lane < 8) {
            const int u = ((blockIdx.x >> 3) * 36 + 32) * 256 + (blockIdx.x & 7) * 128 + warp * 8 + lane;
            uint4 pv[8];
#pragma unroll
            for (int jj = 0; jj < 8; jj++) pv[jj] = __ldcg(g_part + jj * (16 * 36 * 256) + u);
            float a[8];
#pragma unroll
            for (int k = 0; k < 8; k++) a[k] = 0.f;
#pragma unroll
            for (int jj = 0; jj < 8; jj++) add_unit(a, pv[jj]);
            finish_unit(u, a, x, b2);
        }
        __syncwarp();
#pragma unroll
        for (int i = 0; i < 12; i++) qs[i * 512] = qv[i];
        kmax2 = fmaxf(v.x, v.y);
#pragma unroll
        for (int o = 16; o; o >>= 1) kmax2 = fmaxf(kmax2, __shfl_xor_sync(~0u, kmax2, o));
    }
    const uint32_t d0 = (sb & 0x3FFFF) >> 4;

#pragma unroll 1
    for (int pass = 0; pass < 2; pass++) {
        const int row0 = quarter * 512 + (pass * 4 + wg) * 64 + wq * 16;
        uint32_t qa[8];
#pragma unroll
        for (int i = 0; i < 6; i++) qa[i] = qs[(pass * 6 + i) * 512];
        qa[6] = 0u;
        float c0, c1;
        {
            float n0 = bf_lo(qa[0]) * bf_lo(qa[0]) + bf_hi(qa[0]) * bf_hi(qa[0]) + bf_lo(qa[2]) * bf_lo(qa[2]) + bf_hi(qa[2]) * bf_hi(qa[2]) +
                       bf_lo(qa[4]) * bf_lo(qa[4]) + bf_hi(qa[4]) * bf_hi(qa[4]);
            float n1 = bf_lo(qa[1]) * bf_lo(qa[1]) + bf_hi(qa[1]) * bf_hi(qa[1]) + bf_lo(qa[3]) * bf_lo(qa[3]) + bf_hi(qa[3]) * bf_hi(qa[3]) +
                       bf_lo(qa[5]) * bf_lo(qa[5]) + bf_hi(qa[5]) * bf_hi(qa[5]);
            n0 += __shfl_xor_sync(~0u, n0, 1); n1 += __shfl_xor_sync(~0u, n1, 1);
            n0 += __shfl_xor_sync(~0u, n0, 2); n1 += __shfl_xor_sync(~0u, n1, 2);
            c0 = sqrtf(n0 * kmax2) * 1.02f;
            c1 = sqrtf(n1 * kmax2) * 1.02f;
        }
        uint32_t slow;
        {
            const bool bad = !(c0 <= 58.f && c1 <= 58.f);
            asm volatile("{\n.reg .pred p, r;\nsetp.ne.u32 p, %1, 0;\nbarrier.cta.red.or.pred.aligned r, %2, 128, p;\nselp.u32 %0, 1, 0, r;\n}\n"
                         : "=r"(slow) : "r"((uint32_t)bad), "r"(wg + 1) : "memory");
        }
        slow = __any_sync(~0u, slow);
        float o[12];
#pragma unroll
        for (int i = 0; i < 12; i++) o[i] = 0.f;
        if (!slow && q == 1) {
            qa[4] = pack_bf16(-c0, 768.f); qa[5] = pack_bf16(-c1, 768.f);
            qa[6] = 0xC0000000u;
        }
        qa[7] = __shfl_sync(~0u, qa[6], lane);
        qa[6] = __shfl_sync(~0u, qa[6], lane ^ 4);

        if (!slow) {
            float s0[32], s1[32];
            uint32_t p[16];
            mbar_wait(bar0, 0);
            PROF(18 + pass * 3);
            reg_fence(qa);
            reg_fence(o);
            wg_fence();
            issue_qk(s0, qa, d0);
            wg_commit();
            uint32_t d = d0, bar = bar0;
#pragma unroll 1
            for (int t = 0; t < 16; t++) {
                wg_fence();
                issue_qk(s1, qa, d + K2_TILE);
                wg_commit();
                wg_wait<1>();
                reg_fence(s0);
                softmax_fast(s0, p);
                reg_fence(p);
                if (next_chunk < K2_NCHUNK) {
                    mbar_expect(bar0 + next_chunk * 8, K2_CHUNK_BYTES);
                    bulk_load(sb + next_chunk * K2_CHUNK_BYTES, kvsrc + next_chunk * K2_CHUNK_BYTES, K2_CHUNK_BYTES, bar0 + next_chunk * 8);
                    next_chunk++;
                }
                __syncwarp();
                bar += 8;
                mbar_wait(bar, 0);
                wg_fence();
                issue_pv(o, p, d);
                wg_commit();
                issue_qk(s0, qa, d + 2 * K2_TILE);
                wg_commit();
                wg_wait<1>();
                reg_fence(s1);
                softmax_fast(s1, p);
                reg_fence(p);
                wg_fence();
                issue_pv(o, p, d + K2_TILE);
                wg_commit();
                d += 2 * K2_TILE;
            }
            wg_wait<0>();
            reg_fence(o);
            reg_fence(s0);
        } else {
            float m0 = -INFINITY, m1 = -INFINITY;
            float s[32];
            uint32_t p[16];
            reg_fence(qa);
            for (; next_chunk < K2_NCHUNK; next_chunk++) {
                mbar_expect(bar0 + next_chunk * 8, K2_CHUNK_BYTES);
                bulk_load(sb + next_chunk * K2_CHUNK_BYTES, kvsrc + next_chunk * K2_CHUNK_BYTES, K2_CHUNK_BYTES, bar0 + next_chunk * 8);
            }
            __syncwarp();
#pragma unroll 1
            for (int t = 0; t < 32; t++) {
                mbar_wait(bar0 + (t / 2) * 8, 0);
                wg_fence();
                issue_qk(s, qa, d0 + t * K2_TILE);
                wg_commit();
                wg_wait<0>();
                reg_fence(s);
                reg_fence(o);
                float a0 = m0, a1 = m1;
#pragma unroll
                for (int k = 0; k < 8; k++) {
                    if ((POLY_MASK >> k) & 1) {
#pragma unroll
                        for (int i = 0; i < 4; i++) s[k * 4 + i] *= 0.5f;
                    }
                    a0 = fmaxf(a0, fmaxf(s[k * 4 + 0], s[k * 4 + 1]));
                    a1 = fmaxf(a1, fmaxf(s[k * 4 + 2], s[k * 4 + 3]));
                }
                a0 = fmaxf(a0, __shfl_xor_sync(~0u, a0, 1)); a1 = fmaxf(a1, __shfl_xor_sync(~0u, a1, 1));
                a0 = fmaxf(a0, __shfl_xor_sync(~0u, a0, 2)); a1 = fmaxf(a1, __shfl_xor_sync(~0u, a1, 2));
                const float r0 = ex2(m0 - a0), r1 = ex2(m1 - a1);
                m0 = a0; m1 = a1;
#pragma unroll
                for (int i = 0; i < 3; i++) { o[i * 4] *= r0; o[i * 4 + 1] *= r0; o[i * 4 + 2] *= r1; o[i * 4 + 3] *= r1; }
#pragma unroll
                for (int k = 0; k < 8; k++) {
                    p[k * 2 + 0] = pack_bf16(ex2(s[k * 4 + 0] - m0), ex2(s[k * 4 + 1] - m0));
                    p[k * 2 + 1] = pack_bf16(ex2(s[k * 4 + 2] - m1), ex2(s[k * 4 + 3] - m1));
                }
                reg_fence(p);
                reg_fence(o);
                wg_fence();
                issue_pv(o, p, d0 + t * K2_TILE);
                wg_commit();
                wg_wait<0>();
            }
            reg_fence(o);
        }
        PROF(19 + pass * 3);
        const float l0 = __shfl_sync(~0u, o[8], (lane & ~3) | 3), l1 = __shfl_sync(~0u, o[10], (lane & ~3) | 3);
        const float i0 = 1.0f / l0, i1 = 1.0f / l1;
#pragma unroll
        for (int i = 0; i < 3; i++) {
            const int pc = head * 9 + (i < 2 ? i * 4 + q : 8);
            uint32_t* op = g_O + ((((row0 >> 6) * 36 + (pc >> 3)) * 128 + wq * 32 + g * 4 + (pc & 3)) * 4 + ((pc >> 2) & 1) * 2);
            if (i < 2 || q == 2) *reinterpret_cast<uint2*>(op) = make_uint2(pack_bf16(o[i * 4] * i0, o[i * 4 + 1] * i0), pack_bf16(o[i * 4 + 2] * i1, o[i * 4 + 3] * i1));
        }
        PROF(20 + pass * 3);
        PROFT(51);
    }
}

constexpr int K3_PIECE = WO_TILE_BYTES / 9;
constexpr int K3_OFF_BAR = WO_TILE_BYTES;
constexpr int K3_SMEM = K3_OFF_BAR + 128;

__global__ void __cluster_dims__(2, 1, 1) __launch_bounds__(128, 1) k3_kernel(__nv_bfloat16* __restrict__ out) {
    extern __shared__ __align__(1024) uint8_t smem[];
    const uint32_t sb = s2u(smem);
    const int tid = threadIdx.x, warp = tid >> 5, lane = tid & 31;
    const int g = lane >> 2, q = lane & 3;
    const uint32_t rank = blockIdx.x & 1;
    const int ct = (blockIdx.x >> 1) & 3, rt = (blockIdx.x >> 3) * 2 + rank;
    const uint32_t bar0 = sb + K3_OFF_BAR;
    PROF(32);
    if (tid == 0) {
        for (int i = 0; i < 9; i++) { mbar_init(bar0 + i * 8, 1); mbar_expect(bar0 + i * 8, K3_PIECE); }
        fence_barrier_init();
    }
    cluster_arrive();
    cluster_wait();
    griddep_wait();
    PROF(33);
    PROFT(52);
    if (tid == 0) g_flag[blockIdx.x] = 0;
    uint4 a[36];
    const uint4* ap = reinterpret_cast<const uint4*>(g_O) + rt * 36 * 128 + tid;
#pragma unroll
    for (int k = 0; k < 4; k++) a[k] = __ldcg(ap + k * 128);
    if (tid < 9) {
        const uint32_t off = tid * K3_PIECE + rank * (K3_PIECE / 2);
        asm volatile("cp.async.bulk.shared::cluster.global.mbarrier::complete_tx::bytes.multicast::cluster [%0], [%1], %2, [%3], %4;"
                     ::"r"(sb + off), "l"(g_Wo + ct * WO_TILE_BYTES + off), "r"(K3_PIECE / 2), "r"(bar0 + tid * 8), "h"((uint16_t)3) : "memory");
    }
    float acc[72];
    {
        const uint4* bp = g_base + ((rt >> 1) * 36 + ct * 9) * 256 + (rt & 1) * 128 + tid;
        uint4 v[9];
#pragma unroll
        for (int i = 0; i < 9; i++) v[i] = __ldcg(bp + i * 256);
#pragma unroll
        for (int k = 4; k < 36; k++) a[k] = __ldcg(ap + k * 128);
#pragma unroll
        for (int i = 0; i < 9; i++) {
            acc[i * 8 + 0] = bf_lo(v[i].x); acc[i * 8 + 1] = bf_hi(v[i].x); acc[i * 8 + 2] = bf_lo(v[i].y); acc[i * 8 + 3] = bf_hi(v[i].y);
            acc[i * 8 + 4] = bf_lo(v[i].z); acc[i * 8 + 5] = bf_hi(v[i].z); acc[i * 8 + 6] = bf_lo(v[i].w); acc[i * 8 + 7] = bf_hi(v[i].w);
        }
    }
    PROF(34);
    const uint32_t db = desc_lo(sb, 2304);
#pragma unroll
    for (int kb = 0; kb < 9; kb++) {
        mbar_wait(bar0 + kb * 8, 0);
        wg_fence();
#pragma unroll
        for (int k = 0; k < 4; k++) {
            const uint4 f = a[kb * 4 + k];
            wgmma_rs_n144<1>(acc, f.x, f.y, f.z, f.w, db + (((kb * 4 + k) * 4608) >> 4), desc_hi(128, 0), 1);
        }
        wg_commit();
    }
    wg_wait<0>();
    reg_fence(acc);
    PROF(35);
    uint32_t* op = reinterpret_cast<uint32_t*>(out + (size_t)(rt * 64 + warp * 16 + g) * DM + ct * 144 + q * 2);
#pragma unroll
    for (int b = 0; b < 18; b++) {
        op[b * 4] = pack_bf16(acc[b * 4], acc[b * 4 + 1]);
        op[b * 4 + 4 * DM] = pack_bf16(acc[b * 4 + 2], acc[b * 4 + 3]);
    }
    cluster_arrive();
    cluster_wait();
    PROF(36);
    PROFT(53);
}

typedef CUresult (*EncodeFn)(CUtensorMap*, CUtensorMapDataType, cuuint32_t, void*, const cuuint64_t*, const cuuint64_t*, const cuuint32_t*,
                             const cuuint32_t*, CUtensorMapInterleave, CUtensorMapSwizzle, CUtensorMapL2promotion, CUtensorMapFloatOOBfill);

void make_map(EncodeFn fn, CUtensorMap* m, const void* base, int rank, const cuuint64_t* dims, const cuuint64_t* strides, const cuuint32_t* box) {
    cuuint32_t es[3] = {1, 1, 1};
    fn(m, CU_TENSOR_MAP_DATA_TYPE_BFLOAT16, rank, const_cast<void*>(base), dims, strides, box, es, CU_TENSOR_MAP_INTERLEAVE_NONE,
       CU_TENSOR_MAP_SWIZZLE_128B, CU_TENSOR_MAP_L2_PROMOTION_L2_256B, CU_TENSOR_MAP_FLOAT_OOB_FILL_NONE);
}

}

extern "C" void kernel_launch(void* const* d_in, const int* in_sizes, int n_in, void* d_out, int out_size) {
    const __nv_bfloat16* x = (const __nv_bfloat16*)d_in[0];
    const __nv_bfloat16* wqkv = (const __nv_bfloat16*)d_in[1];
    const __nv_bfloat16* wo = (const __nv_bfloat16*)d_in[2];
    const __nv_bfloat16* w1 = (const __nv_bfloat16*)d_in[4];
    const __nv_bfloat16* b1 = (const __nv_bfloat16*)d_in[5];
    const __nv_bfloat16* w2 = (const __nv_bfloat16*)d_in[6];
    const __nv_bfloat16* b2 = (const __nv_bfloat16*)d_in[7];
    __nv_bfloat16* out = (__nv_bfloat16*)d_out;

    EncodeFn fn = nullptr;
    cudaDriverEntryPointQueryResult qr;
    cudaGetDriverEntryPoint("cuTensorMapEncodeTiled", (void**)&fn, cudaEnableDefault, &qr);
    CUtensorMap tmX, tmQ3, tmQ1, tm1, tm2;
    {
        cuuint64_t d[3] = {64, SEQ, 9}, s[2] = {DM * 2, 128};
        cuuint32_t b[3] = {64, 8, 9};
        make_map(fn, &tmX, x, 3, d, s, b);
    }
    {
        cuuint64_t d[3] = {3 * DM, DM, 3}, s[2] = {3 * DM * 2, 128};
        cuuint32_t b[3] = {64, 16, 3};
        make_map(fn, &tmQ3, wqkv, 3, d, s, b);
        make_map(fn, &tmQ1, wqkv, 2, d, s, b);
    }
    {
        cuuint64_t d[2] = {FF, DM}, s[1] = {FF * 2};
        cuuint32_t b[2] = {64, 64};
        make_map(fn, &tm1, w1, 2, d, s, b);
        cuuint64_t d2[2] = {DM, FF}, s2[1] = {DM * 2};
        make_map(fn, &tm2, w2, 2, d2, s2, b);
    }
    cudaFuncSetAttribute(k1_kernel, cudaFuncAttributeMaxDynamicSharedMemorySize, K1_SMEM);
    cudaFuncSetAttribute(k2_kernel, cudaFuncAttributeMaxDynamicSharedMemorySize, K2_SMEM);
    cudaFuncSetAttribute(k3_kernel, cudaFuncAttributeMaxDynamicSharedMemorySize, K3_SMEM);

    cudaStream_t st = cudaStreamPerThread;
    cudaLaunchAttribute pdl[1];
    pdl[0].id = cudaLaunchAttributeProgrammaticStreamSerialization;
    pdl[0].val.programmaticStreamSerializationAllowed = 1;
    {
        cudaLaunchConfig_t cfg = {};
        cfg.gridDim = dim3(128); cfg.blockDim = dim3(384); cfg.dynamicSmemBytes = K1_SMEM; cfg.stream = st;
        cudaLaunchKernelEx(&cfg, k1_kernel, tmX, tmQ3, tmQ1, tm1, tm2, b1, wo, x, b2);
    }
    {
        cudaLaunchConfig_t cfg = {};
        cfg.gridDim = dim3(128); cfg.blockDim = dim3(512); cfg.dynamicSmemBytes = K2_SMEM; cfg.stream = st;
        cfg.attrs = pdl; cfg.numAttrs = 1;
        cudaLaunchKernelEx(&cfg, k2_kernel, x, b2);
    }
    {
        cudaLaunchConfig_t cfg = {};
        cfg.gridDim = dim3(128); cfg.blockDim = dim3(128); cfg.dynamicSmemBytes = K3_SMEM; cfg.stream = st;
        cfg.attrs = pdl; cfg.numAttrs = 1;
        cudaLaunchKernelEx(&cfg, k3_kernel, out);
    }
}
```

```cpp
#include <cuda_runtime.h>
#include <cuda_bf16.h>
#include <cuda.h>
#include <stdint.h>

#define PROF(i) do { } while (0)
#define PROFT(i) do { } while (0)
#define PROF_WG 0

namespace {

constexpr int SEQ = 2048, DM = 576, FF = 4608, NH = 32, DH = 18;

constexpr int KV_GROUP_BYTES = 5 * 128;
constexpr int KV_HEAD_BYTES = (SEQ / 8) * KV_GROUP_BYTES;
constexpr int Q_OFFSET = NH * KV_HEAD_BYTES;
#define POLY_MASK 0x92
__device__ __align__(1024) uint8_t g_QKV[2 * NH * KV_HEAD_BYTES];
__device__ __align__(1024) float g_kmax[NH * 64];
__device__ __align__(1024) uint4 g_part[8 * 16 * 36 * 256];
__device__ __align__(1024) uint4 g_base[16 * 36 * 256];
__device__ __align__(1024) uint32_t g_O[SEQ * DM / 2];
__device__ unsigned int g_flag[16 * 8];
constexpr int WO_TILE_BYTES = DM * 144 * 2;
__device__ __align__(1024) uint8_t g_Wo[4 * WO_TILE_BYTES];

__device__ __forceinline__ uint32_t s2u(const void* p) { return (uint32_t)__cvta_generic_to_shared(p); }
__device__ __forceinline__ void mbar_init(uint32_t b, int c) { asm volatile("mbarrier.init.shared::cta.b64 [%0], %1;" ::"r"(b), "r"(c) : "memory"); }
__device__ __forceinline__ void mbar_expect(uint32_t b, uint32_t bytes) {
    asm volatile("mbarrier.arrive.expect_tx.shared::cta.b64 _, [%0], %1;" ::"r"(b), "r"(bytes) : "memory");
}
__device__ __forceinline__ void mbar_wait(uint32_t b, uint32_t parity) {
    asm volatile(
        "{\n.reg .pred p;\n.reg .u32 c;\n"
        "mbarrier.try_wait.parity.shared::cta.b64 p, [%0], %1;\n"
        "@p bra DONE;\n"
        "mov.u32 c, 0;\n"
        "LOOP:\n"
        "mbarrier.try_wait.parity.shared::cta.b64 p, [%0], %1;\n"
        "@p bra DONE;\n"
        "add.u32 c, c, 1;\n"
        "setp.lt.u32 p, c, 4194304;\n"
        "@p bra LOOP;\n"
        "trap;\n"
        "DONE:\n}\n" ::"r"(b), "r"(parity) : "memory");
}
__device__ __forceinline__ void fence_barrier_init() { asm volatile("fence.mbarrier_init.release.cluster;" ::: "memory"); }
__device__ __forceinline__ void fence_proxy_async() { asm volatile("fence.proxy.async.shared::cta;" ::: "memory"); }
__device__ __forceinline__ void cluster_arrive() { asm volatile("barrier.cluster.arrive.relaxed.aligned;" ::: "memory"); }
__device__ __forceinline__ void cluster_wait() { asm volatile("barrier.cluster.wait.aligned;" ::: "memory"); }
__device__ __forceinline__ void named_bar_sync(int id, int n) { asm volatile("bar.sync %0, %1;" ::"r"(id), "r"(n) : "memory"); }
__device__ __forceinline__ void griddep_wait() { asm volatile("griddepcontrol.wait;" ::: "memory"); }
__device__ __forceinline__ void griddep_launch() { asm volatile("griddepcontrol.launch_dependents;" ::: "memory"); }

__device__ __forceinline__ void tma3d_mc(uint32_t dst, const CUtensorMap* tm, int c0, int c1, int c2, uint32_t bar, uint16_t mask) {
    asm volatile("cp.async.bulk.tensor.3d.shared::cluster.global.mbarrier::complete_tx::bytes.multicast::cluster [%0], [%1, {%3, %4, %5}], [%2], %6;"
                 ::"r"(dst), "l"(tm), "r"(bar), "r"(c0), "r"(c1), "r"(c2), "h"(mask) : "memory");
}
__device__ __forceinline__ void tma2d_mc(uint32_t dst, const CUtensorMap* tm, int c0, int c1, uint32_t bar, uint16_t mask) {
    asm volatile("cp.async.bulk.tensor.2d.shared::cluster.global.mbarrier::complete_tx::bytes.multicast::cluster [%0], [%1, {%3, %4}], [%2], %5;"
                 ::"r"(dst), "l"(tm), "r"(bar), "r"(c0), "r"(c1), "h"(mask) : "memory");
}
__device__ __forceinline__ void tma3d(uint32_t dst, const CUtensorMap* tm, int c0, int c1, int c2, uint32_t bar) {
    asm volatile("cp.async.bulk.tensor.3d.shared::cluster.global.mbarrier::complete_tx::bytes [%0], [%1, {%3, %4, %5}], [%2];"
                 ::"r"(dst), "l"(tm), "r"(bar), "r"(c0), "r"(c1), "r"(c2) : "memory");
}
__device__ __forceinline__ void tma2d(uint32_t dst, const CUtensorMap* tm, int c0, int c1, uint32_t bar) {
    asm volatile("cp.async.bulk.tensor.2d.shared::cluster.global.mbarrier::complete_tx::bytes [%0], [%1, {%3, %4}], [%2];"
                 ::"r"(dst), "l"(tm), "r"(bar), "r"(c0), "r"(c1) : "memory");
}
__device__ __forceinline__ void bulk_load(uint32_t dst, const void* src, uint32_t bytes, uint32_t bar) {
    asm volatile("cp.async.bulk.shared::cluster.global.mbarrier::complete_tx::bytes [%0], [%1], %2, [%3];"
                 ::"r"(dst), "l"(src), "r"(bytes), "r"(bar) : "memory");
}
__device__ __forceinline__ void prefetch_tmap(const CUtensorMap* tm) { asm volatile("prefetch.tensormap [%0];" ::"l"(tm) : "memory"); }

__device__ __forceinline__ void wg_fence() { asm volatile("wgmma.fence.sync.aligned;" ::: "memory"); }
__device__ __forceinline__ void wg_commit() { asm volatile("wgmma.commit_group.sync.aligned;" ::: "memory"); }
template <int N> __device__ __forceinline__ void wg_wait() { asm volatile("wgmma.wait_group.sync.aligned %0;" ::"n"(N) : "memory"); }
template <int N> __device__ __forceinline__ void reg_fence(float (&d)[N]) {
#pragma unroll
    for (int i = 0; i < N; i++) asm volatile("" : "+f"(d[i])::"memory");
}
template <int N> __device__ __forceinline__ void reg_fence(uint32_t (&d)[N]) {
#pragma unroll
    for (int i = 0; i < N; i++) asm volatile("" : "+r"(d[i])::"memory");
}
template <int R> __device__ __forceinline__ void reg_alloc() { asm volatile("setmaxnreg.inc.sync.aligned.u32 %0;" ::"n"(R)); }
template <int R> __device__ __forceinline__ void reg_dealloc() { asm volatile("setmaxnreg.dec.sync.aligned.u32 %0;" ::"n"(R)); }

__device__ __forceinline__ uint32_t desc_lo(uint32_t addr, uint32_t lbo) { return ((addr & 0x3FFFF) >> 4) | ((lbo >> 4) << 16); }
__host__ __device__ constexpr uint32_t desc_hi(uint32_t sbo, uint32_t swz) { return (sbo >> 4) | (swz << 30); }
__device__ __forceinline__ uint32_t pack_bf16(float lo, float hi) {
    uint32_t r;
    asm("cvt.rn.bf16x2.f32 %0, %1, %2;" : "=r"(r) : "f"(hi), "f"(lo));
    return r;
}
__device__ __forceinline__ float bf_lo(uint32_t w) { return __uint_as_float(w << 16); }
__device__ __forceinline__ float bf_hi(uint32_t w) { return __uint_as_float(w & 0xFFFF0000u); }
__device__ __forceinline__ float ex2(float x) {
    float r;
    asm("ex2.approx.ftz.f32 %0, %1;" : "=f"(r) : "f"(x));
    return r;
}
__device__ __forceinline__ float tanh_fast(float x) {
    float r;
    asm("tanh.approx.f32 %0, %1;" : "=f"(r) : "f"(x));
    return r;
}
__device__ __forceinline__ float gelu2(float u) {
    const float w = fmaf(u * u, 0.0356774081f, 0.7978845608f);
    return fmaf(u, tanh_fast(u * w), u);
}

template<int TB> __device__ __forceinline__ void wgmma_ss_n216(float (&d)[108], uint32_t alo, uint32_t ahi, uint32_t blo, uint32_t bhi, int sd) {
    asm volatile("{\n.reg .pred p;\n.reg .b64 da, db;\nsetp.ne.b32 p, %110, 0;\nmov.b64 da, {%108, %112};\nmov.b64 db, {%109, %113};\n"
      "wgmma.mma_async.sync.aligned.m64n216k16.f32.bf16.bf16 {%0, %1, %2, %3, %4, %5, %6, %7, %8, %9, %10, %11, %12, %13, %14, %15, %16, %17, %18, %19, %20, %21, %22, %23, %24, %25, %26, %27, %28, %29, %30, %31, %32, %33, %34, %35, %36, %37, %38, %39, %40, %41, %42, %43, %44, %45, %46, %47, %48, %49, %50, %51, %52, %53, %54, %55, %56, %57, %58, %59, %60, %61, %62, %63, %64, %65, %66, %67, %68, %69, %70, %71, %72, %73, %74, %75, %76, %77, %78, %79, %80, %81, %82, %83, %84, %85, %86, %87, %88, %89, %90, %91, %92, %93, %94, %95, %96, %97, %98, %99, %100, %101, %102, %103, %104, %105, %106, %107}, da, db, p, 1, 1, 0, %111;\n}\n"
      : "+f"(d[0]), "+f"(d[1]), "+f"(d[2]), "+f"(d[3]), "+f"(d[4]), "+f"(d[5]), "+f"(d[6]), "+f"(d[7]), "+f"(d[8]), "+f"(d[9]), "+f"(d[10]), "+f"(d[11]), "+f"(d[12]), "+f"(d[13]), "+f"(d[14]), "+f"(d[15]), "+f"(d[16]), "+f"(d[17]), "+f"(d[18]), "+f"(d[19]), "+f"(d[20]), "+f"(d[21]), "+f"(d[22]), "+f"(d[23]), "+f"(d[24]), "+f"(d[25]), "+f"(d[26]), "+f"(d[27]), "+f"(d[28]), "+f"(d[29]), "+f"(d[30]), "+f"(d[31]), "+f"(d[32]), "+f"(d[33]), "+f"(d[34]), "+f"(d[35]), "+f"(d[36]), "+f"(d[37]), "+f"(d[38]), "+f"(d[39]), "+f"(d[40]), "+f"(d[41]), "+f"(d[42]), "+f"(d[43]), "+f"(d[44]), "+f"(d[45]), "+f"(d[46]), "+f"(d[47]), "+f"(d[48]), "+f"(d[49]), "+f"(d[50]), "+f"(d[51]), "+f"(d[52]), "+f"(d[53]), "+f"(d[54]), "+f"(d[55]), "+f"(d[56]), "+f"(d[57]), "+f"(d[58]), "+f"(d[59]), "+f"(d[60]), "+f"(d[61]), "+f"(d[62]), "+f"(d[63]), "+f"(d[64]), "+f"(d[65]), "+f"(d[66]), "+f"(d[67]), "+f"(d[68]), "+f"(d[69]), "+f"(d[70]), "+f"(d[71]), "+f"(d[72]), "+f"(d[73]), "+f"(d[74]), "+f"(d[75]), "+f"(d[76]), "+f"(d[77]), "+f"(d[78]), "+f"(d[79]), "+f"(d[80]), "+f"(d[81]), "+f"(d[82]), "+f"(d[83]), "+f"(d[84]), "+f"(d[85]), "+f"(d[86]), "+f"(d[87]), "+f"(d[88]), "+f"(d[89]), "+f"(d[90]), "+f"(d[91]), "+f"(d[92]), "+f"(d[93]), "+f"(d[94]), "+f"(d[95]), "+f"(d[96]), "+f"(d[97]), "+f"(d[98]), "+f"(d[99]), "+f"(d[100]), "+f"(d[101]), "+f"(d[102]), "+f"(d[103]), "+f"(d[104]), "+f"(d[105]), "+f"(d[106]), "+f"(d[107])
      : "r"(alo), "r"(blo), "r"(sd), "n"(TB), "r"(ahi), "r"(bhi));
}

template<int TB> __device__ __forceinline__ void wgmma_ss_n64(float (&d)[32], uint32_t alo, uint32_t ahi, uint32_t blo, uint32_t bhi, int sd) {
    asm volatile("{\n.reg .pred p;\n.reg .b64 da, db;\nsetp.ne.b32 p, %34, 0;\nmov.b64 da, {%32, %36};\nmov.b64 db, {%33, %37};\n"
      "wgmma.mma_async.sync.aligned.m64n64k16.f32.bf16.bf16 {%0, %1, %2, %3, %4, %5, %6, %7, %8, %9, %10, %11, %12, %13, %14, %15, %16, %17, %18, %19, %20, %21, %22, %23, %24, %25, %26, %27, %28, %29, %30, %31}, da, db, p, 1, 1, 0, %35;\n}\n"
      : "+f"(d[0]), "+f"(d[1]), "+f"(d[2]), "+f"(d[3]), "+f"(d[4]), "+f"(d[5]), "+f"(d[6]), "+f"(d[7]), "+f"(d[8]), "+f"(d[9]), "+f"(d[10]), "+f"(d[11]), "+f"(d[12]), "+f"(d[13]), "+f"(d[14]), "+f"(d[15]), "+f"(d[16]), "+f"(d[17]), "+f"(d[18]), "+f"(d[19]), "+f"(d[20]), "+f"(d[21]), "+f"(d[22]), "+f"(d[23]), "+f"(d[24]), "+f"(d[25]), "+f"(d[26]), "+f"(d[27]), "+f"(d[28]), "+f"(d[29]), "+f"(d[30]), "+f"(d[31])
      : "r"(alo), "r"(blo), "r"(sd), "n"(TB), "r"(ahi), "r"(bhi));
}

template<int TB> __device__ __forceinline__ void wgmma_rs_n64(float (&d)[32], uint32_t a0, uint32_t a1, uint32_t a2, uint32_t a3, uint32_t blo, uint32_t bhi, int sd) {
    asm volatile("{\n.reg .pred p;\n.reg .b64 db;\nsetp.ne.b32 p, %37, 0;\nmov.b64 db, {%36, %39};\n"
      "wgmma.mma_async.sync.aligned.m64n64k16.f32.bf16.bf16 {%0, %1, %2, %3, %4, %5, %6, %7, %8, %9, %10, %11, %12, %13, %14, %15, %16, %17, %18, %19, %20, %21, %22, %23, %24, %25, %26, %27, %28, %29, %30, %31}, {%32, %33, %34, %35}, db, p, 1, 1, %38;\n}\n"
      : "+f"(d[0]), "+f"(d[1]), "+f"(d[2]), "+f"(d[3]), "+f"(d[4]), "+f"(d[5]), "+f"(d[6]), "+f"(d[7]), "+f"(d[8]), "+f"(d[9]), "+f"(d[10]), "+f"(d[11]), "+f"(d[12]), "+f"(d[13]), "+f"(d[14]), "+f"(d[15]), "+f"(d[16]), "+f"(d[17]), "+f"(d[18]), "+f"(d[19]), "+f"(d[20]), "+f"(d[21]), "+f"(d[22]), "+f"(d[23]), "+f"(d[24]), "+f"(d[25]), "+f"(d[26]), "+f"(d[27]), "+f"(d[28]), "+f"(d[29]), "+f"(d[30]), "+f"(d[31])
      : "r"(a0), "r"(a1), "r"(a2), "r"(a3), "r"(blo), "r"(sd), "n"(TB), "r"(bhi));
}

template<int TB> __device__ __forceinline__ void wgmma_rs_n24(float (&d)[12], uint32_t a0, uint32_t a1, uint32_t a2, uint32_t a3, uint32_t blo, uint32_t bhi, int sd) {
    asm volatile("{\n.reg .pred p;\n.reg .b64 db;\nsetp.ne.b32 p, %17, 0;\nmov.b64 db, {%16, %19};\n"
      "wgmma.mma_async.sync.aligned.m64n24k16.f32.bf16.bf16 {%0, %1, %2, %3, %4, %5, %6, %7, %8, %9, %10, %11}, {%12, %13, %14, %15}, db, p, 1, 1, %18;\n}\n"
      : "+f"(d[0]), "+f"(d[1]), "+f"(d[2]), "+f"(d[3]), "+f"(d[4]), "+f"(d[5]), "+f"(d[6]), "+f"(d[7]), "+f"(d[8]), "+f"(d[9]), "+f"(d[10]), "+f"(d[11])
      : "r"(a0), "r"(a1), "r"(a2), "r"(a3), "r"(blo), "r"(sd), "n"(TB), "r"(bhi));
}

template<int TB> __device__ __forceinline__ void wgmma_rs_n144(float (&d)[72], uint32_t a0, uint32_t a1, uint32_t a2, uint32_t a3, uint32_t blo, uint32_t bhi, int sd) {
    asm volatile("{\n.reg .pred p;\n.reg .b64 db;\nsetp.ne.b32 p, %77, 0;\nmov.b64 db, {%76, %79};\n"
      "wgmma.mma_async.sync.aligned.m64n144k16.f32.bf16.bf16 {%0, %1, %2, %3, %4, %5, %6, %7, %8, %9, %10, %11, %12, %13, %14, %15, %16, %17, %18, %19, %20, %21, %22, %23, %24, %25, %26, %27, %28, %29, %30, %31, %32, %33, %34, %35, %36, %37, %38, %39, %40, %41, %42, %43, %44, %45, %46, %47, %48, %49, %50, %51, %52, %53, %54, %55, %56, %57, %58, %59, %60, %61, %62, %63, %64, %65, %66, %67, %68, %69, %70, %71}, {%72, %73, %74, %75}, db, p, 1, 1, %78;\n}\n"
      : "+f"(d[0]), "+f"(d[1]), "+f"(d[2]), "+f"(d[3]), "+f"(d[4]), "+f"(d[5]), "+f"(d[6]), "+f"(d[7]), "+f"(d[8]), "+f"(d[9]), "+f"(d[10]), "+f"(d[11]), "+f"(d[12]), "+f"(d[13]), "+f"(d[14]), "+f"(d[15]), "+f"(d[16]), "+f"(d[17]), "+f"(d[18]), "+f"(d[19]), "+f"(d[20]), "+f"(d[21]), "+f"(d[22]), "+f"(d[23]), "+f"(d[24]), "+f"(d[25]), "+f"(d[26]), "+f"(d[27]), "+f"(d[28]), "+f"(d[29]), "+f"(d[30]), "+f"(d[31]), "+f"(d[32]), "+f"(d[33]), "+f"(d[34]), "+f"(d[35]), "+f"(d[36]), "+f"(d[37]), "+f"(d[38]), "+f"(d[39]), "+f"(d[40]), "+f"(d[41]), "+f"(d[42]), "+f"(d[43]), "+f"(d[44]), "+f"(d[45]), "+f"(d[46]), "+f"(d[47]), "+f"(d[48]), "+f"(d[49]), "+f"(d[50]), "+f"(d[51]), "+f"(d[52]), "+f"(d[53]), "+f"(d[54]), "+f"(d[55]), "+f"(d[56]), "+f"(d[57]), "+f"(d[58]), "+f"(d[59]), "+f"(d[60]), "+f"(d[61]), "+f"(d[62]), "+f"(d[63]), "+f"(d[64]), "+f"(d[65]), "+f"(d[66]), "+f"(d[67]), "+f"(d[68]), "+f"(d[69]), "+f"(d[70]), "+f"(d[71])
      : "r"(a0), "r"(a1), "r"(a2), "r"(a3), "r"(blo), "r"(sd), "n"(TB), "r"(bhi));
}

__device__ __forceinline__ void init_unit(int u, const __nv_bfloat16* __restrict__ x, const __nv_bfloat16* __restrict__ b2) {
    const int t = u & 255, pbr = u >> 8, rb = pbr / 36, pb = pbr - rb * 36;
    const int row = rb * 128 + (t >> 5) * 16 + ((t & 31) >> 2), col = pb * 16 + (t & 3) * 2;
    const uint32_t* xp = reinterpret_cast<const uint32_t*>(x + (size_t)row * DM + col);
    const uint32_t x0 = __ldg(xp), x1 = __ldg(xp + 4 * DM), x2 = __ldg(xp + 4), x3 = __ldg(xp + 4 * DM + 4);
    const uint32_t ba = __ldg(reinterpret_cast<const uint32_t*>(b2 + col)), bb = __ldg(reinterpret_cast<const uint32_t*>(b2 + col + 8));
    uint4 o;
    o.x = pack_bf16(bf_lo(x0) + bf_lo(ba), bf_hi(x0) + bf_hi(ba));
    o.y = pack_bf16(bf_lo(x1) + bf_lo(ba), bf_hi(x1) + bf_hi(ba));
    o.z = pack_bf16(bf_lo(x2) + bf_lo(bb), bf_hi(x2) + bf_hi(bb));
    o.w = pack_bf16(bf_lo(x3) + bf_lo(bb), bf_hi(x3) + bf_hi(bb));
    g_base[u] = o;
}
__device__ __forceinline__ void finish_unit(int u, const float (&a)[8], const uint4 v) {
    uint4 o;
    o.x = pack_bf16(fmaf(a[0], 0.5f, bf_lo(v.x)), fmaf(a[1], 0.5f, bf_hi(v.x)));
    o.y = pack_bf16(fmaf(a[2], 0.5f, bf_lo(v.y)), fmaf(a[3], 0.5f, bf_hi(v.y)));
    o.z = pack_bf16(fmaf(a[4], 0.5f, bf_lo(v.z)), fmaf(a[5], 0.5f, bf_hi(v.z)));
    o.w = pack_bf16(fmaf(a[6], 0.5f, bf_lo(v.w)), fmaf(a[7], 0.5f, bf_hi(v.w)));
    g_base[u] = o;
}
__device__ __forceinline__ void add_unit(float (&a)[8], const uint4 v) {
    a[0] += bf_lo(v.x); a[1] += bf_hi(v.x); a[2] += bf_lo(v.y); a[3] += bf_hi(v.y);
    a[4] += bf_lo(v.z); a[5] += bf_hi(v.z); a[6] += bf_lo(v.w); a[7] += bf_hi(v.w);
}

constexpr int K1_XN_BYTES = 16 * 9216;
constexpr int K1_SLOT = 16384, K1_NSLOT = 5;
constexpr int K1_OFF_RING = K1_XN_BYTES;
constexpr int K1_OFF_BIAS = K1_OFF_RING + K1_NSLOT * K1_SLOT;
constexpr int K1_OFF_BAR = K1_OFF_BIAS + 576 * 2;
constexpr int K1_SMEM = K1_OFF_BAR + 256 + 128;
constexpr float QSCALE = 0.23570226039551584f * 1.4426950408889634f;

struct Ring {
    uint32_t slot, phase;
    __device__ __forceinline__ void advance() {
        if (++slot == K1_NSLOT) { slot = 0; phase ^= 1; }
    }
};

struct K1Ctx {
    uint32_t full0;
    uint32_t rel_addr;
    uint32_t descA, descB;
    Ring rd;
    uint32_t prev_slot;
    __device__ __forceinline__ uint32_t begin_stage() {
        mbar_wait(full0 + rd.slot * 8, rd.phase);
        wg_fence();
        return descB + rd.slot * (K1_SLOT >> 4);
    }
    __device__ __forceinline__ void end_stage() {
        wg_commit();
        wg_wait<1>();
        if (rel_addr) asm volatile("mbarrier.arrive.shared::cluster.b64 _, [%0];" ::"r"(rel_addr + prev_slot * 8) : "memory");
        prev_slot = rd.slot;
        rd.advance();
    }
};

__device__ __forceinline__ uint32_t descA_step(uint32_t base, int ks) { return base + (((ks >> 2) * 1024 + (ks & 3) * 32) >> 4); }
constexpr uint32_t K1_AHI = desc_hi(9216, 1), K1_BHI = desc_hi(1024, 1);

template <int V> struct IC { static constexpr int value = V; };
template <int I, int N, class F> __device__ __forceinline__ void static_for(F&& f) {
    if constexpr (I < N) { f(IC<I>{}); static_for<I + 1, N>(f); }
}

template <bool A_RS, bool B_RS, class Epi>
__device__ __forceinline__ void tile_pair(K1Ctx& c, float (&accA)[32], float (&accB)[32], uint32_t (&h)[144], Epi&& epi) {
    static_for<0, 9>([&](auto sc) {
        constexpr int s = decltype(sc)::value;
        const uint32_t db = c.begin_stage();
#pragma unroll
        for (int t = 0; t < 8; t++) {
            const int kk = s * 8 + t, ks = kk % 36;
            const uint32_t dbt = db + ((t * 2048) >> 4);
            if (kk < 36) {
                if constexpr (A_RS) wgmma_rs_n64<1>(accA, h[ks * 4], h[ks * 4 + 1], h[ks * 4 + 2], h[ks * 4 + 3], dbt, K1_BHI, ks != 0);
                else wgmma_ss_n64<1>(accA, descA_step(c.descA, ks), K1_AHI, dbt, K1_BHI, ks != 0);
            } else {
                if constexpr (B_RS) wgmma_rs_n64<1>(accB, h[ks * 4], h[ks * 4 + 1], h[ks * 4 + 2], h[ks * 4 + 3], dbt, K1_BHI, ks != 0);
                else wgmma_ss_n64<1>(accB, descA_step(c.descA, ks), K1_AHI, dbt, K1_BHI, ks != 0);
            }
        }
        c.end_stage();
        epi(sc);
    });
}

template <int B0, int NB, int HOFF>
__device__ __forceinline__ void gelu_blocks(const float (&acc)[32], uint32_t (&h)[144], const uint32_t (&bq)[8]) {
#pragma unroll
    for (int b = B0; b < B0 + NB; b++) {
        const float b0 = bf_lo(bq[b]), b1 = bf_hi(bq[b]);
        h[HOFF + b * 2 + 0] = pack_bf16(gelu2(acc[b * 4 + 0] + b0), gelu2(acc[b * 4 + 1] + b1));
        h[HOFF + b * 2 + 1] = pack_bf16(gelu2(acc[b * 4 + 2] + b0), gelu2(acc[b * 4 + 3] + b1));
    }
}
__device__ __forceinline__ void load_bias(uint32_t (&bq)[8], uint32_t addr) {
    asm volatile("ld.shared.v4.u32 {%0, %1, %2, %3}, [%4];" : "=r"(bq[0]), "=r"(bq[1]), "=r"(bq[2]), "=r"(bq[3]) : "r"(addr));
    asm volatile("ld.shared.v4.u32 {%0, %1, %2, %3}, [%4 + 16];" : "=r"(bq[4]), "=r"(bq[5]), "=r"(bq[6]), "=r"(bq[7]) : "r"(addr));
}
template <int S> __device__ __forceinline__ void store_part(const float (&o)[32], uint4* p) {
    uint4 v;
    v.x = pack_bf16(o[S * 8 + 0], o[S * 8 + 1]); v.y = pack_bf16(o[S * 8 + 2], o[S * 8 + 3]);
    v.z = pack_bf16(o[S * 8 + 4], o[S * 8 + 5]); v.w = pack_bf16(o[S * 8 + 6], o[S * 8 + 7]);
    p[S * 256] = v;
}

__global__ void __cluster_dims__(2, 1, 1) __launch_bounds__(384, 1)
k1_kernel(const __grid_constant__ CUtensorMap tmX, const __grid_constant__ CUtensorMap tmQ3, const __grid_constant__ CUtensorMap tmQ1,
          const __grid_constant__ CUtensorMap tm1, const __grid_constant__ CUtensorMap tm2, const __nv_bfloat16* __restrict__ b1,
          const __nv_bfloat16* __restrict__ wo, const __nv_bfloat16* __restrict__ x, const __nv_bfloat16* __restrict__ b2) {
    extern __shared__ __align__(1024) uint8_t smem[];
    const uint32_t sb = s2u(smem);
    const int tid = threadIdx.x, lane = tid & 31;
    const int warp = __shfl_sync(~0u, tid >> 5, 0);
    const uint32_t rank = blockIdx.x & 1;
    const int cl = blockIdx.x >> 1;
    const int rb = (cl & 7) * 2 + rank;
    const int j = cl >> 3;
    const uint32_t full0 = sb + K1_OFF_BAR, empty0 = full0 + 8 * K1_NSLOT, xbar0 = full0 + 128, rbar0 = full0 + 256, sbar0 = full0 + 320;

    if (warp < 8) {
        PROF(0);
        PROFT(48);
        if (lane == 0) {
            mbar_init(xbar0 + warp * 16, 1);
            mbar_init(xbar0 + warp * 16 + 8, 1);
            fence_barrier_init();
            mbar_expect(xbar0 + warp * 16, 9216);
            tma3d(sb + warp * 2 * 9216, &tmX, 0, rb * 128 + warp * 16, 0, xbar0 + warp * 16);
            mbar_expect(xbar0 + warp * 16 + 8, 9216);
            tma3d(sb + (warp * 2 + 1) * 9216, &tmX, 0, rb * 128 + warp * 16 + 8, 0, xbar0 + warp * 16 + 8);
        }
        __syncwarp();
        cluster_arrive();
        reg_alloc<240>();
#pragma unroll 1
        for (int p = 0; p < 4; p++) {
            mbar_wait(xbar0 + warp * 16 + (p >> 1) * 8, 0);
            uint4* row = reinterpret_cast<uint4*>(smem + (warp * 2 + (p >> 1)) * 9216 + (p & 1) * 512 + lane * 16);
            float f[72];
#pragma unroll
            for (int i = 0; i < 9; i++) {
                const uint4 v = row[i * 64];
                f[i * 8 + 0] = bf_lo(v.x); f[i * 8 + 1] = bf_hi(v.x); f[i * 8 + 2] = bf_lo(v.y); f[i * 8 + 3] = bf_hi(v.y);
                f[i * 8 + 4] = bf_lo(v.z); f[i * 8 + 5] = bf_hi(v.z); f[i * 8 + 6] = bf_lo(v.w); f[i * 8 + 7] = bf_hi(v.w);
            }
            float s0 = 0.f, s1 = 0.f, s2 = 0.f, s3 = 0.f;
#pragma unroll
            for (int i = 0; i < 72; i += 4) { s0 += f[i]; s1 += f[i + 1]; s2 += f[i + 2]; s3 += f[i + 3]; }
            float sm = (s0 + s1) + (s2 + s3);
            sm += __shfl_xor_sync(~0u, sm, 1); sm += __shfl_xor_sync(~0u, sm, 2); sm += __shfl_xor_sync(~0u, sm, 4);
            const float mean = sm * (1.0f / DM);
            s0 = s1 = s2 = s3 = 0.f;
#pragma unroll
            for (int i = 0; i < 72; i += 4) {
                f[i] -= mean; f[i + 1] -= mean; f[i + 2] -= mean; f[i + 3] -= mean;
                s0 = fmaf(f[i], f[i], s0); s1 = fmaf(f[i + 1], f[i + 1], s1);
                s2 = fmaf(f[i + 2], f[i + 2], s2); s3 = fmaf(f[i + 3], f[i + 3], s3);
            }
            float sq = (s0 + s1) + (s2 + s3);
            sq += __shfl_xor_sync(~0u, sq, 1); sq += __shfl_xor_sync(~0u, sq, 2); sq += __shfl_xor_sync(~0u, sq, 4);
            const float rstd = rsqrtf(sq * (1.0f / DM) + 1e-5f);
#pragma unroll
            for (int i = 0; i < 9; i++) {
                uint4 o;
                o.x = pack_bf16(f[i * 8 + 0] * rstd, f[i * 8 + 1] * rstd);
                o.y = pack_bf16(f[i * 8 + 2] * rstd, f[i * 8 + 3] * rstd);
                o.z = pack_bf16(f[i * 8 + 4] * rstd, f[i * 8 + 5] * rstd);
                o.w = pack_bf16(f[i * 8 + 6] * rstd, f[i * 8 + 7] * rstd);
                row[i * 64] = o;
            }
        }
        const int wg = warp >> 2, wq = warp & 3;
        fence_proxy_async();
        named_bar_sync(1 + wg, 128);
        cluster_wait();
        PROF(1);

        const int g = lane >> 2, q = lane & 3;
        K1Ctx c;
        c.full0 = full0;
        c.rel_addr = 0;
        c.descA = desc_lo(sb + wg * 8 * 9216, 16);
        c.descB = desc_lo(sb + K1_OFF_RING, 2048);
        c.rd.slot = 0; c.rd.phase = 0; c.prev_slot = 0;
        uint32_t biasq = sb + K1_OFF_BIAS + q * 32;
        uint32_t bq[8];

        uint32_t h[144];
        float accA[32], accB[32];
        {
            float accQ[108];
            uint32_t rel = 0;
            if (lane == 0 && wq < 2) asm("mapa.shared::cluster.u32 %0, %1, %2;" : "=r"(rel) : "r"(empty0), "r"(wq));
#pragma unroll 1
            for (int s = 0; s < 18; s++) {
                const uint32_t db = c.begin_stage();
                const uint32_t da = c.descA + (s >> 1) * 64 + (s & 1) * 4;
                wgmma_ss_n216<1>(accQ, da, K1_AHI, db, K1_BHI, s != 0);
                wgmma_ss_n216<1>(accQ, da + 2, K1_AHI, db + (8192 >> 4), K1_BHI, 1);
                c.end_stage();
                c.rel_addr = rel;
            }
            PROF(2);
            uint32_t rel9[9];
#pragma unroll
            for (int i9 = 0; i9 < 9; i9++) {
                const int p = 4 * i9 + q, hh = (p * 57) >> 9, r = p - 9 * hh;
                rel9[i9] = hh * KV_HEAD_BYTES + (r < 8 ? (r >> 2) * 128 + (r & 3) * 4 : 0);
            }
            uint32_t gb = 0, o2 = 0;
            float scl0 = 1.f, scl1 = 1.f;
            tile_pair<false, false>(c, accA, accB, h, [&](auto sc) {
                constexpr int s = decltype(sc)::value;
                if constexpr (s == 0) reg_fence(accQ);
                if constexpr (s < 6) {
                    constexpr int grp = s / 2, part = s % 2;
                    if constexpr (part == 0) {
                        const int G = 3 * j + grp, type = G >> 3;
                        gb = (G & 7) * 4 * KV_HEAD_BYTES + (rb * 16 + warp * 2) * KV_GROUP_BYTES + g * 16 + (type == 0 ? Q_OFFSET : (type == 2 ? 256 : 0));
                        o2 = type == 0 ? 256 : (type == 2 ? 264 : 512);
                        scl0 = type == 0 ? QSCALE : ((type == 1 && ((POLY_MASK >> (wq * 2)) & 1)) ? 2.f : 1.f);
                        scl1 = type == 0 ? QSCALE : ((type == 1 && ((POLY_MASK >> (wq * 2 + 1)) & 1)) ? 2.f : 1.f);
                    }
#pragma unroll
                    for (int i9 = part * 5; i9 < (part ? 9 : 5); i9++) {
                        const int b = grp * 9 + i9;
                        uint32_t off = gb + rel9[i9];
                        if (i9 >= 2 && (i9 & 1) == 0) off += (q == i9 / 2 - 1) ? o2 : 0;
                        *reinterpret_cast<uint32_t*>(g_QKV + off) = pack_bf16(accQ[b * 4] * scl0, accQ[b * 4 + 1] * scl0);
                        *reinterpret_cast<uint32_t*>(g_QKV + off + KV_GROUP_BYTES) = pack_bf16(accQ[b * 4 + 2] * scl1, accQ[b * 4 + 3] * scl1);
                    }
                    if constexpr (s == 5) asm volatile("bar.arrive 3, 352;" ::: "memory");
                }
                if constexpr (s == 4) { named_bar_sync(4, 288); load_bias(bq, biasq); }
                if constexpr (s == 5) reg_fence(accA);
                if constexpr (s >= 5) gelu_blocks<(s - 5) * 2, 2, 96>(accA, h, bq);
                if constexpr (s == 8) load_bias(bq, biasq + 128);
            });
        }
        PROF(3);
#pragma unroll
        for (int i = 32; i < 96; i++) asm volatile("mov.u32 %0, 0;" : "=r"(h[i]));
#pragma unroll 1
        for (int p = 1; p < 4; p++) {
            biasq += 256;
            tile_pair<false, false>(c, accA, accB, h, [&](auto sc) {
                constexpr int s = decltype(sc)::value;
                if constexpr (s == 0) {
                    reg_fence(accB);
#pragma unroll
                    for (int i = 0; i < 80; i++) h[i] = h[i + 32];
                }
                if constexpr (s < 4) gelu_blocks<s * 2, 2, 80>(accB, h, bq);
                if constexpr (s == 4) load_bias(bq, biasq);
                if constexpr (s == 5) reg_fence(accA);
                if constexpr (s >= 5) gelu_blocks<(s - 5) * 2, 2, 96>(accA, h, bq);
                if constexpr (s == 8) load_bias(bq, biasq + 128);
            });
        }
        PROF(4);
        tile_pair<false, true>(c, accA, accB, h, [&](auto sc) {
            constexpr int s = decltype(sc)::value;
            if constexpr (s == 0) reg_fence(accB);
            if constexpr (s < 4) gelu_blocks<s * 2, 2, 112>(accB, h, bq);
            if constexpr (s == 4) load_bias(bq, biasq + 256);
            if constexpr (s == 5) reg_fence(accA);
            if constexpr (s == 5 || s == 6) gelu_blocks<(s - 5) * 3, 3, 128>(accA, h, bq);
            if constexpr (s == 7) gelu_blocks<6, 2, 128>(accA, h, bq);
            if constexpr (s == 3 || s == 7) reg_fence(h);
        });
        PROF(5);
        uint4* pout = g_part + ((size_t)(j * 16 + rb) * 36) * 256 + tid;
#pragma unroll 1
        for (int p = 0; p < 4; p++) {
            tile_pair<true, true>(c, accA, accB, h, [&](auto sc) {
                constexpr int s = decltype(sc)::value;
                if constexpr (s == 0) reg_fence(accB);
                if constexpr (s < 4) store_part<s>(accB, pout);
                if constexpr (s == 3) { __syncwarp(); if (lane == 0) asm volatile("mbarrier.arrive.shared::cta.b64 _, [%0];" ::"r"(sbar0 + p * 16) : "memory"); }
                if constexpr (s == 5) reg_fence(accA);
                if constexpr (s >= 5) store_part<s - 5>(accA, pout + 1024);
                if constexpr (s == 8) { __syncwarp(); if (lane == 0) asm volatile("mbarrier.arrive.shared::cta.b64 _, [%0];" ::"r"(sbar0 + p * 16 + 8) : "memory"); }
            });
            pout += 2048;
            PROF(6 + p);
        }
        wg_wait<0>();
        reg_fence(accB);
        store_part<0>(accB, pout); store_part<1>(accB, pout); store_part<2>(accB, pout); store_part<3>(accB, pout);
        PROF(10);
        cluster_arrive();
        cluster_wait();
        PROF(11);
        PROFT(49);
    } else {
        reg_dealloc<24>();
        if (warp == 8 && lane == 0) {
            prefetch_tmap(&tmQ3); prefetch_tmap(&tmQ1); prefetch_tmap(&tm1); prefetch_tmap(&tm2);
            for (int i = 0; i < K1_NSLOT; i++) { mbar_init(full0 + i * 8, 1); mbar_init(empty0 + i * 8, 4); }
            for (int i = 0; i < 8; i++) { mbar_init(rbar0 + i * 8, 1); mbar_init(sbar0 + i * 8, 8); }
            fence_barrier_init();
        }
        __syncwarp();
        cluster_arrive();
        cluster_wait();
        if (warp == 8) {
            if (lane == 0) {
                Ring w{0, 1};
                const uint32_t dst0 = sb + K1_OFF_RING + rank * 8192;
#pragma unroll 1
                for (int s = 0; s < 18; s++) {
                    mbar_wait(empty0 + w.slot * 8, w.phase);
                    mbar_expect(full0 + w.slot * 8, 16384);
                    const uint32_t dst = dst0 + w.slot * K1_SLOT;
                    tma3d_mc(dst, &tmQ3, j * 216, s * 32 + rank * 16, 0, full0 + w.slot * 8, 3);
                    tma2d_mc(dst + 6144, &tmQ1, j * 216 + 192, s * 32 + rank * 16, full0 + w.slot * 8, 3);
                    w.advance();
                }
                int tile = 0, kb = rank;
#pragma unroll 1
                for (int s = 0; s < 81; s++) {
                    mbar_wait(empty0 + w.slot * 8, w.phase);
                    mbar_expect(full0 + w.slot * 8, 16384);
                    const uint32_t dst = dst0 + w.slot * K1_SLOT;
                    if (tile < 9) tma2d_mc(dst, &tm1, j * 576 + tile * 64, kb * 64, full0 + w.slot * 8, 3);
                    else tma2d_mc(dst, &tm2, (tile - 9) * 64, j * 576 + kb * 64, full0 + w.slot * 8, 3);
                    kb += 2;
                    if (kb >= 9) { kb -= 9; tile++; }
                    w.advance();
                }
            }
        } else {
            const int ht = tid - 288;
            if (warp == 9) {
                uint32_t* sbias = reinterpret_cast<uint32_t*>(smem + K1_OFF_BIAS);
#pragma unroll 1
                for (int t = 0; t < 9; t++) sbias[t * 32 + (lane & 3) * 8 + (lane >> 2)] = reinterpret_cast<const uint32_t*>(b1 + j * 576)[t * 32 + lane];
                asm volatile("bar.arrive 4, 288;" ::: "memory");
            }
#pragma unroll 1
            for (int i = ht; i < 512; i += 96) {
                const int key = i & 127;
                uint8_t* p = g_QKV + (size_t)(j * 4 + (i >> 7)) * KV_HEAD_BYTES + (rb * 16 + (key >> 3)) * KV_GROUP_BYTES + 512 + (key & 7) * 16;
                *reinterpret_cast<uint32_t*>(p + 4) = ((POLY_MASK >> ((key >> 3) & 7)) & 1) ? 0x3F804000u : 0x00003F80u;
                *reinterpret_cast<uint32_t*>(p + 12) = 0x00003F80u;
            }
#pragma unroll 1
            for (int i = blockIdx.x * 324 + ht; i < blockIdx.x * 324 + 324; i += 96) {
                const int k = i / 72, nc = i - k * 72, ct = nc / 18;
                *reinterpret_cast<uint4*>(g_Wo + ct * WO_TILE_BYTES + (k >> 3) * 2304 + (nc - ct * 18) * 128 + (k & 7) * 16) =
                    __ldg(reinterpret_cast<const uint4*>(wo) + i);
            }
#pragma unroll 1
            for (int i = ht; i < 1152; i += 96) init_unit((rb * 36 + (i >> 7) * 4) * 256 + j * 128 + (i & 127), x, b2);
            named_bar_sync(3, 352);
#pragma unroll 1
            for (int i = warp - 9; i < 48; i += 3) {
                const int G = 3 * j + (i >> 4);
                if ((G >> 3) != 1) continue;
                const int head = (G & 7) * 4 + ((i >> 2) & 3), key = (i & 3) * 32 + lane;
                const uint8_t* p = g_QKV + (size_t)head * KV_HEAD_BYTES + (rb * 16 + (key >> 3)) * KV_GROUP_BYTES + (key & 7) * 16;
                const uint4 a = __ldcg(reinterpret_cast<const uint4*>(p)), b = __ldcg(reinterpret_cast<const uint4*>(p + 128));
                const uint32_t e = __ldcg(reinterpret_cast<const uint32_t*>(p + 512));
                float n = bf_lo(e) * bf_lo(e) + bf_hi(e) * bf_hi(e);
                n += bf_lo(a.x) * bf_lo(a.x) + bf_hi(a.x) * bf_hi(a.x) + bf_lo(a.y) * bf_lo(a.y) + bf_hi(a.y) * bf_hi(a.y);
                n += bf_lo(a.z) * bf_lo(a.z) + bf_hi(a.z) * bf_hi(a.z) + bf_lo(a.w) * bf_lo(a.w) + bf_hi(a.w) * bf_hi(a.w);
                n += bf_lo(b.x) * bf_lo(b.x) + bf_hi(b.x) * bf_hi(b.x) + bf_lo(b.y) * bf_lo(b.y) + bf_hi(b.y) * bf_hi(b.y);
                n += bf_lo(b.z) * bf_lo(b.z) + bf_hi(b.z) * bf_hi(b.z) + bf_lo(b.w) * bf_lo(b.w) + bf_hi(b.w) * bf_hi(b.w);
                if ((POLY_MASK >> ((key >> 3) & 7)) & 1) n *= 0.25f;
#pragma unroll
                for (int o = 16; o; o >>= 1) n = fmaxf(n, __shfl_xor_sync(~0u, n, o));
                if (lane == 0) g_kmax[head * 64 + rb * 4 + (i & 3)] = n;
            }
            named_bar_sync(7, 96);
            if (warp == 9) {
#pragma unroll 1
                for (int t = 0; t < 9; t++) {
                    if (lane == 0) {
                        if (t < 8) {
                            mbar_wait(sbar0 + t * 8, 0);
                            __threadfence();
                            atomicAdd(&g_flag[rb * 8 + t], 1u);
                        }
                        if (t > 0) {
                            const int tt = t - 1;
                            uint32_t v, spins = 0;
                            do {
                                asm volatile("ld.acquire.gpu.global.u32 %0, [%1];" : "=r"(v) : "l"(&g_flag[rb * 8 + tt]) : "memory");
                                if (v < 8 && ++spins > (1u << 22)) __trap();
                            } while (v < 8);
                            asm volatile("fence.proxy.async;" ::: "memory");
                            mbar_expect(rbar0 + tt * 8, 18432);
                            const uint32_t uo = (rb * 36 + tt * 4) * 256 + j * 128;
#pragma unroll 1
                            for (int jj = 0; jj < 8; jj++) bulk_load(sb + tt * 18432 + jj * 2048, g_part + jj * (16 * 36 * 256) + uo, 2048, rbar0 + tt * 8);
                            bulk_load(sb + tt * 18432 + 16384, g_base + uo, 2048, rbar0 + tt * 8);
                        }
                    }
                    __syncwarp();
                }
            } else {
#pragma unroll 1
                for (int i = warp - 10; i < 32; i += 2) {
                    const int t = i >> 2;
                    mbar_wait(rbar0 + t * 8, 0);
                    const uint4* sp = reinterpret_cast<const uint4*>(smem + t * 18432) + (i & 3) * 32 + lane;
                    float a[8];
#pragma unroll
                    for (int k = 0; k < 8; k++) a[k] = 0.f;
#pragma unroll 2
                    for (int jj = 0; jj < 8; jj++) add_unit(a, sp[jj * 128]);
                    finish_unit((rb * 36 + t * 4) * 256 + j * 128 + (i & 3) * 32 + lane, a, sp[1024]);
                }
            }
        }
        __syncwarp();
        cluster_arrive();
        cluster_wait();
    }
}

constexpr int K2_NCHUNK = 16;
constexpr int K2_AHEAD = 4;
constexpr int K2_CHUNK_BYTES = KV_HEAD_BYTES / K2_NCHUNK;
constexpr int K2_OFF_BAR = KV_HEAD_BYTES + 8 * KV_GROUP_BYTES;
constexpr int K2_OFF_Q = K2_OFF_BAR + 256;
constexpr int K2_SMEM = K2_OFF_Q + 12 * 512 * 4;

__device__ __forceinline__ float exp2_fixed(float y) {
    const float u = __uint_as_float(__float_as_uint(y) & 0xFF807FFFu) - 512.02545f;
    float t = fmaf(u, 0.019497588f, 0.114550486f);
    t = fmaf(t, u, -0.29839927f);
    return fmaf(t, u, y);
}
__device__ __forceinline__ uint32_t pack_fixed(float lo, float hi) { return __byte_perm(__float_as_uint(lo), __float_as_uint(hi), 0x6521); }

__device__ __forceinline__ void softmax_fast(const float (&s)[32], uint32_t (&p)[16]) {
#pragma unroll
    for (int b = 0; b < 8; b++) {
        if ((POLY_MASK >> b) & 1) {
            p[b * 2 + 0] = pack_fixed(exp2_fixed(s[b * 4 + 0]), exp2_fixed(s[b * 4 + 1]));
            p[b * 2 + 1] = pack_fixed(exp2_fixed(s[b * 4 + 2]), exp2_fixed(s[b * 4 + 3]));
        } else {
            p[b * 2 + 0] = pack_bf16(ex2(s[b * 4 + 0]), ex2(s[b * 4 + 1]));
            p[b * 2 + 1] = pack_bf16(ex2(s[b * 4 + 2]), ex2(s[b * 4 + 3]));
        }
    }
}

constexpr uint32_t K2_TILE = 8 * KV_GROUP_BYTES / 16;
__device__ __forceinline__ void issue_qk(float (&s)[32], const uint32_t (&qa)[8], uint32_t base) {
    wgmma_rs_n64<0>(s, qa[0], qa[1], qa[2], qa[3], base + (8u << 16), desc_hi(KV_GROUP_BYTES, 0), 0);
    wgmma_rs_n64<0>(s, qa[4], qa[5], qa[6], qa[7], base + 32, desc_hi(KV_GROUP_BYTES, 0), 1);
}
__device__ __forceinline__ void issue_pv(float (&o)[12], const uint32_t (&p)[16], uint32_t base) {
#pragma unroll
    for (int k = 0; k < 4; k++)
        wgmma_rs_n24<1>(o, p[k * 4], p[k * 4 + 1], p[k * 4 + 2], p[k * 4 + 3], base + 16 + ((KV_GROUP_BYTES / 16) << 16) + k * (2 * KV_GROUP_BYTES / 16),
                        desc_hi(128, 0), 1);
}

__global__ void __launch_bounds__(512, 1) k2_kernel() {
    extern __shared__ __align__(1024) uint8_t smem[];
    const uint32_t sb = s2u(smem);
    const int tid = threadIdx.x, lane = tid & 31;
    const int warp = __shfl_sync(~0u, tid >> 5, 0);
    const int wg = warp >> 2, wq = warp & 3, g = lane >> 2, q = lane & 3;
    const int head = blockIdx.x >> 2, quarter = blockIdx.x & 3;
    const uint32_t bar0 = sb + K2_OFF_BAR;
    PROF(16);
    if (tid == 0) {
        for (int i = 0; i <= K2_NCHUNK; i++) mbar_init(bar0 + i * 8, 1);
        asm volatile("mbarrier.arrive.shared::cta.b64 _, [%0];" ::"r"(bar0 + K2_NCHUNK * 8) : "memory");
        fence_barrier_init();
    }
    __syncthreads();
    griddep_wait();
    PROF(17);
    PROFT(50);
    uint32_t* qs = reinterpret_cast<uint32_t*>(smem + K2_OFF_Q) + tid;
    const uint8_t* kvsrc = g_QKV + (size_t)head * KV_HEAD_BYTES;
    int next_chunk = (tid == 0) ? K2_AHEAD : K2_NCHUNK;
    float kmax2;
    {
        uint32_t qv[12];
#pragma unroll
        for (int pass = 0; pass < 2; pass++) {
            const int row0 = quarter * 512 + (pass * 4 + wg) * 64 + wq * 16;
            const uint8_t* qp = g_QKV + Q_OFFSET + (size_t)head * KV_HEAD_BYTES + (row0 >> 3) * KV_GROUP_BYTES + g * 16 + q * 4;
            qv[pass * 6 + 0] = __ldcg(reinterpret_cast<const uint32_t*>(qp));
            qv[pass * 6 + 1] = __ldcg(reinterpret_cast<const uint32_t*>(qp + KV_GROUP_BYTES));
            qv[pass * 6 + 2] = __ldcg(reinterpret_cast<const uint32_t*>(qp + 128));
            qv[pass * 6 + 3] = __ldcg(reinterpret_cast<const uint32_t*>(qp + KV_GROUP_BYTES + 128));
            qv[pass * 6 + 4] = (q == 0) ? __ldcg(reinterpret_cast<const uint32_t*>(qp + 256)) : 0u;
            qv[pass * 6 + 5] = (q == 0) ? __ldcg(reinterpret_cast<const uint32_t*>(qp + KV_GROUP_BYTES + 256)) : 0u;
        }
        const float2 v = __ldcg(reinterpret_cast<const float2*>(g_kmax + head * 64 + lane * 2));
        if (lane == 0 && warp < K2_AHEAD) {
            mbar_expect(bar0 + warp * 8, K2_CHUNK_BYTES);
            bulk_load(sb + warp * K2_CHUNK_BYTES, kvsrc + warp * K2_CHUNK_BYTES, K2_CHUNK_BYTES, bar0 + warp * 8);
        }
        __syncwarp();
        if (lane < 8) {
            const int u = ((blockIdx.x >> 3) * 36 + 32) * 256 + (blockIdx.x & 7) * 128 + warp * 8 + lane;
            uint4 pv[8];
#pragma unroll
            for (int jj = 0; jj < 8; jj++) pv[jj] = __ldcg(g_part + jj * (16 * 36 * 256) + u);
            const uint4 bv = __ldcg(g_base + u);
            float a[8];
#pragma unroll
            for (int k = 0; k < 8; k++) a[k] = 0.f;
#pragma unroll
            for (int jj = 0; jj < 8; jj++) add_unit(a, pv[jj]);
            finish_unit(u, a, bv);
        }
        __syncwarp();
#pragma unroll
        for (int i = 0; i < 12; i++) qs[i * 512] = qv[i];
        kmax2 = fmaxf(v.x, v.y);
#pragma unroll
        for (int o = 16; o; o >>= 1) kmax2 = fmaxf(kmax2, __shfl_xor_sync(~0u, kmax2, o));
    }
    const uint32_t d0 = (sb & 0x3FFFF) >> 4;

#pragma unroll 1
    for (int pass = 0; pass < 2; pass++) {
        const int row0 = quarter * 512 + (pass * 4 + wg) * 64 + wq * 16;
        uint32_t qa[8];
#pragma unroll
        for (int i = 0; i < 6; i++) qa[i] = qs[(pass * 6 + i) * 512];
        qa[6] = 0u;
        float c0, c1;
        {
            float n0 = bf_lo(qa[0]) * bf_lo(qa[0]) + bf_hi(qa[0]) * bf_hi(qa[0]) + bf_lo(qa[2]) * bf_lo(qa[2]) + bf_hi(qa[2]) * bf_hi(qa[2]) +
                       bf_lo(qa[4]) * bf_lo(qa[4]) + bf_hi(qa[4]) * bf_hi(qa[4]);
            float n1 = bf_lo(qa[1]) * bf_lo(qa[1]) + bf_hi(qa[1]) * bf_hi(qa[1]) + bf_lo(qa[3]) * bf_lo(qa[3]) + bf_hi(qa[3]) * bf_hi(qa[3]) +
                       bf_lo(qa[5]) * bf_lo(qa[5]) + bf_hi(qa[5]) * bf_hi(qa[5]);
            n0 += __shfl_xor_sync(~0u, n0, 1); n1 += __shfl_xor_sync(~0u, n1, 1);
            n0 += __shfl_xor_sync(~0u, n0, 2); n1 += __shfl_xor_sync(~0u, n1, 2);
            c0 = sqrtf(n0 * kmax2) * 1.02f;
            c1 = sqrtf(n1 * kmax2) * 1.02f;
        }
        uint32_t slow;
        {
            const bool bad = !(c0 <= 58.f && c1 <= 58.f);
            asm volatile("{\n.reg .pred p, r;\nsetp.ne.u32 p, %1, 0;\nbarrier.cta.red.or.pred.aligned r, %2, 128, p;\nselp.u32 %0, 1, 0, r;\n}\n"
                         : "=r"(slow) : "r"((uint32_t)bad), "r"(wg + 1) : "memory");
        }
        slow = __any_sync(~0u, slow);
        float o[12];
#pragma unroll
        for (int i = 0; i < 12; i++) o[i] = 0.f;
        if (!slow && q == 1) {
            qa[4] = pack_bf16(-c0, 768.f); qa[5] = pack_bf16(-c1, 768.f);
            qa[6] = 0xC0000000u;
        }
        qa[7] = __shfl_sync(~0u, qa[6], lane);
        qa[6] = __shfl_sync(~0u, qa[6], lane ^ 4);

        if (!slow) {
            float s0[32], s1[32];
            uint32_t p[16];
            mbar_wait(bar0, 0);
            PROF(18 + pass * 3);
            reg_fence(qa);
            reg_fence(o);
            wg_fence();
            issue_qk(s0, qa, d0);
            wg_commit();
            uint32_t d = d0, bar = bar0;
#pragma unroll 1
            for (int t = 0; t < 16; t++) {
                wg_fence();
                issue_qk(s1, qa, d + K2_TILE);
                wg_commit();
                wg_wait<1>();
                reg_fence(s0);
                softmax_fast(s0, p);
                reg_fence(p);
                if (next_chunk < K2_NCHUNK) {
                    mbar_expect(bar0 + next_chunk * 8, K2_CHUNK_BYTES);
                    bulk_load(sb + next_chunk * K2_CHUNK_BYTES, kvsrc + next_chunk * K2_CHUNK_BYTES, K2_CHUNK_BYTES, bar0 + next_chunk * 8);
                    next_chunk++;
                }
                __syncwarp();
                bar += 8;
                mbar_wait(bar, 0);
                wg_fence();
                issue_pv(o, p, d);
                wg_commit();
                issue_qk(s0, qa, d + 2 * K2_TILE);
                wg_commit();
                wg_wait<1>();
                reg_fence(s1);
                softmax_fast(s1, p);
                reg_fence(p);
                wg_fence();
                issue_pv(o, p, d + K2_TILE);
                wg_commit();
                d += 2 * K2_TILE;
            }
            wg_wait<0>();
            reg_fence(o);
            reg_fence(s0);
        } else {
            float m0 = -INFINITY, m1 = -INFINITY;
            float s[32];
            uint32_t p[16];
            reg_fence(qa);
            for (; next_chunk < K2_NCHUNK; next_chunk++) {
                mbar_expect(bar0 + next_chunk * 8, K2_CHUNK_BYTES);
                bulk_load(sb + next_chunk * K2_CHUNK_BYTES, kvsrc + next_chunk * K2_CHUNK_BYTES, K2_CHUNK_BYTES, bar0 + next_chunk * 8);
            }
            __syncwarp();
#pragma unroll 1
            for (int t = 0; t < 32; t++) {
                mbar_wait(bar0 + (t / 2) * 8, 0);
                wg_fence();
                issue_qk(s, qa, d0 + t * K2_TILE);
                wg_commit();
                wg_wait<0>();
                reg_fence(s);
                reg_fence(o);
                float a0 = m0, a1 = m1;
#pragma unroll
                for (int k = 0; k < 8; k++) {
                    if ((POLY_MASK >> k) & 1) {
#pragma unroll
                        for (int i = 0; i < 4; i++) s[k * 4 + i] *= 0.5f;
                    }
                    a0 = fmaxf(a0, fmaxf(s[k * 4 + 0], s[k * 4 + 1]));
                    a1 = fmaxf(a1, fmaxf(s[k * 4 + 2], s[k * 4 + 3]));
                }
                a0 = fmaxf(a0, __shfl_xor_sync(~0u, a0, 1)); a1 = fmaxf(a1, __shfl_xor_sync(~0u, a1, 1));
                a0 = fmaxf(a0, __shfl_xor_sync(~0u, a0, 2)); a1 = fmaxf(a1, __shfl_xor_sync(~0u, a1, 2));
                const float r0 = ex2(m0 - a0), r1 = ex2(m1 - a1);
                m0 = a0; m1 = a1;
#pragma unroll
                for (int i = 0; i < 3; i++) { o[i * 4] *= r0; o[i * 4 + 1] *= r0; o[i * 4 + 2] *= r1; o[i * 4 + 3] *= r1; }
#pragma unroll
                for (int k = 0; k < 8; k++) {
                    p[k * 2 + 0] = pack_bf16(ex2(s[k * 4 + 0] - m0), ex2(s[k * 4 + 1] - m0));
                    p[k * 2 + 1] = pack_bf16(ex2(s[k * 4 + 2] - m1), ex2(s[k * 4 + 3] - m1));
                }
                reg_fence(p);
                reg_fence(o);
                wg_fence();
                issue_pv(o, p, d0 + t * K2_TILE);
                wg_commit();
                wg_wait<0>();
            }
            reg_fence(o);
        }
        PROF(19 + pass * 3);
        const float l0 = __shfl_sync(~0u, o[8], (lane & ~3) | 3), l1 = __shfl_sync(~0u, o[10], (lane & ~3) | 3);
        const float i0 = 1.0f / l0, i1 = 1.0f / l1;
#pragma unroll
        for (int i = 0; i < 3; i++) {
            const int pc = head * 9 + (i < 2 ? i * 4 + q : 8);
            uint32_t* op = g_O + ((((row0 >> 6) * 36 + (pc >> 3)) * 128 + wq * 32 + g * 4 + (pc & 3)) * 4 + ((pc >> 2) & 1) * 2);
            if (i < 2 || q == 2) *reinterpret_cast<uint2*>(op) = make_uint2(pack_bf16(o[i * 4] * i0, o[i * 4 + 1] * i0), pack_bf16(o[i * 4 + 2] * i1, o[i * 4 + 3] * i1));
        }
        PROF(20 + pass * 3);
        PROFT(51);
    }
}

constexpr int K3_PIECE = WO_TILE_BYTES / 9;
constexpr int K3_OFF_BAR = WO_TILE_BYTES;
constexpr int K3_SMEM = K3_OFF_BAR + 128;

__global__ void __cluster_dims__(2, 1, 1) __launch_bounds__(128, 1) k3_kernel(__nv_bfloat16* __restrict__ out) {
    extern __shared__ __align__(1024) uint8_t smem[];
    const uint32_t sb = s2u(smem);
    const int tid = threadIdx.x, warp = tid >> 5, lane = tid & 31;
    const int g = lane >> 2, q = lane & 3;
    const uint32_t rank = blockIdx.x & 1;
    const int ct = (blockIdx.x >> 1) & 3, rt = (blockIdx.x >> 3) * 2 + rank;
    const uint32_t bar0 = sb + K3_OFF_BAR;
    PROF(32);
    if (tid == 0) {
        for (int i = 0; i < 9; i++) { mbar_init(bar0 + i * 8, 1); mbar_expect(bar0 + i * 8, K3_PIECE); }
        fence_barrier_init();
    }
    cluster_arrive();
    cluster_wait();
    griddep_wait();
    PROF(33);
    PROFT(52);
    if (tid == 0) g_flag[blockIdx.x] = 0;
    uint4 a[36];
    const uint4* ap = reinterpret_cast<const uint4*>(g_O) + rt * 36 * 128 + tid;
#pragma unroll
    for (int k = 0; k < 4; k++) a[k] = __ldcg(ap + k * 128);
    if (tid < 9) {
        const uint32_t off = tid * K3_PIECE + rank * (K3_PIECE / 2);
        asm volatile("cp.async.bulk.shared::cluster.global.mbarrier::complete_tx::bytes.multicast::cluster [%0], [%1], %2, [%3], %4;"
                     ::"r"(sb + off), "l"(g_Wo + ct * WO_TILE_BYTES + off), "r"(K3_PIECE / 2), "r"(bar0 + tid * 8), "h"((uint16_t)3) : "memory");
    }
    float acc[72];
    {
        const uint4* bp = g_base + ((rt >> 1) * 36 + ct * 9) * 256 + (rt & 1) * 128 + tid;
        uint4 v[9];
#pragma unroll
        for (int i = 0; i < 9; i++) v[i] = __ldcg(bp + i * 256);
#pragma unroll
        for (int k = 4; k < 36; k++) a[k] = __ldcg(ap + k * 128);
#pragma unroll
        for (int i = 0; i < 9; i++) {
            acc[i * 8 + 0] = bf_lo(v[i].x); acc[i * 8 + 1] = bf_hi(v[i].x); acc[i * 8 + 2] = bf_lo(v[i].y); acc[i * 8 + 3] = bf_hi(v[i].y);
            acc[i * 8 + 4] = bf_lo(v[i].z); acc[i * 8 + 5] = bf_hi(v[i].z); acc[i * 8 + 6] = bf_lo(v[i].w); acc[i * 8 + 7] = bf_hi(v[i].w);
        }
    }
    PROF(34);
    const uint32_t db = desc_lo(sb, 2304);
#pragma unroll
    for (int kb = 0; kb < 9; kb++) {
        mbar_wait(bar0 + kb * 8, 0);
        wg_fence();
#pragma unroll
        for (int k = 0; k < 4; k++) {
            const uint4 f = a[kb * 4 + k];
            wgmma_rs_n144<1>(acc, f.x, f.y, f.z, f.w, db + (((kb * 4 + k) * 4608) >> 4), desc_hi(128, 0), 1);
        }
        wg_commit();
    }
    wg_wait<0>();
    reg_fence(acc);
    PROF(35);
    uint32_t* op = reinterpret_cast<uint32_t*>(out + (size_t)(rt * 64 + warp * 16 + g) * DM + ct * 144 + q * 2);
#pragma unroll
    for (int b = 0; b < 18; b++) {
        op[b * 4] = pack_bf16(acc[b * 4], acc[b * 4 + 1]);
        op[b * 4 + 4 * DM] = pack_bf16(acc[b * 4 + 2], acc[b * 4 + 3]);
    }
    cluster_arrive();
    cluster_wait();
    PROF(36);
    PROFT(53);
}

typedef CUresult (*EncodeFn)(CUtensorMap*, CUtensorMapDataType, cuuint32_t, void*, const cuuint64_t*, const cuuint64_t*, const cuuint32_t*,
                             const cuuint32_t*, CUtensorMapInterleave, CUtensorMapSwizzle, CUtensorMapL2promotion, CUtensorMapFloatOOBfill);

void make_map(EncodeFn fn, CUtensorMap* m, const void* base, int rank, const cuuint64_t* dims, const cuuint64_t* strides, const cuuint32_t* box) {
    cuuint32_t es[3] = {1, 1, 1};
    fn(m, CU_TENSOR_MAP_DATA_TYPE_BFLOAT16, rank, const_cast<void*>(base), dims, strides, box, es, CU_TENSOR_MAP_INTERLEAVE_NONE,
       CU_TENSOR_MAP_SWIZZLE_128B, CU_TENSOR_MAP_L2_PROMOTION_L2_256B, CU_TENSOR_MAP_FLOAT_OOB_FILL_NONE);
}

}

extern "C" void kernel_launch(void* const* d_in, const int* in_sizes, int n_in, void* d_out, int out_size) {
    const __nv_bfloat16* x = (const __nv_bfloat16*)d_in[0];
    const __nv_bfloat16* wqkv = (const __nv_bfloat16*)d_in[1];
    const __nv_bfloat16* wo = (const __nv_bfloat16*)d_in[2];
    const __nv_bfloat16* w1 = (const __nv_bfloat16*)d_in[4];
    const __nv_bfloat16* b1 = (const __nv_bfloat16*)d_in[5];
    const __nv_bfloat16* w2 = (const __nv_bfloat16*)d_in[6];
    const __nv_bfloat16* b2 = (const __nv_bfloat16*)d_in[7];
    __nv_bfloat16* out = (__nv_bfloat16*)d_out;

    EncodeFn fn = nullptr;
    cudaDriverEntryPointQueryResult qr;
    cudaGetDriverEntryPoint("cuTensorMapEncodeTiled", (void**)&fn, cudaEnableDefault, &qr);
    CUtensorMap tmX, tmQ3, tmQ1, tm1, tm2;
    {
        cuuint64_t d[3] = {64, SEQ, 9}, s[2] = {DM * 2, 128};
        cuuint32_t b[3] = {64, 8, 9};
        make_map(fn, &tmX, x, 3, d, s, b);
    }
    {
        cuuint64_t d[3] = {3 * DM, DM, 3}, s[2] = {3 * DM * 2, 128};
        cuuint32_t b[3] = {64, 16, 3};
        make_map(fn, &tmQ3, wqkv, 3, d, s, b);
        make_map(fn, &tmQ1, wqkv, 2, d, s, b);
    }
    {
        cuuint64_t d[2] = {FF, DM}, s[1] = {FF * 2};
        cuuint32_t b[2] = {64, 64};
        make_map(fn, &tm1, w1, 2, d, s, b);
        cuuint64_t d2[2] = {DM, FF}, s2[1] = {DM * 2};
        make_map(fn, &tm2, w2, 2, d2, s2, b);
    }
    cudaFuncSetAttribute(k1_kernel, cudaFuncAttributeMaxDynamicSharedMemorySize, K1_SMEM);
    cudaFuncSetAttribute(k2_kernel, cudaFuncAttributeMaxDynamicSharedMemorySize, K2_SMEM);
    cudaFuncSetAttribute(k3_kernel, cudaFuncAttributeMaxDynamicSharedMemorySize, K3_SMEM);

    cudaStream_t st = cudaStreamPerThread;
    cudaLaunchAttribute pdl[1];
    pdl[0].id = cudaLaunchAttributeProgrammaticStreamSerialization;
    pdl[0].val.programmaticStreamSerializationAllowed = 1;
    {
        cudaLaunchConfig_t cfg = {};
        cfg.gridDim = dim3(128); cfg.blockDim = dim3(384); cfg.dynamicSmemBytes = K1_SMEM; cfg.stream = st;
        cudaLaunchKernelEx(&cfg, k1_kernel, tmX, tmQ3, tmQ1, tm1, tm2, b1, wo, x, b2);
    }
    {
        cudaLaunchConfig_t cfg = {};
        cfg.gridDim = dim3(128); cfg.blockDim = dim3(512); cfg.dynamicSmemBytes = K2_SMEM; cfg.stream = st;
        cfg.attrs = pdl; cfg.numAttrs = 1;
        cudaLaunchKernelEx(&cfg, k2_kernel);
    }
    {
        cudaLaunchConfig_t cfg = {};
        cfg.gridDim = dim3(128); cfg.blockDim = dim3(128); cfg.dynamicSmemBytes = K3_SMEM; cfg.stream = st;
        cfg.attrs = pdl; cfg.numAttrs = 1;
        cudaLaunchKernelEx(&cfg, k3_kernel, out);
    }
}
```

```cpp
#include <cuda_runtime.h>
#include <cuda_bf16.h>
#include <cuda.h>
#include <stdint.h>

#define PROF(i) do { } while (0)
#define PROFT(i) do { } while (0)
#define PROFH(i) do { } while (0)
#define PROF_WG 0

namespace {

constexpr int SEQ = 2048, DM = 576, FF = 4608, NH = 32, DH = 18;

constexpr int KV_GROUP_BYTES = 5 * 128;
constexpr int KV_HEAD_BYTES = (SEQ / 8) * KV_GROUP_BYTES;
constexpr int Q_OFFSET = NH * KV_HEAD_BYTES;
#define POLY_MASK 0x92
__device__ __align__(1024) uint8_t g_QKV[2 * NH * KV_HEAD_BYTES];
__device__ __align__(1024) float g_kmax[NH * 64];
constexpr int SLAB = 16 * 36 * 256;
__device__ __align__(1024) uint4 g_part[9 * SLAB];
#define g_base (g_part + 8 * SLAB)
__device__ __align__(1024) uint32_t g_O[SEQ * DM / 2];
__device__ unsigned int g_flag[16 * 8];
constexpr int WO_TILE_BYTES = DM * 144 * 2;
__device__ __align__(1024) uint8_t g_Wo[4 * WO_TILE_BYTES];

__device__ __forceinline__ uint32_t s2u(const void* p) { return (uint32_t)__cvta_generic_to_shared(p); }
__device__ __forceinline__ void mbar_init(uint32_t b, int c) { asm volatile("mbarrier.init.shared::cta.b64 [%0], %1;" ::"r"(b), "r"(c) : "memory"); }
__device__ __forceinline__ void mbar_expect(uint32_t b, uint32_t bytes) {
    asm volatile("mbarrier.arrive.expect_tx.shared::cta.b64 _, [%0], %1;" ::"r"(b), "r"(bytes) : "memory");
}
__device__ __forceinline__ void mbar_wait(uint32_t b, uint32_t parity) {
    asm volatile(
        "{\n.reg .pred p;\n.reg .u32 c;\n"
        "mbarrier.try_wait.parity.shared::cta.b64 p, [%0], %1;\n"
        "@p bra DONE;\n"
        "mov.u32 c, 0;\n"
        "LOOP:\n"
        "mbarrier.try_wait.parity.shared::cta.b64 p, [%0], %1;\n"
        "@p bra DONE;\n"
        "add.u32 c, c, 1;\n"
        "setp.lt.u32 p, c, 4194304;\n"
        "@p bra LOOP;\n"
        "trap;\n"
        "DONE:\n}\n" ::"r"(b), "r"(parity) : "memory");
}
__device__ __forceinline__ void fence_barrier_init() { asm volatile("fence.mbarrier_init.release.cluster;" ::: "memory"); }
__device__ __forceinline__ void fence_proxy_async() { asm volatile("fence.proxy.async.shared::cta;" ::: "memory"); }
__device__ __forceinline__ void cluster_arrive() { asm volatile("barrier.cluster.arrive.relaxed.aligned;" ::: "memory"); }
__device__ __forceinline__ void cluster_wait() { asm volatile("barrier.cluster.wait.aligned;" ::: "memory"); }
__device__ __forceinline__ void named_bar_sync(int id, int n) { asm volatile("bar.sync %0, %1;" ::"r"(id), "r"(n) : "memory"); }
__device__ __forceinline__ void griddep_wait() { asm volatile("griddepcontrol.wait;" ::: "memory"); }
__device__ __forceinline__ void griddep_launch() { asm volatile("griddepcontrol.launch_dependents;" ::: "memory"); }

__device__ __forceinline__ void tma3d_mc(uint32_t dst, const CUtensorMap* tm, int c0, int c1, int c2, uint32_t bar, uint16_t mask) {
    asm volatile("cp.async.bulk.tensor.3d.shared::cluster.global.mbarrier::complete_tx::bytes.multicast::cluster [%0], [%1, {%3, %4, %5}], [%2], %6;"
                 ::"r"(dst), "l"(tm), "r"(bar), "r"(c0), "r"(c1), "r"(c2), "h"(mask) : "memory");
}
__device__ __forceinline__ void tma2d_mc(uint32_t dst, const CUtensorMap* tm, int c0, int c1, uint32_t bar, uint16_t mask) {
    asm volatile("cp.async.bulk.tensor.2d.shared::cluster.global.mbarrier::complete_tx::bytes.multicast::cluster [%0], [%1, {%3, %4}], [%2], %5;"
                 ::"r"(dst), "l"(tm), "r"(bar), "r"(c0), "r"(c1), "h"(mask) : "memory");
}
__device__ __forceinline__ void tma3d(uint32_t dst, const CUtensorMap* tm, int c0, int c1, int c2, uint32_t bar) {
    asm volatile("cp.async.bulk.tensor.3d.shared::cluster.global.mbarrier::complete_tx::bytes [%0], [%1, {%3, %4, %5}], [%2];"
                 ::"r"(dst), "l"(tm), "r"(bar), "r"(c0), "r"(c1), "r"(c2) : "memory");
}
__device__ __forceinline__ void tma2d(uint32_t dst, const CUtensorMap* tm, int c0, int c1, uint32_t bar) {
    asm volatile("cp.async.bulk.tensor.2d.shared::cluster.global.mbarrier::complete_tx::bytes [%0], [%1, {%3, %4}], [%2];"
                 ::"r"(dst), "l"(tm), "r"(bar), "r"(c0), "r"(c1) : "memory");
}
__device__ __forceinline__ void bulk_load(uint32_t dst, const void* src, uint32_t bytes, uint32_t bar) {
    asm volatile("cp.async.bulk.shared::cluster.global.mbarrier::complete_tx::bytes [%0], [%1], %2, [%3];"
                 ::"r"(dst), "l"(src), "r"(bytes), "r"(bar) : "memory");
}
__device__ __forceinline__ void prefetch_tmap(const CUtensorMap* tm) { asm volatile("prefetch.tensormap [%0];" ::"l"(tm) : "memory"); }

__device__ __forceinline__ void wg_fence() { asm volatile("wgmma.fence.sync.aligned;" ::: "memory"); }
__device__ __forceinline__ void wg_commit() { asm volatile("wgmma.commit_group.sync.aligned;" ::: "memory"); }
template <int N> __device__ __forceinline__ void wg_wait() { asm volatile("wgmma.wait_group.sync.aligned %0;" ::"n"(N) : "memory"); }
template <int N> __device__ __forceinline__ void reg_fence(float (&d)[N]) {
#pragma unroll
    for (int i = 0; i < N; i++) asm volatile("" : "+f"(d[i])::"memory");
}
template <int N> __device__ __forceinline__ void reg_fence(uint32_t (&d)[N]) {
#pragma unroll
    for (int i = 0; i < N; i++) asm volatile("" : "+r"(d[i])::"memory");
}
template <int R> __device__ __forceinline__ void reg_alloc() { asm volatile("setmaxnreg.inc.sync.aligned.u32 %0;" ::"n"(R)); }
template <int R> __device__ __forceinline__ void reg_dealloc() { asm volatile("setmaxnreg.dec.sync.aligned.u32 %0;" ::"n"(R)); }

__device__ __forceinline__ uint32_t desc_lo(uint32_t addr, uint32_t lbo) { return ((addr & 0x3FFFF) >> 4) | ((lbo >> 4) << 16); }
__host__ __device__ constexpr uint32_t desc_hi(uint32_t sbo, uint32_t swz) { return (sbo >> 4) | (swz << 30); }
__device__ __forceinline__ uint32_t pack_bf16(float lo, float hi) {
    uint32_t r;
    asm("cvt.rn.bf16x2.f32 %0, %1, %2;" : "=r"(r) : "f"(hi), "f"(lo));
    return r;
}
__device__ __forceinline__ float bf_lo(uint32_t w) { return __uint_as_float(w << 16); }
__device__ __forceinline__ float bf_hi(uint32_t w) { return __uint_as_float(w & 0xFFFF0000u); }
__device__ __forceinline__ float ex2(float x) {
    float r;
    asm("ex2.approx.ftz.f32 %0, %1;" : "=f"(r) : "f"(x));
    return r;
}
__device__ __forceinline__ float tanh_fast(float x) {
    float r;
    asm("tanh.approx.f32 %0, %1;" : "=f"(r) : "f"(x));
    return r;
}
__device__ __forceinline__ float gelu2(float u) {
    const float w = fmaf(u * u, 0.0356774081f, 0.7978845608f);
    return fmaf(u, tanh_fast(u * w), u);
}

template<int TB> __device__ __forceinline__ void wgmma_ss_n216(float (&d)[108], uint32_t alo, uint32_t ahi, uint32_t blo, uint32_t bhi, int sd) {
    asm volatile("{\n.reg .pred p;\n.reg .b64 da, db;\nsetp.ne.b32 p, %110, 0;\nmov.b64 da, {%108, %112};\nmov.b64 db, {%109, %113};\n"
      "wgmma.mma_async.sync.aligned.m64n216k16.f32.bf16.bf16 {%0, %1, %2, %3, %4, %5, %6, %7, %8, %9, %10, %11, %12, %13, %14, %15, %16, %17, %18, %19, %20, %21, %22, %23, %24, %25, %26, %27, %28, %29, %30, %31, %32, %33, %34, %35, %36, %37, %38, %39, %40, %41, %42, %43, %44, %45, %46, %47, %48, %49, %50, %51, %52, %53, %54, %55, %56, %57, %58, %59, %60, %61, %62, %63, %64, %65, %66, %67, %68, %69, %70, %71, %72, %73, %74, %75, %76, %77, %78, %79, %80, %81, %82, %83, %84, %85, %86, %87, %88, %89, %90, %91, %92, %93, %94, %95, %96, %97, %98, %99, %100, %101, %102, %103, %104, %105, %106, %107}, da, db, p, 1, 1, 0, %111;\n}\n"
      : "+f"(d[0]), "+f"(d[1]), "+f"(d[2]), "+f"(d[3]), "+f"(d[4]), "+f"(d[5]), "+f"(d[6]), "+f"(d[7]), "+f"(d[8]), "+f"(d[9]), "+f"(d[10]), "+f"(d[11]), "+f"(d[12]), "+f"(d[13]), "+f"(d[14]), "+f"(d[15]), "+f"(d[16]), "+f"(d[17]), "+f"(d[18]), "+f"(d[19]), "+f"(d[20]), "+f"(d[21]), "+f"(d[22]), "+f"(d[23]), "+f"(d[24]), "+f"(d[25]), "+f"(d[26]), "+f"(d[27]), "+f"(d[28]), "+f"(d[29]), "+f"(d[30]), "+f"(d[31]), "+f"(d[32]), "+f"(d[33]), "+f"(d[34]), "+f"(d[35]), "+f"(d[36]), "+f"(d[37]), "+f"(d[38]), "+f"(d[39]), "+f"(d[40]), "+f"(d[41]), "+f"(d[42]), "+f"(d[43]), "+f"(d[44]), "+f"(d[45]), "+f"(d[46]), "+f"(d[47]), "+f"(d[48]), "+f"(d[49]), "+f"(d[50]), "+f"(d[51]), "+f"(d[52]), "+f"(d[53]), "+f"(d[54]), "+f"(d[55]), "+f"(d[56]), "+f"(d[57]), "+f"(d[58]), "+f"(d[59]), "+f"(d[60]), "+f"(d[61]), "+f"(d[62]), "+f"(d[63]), "+f"(d[64]), "+f"(d[65]), "+f"(d[66]), "+f"(d[67]), "+f"(d[68]), "+f"(d[69]), "+f"(d[70]), "+f"(d[71]), "+f"(d[72]), "+f"(d[73]), "+f"(d[74]), "+f"(d[75]), "+f"(d[76]), "+f"(d[77]), "+f"(d[78]), "+f"(d[79]), "+f"(d[80]), "+f"(d[81]), "+f"(d[82]), "+f"(d[83]), "+f"(d[84]), "+f"(d[85]), "+f"(d[86]), "+f"(d[87]), "+f"(d[88]), "+f"(d[89]), "+f"(d[90]), "+f"(d[91]), "+f"(d[92]), "+f"(d[93]), "+f"(d[94]), "+f"(d[95]), "+f"(d[96]), "+f"(d[97]), "+f"(d[98]), "+f"(d[99]), "+f"(d[100]), "+f"(d[101]), "+f"(d[102]), "+f"(d[103]), "+f"(d[104]), "+f"(d[105]), "+f"(d[106]), "+f"(d[107])
      : "r"(alo), "r"(blo), "r"(sd), "n"(TB), "r"(ahi), "r"(bhi));
}

template<int TB> __device__ __forceinline__ void wgmma_ss_n64(float (&d)[32], uint32_t alo, uint32_t ahi, uint32_t blo, uint32_t bhi, int sd) {
    asm volatile("{\n.reg .pred p;\n.reg .b64 da, db;\nsetp.ne.b32 p, %34, 0;\nmov.b64 da, {%32, %36};\nmov.b64 db, {%33, %37};\n"
      "wgmma.mma_async.sync.aligned.m64n64k16.f32.bf16.bf16 {%0, %1, %2, %3, %4, %5, %6, %7, %8, %9, %10, %11, %12, %13, %14, %15, %16, %17, %18, %19, %20, %21, %22, %23, %24, %25, %26, %27, %28, %29, %30, %31}, da, db, p, 1, 1, 0, %35;\n}\n"
      : "+f"(d[0]), "+f"(d[1]), "+f"(d[2]), "+f"(d[3]), "+f"(d[4]), "+f"(d[5]), "+f"(d[6]), "+f"(d[7]), "+f"(d[8]), "+f"(d[9]), "+f"(d[10]), "+f"(d[11]), "+f"(d[12]), "+f"(d[13]), "+f"(d[14]), "+f"(d[15]), "+f"(d[16]), "+f"(d[17]), "+f"(d[18]), "+f"(d[19]), "+f"(d[20]), "+f"(d[21]), "+f"(d[22]), "+f"(d[23]), "+f"(d[24]), "+f"(d[25]), "+f"(d[26]), "+f"(d[27]), "+f"(d[28]), "+f"(d[29]), "+f"(d[30]), "+f"(d[31])
      : "r"(alo), "r"(blo), "r"(sd), "n"(TB), "r"(ahi), "r"(bhi));
}

template<int TB> __device__ __forceinline__ void wgmma_rs_n64(float (&d)[32], uint32_t a0, uint32_t a1, uint32_t a2, uint32_t a3, uint32_t blo, uint32_t bhi, int sd) {
    asm volatile("{\n.reg .pred p;\n.reg .b64 db;\nsetp.ne.b32 p, %37, 0;\nmov.b64 db, {%36, %39};\n"
      "wgmma.mma_async.sync.aligned.m64n64k16.f32.bf16.bf16 {%0, %1, %2, %3, %4, %5, %6, %7, %8, %9, %10, %11, %12, %13, %14, %15, %16, %17, %18, %19, %20, %21, %22, %23, %24, %25, %26, %27, %28, %29, %30, %31}, {%32, %33, %34, %35}, db, p, 1, 1, %38;\n}\n"
      : "+f"(d[0]), "+f"(d[1]), "+f"(d[2]), "+f"(d[3]), "+f"(d[4]), "+f"(d[5]), "+f"(d[6]), "+f"(d[7]), "+f"(d[8]), "+f"(d[9]), "+f"(d[10]), "+f"(d[11]), "+f"(d[12]), "+f"(d[13]), "+f"(d[14]), "+f"(d[15]), "+f"(d[16]), "+f"(d[17]), "+f"(d[18]), "+f"(d[19]), "+f"(d[20]), "+f"(d[21]), "+f"(d[22]), "+f"(d[23]), "+f"(d[24]), "+f"(d[25]), "+f"(d[26]), "+f"(d[27]), "+f"(d[28]), "+f"(d[29]), "+f"(d[30]), "+f"(d[31])
      : "r"(a0), "r"(a1), "r"(a2), "r"(a3), "r"(blo), "r"(sd), "n"(TB), "r"(bhi));
}

template<int TB> __device__ __forceinline__ void wgmma_rs_n24(float (&d)[12], uint32_t a0, uint32_t a1, uint32_t a2, uint32_t a3, uint32_t blo, uint32_t bhi, int sd) {
    asm volatile("{\n.reg .pred p;\n.reg .b64 db;\nsetp.ne.b32 p, %17, 0;\nmov.b64 db, {%16, %19};\n"
      "wgmma.mma_async.sync.aligned.m64n24k16.f32.bf16.bf16 {%0, %1, %2, %3, %4, %5, %6, %7, %8, %9, %10, %11}, {%12, %13, %14, %15}, db, p, 1, 1, %18;\n}\n"
      : "+f"(d[0]), "+f"(d[1]), "+f"(d[2]), "+f"(d[3]), "+f"(d[4]), "+f"(d[5]), "+f"(d[6]), "+f"(d[7]), "+f"(d[8]), "+f"(d[9]), "+f"(d[10]), "+f"(d[11])
      : "r"(a0), "r"(a1), "r"(a2), "r"(a3), "r"(blo), "r"(sd), "n"(TB), "r"(bhi));
}

template<int TB> __device__ __forceinline__ void wgmma_rs_n144(float (&d)[72], uint32_t a0, uint32_t a1, uint32_t a2, uint32_t a3, uint32_t blo, uint32_t bhi, int sd) {
    asm volatile("{\n.reg .pred p;\n.reg .b64 db;\nsetp.ne.b32 p, %77, 0;\nmov.b64 db, {%76, %79};\n"
      "wgmma.mma_async.sync.aligned.m64n144k16.f32.bf16.bf16 {%0, %1, %2, %3, %4, %5, %6, %7, %8, %9, %10, %11, %12, %13, %14, %15, %16, %17, %18, %19, %20, %21, %22, %23, %24, %25, %26, %27, %28, %29, %30, %31, %32, %33, %34, %35, %36, %37, %38, %39, %40, %41, %42, %43, %44, %45, %46, %47, %48, %49, %50, %51, %52, %53, %54, %55, %56, %57, %58, %59, %60, %61, %62, %63, %64, %65, %66, %67, %68, %69, %70, %71}, {%72, %73, %74, %75}, db, p, 1, 1, %78;\n}\n"
      : "+f"(d[0]), "+f"(d[1]), "+f"(d[2]), "+f"(d[3]), "+f"(d[4]), "+f"(d[5]), "+f"(d[6]), "+f"(d[7]), "+f"(d[8]), "+f"(d[9]), "+f"(d[10]), "+f"(d[11]), "+f"(d[12]), "+f"(d[13]), "+f"(d[14]), "+f"(d[15]), "+f"(d[16]), "+f"(d[17]), "+f"(d[18]), "+f"(d[19]), "+f"(d[20]), "+f"(d[21]), "+f"(d[22]), "+f"(d[23]), "+f"(d[24]), "+f"(d[25]), "+f"(d[26]), "+f"(d[27]), "+f"(d[28]), "+f"(d[29]), "+f"(d[30]), "+f"(d[31]), "+f"(d[32]), "+f"(d[33]), "+f"(d[34]), "+f"(d[35]), "+f"(d[36]), "+f"(d[37]), "+f"(d[38]), "+f"(d[39]), "+f"(d[40]), "+f"(d[41]), "+f"(d[42]), "+f"(d[43]), "+f"(d[44]), "+f"(d[45]), "+f"(d[46]), "+f"(d[47]), "+f"(d[48]), "+f"(d[49]), "+f"(d[50]), "+f"(d[51]), "+f"(d[52]), "+f"(d[53]), "+f"(d[54]), "+f"(d[55]), "+f"(d[56]), "+f"(d[57]), "+f"(d[58]), "+f"(d[59]), "+f"(d[60]), "+f"(d[61]), "+f"(d[62]), "+f"(d[63]), "+f"(d[64]), "+f"(d[65]), "+f"(d[66]), "+f"(d[67]), "+f"(d[68]), "+f"(d[69]), "+f"(d[70]), "+f"(d[71])
      : "r"(a0), "r"(a1), "r"(a2), "r"(a3), "r"(blo), "r"(sd), "n"(TB), "r"(bhi));
}

__device__ __forceinline__ void init_unit(int u, const __nv_bfloat16* __restrict__ x, const __nv_bfloat16* __restrict__ b2) {
    const int t = u & 255, pbr = u >> 8, rb = pbr / 36, pb = pbr - rb * 36;
    const int row = rb * 128 + (t >> 5) * 16 + ((t & 31) >> 2), col = pb * 16 + (t & 3) * 2;
    const uint32_t* xp = reinterpret_cast<const uint32_t*>(x + (size_t)row * DM + col);
    const uint32_t x0 = __ldg(xp), x1 = __ldg(xp + 4 * DM), x2 = __ldg(xp + 4), x3 = __ldg(xp + 4 * DM + 4);
    const uint32_t ba = __ldg(reinterpret_cast<const uint32_t*>(b2 + col)), bb = __ldg(reinterpret_cast<const uint32_t*>(b2 + col + 8));
    uint4 o;
    o.x = pack_bf16(bf_lo(x0) + bf_lo(ba), bf_hi(x0) + bf_hi(ba));
    o.y = pack_bf16(bf_lo(x1) + bf_lo(ba), bf_hi(x1) + bf_hi(ba));
    o.z = pack_bf16(bf_lo(x2) + bf_lo(bb), bf_hi(x2) + bf_hi(bb));
    o.w = pack_bf16(bf_lo(x3) + bf_lo(bb), bf_hi(x3) + bf_hi(bb));
    g_base[u] = o;
}
__device__ __forceinline__ void finish_unit(int u, const float (&a)[8], const uint4 v) {
    uint4 o;
    o.x = pack_bf16(fmaf(a[0], 0.5f, bf_lo(v.x)), fmaf(a[1], 0.5f, bf_hi(v.x)));
    o.y = pack_bf16(fmaf(a[2], 0.5f, bf_lo(v.y)), fmaf(a[3], 0.5f, bf_hi(v.y)));
    o.z = pack_bf16(fmaf(a[4], 0.5f, bf_lo(v.z)), fmaf(a[5], 0.5f, bf_hi(v.z)));
    o.w = pack_bf16(fmaf(a[6], 0.5f, bf_lo(v.w)), fmaf(a[7], 0.5f, bf_hi(v.w)));
    g_base[u] = o;
}
__device__ __forceinline__ void add_unit(float (&a)[8], const uint4 v) {
    a[0] += bf_lo(v.x); a[1] += bf_hi(v.x); a[2] += bf_lo(v.y); a[3] += bf_hi(v.y);
    a[4] += bf_lo(v.z); a[5] += bf_hi(v.z); a[6] += bf_lo(v.w); a[7] += bf_hi(v.w);
}

constexpr int K1_XN_BYTES = 16 * 9216;
constexpr int K1_SLOT = 16384, K1_NSLOT = 5;
constexpr int K1_OFF_RING = K1_XN_BYTES;
constexpr int K1_OFF_BIAS = K1_OFF_RING + K1_NSLOT * K1_SLOT;
constexpr int K1_OFF_BAR = K1_OFF_BIAS + 576 * 2;
constexpr int K1_SMEM = K1_OFF_BAR + 256 + 128;
constexpr float QSCALE = 0.23570226039551584f * 1.4426950408889634f;

struct Ring {
    uint32_t slot, phase;
    __device__ __forceinline__ void advance() {
        if (++slot == K1_NSLOT) { slot = 0; phase ^= 1; }
    }
};

struct K1Ctx {
    uint32_t full0;
    uint32_t rel_addr;
    uint32_t descA, descB;
    Ring rd;
    uint32_t prev_slot;
    __device__ __forceinline__ uint32_t begin_stage() {
        mbar_wait(full0 + rd.slot * 8, rd.phase);
        wg_fence();
        return descB + rd.slot * (K1_SLOT >> 4);
    }
    __device__ __forceinline__ void end_stage() {
        wg_commit();
        wg_wait<1>();
        if (rel_addr) asm volatile("mbarrier.arrive.shared::cluster.b64 _, [%0];" ::"r"(rel_addr + prev_slot * 8) : "memory");
        prev_slot = rd.slot;
        rd.advance();
    }
};

__device__ __forceinline__ uint32_t descA_step(uint32_t base, int ks) { return base + (((ks >> 2) * 1024 + (ks & 3) * 32) >> 4); }
constexpr uint32_t K1_AHI = desc_hi(9216, 1), K1_BHI = desc_hi(1024, 1);

template <int V> struct IC { static constexpr int value = V; };
template <int I, int N, class F> __device__ __forceinline__ void static_for(F&& f) {
    if constexpr (I < N) { f(IC<I>{}); static_for<I + 1, N>(f); }
}

template <bool A_RS, bool B_RS, class Epi>
__device__ __forceinline__ void tile_pair(K1Ctx& c, float (&accA)[32], float (&accB)[32], uint32_t (&h)[144], Epi&& epi) {
    static_for<0, 9>([&](auto sc) {
        constexpr int s = decltype(sc)::value;
        const uint32_t db = c.begin_stage();
#pragma unroll
        for (int t = 0; t < 8; t++) {
            const int kk = s * 8 + t, ks = kk % 36;
            const uint32_t dbt = db + ((t * 2048) >> 4);
            if (kk < 36) {
                if constexpr (A_RS) wgmma_rs_n64<1>(accA, h[ks * 4], h[ks * 4 + 1], h[ks * 4 + 2], h[ks * 4 + 3], dbt, K1_BHI, ks != 0);
                else wgmma_ss_n64<1>(accA, descA_step(c.descA, ks), K1_AHI, dbt, K1_BHI, ks != 0);
            } else {
                if constexpr (B_RS) wgmma_rs_n64<1>(accB, h[ks * 4], h[ks * 4 + 1], h[ks * 4 + 2], h[ks * 4 + 3], dbt, K1_BHI, ks != 0);
                else wgmma_ss_n64<1>(accB, descA_step(c.descA, ks), K1_AHI, dbt, K1_BHI, ks != 0);
            }
        }
        c.end_stage();
        epi(sc);
    });
}

template <int B0, int NB, int HOFF>
__device__ __forceinline__ void gelu_blocks(const float (&acc)[32], uint32_t (&h)[144], const uint32_t (&bq)[8]) {
#pragma unroll
    for (int b = B0; b < B0 + NB; b++) {
        const float b0 = bf_lo(bq[b]), b1 = bf_hi(bq[b]);
        h[HOFF + b * 2 + 0] = pack_bf16(gelu2(acc[b * 4 + 0] + b0), gelu2(acc[b * 4 + 1] + b1));
        h[HOFF + b * 2 + 1] = pack_bf16(gelu2(acc[b * 4 + 2] + b0), gelu2(acc[b * 4 + 3] + b1));
    }
}
__device__ __forceinline__ void load_bias(uint32_t (&bq)[8], uint32_t addr) {
    asm volatile("ld.shared.v4.u32 {%0, %1, %2, %3}, [%4];" : "=r"(bq[0]), "=r"(bq[1]), "=r"(bq[2]), "=r"(bq[3]) : "r"(addr));
    asm volatile("ld.shared.v4.u32 {%0, %1, %2, %3}, [%4 + 16];" : "=r"(bq[4]), "=r"(bq[5]), "=r"(bq[6]), "=r"(bq[7]) : "r"(addr));
}
template <int S> __device__ __forceinline__ void store_part(const float (&o)[32], uint4* p) {
    uint4 v;
    v.x = pack_bf16(o[S * 8 + 0], o[S * 8 + 1]); v.y = pack_bf16(o[S * 8 + 2], o[S * 8 + 3]);
    v.z = pack_bf16(o[S * 8 + 4], o[S * 8 + 5]); v.w = pack_bf16(o[S * 8 + 6], o[S * 8 + 7]);
    p[S * 256] = v;
}

__global__ void __cluster_dims__(2, 1, 1) __launch_bounds__(384, 1)
k1_kernel(const __grid_constant__ CUtensorMap tmX, const __grid_constant__ CUtensorMap tmQ3, const __grid_constant__ CUtensorMap tmQ1,
          const __grid_constant__ CUtensorMap tm1, const __grid_constant__ CUtensorMap tm2, const __grid_constant__ CUtensorMap tmP,
          const __nv_bfloat16* __restrict__ b1,
          const __nv_bfloat16* __restrict__ wo, const __nv_bfloat16* __restrict__ x, const __nv_bfloat16* __restrict__ b2) {
    extern __shared__ __align__(1024) uint8_t smem[];
    const uint32_t sb = s2u(smem);
    const int tid = threadIdx.x, lane = tid & 31;
    const int warp = __shfl_sync(~0u, tid >> 5, 0);
    const uint32_t rank = blockIdx.x & 1;
    const int cl = blockIdx.x >> 1;
    const int rb = (cl & 7) * 2 + rank;
    const int j = cl >> 3;
    const uint32_t full0 = sb + K1_OFF_BAR, empty0 = full0 + 8 * K1_NSLOT, xbar0 = full0 + 128, rbar0 = full0 + 256, sbar0 = full0 + 320;

    if (warp < 8) {
        PROF(0);
        PROFT(48);
        if (lane == 0) {
            mbar_init(xbar0 + warp * 16, 1);
            mbar_init(xbar0 + warp * 16 + 8, 1);
            fence_barrier_init();
            mbar_expect(xbar0 + warp * 16, 9216);
            tma3d(sb + warp * 2 * 9216, &tmX, 0, rb * 128 + warp * 16, 0, xbar0 + warp * 16);
            mbar_expect(xbar0 + warp * 16 + 8, 9216);
            tma3d(sb + (warp * 2 + 1) * 9216, &tmX, 0, rb * 128 + warp * 16 + 8, 0, xbar0 + warp * 16 + 8);
        }
        __syncwarp();
        cluster_arrive();
        reg_alloc<240>();
#pragma unroll 1
        for (int p = 0; p < 4; p++) {
            mbar_wait(xbar0 + warp * 16 + (p >> 1) * 8, 0);
            uint4* row = reinterpret_cast<uint4*>(smem + (warp * 2 + (p >> 1)) * 9216 + (p & 1) * 512 + lane * 16);
            float f[72];
#pragma unroll
            for (int i = 0; i < 9; i++) {
                const uint4 v = row[i * 64];
                f[i * 8 + 0] = bf_lo(v.x); f[i * 8 + 1] = bf_hi(v.x); f[i * 8 + 2] = bf_lo(v.y); f[i * 8 + 3] = bf_hi(v.y);
                f[i * 8 + 4] = bf_lo(v.z); f[i * 8 + 5] = bf_hi(v.z); f[i * 8 + 6] = bf_lo(v.w); f[i * 8 + 7] = bf_hi(v.w);
            }
            float s0 = 0.f, s1 = 0.f, s2 = 0.f, s3 = 0.f;
#pragma unroll
            for (int i = 0; i < 72; i += 4) { s0 += f[i]; s1 += f[i + 1]; s2 += f[i + 2]; s3 += f[i + 3]; }
            float sm = (s0 + s1) + (s2 + s3);
            sm += __shfl_xor_sync(~0u, sm, 1); sm += __shfl_xor_sync(~0u, sm, 2); sm += __shfl_xor_sync(~0u, sm, 4);
            const float mean = sm * (1.0f / DM);
            s0 = s1 = s2 = s3 = 0.f;
#pragma unroll
            for (int i = 0; i < 72; i += 4) {
                f[i] -= mean; f[i + 1] -= mean; f[i + 2] -= mean; f[i + 3] -= mean;
                s0 = fmaf(f[i], f[i], s0); s1 = fmaf(f[i + 1], f[i + 1], s1);
                s2 = fmaf(f[i + 2], f[i + 2], s2); s3 = fmaf(f[i + 3], f[i + 3], s3);
            }
            float sq = (s0 + s1) + (s2 + s3);
            sq += __shfl_xor_sync(~0u, sq, 1); sq += __shfl_xor_sync(~0u, sq, 2); sq += __shfl_xor_sync(~0u, sq, 4);
            const float rstd = rsqrtf(sq * (1.0f / DM) + 1e-5f);
#pragma unroll
            for (int i = 0; i < 9; i++) {
                uint4 o;
                o.x = pack_bf16(f[i * 8 + 0] * rstd, f[i * 8 + 1] * rstd);
                o.y = pack_bf16(f[i * 8 + 2] * rstd, f[i * 8 + 3] * rstd);
                o.z = pack_bf16(f[i * 8 + 4] * rstd, f[i * 8 + 5] * rstd);
                o.w = pack_bf16(f[i * 8 + 6] * rstd, f[i * 8 + 7] * rstd);
                row[i * 64] = o;
            }
        }
        const int wg = warp >> 2, wq = warp & 3;
        fence_proxy_async();
        named_bar_sync(1 + wg, 128);
        cluster_wait();
        PROF(1);

        const int g = lane >> 2, q = lane & 3;
        K1Ctx c;
        c.full0 = full0;
        c.rel_addr = 0;
        c.descA = desc_lo(sb + wg * 8 * 9216, 16);
        c.descB = desc_lo(sb + K1_OFF_RING, 2048);
        c.rd.slot = 0; c.rd.phase = 0; c.prev_slot = 0;
        uint32_t biasq = sb + K1_OFF_BIAS + q * 32;
        uint32_t bq[8];

        uint32_t h[144];
        float accA[32], accB[32];
        {
            float accQ[108];
            uint32_t rel = 0;
            if (lane == 0 && wq < 2) asm("mapa.shared::cluster.u32 %0, %1, %2;" : "=r"(rel) : "r"(empty0), "r"(wq));
#pragma unroll 1
            for (int s = 0; s < 18; s++) {
                const uint32_t db = c.begin_stage();
                const uint32_t da = c.descA + (s >> 1) * 64 + (s & 1) * 4;
                wgmma_ss_n216<1>(accQ, da, K1_AHI, db, K1_BHI, s != 0);
                wgmma_ss_n216<1>(accQ, da + 2, K1_AHI, db + (8192 >> 4), K1_BHI, 1);
                c.end_stage();
                c.rel_addr = rel;
            }
            PROF(2);
            uint32_t rel9[9];
#pragma unroll
            for (int i9 = 0; i9 < 9; i9++) {
                const int p = 4 * i9 + q, hh = (p * 57) >> 9, r = p - 9 * hh;
                rel9[i9] = hh * KV_HEAD_BYTES + (r < 8 ? (r >> 2) * 128 + (r & 3) * 4 : 0);
            }
            uint32_t gb = 0, o2 = 0;
            float scl0 = 1.f, scl1 = 1.f;
            tile_pair<false, false>(c, accA, accB, h, [&](auto sc) {
                constexpr int s = decltype(sc)::value;
                if constexpr (s == 0) reg_fence(accQ);
                if constexpr (s < 6) {
                    constexpr int grp = s / 2, part = s % 2;
                    if constexpr (part == 0) {
                        const int G = 3 * j + grp, type = G >> 3;
                        gb = (G & 7) * 4 * KV_HEAD_BYTES + (rb * 16 + warp * 2) * KV_GROUP_BYTES + g * 16 + (type == 0 ? Q_OFFSET : (type == 2 ? 256 : 0));
                        o2 = type == 0 ? 256 : (type == 2 ? 264 : 512);
                        scl0 = type == 0 ? QSCALE : ((type == 1 && ((POLY_MASK >> (wq * 2)) & 1)) ? 2.f : 1.f);
                        scl1 = type == 0 ? QSCALE : ((type == 1 && ((POLY_MASK >> (wq * 2 + 1)) & 1)) ? 2.f : 1.f);
                    }
#pragma unroll
                    for (int i9 = part * 5; i9 < (part ? 9 : 5); i9++) {
                        const int b = grp * 9 + i9;
                        uint32_t off = gb + rel9[i9];
                        if (i9 >= 2 && (i9 & 1) == 0) off += (q == i9 / 2 - 1) ? o2 : 0;
                        *reinterpret_cast<uint32_t*>(g_QKV + off) = pack_bf16(accQ[b * 4] * scl0, accQ[b * 4 + 1] * scl0);
                        *reinterpret_cast<uint32_t*>(g_QKV + off + KV_GROUP_BYTES) = pack_bf16(accQ[b * 4 + 2] * scl1, accQ[b * 4 + 3] * scl1);
                    }
                    if constexpr (s == 5) asm volatile("bar.arrive 3, 352;" ::: "memory");
                }
                if constexpr (s == 4) { named_bar_sync(4, 352); load_bias(bq, biasq); }
                if constexpr (s == 5) reg_fence(accA);
                if constexpr (s >= 5) gelu_blocks<(s - 5) * 2, 2, 96>(accA, h, bq);
                if constexpr (s == 8) load_bias(bq, biasq + 128);
            });
        }
        PROF(3);
#pragma unroll
        for (int i = 32; i < 96; i++) asm volatile("mov.u32 %0, 0;" : "=r"(h[i]));
#pragma unroll 1
        for (int p = 1; p < 4; p++) {
            biasq += 256;
            tile_pair<false, false>(c, accA, accB, h, [&](auto sc) {
                constexpr int s = decltype(sc)::value;
                if constexpr (s == 0) {
                    reg_fence(accB);
#pragma unroll
                    for (int i = 0; i < 80; i++) h[i] = h[i + 32];
                }
                if constexpr (s < 4) gelu_blocks<s * 2, 2, 80>(accB, h, bq);
                if constexpr (s == 4) load_bias(bq, biasq);
                if constexpr (s == 5) reg_fence(accA);
                if constexpr (s >= 5) gelu_blocks<(s - 5) * 2, 2, 96>(accA, h, bq);
                if constexpr (s == 8) load_bias(bq, biasq + 128);
            });
        }
        PROF(4);
        tile_pair<false, true>(c, accA, accB, h, [&](auto sc) {
            constexpr int s = decltype(sc)::value;
            if constexpr (s == 0) reg_fence(accB);
            if constexpr (s < 4) gelu_blocks<s * 2, 2, 112>(accB, h, bq);
            if constexpr (s == 4) load_bias(bq, biasq + 256);
            if constexpr (s == 5) reg_fence(accA);
            if constexpr (s == 5 || s == 6) gelu_blocks<(s - 5) * 3, 3, 128>(accA, h, bq);
            if constexpr (s == 7) gelu_blocks<6, 2, 128>(accA, h, bq);
            if constexpr (s == 3 || s == 7) reg_fence(h);
        });
        PROF(5);
        uint4* pout = g_part + ((size_t)(j * 16 + rb) * 36) * 256 + tid;
#pragma unroll 1
        for (int p = 0; p < 4; p++) {
            tile_pair<true, true>(c, accA, accB, h, [&](auto sc) {
                constexpr int s = decltype(sc)::value;
                if constexpr (s == 0) reg_fence(accB);
                if constexpr (s < 4) store_part<s>(accB, pout);
                if constexpr (s == 3) { __syncwarp(); if (lane == 0) asm volatile("mbarrier.arrive.shared::cta.b64 _, [%0];" ::"r"(sbar0 + p * 16) : "memory"); }
                if constexpr (s == 5) reg_fence(accA);
                if constexpr (s >= 5) store_part<s - 5>(accA, pout + 1024);
                if constexpr (s == 8) { __syncwarp(); if (lane == 0) asm volatile("mbarrier.arrive.shared::cta.b64 _, [%0];" ::"r"(sbar0 + p * 16 + 8) : "memory"); }
            });
            pout += 2048;
            PROF(6 + p);
        }
        wg_wait<0>();
        reg_fence(accB);
        store_part<0>(accB, pout); store_part<1>(accB, pout); store_part<2>(accB, pout); store_part<3>(accB, pout);
        PROF(10);
        cluster_arrive();
        cluster_wait();
        PROF(11);
        PROFT(49);
    } else {
        reg_dealloc<24>();
        if (warp == 8 && lane == 0) {
            prefetch_tmap(&tmQ3); prefetch_tmap(&tmQ1); prefetch_tmap(&tm1); prefetch_tmap(&tm2);
            for (int i = 0; i < K1_NSLOT; i++) { mbar_init(full0 + i * 8, 1); mbar_init(empty0 + i * 8, 4); }
            for (int i = 0; i < 8; i++) { mbar_init(rbar0 + i * 8, 1); mbar_init(sbar0 + i * 8, 8); }
            fence_barrier_init();
        }
        __syncwarp();
        cluster_arrive();
        cluster_wait();
        if (warp == 8) {
            if (lane == 0) {
                Ring w{0, 1};
                const uint32_t dst0 = sb + K1_OFF_RING + rank * 8192;
#pragma unroll 1
                for (int s = 0; s < 18; s++) {
                    mbar_wait(empty0 + w.slot * 8, w.phase);
                    mbar_expect(full0 + w.slot * 8, 16384);
                    const uint32_t dst = dst0 + w.slot * K1_SLOT;
                    tma3d_mc(dst, &tmQ3, j * 216, s * 32 + rank * 16, 0, full0 + w.slot * 8, 3);
                    tma2d_mc(dst + 6144, &tmQ1, j * 216 + 192, s * 32 + rank * 16, full0 + w.slot * 8, 3);
                    w.advance();
                }
                int tile = 0, kb = rank;
#pragma unroll 1
                for (int s = 0; s < 81; s++) {
                    mbar_wait(empty0 + w.slot * 8, w.phase);
                    mbar_expect(full0 + w.slot * 8, 16384);
                    const uint32_t dst = dst0 + w.slot * K1_SLOT;
                    if (tile < 9) tma2d_mc(dst, &tm1, j * 576 + tile * 64, kb * 64, full0 + w.slot * 8, 3);
                    else tma2d_mc(dst, &tm2, (tile - 9) * 64, j * 576 + kb * 64, full0 + w.slot * 8, 3);
                    kb += 2;
                    if (kb >= 9) { kb -= 9; tile++; }
                    w.advance();
                }
            }
        } else {
            const int ht = tid - 288;
            if (ht < 72) {
                const uint4 v = __ldg(reinterpret_cast<const uint4*>(b1 + j * 576) + ht);
                uint32_t* sbias = reinterpret_cast<uint32_t*>(smem + K1_OFF_BIAS) + (ht >> 3) * 32 + (ht & 7);
                sbias[0] = v.x; sbias[8] = v.y; sbias[16] = v.z; sbias[24] = v.w;
            }
            asm volatile("bar.arrive 4, 352;" ::: "memory");
#pragma unroll 1
            for (int i = ht; i < 512; i += 96) {
                const int key = i & 127;
                uint8_t* p = g_QKV + (size_t)(j * 4 + (i >> 7)) * KV_HEAD_BYTES + (rb * 16 + (key >> 3)) * KV_GROUP_BYTES + 512 + (key & 7) * 16;
                *reinterpret_cast<uint32_t*>(p + 4) = ((POLY_MASK >> ((key >> 3) & 7)) & 1) ? 0x3F804000u : 0x00003F80u;
                *reinterpret_cast<uint32_t*>(p + 12) = 0x00003F80u;
            }
#pragma unroll 2
            for (int i = blockIdx.x * 324 + ht; i < blockIdx.x * 324 + 324; i += 96) {
                const int k = i / 72, nc = i - k * 72, ct = nc / 18;
                *reinterpret_cast<uint4*>(g_Wo + ct * WO_TILE_BYTES + (k >> 3) * 2304 + (nc - ct * 18) * 128 + (k & 7) * 16) =
                    __ldg(reinterpret_cast<const uint4*>(wo) + i);
            }
            PROFH(37);
#pragma unroll 2
            for (int i = ht; i < 1152; i += 96) init_unit((rb * 36 + (i >> 7) * 4) * 256 + j * 128 + (i & 127), x, b2);
            PROFH(38);
            named_bar_sync(3, 352);
#pragma unroll 1
            for (int i = warp - 9; i < 48; i += 3) {
                const int G = 3 * j + (i >> 4);
                if ((G >> 3) != 1) continue;
                const int head = (G & 7) * 4 + ((i >> 2) & 3), key = (i & 3) * 32 + lane;
                const uint8_t* p = g_QKV + (size_t)head * KV_HEAD_BYTES + (rb * 16 + (key >> 3)) * KV_GROUP_BYTES + (key & 7) * 16;
                const uint4 a = __ldcg(reinterpret_cast<const uint4*>(p)), b = __ldcg(reinterpret_cast<const uint4*>(p + 128));
                const uint32_t e = __ldcg(reinterpret_cast<const uint32_t*>(p + 512));
                float n = bf_lo(e) * bf_lo(e) + bf_hi(e) * bf_hi(e);
                n += bf_lo(a.x) * bf_lo(a.x) + bf_hi(a.x) * bf_hi(a.x) + bf_lo(a.y) * bf_lo(a.y) + bf_hi(a.y) * bf_hi(a.y);
                n += bf_lo(a.z) * bf_lo(a.z) + bf_hi(a.z) * bf_hi(a.z) + bf_lo(a.w) * bf_lo(a.w) + bf_hi(a.w) * bf_hi(a.w);
                n += bf_lo(b.x) * bf_lo(b.x) + bf_hi(b.x) * bf_hi(b.x) + bf_lo(b.y) * bf_lo(b.y) + bf_hi(b.y) * bf_hi(b.y);
                n += bf_lo(b.z) * bf_lo(b.z) + bf_hi(b.z) * bf_hi(b.z) + bf_lo(b.w) * bf_lo(b.w) + bf_hi(b.w) * bf_hi(b.w);
                if ((POLY_MASK >> ((key >> 3) & 7)) & 1) n *= 0.25f;
#pragma unroll
                for (int o = 16; o; o >>= 1) n = fmaxf(n, __shfl_xor_sync(~0u, n, o));
                if (lane == 0) g_kmax[head * 64 + rb * 4 + (i & 3)] = n;
            }
            named_bar_sync(7, 96);
            PROFH(39);
            if (warp == 9) {
                if (lane == 0) {
#pragma unroll 1
                    for (int t = 0; t < 8; t++) {
                        mbar_wait(sbar0 + t * 8, 0);
                        __threadfence();
                        atomicAdd(&g_flag[rb * 8 + t], 1u);
                        PROFH(40 + t);
                    }
                }
            } else {
#pragma unroll 1
                for (int t = 0; t < 9; t++) {
                    if (warp == 10 && lane == 0 && t < 8) {
                        uint32_t v, spins = 0;
                        do {
                            asm volatile("ld.acquire.gpu.global.u32 %0, [%1];" : "=r"(v) : "l"(&g_flag[rb * 8 + t]) : "memory");
                            if (v < 8 && ++spins > (1u << 22)) __trap();
                        } while (v < 8);
                        asm volatile("fence.proxy.async;" ::: "memory");
                        mbar_expect(rbar0 + t * 8, 18432);
                        tma2d(sb + t * 18432, &tmP, ((rb * 36 + t * 4) * 256 + j * 128) * 2, 0, rbar0 + t * 8);
                    }
                    __syncwarp();
                    const int tt = t - (warp == 10 ? 1 : 0);
                    if (tt < 0 || tt > 7) continue;
                    mbar_wait(rbar0 + tt * 8, 0);
#pragma unroll 1
                    for (int i = warp - 10; i < 4; i += 2) {
                        const uint4* sp = reinterpret_cast<const uint4*>(smem + tt * 18432) + i * 32 + lane;
                        float a[8];
#pragma unroll
                        for (int k = 0; k < 8; k++) a[k] = 0.f;
#pragma unroll 2
                        for (int jj = 0; jj < 8; jj++) add_unit(a, sp[jj * 128]);
                        finish_unit((rb * 36 + tt * 4) * 256 + j * 128 + i * 32 + lane, a, sp[1024]);
                    }
                }
            }
        }
        __syncwarp();
        cluster_arrive();
        cluster_wait();
    }
}

constexpr int K2_NCHUNK = 16;
constexpr int K2_AHEAD = 4;
constexpr int K2_CHUNK_BYTES = KV_HEAD_BYTES / K2_NCHUNK;
constexpr int K2_OFF_BAR = KV_HEAD_BYTES + 8 * KV_GROUP_BYTES;
constexpr int K2_OFF_Q = K2_OFF_BAR + 256;
constexpr int K2_SMEM = K2_OFF_Q + 12 * 512 * 4;

__device__ __forceinline__ float exp2_fixed(float y) {
    const float u = __uint_as_float(__float_as_uint(y) & 0xFF807FFFu) - 512.02545f;
    float t = fmaf(u, 0.019497588f, 0.114550486f);
    t = fmaf(t, u, -0.29839927f);
    return fmaf(t, u, y);
}
__device__ __forceinline__ uint32_t pack_fixed(float lo, float hi) { return __byte_perm(__float_as_uint(lo), __float_as_uint(hi), 0x6521); }

__device__ __forceinline__ void softmax_fast(const float (&s)[32], uint32_t (&p)[16]) {
#pragma unroll
    for (int b = 0; b < 8; b++) {
        if ((POLY_MASK >> b) & 1) {
            p[b * 2 + 0] = pack_fixed(exp2_fixed(s[b * 4 + 0]), exp2_fixed(s[b * 4 + 1]));
            p[b * 2 + 1] = pack_fixed(exp2_fixed(s[b * 4 + 2]), exp2_fixed(s[b * 4 + 3]));
        } else {
            p[b * 2 + 0] = pack_bf16(ex2(s[b * 4 + 0]), ex2(s[b * 4 + 1]));
            p[b * 2 + 1] = pack_bf16(ex2(s[b * 4 + 2]), ex2(s[b * 4 + 3]));
        }
    }
}

constexpr uint32_t K2_TILE = 8 * KV_GROUP_BYTES / 16;
__device__ __forceinline__ void issue_qk(float (&s)[32], const uint32_t (&qa)[8], uint32_t base) {
    wgmma_rs_n64<0>(s, qa[0], qa[1], qa[2], qa[3], base + (8u << 16), desc_hi(KV_GROUP_BYTES, 0), 0);
    wgmma_rs_n64<0>(s, qa[4], qa[5], qa[6], qa[7], base + 32, desc_hi(KV_GROUP_BYTES, 0), 1);
}
__device__ __forceinline__ void issue_pv(float (&o)[12], const uint32_t (&p)[16], uint32_t base) {
#pragma unroll
    for (int k = 0; k < 4; k++)
        wgmma_rs_n24<1>(o, p[k * 4], p[k * 4 + 1], p[k * 4 + 2], p[k * 4 + 3], base + 16 + ((KV_GROUP_BYTES / 16) << 16) + k * (2 * KV_GROUP_BYTES / 16),
                        desc_hi(128, 0), 1);
}

__global__ void __launch_bounds__(512, 1) k2_kernel() {
    extern __shared__ __align__(1024) uint8_t smem[];
    const uint32_t sb = s2u(smem);
    const int tid = threadIdx.x, lane = tid & 31;
    const int warp = __shfl_sync(~0u, tid >> 5, 0);
    const int wg = warp >> 2, wq = warp & 3, g = lane >> 2, q = lane & 3;
    const int head = blockIdx.x >> 2, quarter = blockIdx.x & 3;
    const uint32_t bar0 = sb + K2_OFF_BAR;
    PROF(16);
    if (tid == 0) {
        for (int i = 0; i <= K2_NCHUNK; i++) mbar_init(bar0 + i * 8, 1);
        asm volatile("mbarrier.arrive.shared::cta.b64 _, [%0];" ::"r"(bar0 + K2_NCHUNK * 8) : "memory");
        fence_barrier_init();
    }
    __syncthreads();
    griddep_wait();
    PROF(17);
    PROFT(50);
    uint32_t* qs = reinterpret_cast<uint32_t*>(smem + K2_OFF_Q) + tid;
    const uint8_t* kvsrc = g_QKV + (size_t)head * KV_HEAD_BYTES;
    int next_chunk = (tid == 0) ? K2_AHEAD : K2_NCHUNK;
    float kmax2;
    {
        uint32_t qv[12];
#pragma unroll
        for (int pass = 0; pass < 2; pass++) {
            const int row0 = quarter * 512 + (pass * 4 + wg) * 64 + wq * 16;
            const uint8_t* qp = g_QKV + Q_OFFSET + (size_t)head * KV_HEAD_BYTES + (row0 >> 3) * KV_GROUP_BYTES + g * 16 + q * 4;
            qv[pass * 6 + 0] = __ldcg(reinterpret_cast<const uint32_t*>(qp));
            qv[pass * 6 + 1] = __ldcg(reinterpret_cast<const uint32_t*>(qp + KV_GROUP_BYTES));
            qv[pass * 6 + 2] = __ldcg(reinterpret_cast<const uint32_t*>(qp + 128));
            qv[pass * 6 + 3] = __ldcg(reinterpret_cast<const uint32_t*>(qp + KV_GROUP_BYTES + 128));
            qv[pass * 6 + 4] = (q == 0) ? __ldcg(reinterpret_cast<const uint32_t*>(qp + 256)) : 0u;
            qv[pass * 6 + 5] = (q == 0) ? __ldcg(reinterpret_cast<const uint32_t*>(qp + KV_GROUP_BYTES + 256)) : 0u;
        }
        const float2 v = __ldcg(reinterpret_cast<const float2*>(g_kmax + head * 64 + lane * 2));
        if (lane == 0 && warp < K2_AHEAD) {
            mbar_expect(bar0 + warp * 8, K2_CHUNK_BYTES);
            bulk_load(sb + warp * K2_CHUNK_BYTES, kvsrc + warp * K2_CHUNK_BYTES, K2_CHUNK_BYTES, bar0 + warp * 8);
        }
        __syncwarp();
        if (lane < 8) {
            const int u = ((blockIdx.x >> 3) * 36 + 32) * 256 + (blockIdx.x & 7) * 128 + warp * 8 + lane;
            uint4 pv[8];
#pragma unroll
            for (int jj = 0; jj < 8; jj++) pv[jj] = __ldcg(g_part + jj * SLAB + u);
            const uint4 bv = __ldcg(g_base + u);
            float a[8];
#pragma unroll
            for (int k = 0; k < 8; k++) a[k] = 0.f;
#pragma unroll
            for (int jj = 0; jj < 8; jj++) add_unit(a, pv[jj]);
            finish_unit(u, a, bv);
        }
        __syncwarp();
#pragma unroll
        for (int i = 0; i < 12; i++) qs[i * 512] = qv[i];
        kmax2 = fmaxf(v.x, v.y);
#pragma unroll
        for (int o = 16; o; o >>= 1) kmax2 = fmaxf(kmax2, __shfl_xor_sync(~0u, kmax2, o));
    }
    const uint32_t d0 = (sb & 0x3FFFF) >> 4;

#pragma unroll 1
    for (int pass = 0; pass < 2; pass++) {
        const int row0 = quarter * 512 + (pass * 4 + wg) * 64 + wq * 16;
        uint32_t qa[8];
#pragma unroll
        for (int i = 0; i < 6; i++) qa[i] = qs[(pass * 6 + i) * 512];
        qa[6] = 0u;
        float c0, c1;
        {
            float n0 = bf_lo(qa[0]) * bf_lo(qa[0]) + bf_hi(qa[0]) * bf_hi(qa[0]) + bf_lo(qa[2]) * bf_lo(qa[2]) + bf_hi(qa[2]) * bf_hi(qa[2]) +
                       bf_lo(qa[4]) * bf_lo(qa[4]) + bf_hi(qa[4]) * bf_hi(qa[4]);
            float n1 = bf_lo(qa[1]) * bf_lo(qa[1]) + bf_hi(qa[1]) * bf_hi(qa[1]) + bf_lo(qa[3]) * bf_lo(qa[3]) + bf_hi(qa[3]) * bf_hi(qa[3]) +
                       bf_lo(qa[5]) * bf_lo(qa[5]) + bf_hi(qa[5]) * bf_hi(qa[5]);
            n0 += __shfl_xor_sync(~0u, n0, 1); n1 += __shfl_xor_sync(~0u, n1, 1);
            n0 += __shfl_xor_sync(~0u, n0, 2); n1 += __shfl_xor_sync(~0u, n1, 2);
            c0 = sqrtf(n0 * kmax2) * 1.02f;
            c1 = sqrtf(n1 * kmax2) * 1.02f;
        }
        uint32_t slow;
        {
            const bool bad = !(c0 <= 58.f && c1 <= 58.f);
            asm volatile("{\n.reg .pred p, r;\nsetp.ne.u32 p, %1, 0;\nbarrier.cta.red.or.pred.aligned r, %2, 128, p;\nselp.u32 %0, 1, 0, r;\n}\n"
                         : "=r"(slow) : "r"((uint32_t)bad), "r"(wg + 1) : "memory");
        }
        slow = __any_sync(~0u, slow);
        float o[12];
#pragma unroll
        for (int i = 0; i < 12; i++) o[i] = 0.f;
        if (!slow && q == 1) {
            qa[4] = pack_bf16(-c0, 768.f); qa[5] = pack_bf16(-c1, 768.f);
            qa[6] = 0xC0000000u;
        }
        qa[7] = __shfl_sync(~0u, qa[6], lane);
        qa[6] = __shfl_sync(~0u, qa[6], lane ^ 4);

        if (!slow) {
            float s0[32], s1[32];
            uint32_t p[16];
            mbar_wait(bar0, 0);
            PROF(18 + pass * 3);
            reg_fence(qa);
            reg_fence(o);
            wg_fence();
            issue_qk(s0, qa, d0);
            wg_commit();
            uint32_t d = d0, bar = bar0;
#pragma unroll 1
            for (int t = 0; t < 16; t++) {
                wg_fence();
                issue_qk(s1, qa, d + K2_TILE);
                wg_commit();
                wg_wait<1>();
                reg_fence(s0);
                softmax_fast(s0, p);
                reg_fence(p);
                if (next_chunk < K2_NCHUNK) {
                    mbar_expect(bar0 + next_chunk * 8, K2_CHUNK_BYTES);
                    bulk_load(sb + next_chunk * K2_CHUNK_BYTES, kvsrc + next_chunk * K2_CHUNK_BYTES, K2_CHUNK_BYTES, bar0 + next_chunk * 8);
                    next_chunk++;
                }
                __syncwarp();
                bar += 8;
                mbar_wait(bar, 0);
                wg_fence();
                issue_pv(o, p, d);
                wg_commit();
                issue_qk(s0, qa, d + 2 * K2_TILE);
                wg_commit();
                wg_wait<1>();
                reg_fence(s1);
                softmax_fast(s1, p);
                reg_fence(p);
                wg_fence();
                issue_pv(o, p, d + K2_TILE);
                wg_commit();
                d += 2 * K2_TILE;
            }
            wg_wait<0>();
            reg_fence(o);
            reg_fence(s0);
        } else {
            float m0 = -INFINITY, m1 = -INFINITY;
            float s[32];
            uint32_t p[16];
            reg_fence(qa);
            for (; next_chunk < K2_NCHUNK; next_chunk++) {
                mbar_expect(bar0 + next_chunk * 8, K2_CHUNK_BYTES);
                bulk_load(sb + next_chunk * K2_CHUNK_BYTES, kvsrc + next_chunk * K2_CHUNK_BYTES, K2_CHUNK_BYTES, bar0 + next_chunk * 8);
            }
            __syncwarp();
#pragma unroll 1
            for (int t = 0; t < 32; t++) {
                mbar_wait(bar0 + (t / 2) * 8, 0);
                wg_fence();
                issue_qk(s, qa, d0 + t * K2_TILE);
                wg_commit();
                wg_wait<0>();
                reg_fence(s);
                reg_fence(o);
                float a0 = m0, a1 = m1;
#pragma unroll
                for (int k = 0; k < 8; k++) {
                    if ((POLY_MASK >> k) & 1) {
#pragma unroll
                        for (int i = 0; i < 4; i++) s[k * 4 + i] *= 0.5f;
                    }
                    a0 = fmaxf(a0, fmaxf(s[k * 4 + 0], s[k * 4 + 1]));
                    a1 = fmaxf(a1, fmaxf(s[k * 4 + 2], s[k * 4 + 3]));
                }
                a0 = fmaxf(a0, __shfl_xor_sync(~0u, a0, 1)); a1 = fmaxf(a1, __shfl_xor_sync(~0u, a1, 1));
                a0 = fmaxf(a0, __shfl_xor_sync(~0u, a0, 2)); a1 = fmaxf(a1, __shfl_xor_sync(~0u, a1, 2));
                const float r0 = ex2(m0 - a0), r1 = ex2(m1 - a1);
                m0 = a0; m1 = a1;
#pragma unroll
                for (int i = 0; i < 3; i++) { o[i * 4] *= r0; o[i * 4 + 1] *= r0; o[i * 4 + 2] *= r1; o[i * 4 + 3] *= r1; }
#pragma unroll
                for (int k = 0; k < 8; k++) {
                    p[k * 2 + 0] = pack_bf16(ex2(s[k * 4 + 0] - m0), ex2(s[k * 4 + 1] - m0));
                    p[k * 2 + 1] = pack_bf16(ex2(s[k * 4 + 2] - m1), ex2(s[k * 4 + 3] - m1));
                }
                reg_fence(p);
                reg_fence(o);
                wg_fence();
                issue_pv(o, p, d0 + t * K2_TILE);
                wg_commit();
                wg_wait<0>();
            }
            reg_fence(o);
        }
        PROF(19 + pass * 3);
        const float l0 = __shfl_sync(~0u, o[8], (lane & ~3) | 3), l1 = __shfl_sync(~0u, o[10], (lane & ~3) | 3);
        const float i0 = 1.0f / l0, i1 = 1.0f / l1;
#pragma unroll
        for (int i = 0; i < 3; i++) {
            const int pc = head * 9 + (i < 2 ? i * 4 + q : 8);
            uint32_t* op = g_O + ((((row0 >> 6) * 36 + (pc >> 3)) * 128 + wq * 32 + g * 4 + (pc & 3)) * 4 + ((pc >> 2) & 1) * 2);
            if (i < 2 || q == 2) *reinterpret_cast<uint2*>(op) = make_uint2(pack_bf16(o[i * 4] * i0, o[i * 4 + 1] * i0), pack_bf16(o[i * 4 + 2] * i1, o[i * 4 + 3] * i1));
        }
        PROF(20 + pass * 3);
        PROFT(51);
    }
}

constexpr int K3_PIECE = WO_TILE_BYTES / 9;
constexpr int K3_OFF_BAR = WO_TILE_BYTES;
constexpr int K3_SMEM = K3_OFF_BAR + 128;

__global__ void __cluster_dims__(2, 1, 1) __launch_bounds__(128, 1) k3_kernel(__nv_bfloat16* __restrict__ out) {
    extern __shared__ __align__(1024) uint8_t smem[];
    const uint32_t sb = s2u(smem);
    const int tid = threadIdx.x, warp = tid >> 5, lane = tid & 31;
    const int g = lane >> 2, q = lane & 3;
    const uint32_t rank = blockIdx.x & 1;
    const int ct = (blockIdx.x >> 1) & 3, rt = (blockIdx.x >> 3) * 2 + rank;
    const uint32_t bar0 = sb + K3_OFF_BAR;
    PROF(32);
    if (tid == 0) {
        for (int i = 0; i < 9; i++) { mbar_init(bar0 + i * 8, 1); mbar_expect(bar0 + i * 8, K3_PIECE); }
        fence_barrier_init();
    }
    cluster_arrive();
    cluster_wait();
    griddep_wait();
    PROF(33);
    PROFT(52);
    if (tid == 0) g_flag[blockIdx.x] = 0;
    uint4 a[36];
    const uint4* ap = reinterpret_cast<const uint4*>(g_O) + rt * 36 * 128 + tid;
#pragma unroll
    for (int k = 0; k < 4; k++) a[k] = __ldcg(ap + k * 128);
    if (tid < 9) {
        const uint32_t off = tid * K3_PIECE + rank * (K3_PIECE / 2);
        asm volatile("cp.async.bulk.shared::cluster.global.mbarrier::complete_tx::bytes.multicast::cluster [%0], [%1], %2, [%3], %4;"
                     ::"r"(sb + off), "l"(g_Wo + ct * WO_TILE_BYTES + off), "r"(K3_PIECE / 2), "r"(bar0 + tid * 8), "h"((uint16_t)3) : "memory");
    }
    float acc[72];
    {
        const uint4* bp = g_base + ((rt >> 1) * 36 + ct * 9) * 256 + (rt & 1) * 128 + tid;
        uint4 v[9];
#pragma unroll
        for (int i = 0; i < 9; i++) v[i] = __ldcg(bp + i * 256);
#pragma unroll
        for (int k = 4; k < 36; k++) a[k] = __ldcg(ap + k * 128);
#pragma unroll
        for (int i = 0; i < 9; i++) {
            acc[i * 8 + 0] = bf_lo(v[i].x); acc[i * 8 + 1] = bf_hi(v[i].x); acc[i * 8 + 2] = bf_lo(v[i].y); acc[i * 8 + 3] = bf_hi(v[i].y);
            acc[i * 8 + 4] = bf_lo(v[i].z); acc[i * 8 + 5] = bf_hi(v[i].z); acc[i * 8 + 6] = bf_lo(v[i].w); acc[i * 8 + 7] = bf_hi(v[i].w);
        }
    }
    PROF(34);
    const uint32_t db = desc_lo(sb, 2304);
#pragma unroll
    for (int kb = 0; kb < 9; kb++) {
        mbar_wait(bar0 + kb * 8, 0);
        wg_fence();
#pragma unroll
        for (int k = 0; k < 4; k++) {
            const uint4 f = a[kb * 4 + k];
            wgmma_rs_n144<1>(acc, f.x, f.y, f.z, f.w, db + (((kb * 4 + k) * 4608) >> 4), desc_hi(128, 0), 1);
        }
        wg_commit();
    }
    wg_wait<0>();
    reg_fence(acc);
    PROF(35);
    uint32_t* op = reinterpret_cast<uint32_t*>(out + (size_t)(rt * 64 + warp * 16 + g) * DM + ct * 144 + q * 2);
#pragma unroll
    for (int b = 0; b < 18; b++) {
        op[b * 4] = pack_bf16(acc[b * 4], acc[b * 4 + 1]);
        op[b * 4 + 4 * DM] = pack_bf16(acc[b * 4 + 2], acc[b * 4 + 3]);
    }
    cluster_arrive();
    cluster_wait();
    PROF(36);
    PROFT(53);
}

typedef CUresult (*EncodeFn)(CUtensorMap*, CUtensorMapDataType, cuuint32_t, void*, const cuuint64_t*, const cuuint64_t*, const cuuint32_t*,
                             const cuuint32_t*, CUtensorMapInterleave, CUtensorMapSwizzle, CUtensorMapL2promotion, CUtensorMapFloatOOBfill);

void make_map(EncodeFn fn, CUtensorMap* m, const void* base, int rank, const cuuint64_t* dims, const cuuint64_t* strides, const cuuint32_t* box) {
    cuuint32_t es[3] = {1, 1, 1};
    fn(m, CU_TENSOR_MAP_DATA_TYPE_BFLOAT16, rank, const_cast<void*>(base), dims, strides, box, es, CU_TENSOR_MAP_INTERLEAVE_NONE,
       CU_TENSOR_MAP_SWIZZLE_128B, CU_TENSOR_MAP_L2_PROMOTION_L2_256B, CU_TENSOR_MAP_FLOAT_OOB_FILL_NONE);
}

}

extern "C" void kernel_launch(void* const* d_in, const int* in_sizes, int n_in, void* d_out, int out_size) {
    const __nv_bfloat16* x = (const __nv_bfloat16*)d_in[0];
    const __nv_bfloat16* wqkv = (const __nv_bfloat16*)d_in[1];
    const __nv_bfloat16* wo = (const __nv_bfloat16*)d_in[2];
    const __nv_bfloat16* w1 = (const __nv_bfloat16*)d_in[4];
    const __nv_bfloat16* b1 = (const __nv_bfloat16*)d_in[5];
    const __nv_bfloat16* w2 = (const __nv_bfloat16*)d_in[6];
    const __nv_bfloat16* b2 = (const __nv_bfloat16*)d_in[7];
    __nv_bfloat16* out = (__nv_bfloat16*)d_out;

    EncodeFn fn = nullptr;
    cudaDriverEntryPointQueryResult qr;
    cudaGetDriverEntryPoint("cuTensorMapEncodeTiled", (void**)&fn, cudaEnableDefault, &qr);
    CUtensorMap tmX, tmQ3, tmQ1, tm1, tm2, tmP;
    {
        void* gp = nullptr;
        cudaGetSymbolAddress(&gp, g_part);
        cuuint64_t d[2] = {SLAB * 2, 9}, s[1] = {SLAB * 16};
        cuuint32_t b[2] = {256, 9}, es[2] = {1, 1};
        fn(&tmP, CU_TENSOR_MAP_DATA_TYPE_INT64, 2, gp, d, s, b, es, CU_TENSOR_MAP_INTERLEAVE_NONE, CU_TENSOR_MAP_SWIZZLE_NONE,
           CU_TENSOR_MAP_L2_PROMOTION_NONE, CU_TENSOR_MAP_FLOAT_OOB_FILL_NONE);
    }
    {
        cuuint64_t d[3] = {64, SEQ, 9}, s[2] = {DM * 2, 128};
        cuuint32_t b[3] = {64, 8, 9};
        make_map(fn, &tmX, x, 3, d, s, b);
    }
    {
        cuuint64_t d[3] = {3 * DM, DM, 3}, s[2] = {3 * DM * 2, 128};
        cuuint32_t b[3] = {64, 16, 3};
        make_map(fn, &tmQ3, wqkv, 3, d, s, b);
        make_map(fn, &tmQ1, wqkv, 2, d, s, b);
    }
    {
        cuuint64_t d[2] = {FF, DM}, s[1] = {FF * 2};
        cuuint32_t b[2] = {64, 64};
        make_map(fn, &tm1, w1, 2, d, s, b);
        cuuint64_t d2[2] = {DM, FF}, s2[1] = {DM * 2};
        make_map(fn, &tm2, w2, 2, d2, s2, b);
    }
    cudaFuncSetAttribute(k1_kernel, cudaFuncAttributeMaxDynamicSharedMemorySize, K1_SMEM);
    cudaFuncSetAttribute(k2_kernel, cudaFuncAttributeMaxDynamicSharedMemorySize, K2_SMEM);
    cudaFuncSetAttribute(k3_kernel, cudaFuncAttributeMaxDynamicSharedMemorySize, K3_SMEM);

    cudaStream_t st = cudaStreamPerThread;
    cudaLaunchAttribute pdl[1];
    pdl[0].id = cudaLaunchAttributeProgrammaticStreamSerialization;
    pdl[0].val.programmaticStreamSerializationAllowed = 1;
    {
        cudaLaunchConfig_t cfg = {};
        cfg.gridDim = dim3(128); cfg.blockDim = dim3(384); cfg.dynamicSmemBytes = K1_SMEM; cfg.stream = st;
        cudaLaunchKernelEx(&cfg, k1_kernel, tmX, tmQ3, tmQ1, tm1, tm2, tmP, b1, wo, x, b2);
    }
    {
        cudaLaunchConfig_t cfg = {};
        cfg.gridDim = dim3(128); cfg.blockDim = dim3(512); cfg.dynamicSmemBytes = K2_SMEM; cfg.stream = st;
        cfg.attrs = pdl; cfg.numAttrs = 1;
        cudaLaunchKernelEx(&cfg, k2_kernel);
    }
    {
        cudaLaunchConfig_t cfg = {};
        cfg.gridDim = dim3(128); cfg.blockDim = dim3(128); cfg.dynamicSmemBytes = K3_SMEM; cfg.stream = st;
        cfg.attrs = pdl; cfg.numAttrs = 1;
        cudaLaunchKernelEx(&cfg, k3_kernel, out);
    }
}
```

```cpp
#include <cuda_runtime.h>
#include <cuda_bf16.h>
#include <cuda.h>
#include <stdint.h>

#define PROF(i) do { } while (0)
#define PROFT(i) do { } while (0)
#define PROFH(i) do { } while (0)
#define PROF_WG 0

namespace {

constexpr int SEQ = 2048, DM = 576, FF = 4608, NH = 32, DH = 18;

constexpr int KV_GROUP_BYTES = 5 * 128;
constexpr int KV_HEAD_BYTES = (SEQ / 8) * KV_GROUP_BYTES;
constexpr int Q_OFFSET = NH * KV_HEAD_BYTES;
#define POLY_MASK 0x92
__device__ __align__(1024) uint8_t g_QKV[2 * NH * KV_HEAD_BYTES];
__device__ __align__(1024) float g_kmax[NH * 64];
__device__ __align__(1024) float4 g_base[16 * 72 * 256];
__device__ __align__(1024) uint32_t g_O[SEQ * DM / 2];
__device__ unsigned int g_flag[16];
constexpr int WO_TILE_BYTES = DM * 144 * 2;
__device__ __align__(1024) uint8_t g_Wo[4 * WO_TILE_BYTES];

__device__ __forceinline__ uint32_t s2u(const void* p) { return (uint32_t)__cvta_generic_to_shared(p); }
__device__ __forceinline__ void mbar_init(uint32_t b, int c) { asm volatile("mbarrier.init.shared::cta.b64 [%0], %1;" ::"r"(b), "r"(c) : "memory"); }
__device__ __forceinline__ void mbar_expect(uint32_t b, uint32_t bytes) {
    asm volatile("mbarrier.arrive.expect_tx.shared::cta.b64 _, [%0], %1;" ::"r"(b), "r"(bytes) : "memory");
}
__device__ __forceinline__ void mbar_wait(uint32_t b, uint32_t parity) {
    asm volatile(
        "{\n.reg .pred p;\n.reg .u32 c;\n"
        "mbarrier.try_wait.parity.shared::cta.b64 p, [%0], %1;\n"
        "@p bra DONE;\n"
        "mov.u32 c, 0;\n"
        "LOOP:\n"
        "mbarrier.try_wait.parity.shared::cta.b64 p, [%0], %1;\n"
        "@p bra DONE;\n"
        "add.u32 c, c, 1;\n"
        "setp.lt.u32 p, c, 4194304;\n"
        "@p bra LOOP;\n"
        "trap;\n"
        "DONE:\n}\n" ::"r"(b), "r"(parity) : "memory");
}
__device__ __forceinline__ void fence_barrier_init() { asm volatile("fence.mbarrier_init.release.cluster;" ::: "memory"); }
__device__ __forceinline__ void fence_proxy_async() { asm volatile("fence.proxy.async.shared::cta;" ::: "memory"); }
__device__ __forceinline__ void cluster_arrive() { asm volatile("barrier.cluster.arrive.relaxed.aligned;" ::: "memory"); }
__device__ __forceinline__ void cluster_wait() { asm volatile("barrier.cluster.wait.aligned;" ::: "memory"); }
__device__ __forceinline__ void named_bar_sync(int id, int n) { asm volatile("bar.sync %0, %1;" ::"r"(id), "r"(n) : "memory"); }
__device__ __forceinline__ void griddep_wait() { asm volatile("griddepcontrol.wait;" ::: "memory"); }
__device__ __forceinline__ void griddep_launch() { asm volatile("griddepcontrol.launch_dependents;" ::: "memory"); }

__device__ __forceinline__ void tma3d_mc(uint32_t dst, const CUtensorMap* tm, int c0, int c1, int c2, uint32_t bar, uint16_t mask) {
    asm volatile("cp.async.bulk.tensor.3d.shared::cluster.global.mbarrier::complete_tx::bytes.multicast::cluster [%0], [%1, {%3, %4, %5}], [%2], %6;"
                 ::"r"(dst), "l"(tm), "r"(bar), "r"(c0), "r"(c1), "r"(c2), "h"(mask) : "memory");
}
__device__ __forceinline__ void tma2d_mc(uint32_t dst, const CUtensorMap* tm, int c0, int c1, uint32_t bar, uint16_t mask) {
    asm volatile("cp.async.bulk.tensor.2d.shared::cluster.global.mbarrier::complete_tx::bytes.multicast::cluster [%0], [%1, {%3, %4}], [%2], %5;"
                 ::"r"(dst), "l"(tm), "r"(bar), "r"(c0), "r"(c1), "h"(mask) : "memory");
}
__device__ __forceinline__ void tma3d(uint32_t dst, const CUtensorMap* tm, int c0, int c1, int c2, uint32_t bar) {
    asm volatile("cp.async.bulk.tensor.3d.shared::cluster.global.mbarrier::complete_tx::bytes [%0], [%1, {%3, %4, %5}], [%2];"
                 ::"r"(dst), "l"(tm), "r"(bar), "r"(c0), "r"(c1), "r"(c2) : "memory");
}
__device__ __forceinline__ void tma2d(uint32_t dst, const CUtensorMap* tm, int c0, int c1, uint32_t bar) {
    asm volatile("cp.async.bulk.tensor.2d.shared::cluster.global.mbarrier::complete_tx::bytes [%0], [%1, {%3, %4}], [%2];"
                 ::"r"(dst), "l"(tm), "r"(bar), "r"(c0), "r"(c1) : "memory");
}
__device__ __forceinline__ void bulk_load(uint32_t dst, const void* src, uint32_t bytes, uint32_t bar) {
    asm volatile("cp.async.bulk.shared::cluster.global.mbarrier::complete_tx::bytes [%0], [%1], %2, [%3];"
                 ::"r"(dst), "l"(src), "r"(bytes), "r"(bar) : "memory");
}
__device__ __forceinline__ void prefetch_tmap(const CUtensorMap* tm) { asm volatile("prefetch.tensormap [%0];" ::"l"(tm) : "memory"); }

__device__ __forceinline__ void wg_fence() { asm volatile("wgmma.fence.sync.aligned;" ::: "memory"); }
__device__ __forceinline__ void wg_commit() { asm volatile("wgmma.commit_group.sync.aligned;" ::: "memory"); }
template <int N> __device__ __forceinline__ void wg_wait() { asm volatile("wgmma.wait_group.sync.aligned %0;" ::"n"(N) : "memory"); }
template <int N> __device__ __forceinline__ void reg_fence(float (&d)[N]) {
#pragma unroll
    for (int i = 0; i < N; i++) asm volatile("" : "+f"(d[i])::"memory");
}
template <int N> __device__ __forceinline__ void reg_fence(uint32_t (&d)[N]) {
#pragma unroll
    for (int i = 0; i < N; i++) asm volatile("" : "+r"(d[i])::"memory");
}
template <int R> __device__ __forceinline__ void reg_alloc() { asm volatile("setmaxnreg.inc.sync.aligned.u32 %0;" ::"n"(R)); }
template <int R> __device__ __forceinline__ void reg_dealloc() { asm volatile("setmaxnreg.dec.sync.aligned.u32 %0;" ::"n"(R)); }

__device__ __forceinline__ uint32_t desc_lo(uint32_t addr, uint32_t lbo) { return ((addr & 0x3FFFF) >> 4) | ((lbo >> 4) << 16); }
__host__ __device__ constexpr uint32_t desc_hi(uint32_t sbo, uint32_t swz) { return (sbo >> 4) | (swz << 30); }
__device__ __forceinline__ uint32_t pack_bf16(float lo, float hi) {
    uint32_t r;
    asm("cvt.rn.bf16x2.f32 %0, %1, %2;" : "=r"(r) : "f"(hi), "f"(lo));
    return r;
}
__device__ __forceinline__ float bf_lo(uint32_t w) { return __uint_as_float(w << 16); }
__device__ __forceinline__ float bf_hi(uint32_t w) { return __uint_as_float(w & 0xFFFF0000u); }
__device__ __forceinline__ float ex2(float x) {
    float r;
    asm("ex2.approx.ftz.f32 %0, %1;" : "=f"(r) : "f"(x));
    return r;
}
__device__ __forceinline__ float tanh_fast(float x) {
    float r;
    asm("tanh.approx.f32 %0, %1;" : "=f"(r) : "f"(x));
    return r;
}
__device__ __forceinline__ float gelu2(float u) {
    const float w = fmaf(u * u, 0.0356774081f, 0.7978845608f);
    return fmaf(u, tanh_fast(u * w), u);
}

template<int TB> __device__ __forceinline__ void wgmma_ss_n216(float (&d)[108], uint32_t alo, uint32_t ahi, uint32_t blo, uint32_t bhi, int sd) {
    asm volatile("{\n.reg .pred p;\n.reg .b64 da, db;\nsetp.ne.b32 p, %110, 0;\nmov.b64 da, {%108, %112};\nmov.b64 db, {%109, %113};\n"
      "wgmma.mma_async.sync.aligned.m64n216k16.f32.bf16.bf16 {%0, %1, %2, %3, %4, %5, %6, %7, %8, %9, %10, %11, %12, %13, %14, %15, %16, %17, %18, %19, %20, %21, %22, %23, %24, %25, %26, %27, %28, %29, %30, %31, %32, %33, %34, %35, %36, %37, %38, %39, %40, %41, %42, %43, %44, %45, %46, %47, %48, %49, %50, %51, %52, %53, %54, %55, %56, %57, %58, %59, %60, %61, %62, %63, %64, %65, %66, %67, %68, %69, %70, %71, %72, %73, %74, %75, %76, %77, %78, %79, %80, %81, %82, %83, %84, %85, %86, %87, %88, %89, %90, %91, %92, %93, %94, %95, %96, %97, %98, %99, %100, %101, %102, %103, %104, %105, %106, %107}, da, db, p, 1, 1, 0, %111;\n}\n"
      : "+f"(d[0]), "+f"(d[1]), "+f"(d[2]), "+f"(d[3]), "+f"(d[4]), "+f"(d[5]), "+f"(d[6]), "+f"(d[7]), "+f"(d[8]), "+f"(d[9]), "+f"(d[10]), "+f"(d[11]), "+f"(d[12]), "+f"(d[13]), "+f"(d[14]), "+f"(d[15]), "+f"(d[16]), "+f"(d[17]), "+f"(d[18]), "+f"(d[19]), "+f"(d[20]), "+f"(d[21]), "+f"(d[22]), "+f"(d[23]), "+f"(d[24]), "+f"(d[25]), "+f"(d[26]), "+f"(d[27]), "+f"(d[28]), "+f"(d[29]), "+f"(d[30]), "+f"(d[31]), "+f"(d[32]), "+f"(d[33]), "+f"(d[34]), "+f"(d[35]), "+f"(d[36]), "+f"(d[37]), "+f"(d[38]), "+f"(d[39]), "+f"(d[40]), "+f"(d[41]), "+f"(d[42]), "+f"(d[43]), "+f"(d[44]), "+f"(d[45]), "+f"(d[46]), "+f"(d[47]), "+f"(d[48]), "+f"(d[49]), "+f"(d[50]), "+f"(d[51]), "+f"(d[52]), "+f"(d[53]), "+f"(d[54]), "+f"(d[55]), "+f"(d[56]), "+f"(d[57]), "+f"(d[58]), "+f"(d[59]), "+f"(d[60]), "+f"(d[61]), "+f"(d[62]), "+f"(d[63]), "+f"(d[64]), "+f"(d[65]), "+f"(d[66]), "+f"(d[67]), "+f"(d[68]), "+f"(d[69]), "+f"(d[70]), "+f"(d[71]), "+f"(d[72]), "+f"(d[73]), "+f"(d[74]), "+f"(d[75]), "+f"(d[76]), "+f"(d[77]), "+f"(d[78]), "+f"(d[79]), "+f"(d[80]), "+f"(d[81]), "+f"(d[82]), "+f"(d[83]), "+f"(d[84]), "+f"(d[85]), "+f"(d[86]), "+f"(d[87]), "+f"(d[88]), "+f"(d[89]), "+f"(d[90]), "+f"(d[91]), "+f"(d[92]), "+f"(d[93]), "+f"(d[94]), "+f"(d[95]), "+f"(d[96]), "+f"(d[97]), "+f"(d[98]), "+f"(d[99]), "+f"(d[100]), "+f"(d[101]), "+f"(d[102]), "+f"(d[103]), "+f"(d[104]), "+f"(d[105]), "+f"(d[106]), "+f"(d[107])
      : "r"(alo), "r"(blo), "r"(sd), "n"(TB), "r"(ahi), "r"(bhi));
}

template<int TB> __device__ __forceinline__ void wgmma_ss_n64(float (&d)[32], uint32_t alo, uint32_t ahi, uint32_t blo, uint32_t bhi, int sd) {
    asm volatile("{\n.reg .pred p;\n.reg .b64 da, db;\nsetp.ne.b32 p, %34, 0;\nmov.b64 da, {%32, %36};\nmov.b64 db, {%33, %37};\n"
      "wgmma.mma_async.sync.aligned.m64n64k16.f32.bf16.bf16 {%0, %1, %2, %3, %4, %5, %6, %7, %8, %9, %10, %11, %12, %13, %14, %15, %16, %17, %18, %19, %20, %21, %22, %23, %24, %25, %26, %27, %28, %29, %30, %31}, da, db, p, 1, 1, 0, %35;\n}\n"
      : "+f"(d[0]), "+f"(d[1]), "+f"(d[2]), "+f"(d[3]), "+f"(d[4]), "+f"(d[5]), "+f"(d[6]), "+f"(d[7]), "+f"(d[8]), "+f"(d[9]), "+f"(d[10]), "+f"(d[11]), "+f"(d[12]), "+f"(d[13]), "+f"(d[14]), "+f"(d[15]), "+f"(d[16]), "+f"(d[17]), "+f"(d[18]), "+f"(d[19]), "+f"(d[20]), "+f"(d[21]), "+f"(d[22]), "+f"(d[23]), "+f"(d[24]), "+f"(d[25]), "+f"(d[26]), "+f"(d[27]), "+f"(d[28]), "+f"(d[29]), "+f"(d[30]), "+f"(d[31])
      : "r"(alo), "r"(blo), "r"(sd), "n"(TB), "r"(ahi), "r"(bhi));
}

template<int TB> __device__ __forceinline__ void wgmma_rs_n64(float (&d)[32], uint32_t a0, uint32_t a1, uint32_t a2, uint32_t a3, uint32_t blo, uint32_t bhi, int sd) {
    asm volatile("{\n.reg .pred p;\n.reg .b64 db;\nsetp.ne.b32 p, %37, 0;\nmov.b64 db, {%36, %39};\n"
      "wgmma.mma_async.sync.aligned.m64n64k16.f32.bf16.bf16 {%0, %1, %2, %3, %4, %5, %6, %7, %8, %9, %10, %11, %12, %13, %14, %15, %16, %17, %18, %19, %20, %21, %22, %23, %24, %25, %26, %27, %28, %29, %30, %31}, {%32, %33, %34, %35}, db, p, 1, 1, %38;\n}\n"
      : "+f"(d[0]), "+f"(d[1]), "+f"(d[2]), "+f"(d[3]), "+f"(d[4]), "+f"(d[5]), "+f"(d[6]), "+f"(d[7]), "+f"(d[8]), "+f"(d[9]), "+f"(d[10]), "+f"(d[11]), "+f"(d[12]), "+f"(d[13]), "+f"(d[14]), "+f"(d[15]), "+f"(d[16]), "+f"(d[17]), "+f"(d[18]), "+f"(d[19]), "+f"(d[20]), "+f"(d[21]), "+f"(d[22]), "+f"(d[23]), "+f"(d[24]), "+f"(d[25]), "+f"(d[26]), "+f"(d[27]), "+f"(d[28]), "+f"(d[29]), "+f"(d[30]), "+f"(d[31])
      : "r"(a0), "r"(a1), "r"(a2), "r"(a3), "r"(blo), "r"(sd), "n"(TB), "r"(bhi));
}

template<int TB> __device__ __forceinline__ void wgmma_rs_n24(float (&d)[12], uint32_t a0, uint32_t a1, uint32_t a2, uint32_t a3, uint32_t blo, uint32_t bhi, int sd) {
    asm volatile("{\n.reg .pred p;\n.reg .b64 db;\nsetp.ne.b32 p, %17, 0;\nmov.b64 db, {%16, %19};\n"
      "wgmma.mma_async.sync.aligned.m64n24k16.f32.bf16.bf16 {%0, %1, %2, %3, %4, %5, %6, %7, %8, %9, %10, %11}, {%12, %13, %14, %15}, db, p, 1, 1, %18;\n}\n"
      : "+f"(d[0]), "+f"(d[1]), "+f"(d[2]), "+f"(d[3]), "+f"(d[4]), "+f"(d[5]), "+f"(d[6]), "+f"(d[7]), "+f"(d[8]), "+f"(d[9]), "+f"(d[10]), "+f"(d[11])
      : "r"(a0), "r"(a1), "r"(a2), "r"(a3), "r"(blo), "r"(sd), "n"(TB), "r"(bhi));
}

template<int TB> __device__ __forceinline__ void wgmma_rs_n144(float (&d)[72], uint32_t a0, uint32_t a1, uint32_t a2, uint32_t a3, uint32_t blo, uint32_t bhi, int sd) {
    asm volatile("{\n.reg .pred p;\n.reg .b64 db;\nsetp.ne.b32 p, %77, 0;\nmov.b64 db, {%76, %79};\n"
      "wgmma.mma_async.sync.aligned.m64n144k16.f32.bf16.bf16 {%0, %1, %2, %3, %4, %5, %6, %7, %8, %9, %10, %11, %12, %13, %14, %15, %16, %17, %18, %19, %20, %21, %22, %23, %24, %25, %26, %27, %28, %29, %30, %31, %32, %33, %34, %35, %36, %37, %38, %39, %40, %41, %42, %43, %44, %45, %46, %47, %48, %49, %50, %51, %52, %53, %54, %55, %56, %57, %58, %59, %60, %61, %62, %63, %64, %65, %66, %67, %68, %69, %70, %71}, {%72, %73, %74, %75}, db, p, 1, 1, %78;\n}\n"
      : "+f"(d[0]), "+f"(d[1]), "+f"(d[2]), "+f"(d[3]), "+f"(d[4]), "+f"(d[5]), "+f"(d[6]), "+f"(d[7]), "+f"(d[8]), "+f"(d[9]), "+f"(d[10]), "+f"(d[11]), "+f"(d[12]), "+f"(d[13]), "+f"(d[14]), "+f"(d[15]), "+f"(d[16]), "+f"(d[17]), "+f"(d[18]), "+f"(d[19]), "+f"(d[20]), "+f"(d[21]), "+f"(d[22]), "+f"(d[23]), "+f"(d[24]), "+f"(d[25]), "+f"(d[26]), "+f"(d[27]), "+f"(d[28]), "+f"(d[29]), "+f"(d[30]), "+f"(d[31]), "+f"(d[32]), "+f"(d[33]), "+f"(d[34]), "+f"(d[35]), "+f"(d[36]), "+f"(d[37]), "+f"(d[38]), "+f"(d[39]), "+f"(d[40]), "+f"(d[41]), "+f"(d[42]), "+f"(d[43]), "+f"(d[44]), "+f"(d[45]), "+f"(d[46]), "+f"(d[47]), "+f"(d[48]), "+f"(d[49]), "+f"(d[50]), "+f"(d[51]), "+f"(d[52]), "+f"(d[53]), "+f"(d[54]), "+f"(d[55]), "+f"(d[56]), "+f"(d[57]), "+f"(d[58]), "+f"(d[59]), "+f"(d[60]), "+f"(d[61]), "+f"(d[62]), "+f"(d[63]), "+f"(d[64]), "+f"(d[65]), "+f"(d[66]), "+f"(d[67]), "+f"(d[68]), "+f"(d[69]), "+f"(d[70]), "+f"(d[71])
      : "r"(a0), "r"(a1), "r"(a2), "r"(a3), "r"(blo), "r"(sd), "n"(TB), "r"(bhi));
}

constexpr int K1_XN_BYTES = 16 * 9216;
constexpr int K1_SLOT = 16384, K1_NSLOT = 5;
constexpr int K1_OFF_RING = K1_XN_BYTES;
constexpr int K1_OFF_BIAS = K1_OFF_RING + K1_NSLOT * K1_SLOT;
constexpr int K1_OFF_BAR = K1_OFF_BIAS + 576 * 2;
constexpr int K1_SMEM = K1_OFF_BAR + 256 + 128;
constexpr float QSCALE = 0.23570226039551584f * 1.4426950408889634f;

struct Ring {
    uint32_t slot, phase;
    __device__ __forceinline__ void advance() {
        if (++slot == K1_NSLOT) { slot = 0; phase ^= 1; }
    }
};

struct K1Ctx {
    uint32_t full0;
    uint32_t rel_addr;
    uint32_t descA, descB;
    Ring rd;
    uint32_t prev_slot;
    __device__ __forceinline__ uint32_t begin_stage() {
        mbar_wait(full0 + rd.slot * 8, rd.phase);
        wg_fence();
        return descB + rd.slot * (K1_SLOT >> 4);
    }
    __device__ __forceinline__ void end_stage() {
        wg_commit();
        wg_wait<1>();
        if (rel_addr) asm volatile("mbarrier.arrive.shared::cluster.b64 _, [%0];" ::"r"(rel_addr + prev_slot * 8) : "memory");
        prev_slot = rd.slot;
        rd.advance();
    }
};

__device__ __forceinline__ uint32_t descA_step(uint32_t base, int ks) { return base + (((ks >> 2) * 1024 + (ks & 3) * 32) >> 4); }
constexpr uint32_t K1_AHI = desc_hi(9216, 1), K1_BHI = desc_hi(1024, 1);

template <int V> struct IC { static constexpr int value = V; };
template <int I, int N, class F> __device__ __forceinline__ void static_for(F&& f) {
    if constexpr (I < N) { f(IC<I>{}); static_for<I + 1, N>(f); }
}

template <bool A_RS, bool B_RS, class Epi>
__device__ __forceinline__ void tile_pair(K1Ctx& c, float (&accA)[32], float (&accB)[32], uint32_t (&h)[144], Epi&& epi) {
    static_for<0, 9>([&](auto sc) {
        constexpr int s = decltype(sc)::value;
        const uint32_t db = c.begin_stage();
#pragma unroll
        for (int t = 0; t < 8; t++) {
            const int kk = s * 8 + t, ks = kk % 36;
            const uint32_t dbt = db + ((t * 2048) >> 4);
            if (kk < 36) {
                if constexpr (A_RS) wgmma_rs_n64<1>(accA, h[ks * 4], h[ks * 4 + 1], h[ks * 4 + 2], h[ks * 4 + 3], dbt, K1_BHI, ks != 0);
                else wgmma_ss_n64<1>(accA, descA_step(c.descA, ks), K1_AHI, dbt, K1_BHI, ks != 0);
            } else {
                if constexpr (B_RS) wgmma_rs_n64<1>(accB, h[ks * 4], h[ks * 4 + 1], h[ks * 4 + 2], h[ks * 4 + 3], dbt, K1_BHI, ks != 0);
                else wgmma_ss_n64<1>(accB, descA_step(c.descA, ks), K1_AHI, dbt, K1_BHI, ks != 0);
            }
        }
        c.end_stage();
        epi(sc);
    });
}

template <int B0, int NB, int HOFF>
__device__ __forceinline__ void gelu_blocks(const float (&acc)[32], uint32_t (&h)[144], const uint32_t (&bq)[8]) {
#pragma unroll
    for (int b = B0; b < B0 + NB; b++) {
        const float b0 = bf_lo(bq[b]), b1 = bf_hi(bq[b]);
        h[HOFF + b * 2 + 0] = pack_bf16(gelu2(acc[b * 4 + 0] + b0), gelu2(acc[b * 4 + 1] + b1));
        h[HOFF + b * 2 + 1] = pack_bf16(gelu2(acc[b * 4 + 2] + b0), gelu2(acc[b * 4 + 3] + b1));
    }
}
__device__ __forceinline__ void load_bias(uint32_t (&bq)[8], uint32_t addr) {
    asm volatile("ld.shared.v4.u32 {%0, %1, %2, %3}, [%4];" : "=r"(bq[0]), "=r"(bq[1]), "=r"(bq[2]), "=r"(bq[3]) : "r"(addr));
    asm volatile("ld.shared.v4.u32 {%0, %1, %2, %3}, [%4 + 16];" : "=r"(bq[4]), "=r"(bq[5]), "=r"(bq[6]), "=r"(bq[7]) : "r"(addr));
}
template <int S> __device__ __forceinline__ void store_part(const float (&o)[32], float4* p) {
    asm volatile("red.global.add.v4.f32 [%0], {%1, %2, %3, %4};" ::"l"(p + S * 512), "f"(o[S * 8]), "f"(o[S * 8 + 1]), "f"(o[S * 8 + 2]), "f"(o[S * 8 + 3]) : "memory");
    asm volatile("red.global.add.v4.f32 [%0], {%1, %2, %3, %4};" ::"l"(p + S * 512 + 256), "f"(o[S * 8 + 4]), "f"(o[S * 8 + 5]), "f"(o[S * 8 + 6]), "f"(o[S * 8 + 7]) : "memory");
}

__global__ void __cluster_dims__(2, 1, 1) __launch_bounds__(384, 1)
k1_kernel(const __grid_constant__ CUtensorMap tmX, const __grid_constant__ CUtensorMap tmQ3, const __grid_constant__ CUtensorMap tmQ1,
          const __grid_constant__ CUtensorMap tm1, const __grid_constant__ CUtensorMap tm2, const __nv_bfloat16* __restrict__ b1,
          const __nv_bfloat16* __restrict__ wo, const __nv_bfloat16* __restrict__ x, const __nv_bfloat16* __restrict__ b2) {
    extern __shared__ __align__(1024) uint8_t smem[];
    const uint32_t sb = s2u(smem);
    const int tid = threadIdx.x, lane = tid & 31;
    const int warp = __shfl_sync(~0u, tid >> 5, 0);
    const uint32_t rank = blockIdx.x & 1;
    const int cl = blockIdx.x >> 1;
    const int rb = (cl & 7) * 2 + rank;
    const int j = cl >> 3;
    const uint32_t full0 = sb + K1_OFF_BAR, empty0 = full0 + 8 * K1_NSLOT, xbar0 = full0 + 128, ibar = full0 + 256;

    if (warp < 8) {
        PROF(0);
        PROFT(48);
        if (lane == 0) {
            mbar_init(xbar0 + warp * 16, 1);
            mbar_init(xbar0 + warp * 16 + 8, 1);
            fence_barrier_init();
            mbar_expect(xbar0 + warp * 16, 9216);
            tma3d(sb + warp * 2 * 9216, &tmX, 0, rb * 128 + warp * 16, 0, xbar0 + warp * 16);
            mbar_expect(xbar0 + warp * 16 + 8, 9216);
            tma3d(sb + (warp * 2 + 1) * 9216, &tmX, 0, rb * 128 + warp * 16 + 8, 0, xbar0 + warp * 16 + 8);
        }
        __syncwarp();
        cluster_arrive();
        reg_alloc<240>();
#pragma unroll 1
        for (int p = 0; p < 4; p++) {
            mbar_wait(xbar0 + warp * 16 + (p >> 1) * 8, 0);
            uint4* row = reinterpret_cast<uint4*>(smem + (warp * 2 + (p >> 1)) * 9216 + (p & 1) * 512 + lane * 16);
            float f[72];
#pragma unroll
            for (int i = 0; i < 9; i++) {
                const uint4 v = row[i * 64];
                f[i * 8 + 0] = bf_lo(v.x); f[i * 8 + 1] = bf_hi(v.x); f[i * 8 + 2] = bf_lo(v.y); f[i * 8 + 3] = bf_hi(v.y);
                f[i * 8 + 4] = bf_lo(v.z); f[i * 8 + 5] = bf_hi(v.z); f[i * 8 + 6] = bf_lo(v.w); f[i * 8 + 7] = bf_hi(v.w);
            }
            float s0 = 0.f, s1 = 0.f, s2 = 0.f, s3 = 0.f;
#pragma unroll
            for (int i = 0; i < 72; i += 4) { s0 += f[i]; s1 += f[i + 1]; s2 += f[i + 2]; s3 += f[i + 3]; }
            float sm = (s0 + s1) + (s2 + s3);
            sm += __shfl_xor_sync(~0u, sm, 1); sm += __shfl_xor_sync(~0u, sm, 2); sm += __shfl_xor_sync(~0u, sm, 4);
            const float mean = sm * (1.0f / DM);
            s0 = s1 = s2 = s3 = 0.f;
#pragma unroll
            for (int i = 0; i < 72; i += 4) {
                f[i] -= mean; f[i + 1] -= mean; f[i + 2] -= mean; f[i + 3] -= mean;
                s0 = fmaf(f[i], f[i], s0); s1 = fmaf(f[i + 1], f[i + 1], s1);
                s2 = fmaf(f[i + 2], f[i + 2], s2); s3 = fmaf(f[i + 3], f[i + 3], s3);
            }
            float sq = (s0 + s1) + (s2 + s3);
            sq += __shfl_xor_sync(~0u, sq, 1); sq += __shfl_xor_sync(~0u, sq, 2); sq += __shfl_xor_sync(~0u, sq, 4);
            const float rstd = rsqrtf(sq * (1.0f / DM) + 1e-5f);
#pragma unroll
            for (int i = 0; i < 9; i++) {
                uint4 o;
                o.x = pack_bf16(f[i * 8 + 0] * rstd, f[i * 8 + 1] * rstd);
                o.y = pack_bf16(f[i * 8 + 2] * rstd, f[i * 8 + 3] * rstd);
                o.z = pack_bf16(f[i * 8 + 4] * rstd, f[i * 8 + 5] * rstd);
                o.w = pack_bf16(f[i * 8 + 6] * rstd, f[i * 8 + 7] * rstd);
                row[i * 64] = o;
            }
        }
        const int wg = warp >> 2, wq = warp & 3;
        fence_proxy_async();
        named_bar_sync(1 + wg, 128);
        cluster_wait();
        PROF(1);

        const int g = lane >> 2, q = lane & 3;
        K1Ctx c;
        c.full0 = full0;
        c.rel_addr = 0;
        c.descA = desc_lo(sb + wg * 8 * 9216, 16);
        c.descB = desc_lo(sb + K1_OFF_RING, 2048);
        c.rd.slot = 0; c.rd.phase = 0; c.prev_slot = 0;
        uint32_t biasq = sb + K1_OFF_BIAS + q * 32;
        uint32_t bq[8];

        uint32_t h[144];
        float accA[32], accB[32];
        {
            float accQ[108];
            uint32_t rel = 0;
            if (lane == 0 && wq < 2) asm("mapa.shared::cluster.u32 %0, %1, %2;" : "=r"(rel) : "r"(empty0), "r"(wq));
#pragma unroll 1
            for (int s = 0; s < 18; s++) {
                const uint32_t db = c.begin_stage();
                const uint32_t da = c.descA + (s >> 1) * 64 + (s & 1) * 4;
                wgmma_ss_n216<1>(accQ, da, K1_AHI, db, K1_BHI, s != 0);
                wgmma_ss_n216<1>(accQ, da + 2, K1_AHI, db + (8192 >> 4), K1_BHI, 1);
                c.end_stage();
                c.rel_addr = rel;
            }
            PROF(2);
            uint32_t rel9[9];
#pragma unroll
            for (int i9 = 0; i9 < 9; i9++) {
                const int p = 4 * i9 + q, hh = (p * 57) >> 9, r = p - 9 * hh;
                rel9[i9] = hh * KV_HEAD_BYTES + (r < 8 ? (r >> 2) * 128 + (r & 3) * 4 : 0);
            }
            uint32_t gb = 0, o2 = 0;
            float scl0 = 1.f, scl1 = 1.f;
            tile_pair<false, false>(c, accA, accB, h, [&](auto sc) {
                constexpr int s = decltype(sc)::value;
                if constexpr (s == 0) reg_fence(accQ);
                if constexpr (s < 6) {
                    constexpr int grp = s / 2, part = s % 2;
                    if constexpr (part == 0) {
                        const int G = 3 * j + grp, type = G >> 3;
                        gb = (G & 7) * 4 * KV_HEAD_BYTES + (rb * 16 + warp * 2) * KV_GROUP_BYTES + g * 16 + (type == 0 ? Q_OFFSET : (type == 2 ? 256 : 0));
                        o2 = type == 0 ? 256 : (type == 2 ? 264 : 512);
                        scl0 = type == 0 ? QSCALE : ((type == 1 && ((POLY_MASK >> (wq * 2)) & 1)) ? 2.f : 1.f);
                        scl1 = type == 0 ? QSCALE : ((type == 1 && ((POLY_MASK >> (wq * 2 + 1)) & 1)) ? 2.f : 1.f);
                    }
#pragma unroll
                    for (int i9 = part * 5; i9 < (part ? 9 : 5); i9++) {
                        const int b = grp * 9 + i9;
                        uint32_t off = gb + rel9[i9];
                        if (i9 >= 2 && (i9 & 1) == 0) off += (q == i9 / 2 - 1) ? o2 : 0;
                        *reinterpret_cast<uint32_t*>(g_QKV + off) = pack_bf16(accQ[b * 4] * scl0, accQ[b * 4 + 1] * scl0);
                        *reinterpret_cast<uint32_t*>(g_QKV + off + KV_GROUP_BYTES) = pack_bf16(accQ[b * 4 + 2] * scl1, accQ[b * 4 + 3] * scl1);
                    }
                    if constexpr (s == 5) asm volatile("bar.arrive 3, 352;" ::: "memory");
                }
                if constexpr (s == 4) { named_bar_sync(4, 352); load_bias(bq, biasq); }
                if constexpr (s == 5) reg_fence(accA);
                if constexpr (s >= 5) gelu_blocks<(s - 5) * 2, 2, 96>(accA, h, bq);
                if constexpr (s == 8) load_bias(bq, biasq + 128);
            });
        }
        PROF(3);
#pragma unroll
        for (int i = 32; i < 96; i++) asm volatile("mov.u32 %0, 0;" : "=r"(h[i]));
#pragma unroll 1
        for (int p = 1; p < 4; p++) {
            biasq += 256;
            tile_pair<false, false>(c, accA, accB, h, [&](auto sc) {
                constexpr int s = decltype(sc)::value;
                if constexpr (s == 0) {
                    reg_fence(accB);
#pragma unroll
                    for (int i = 0; i < 80; i++) h[i] = h[i + 32];
                }
                if constexpr (s < 4) gelu_blocks<s * 2, 2, 80>(accB, h, bq);
                if constexpr (s == 4) load_bias(bq, biasq);
                if constexpr (s == 5) reg_fence(accA);
                if constexpr (s >= 5) gelu_blocks<(s - 5) * 2, 2, 96>(accA, h, bq);
                if constexpr (s == 8) load_bias(bq, biasq + 128);
            });
        }
        PROF(4);
        tile_pair<false, true>(c, accA, accB, h, [&](auto sc) {
            constexpr int s = decltype(sc)::value;
            if constexpr (s == 0) reg_fence(accB);
            if constexpr (s < 4) gelu_blocks<s * 2, 2, 112>(accB, h, bq);
            if constexpr (s == 4) load_bias(bq, biasq + 256);
            if constexpr (s == 5) reg_fence(accA);
            if constexpr (s == 5 || s == 6) gelu_blocks<(s - 5) * 3, 3, 128>(accA, h, bq);
            if constexpr (s == 7) gelu_blocks<6, 2, 128>(accA, h, bq);
            if constexpr (s == 3 || s == 7) reg_fence(h);
        });
        PROF(5);
        float4* const pbase = g_base + rb * 72 * 256 + tid;
        int tb = j;
        mbar_wait(ibar, 0);
#pragma unroll 1
        for (int p = 0; p < 4; p++) {
            const int ta = tb == 8 ? 0 : tb + 1;
            float4* const pb = pbase + tb * 2048;
            float4* const pa = pbase + ta * 2048;
            tile_pair<true, true>(c, accA, accB, h, [&](auto sc) {
                constexpr int s = decltype(sc)::value;
                if constexpr (s == 0) reg_fence(accB);
                if constexpr (s < 4) store_part<s>(accB, pb);
                if constexpr (s == 5) reg_fence(accA);
                if constexpr (s >= 5) store_part<s - 5>(accA, pa);
            });
            tb = ta == 8 ? 0 : ta + 1;
            PROF(6 + p);
        }
        wg_wait<0>();
        reg_fence(accB);
        {
            float4* const pb = pbase + tb * 2048;
            store_part<0>(accB, pb); store_part<1>(accB, pb); store_part<2>(accB, pb); store_part<3>(accB, pb);
        }
        PROF(10);
        cluster_arrive();
        cluster_wait();
        PROF(11);
        PROFT(49);
    } else {
        reg_dealloc<24>();
        if (warp == 8 && lane == 0) {
            prefetch_tmap(&tmQ3); prefetch_tmap(&tmQ1); prefetch_tmap(&tm1); prefetch_tmap(&tm2);
            for (int i = 0; i < K1_NSLOT; i++) { mbar_init(full0 + i * 8, 1); mbar_init(empty0 + i * 8, 4); }
            mbar_init(ibar, 1);
            fence_barrier_init();
        }
        __syncwarp();
        cluster_arrive();
        cluster_wait();
        if (warp == 8) {
            if (lane == 0) {
                Ring w{0, 1};
                const uint32_t dst0 = sb + K1_OFF_RING + rank * 8192;
#pragma unroll 1
                for (int s = 0; s < 18; s++) {
                    mbar_wait(empty0 + w.slot * 8, w.phase);
                    mbar_expect(full0 + w.slot * 8, 16384);
                    const uint32_t dst = dst0 + w.slot * K1_SLOT;
                    tma3d_mc(dst, &tmQ3, j * 216, s * 32 + rank * 16, 0, full0 + w.slot * 8, 3);
                    tma2d_mc(dst + 6144, &tmQ1, j * 216 + 192, s * 32 + rank * 16, full0 + w.slot * 8, 3);
                    w.advance();
                }
                int tile = 0, kb = rank;
#pragma unroll 1
                for (int s = 0; s < 81; s++) {
                    mbar_wait(empty0 + w.slot * 8, w.phase);
                    mbar_expect(full0 + w.slot * 8, 16384);
                    const uint32_t dst = dst0 + w.slot * K1_SLOT;
                    if (tile < 9) tma2d_mc(dst, &tm1, j * 576 + tile * 64, kb * 64, full0 + w.slot * 8, 3);
                    else tma2d_mc(dst, &tm2, (tile + j >= 18 ? tile + j - 18 : tile + j - 9) * 64, j * 576 + kb * 64, full0 + w.slot * 8, 3);
                    kb += 2;
                    if (kb >= 9) { kb -= 9; tile++; }
                    w.advance();
                }
            }
        } else {
            const int ht = tid - 288;
            if (ht < 72) {
                const uint4 v = __ldg(reinterpret_cast<const uint4*>(b1 + j * 576) + ht);
                uint32_t* sbias = reinterpret_cast<uint32_t*>(smem + K1_OFF_BIAS) + (ht >> 3) * 32 + (ht & 7);
                sbias[0] = v.x; sbias[8] = v.y; sbias[16] = v.z; sbias[24] = v.w;
            }
            asm volatile("bar.arrive 4, 352;" ::: "memory");
#pragma unroll 1
            for (int i = ht; i < 512; i += 96) {
                const int key = i & 127;
                uint8_t* p = g_QKV + (size_t)(j * 4 + (i >> 7)) * KV_HEAD_BYTES + (rb * 16 + (key >> 3)) * KV_GROUP_BYTES + 512 + (key & 7) * 16;
                *reinterpret_cast<uint32_t*>(p + 4) = ((POLY_MASK >> ((key >> 3) & 7)) & 1) ? 0x3F804000u : 0x00003F80u;
                *reinterpret_cast<uint32_t*>(p + 12) = 0x00003F80u;
            }
#pragma unroll 2
            for (int i = blockIdx.x * 324 + ht; i < blockIdx.x * 324 + 324; i += 96) {
                const int k = i / 72, nc = i - k * 72, ct = nc / 18;
                *reinterpret_cast<uint4*>(g_Wo + ct * WO_TILE_BYTES + (k >> 3) * 2304 + (nc - ct * 18) * 128 + (k & 7) * 16) =
                    __ldg(reinterpret_cast<const uint4*>(wo) + i);
            }
            PROFH(37);
#pragma unroll 4
            for (int i = ht; i < 9 * 256; i += 96) {
                const int t = i & 255, nb = j * 9 + (i >> 8);
                const int row = rb * 128 + (t >> 5) * 16 + ((t & 31) >> 2), col = nb * 8 + (t & 3) * 2;
                const uint32_t* xp = reinterpret_cast<const uint32_t*>(x + (size_t)row * DM + col);
                const uint32_t x0 = __ldg(xp), x1 = __ldg(xp + 4 * DM), bb = __ldg(reinterpret_cast<const uint32_t*>(b2 + col));
                g_base[(rb * 72 + nb) * 256 + t] = make_float4(2.f * (bf_lo(x0) + bf_lo(bb)), 2.f * (bf_hi(x0) + bf_hi(bb)),
                                                               2.f * (bf_lo(x1) + bf_lo(bb)), 2.f * (bf_hi(x1) + bf_hi(bb)));
            }
            named_bar_sync(7, 96);
            if (ht == 0) {
                __threadfence();
                atomicAdd(&g_flag[rb], 1u);
                uint32_t v, spins = 0;
                do {
                    __nanosleep(200);
                    asm volatile("ld.acquire.gpu.global.u32 %0, [%1];" : "=r"(v) : "l"(&g_flag[rb]) : "memory");
                    if (++spins > (1u << 20)) __trap();
                } while (v < 8);
                asm volatile("mbarrier.arrive.shared::cta.b64 _, [%0];" ::"r"(ibar) : "memory");
            }
            __syncwarp();
            PROFH(38);
            named_bar_sync(3, 352);
#pragma unroll 1
            for (int i = warp - 9; i < 48; i += 3) {
                const int G = 3 * j + (i >> 4);
                if ((G >> 3) != 1) continue;
                const int head = (G & 7) * 4 + ((i >> 2) & 3), key = (i & 3) * 32 + lane;
                const uint8_t* p = g_QKV + (size_t)head * KV_HEAD_BYTES + (rb * 16 + (key >> 3)) * KV_GROUP_BYTES + (key & 7) * 16;
                const uint4 a = __ldcg(reinterpret_cast<const uint4*>(p)), b = __ldcg(reinterpret_cast<const uint4*>(p + 128));
                const uint32_t e = __ldcg(reinterpret_cast<const uint32_t*>(p + 512));
                float n = bf_lo(e) * bf_lo(e) + bf_hi(e) * bf_hi(e);
                n += bf_lo(a.x) * bf_lo(a.x) + bf_hi(a.x) * bf_hi(a.x) + bf_lo(a.y) * bf_lo(a.y) + bf_hi(a.y) * bf_hi(a.y);
                n += bf_lo(a.z) * bf_lo(a.z) + bf_hi(a.z) * bf_hi(a.z) + bf_lo(a.w) * bf_lo(a.w) + bf_hi(a.w) * bf_hi(a.w);
                n += bf_lo(b.x) * bf_lo(b.x) + bf_hi(b.x) * bf_hi(b.x) + bf_lo(b.y) * bf_lo(b.y) + bf_hi(b.y) * bf_hi(b.y);
                n += bf_lo(b.z) * bf_lo(b.z) + bf_hi(b.z) * bf_hi(b.z) + bf_lo(b.w) * bf_lo(b.w) + bf_hi(b.w) * bf_hi(b.w);
                if ((POLY_MASK >> ((key >> 3) & 7)) & 1) n *= 0.25f;
#pragma unroll
                for (int o = 16; o; o >>= 1) n = fmaxf(n, __shfl_xor_sync(~0u, n, o));
                if (lane == 0) g_kmax[head * 64 + rb * 4 + (i & 3)] = n;
            }
            PROFH(39);
        }
        __syncwarp();
        cluster_arrive();
        cluster_wait();
    }
}

constexpr int K2_NCHUNK = 16;
constexpr int K2_AHEAD = 4;
constexpr int K2_CHUNK_BYTES = KV_HEAD_BYTES / K2_NCHUNK;
constexpr int K2_OFF_BAR = KV_HEAD_BYTES + 8 * KV_GROUP_BYTES;
constexpr int K2_OFF_Q = K2_OFF_BAR + 256;
constexpr int K2_SMEM = K2_OFF_Q + 12 * 512 * 4;

__device__ __forceinline__ float exp2_fixed(float y) {
    const float u = __uint_as_float(__float_as_uint(y) & 0xFF807FFFu) - 512.02545f;
    float t = fmaf(u, 0.019497588f, 0.114550486f);
    t = fmaf(t, u, -0.29839927f);
    return fmaf(t, u, y);
}
__device__ __forceinline__ uint32_t pack_fixed(float lo, float hi) { return __byte_perm(__float_as_uint(lo), __float_as_uint(hi), 0x6521); }

__device__ __forceinline__ void softmax_fast(const float (&s)[32], uint32_t (&p)[16]) {
#pragma unroll
    for (int b = 0; b < 8; b++) {
        if ((POLY_MASK >> b) & 1) {
            p[b * 2 + 0] = pack_fixed(exp2_fixed(s[b * 4 + 0]), exp2_fixed(s[b * 4 + 1]));
            p[b * 2 + 1] = pack_fixed(exp2_fixed(s[b * 4 + 2]), exp2_fixed(s[b * 4 + 3]));
        } else {
            p[b * 2 + 0] = pack_bf16(ex2(s[b * 4 + 0]), ex2(s[b * 4 + 1]));
            p[b * 2 + 1] = pack_bf16(ex2(s[b * 4 + 2]), ex2(s[b * 4 + 3]));
        }
    }
}

constexpr uint32_t K2_TILE = 8 * KV_GROUP_BYTES / 16;
__device__ __forceinline__ void issue_qk(float (&s)[32], const uint32_t (&qa)[8], uint32_t base) {
    wgmma_rs_n64<0>(s, qa[0], qa[1], qa[2], qa[3], base + (8u << 16), desc_hi(KV_GROUP_BYTES, 0), 0);
    wgmma_rs_n64<0>(s, qa[4], qa[5], qa[6], qa[7], base + 32, desc_hi(KV_GROUP_BYTES, 0), 1);
}
__device__ __forceinline__ void issue_pv(float (&o)[12], const uint32_t (&p)[16], uint32_t base) {
#pragma unroll
    for (int k = 0; k < 4; k++)
        wgmma_rs_n24<1>(o, p[k * 4], p[k * 4 + 1], p[k * 4 + 2], p[k * 4 + 3], base + 16 + ((KV_GROUP_BYTES / 16) << 16) + k * (2 * KV_GROUP_BYTES / 16),
                        desc_hi(128, 0), 1);
}

__global__ void __launch_bounds__(512, 1) k2_kernel() {
    extern __shared__ __align__(1024) uint8_t smem[];
    const uint32_t sb = s2u(smem);
    const int tid = threadIdx.x, lane = tid & 31;
    const int warp = __shfl_sync(~0u, tid >> 5, 0);
    const int wg = warp >> 2, wq = warp & 3, g = lane >> 2, q = lane & 3;
    const int head = blockIdx.x >> 2, quarter = blockIdx.x & 3;
    const uint32_t bar0 = sb + K2_OFF_BAR;
    PROF(16);
    if (tid == 0) {
        for (int i = 0; i <= K2_NCHUNK; i++) mbar_init(bar0 + i * 8, 1);
        asm volatile("mbarrier.arrive.shared::cta.b64 _, [%0];" ::"r"(bar0 + K2_NCHUNK * 8) : "memory");
        fence_barrier_init();
    }
    __syncthreads();
    griddep_wait();
    PROF(17);
    PROFT(50);
    uint32_t* qs = reinterpret_cast<uint32_t*>(smem + K2_OFF_Q) + tid;
    const uint8_t* kvsrc = g_QKV + (size_t)head * KV_HEAD_BYTES;
    int next_chunk = (tid == 0) ? K2_AHEAD : K2_NCHUNK;
    float kmax2;
    {
        uint32_t qv[12];
#pragma unroll
        for (int pass = 0; pass < 2; pass++) {
            const int row0 = quarter * 512 + (pass * 4 + wg) * 64 + wq * 16;
            const uint8_t* qp = g_QKV + Q_OFFSET + (size_t)head * KV_HEAD_BYTES + (row0 >> 3) * KV_GROUP_BYTES + g * 16 + q * 4;
            qv[pass * 6 + 0] = __ldcg(reinterpret_cast<const uint32_t*>(qp));
            qv[pass * 6 + 1] = __ldcg(reinterpret_cast<const uint32_t*>(qp + KV_GROUP_BYTES));
            qv[pass * 6 + 2] = __ldcg(reinterpret_cast<const uint32_t*>(qp + 128));
            qv[pass * 6 + 3] = __ldcg(reinterpret_cast<const uint32_t*>(qp + KV_GROUP_BYTES + 128));
            qv[pass * 6 + 4] = (q == 0) ? __ldcg(reinterpret_cast<const uint32_t*>(qp + 256)) : 0u;
            qv[pass * 6 + 5] = (q == 0) ? __ldcg(reinterpret_cast<const uint32_t*>(qp + KV_GROUP_BYTES + 256)) : 0u;
        }
        const float2 v = __ldcg(reinterpret_cast<const float2*>(g_kmax + head * 64 + lane * 2));
        if (lane == 0 && warp < K2_AHEAD) {
            mbar_expect(bar0 + warp * 8, K2_CHUNK_BYTES);
            bulk_load(sb + warp * K2_CHUNK_BYTES, kvsrc + warp * K2_CHUNK_BYTES, K2_CHUNK_BYTES, bar0 + warp * 8);
        }
        __syncwarp();
#pragma unroll
        for (int i = 0; i < 12; i++) qs[i * 512] = qv[i];
        kmax2 = fmaxf(v.x, v.y);
#pragma unroll
        for (int o = 16; o; o >>= 1) kmax2 = fmaxf(kmax2, __shfl_xor_sync(~0u, kmax2, o));
    }
    const uint32_t d0 = (sb & 0x3FFFF) >> 4;

#pragma unroll 1
    for (int pass = 0; pass < 2; pass++) {
        const int row0 = quarter * 512 + (pass * 4 + wg) * 64 + wq * 16;
        uint32_t qa[8];
#pragma unroll
        for (int i = 0; i < 6; i++) qa[i] = qs[(pass * 6 + i) * 512];
        qa[6] = 0u;
        float c0, c1;
        {
            float n0 = bf_lo(qa[0]) * bf_lo(qa[0]) + bf_hi(qa[0]) * bf_hi(qa[0]) + bf_lo(qa[2]) * bf_lo(qa[2]) + bf_hi(qa[2]) * bf_hi(qa[2]) +
                       bf_lo(qa[4]) * bf_lo(qa[4]) + bf_hi(qa[4]) * bf_hi(qa[4]);
            float n1 = bf_lo(qa[1]) * bf_lo(qa[1]) + bf_hi(qa[1]) * bf_hi(qa[1]) + bf_lo(qa[3]) * bf_lo(qa[3]) + bf_hi(qa[3]) * bf_hi(qa[3]) +
                       bf_lo(qa[5]) * bf_lo(qa[5]) + bf_hi(qa[5]) * bf_hi(qa[5]);
            n0 += __shfl_xor_sync(~0u, n0, 1); n1 += __shfl_xor_sync(~0u, n1, 1);
            n0 += __shfl_xor_sync(~0u, n0, 2); n1 += __shfl_xor_sync(~0u, n1, 2);
            c0 = sqrtf(n0 * kmax2) * 1.02f;
            c1 = sqrtf(n1 * kmax2) * 1.02f;
        }
        uint32_t slow;
        {
            const bool bad = !(c0 <= 58.f && c1 <= 58.f);
            asm volatile("{\n.reg .pred p, r;\nsetp.ne.u32 p, %1, 0;\nbarrier.cta.red.or.pred.aligned r, %2, 128, p;\nselp.u32 %0, 1, 0, r;\n}\n"
                         : "=r"(slow) : "r"((uint32_t)bad), "r"(wg + 1) : "memory");
        }
        slow = __any_sync(~0u, slow);
        float o[12];
#pragma unroll
        for (int i = 0; i < 12; i++) o[i] = 0.f;
        if (!slow && q == 1) {
            qa[4] = pack_bf16(-c0, 768.f); qa[5] = pack_bf16(-c1, 768.f);
            qa[6] = 0xC0000000u;
        }
        qa[7] = __shfl_sync(~0u, qa[6], lane);
        qa[6] = __shfl_sync(~0u, qa[6], lane ^ 4);

        if (!slow) {
            float s0[32], s1[32];
            uint32_t p[16];
            mbar_wait(bar0, 0);
            PROF(18 + pass * 3);
            reg_fence(qa);
            reg_fence(o);
            wg_fence();
            issue_qk(s0, qa, d0);
            wg_commit();
            uint32_t d = d0, bar = bar0;
#pragma unroll 1
            for (int t = 0; t < 16; t++) {
                wg_fence();
                issue_qk(s1, qa, d + K2_TILE);
                wg_commit();
                wg_wait<1>();
                reg_fence(s0);
                softmax_fast(s0, p);
                reg_fence(p);
                if (next_chunk < K2_NCHUNK) {
                    mbar_expect(bar0 + next_chunk * 8, K2_CHUNK_BYTES);
                    bulk_load(sb + next_chunk * K2_CHUNK_BYTES, kvsrc + next_chunk * K2_CHUNK_BYTES, K2_CHUNK_BYTES, bar0 + next_chunk * 8);
                    next_chunk++;
                }
                __syncwarp();
                bar += 8;
                mbar_wait(bar, 0);
                wg_fence();
                issue_pv(o, p, d);
                wg_commit();
                issue_qk(s0, qa, d + 2 * K2_TILE);
                wg_commit();
                wg_wait<1>();
                reg_fence(s1);
                softmax_fast(s1, p);
                reg_fence(p);
                wg_fence();
                issue_pv(o, p, d + K2_TILE);
                wg_commit();
                d += 2 * K2_TILE;
            }
            wg_wait<0>();
            reg_fence(o);
            reg_fence(s0);
        } else {
            float m0 = -INFINITY, m1 = -INFINITY;
            float s[32];
            uint32_t p[16];
            reg_fence(qa);
            for (; next_chunk < K2_NCHUNK; next_chunk++) {
                mbar_expect(bar0 + next_chunk * 8, K2_CHUNK_BYTES);
                bulk_load(sb + next_chunk * K2_CHUNK_BYTES, kvsrc + next_chunk * K2_CHUNK_BYTES, K2_CHUNK_BYTES, bar0 + next_chunk * 8);
            }
            __syncwarp();
#pragma unroll 1
            for (int t = 0; t < 32; t++) {
                mbar_wait(bar0 + (t / 2) * 8, 0);
                wg_fence();
                issue_qk(s, qa, d0 + t * K2_TILE);
                wg_commit();
                wg_wait<0>();
                reg_fence(s);
                reg_fence(o);
                float a0 = m0, a1 = m1;
#pragma unroll
                for (int k = 0; k < 8; k++) {
                    if ((POLY_MASK >> k) & 1) {
#pragma unroll
                        for (int i = 0; i < 4; i++) s[k * 4 + i] *= 0.5f;
                    }
                    a0 = fmaxf(a0, fmaxf(s[k * 4 + 0], s[k * 4 + 1]));
                    a1 = fmaxf(a1, fmaxf(s[k * 4 + 2], s[k * 4 + 3]));
                }
                a0 = fmaxf(a0, __shfl_xor_sync(~0u, a0, 1)); a1 = fmaxf(a1, __shfl_xor_sync(~0u, a1, 1));
                a0 = fmaxf(a0, __shfl_xor_sync(~0u, a0, 2)); a1 = fmaxf(a1, __shfl_xor_sync(~0u, a1, 2));
                const float r0 = ex2(m0 - a0), r1 = ex2(m1 - a1);
                m0 = a0; m1 = a1;
#pragma unroll
                for (int i = 0; i < 3; i++) { o[i * 4] *= r0; o[i * 4 + 1] *= r0; o[i * 4 + 2] *= r1; o[i * 4 + 3] *= r1; }
#pragma unroll
                for (int k = 0; k < 8; k++) {
                    p[k * 2 + 0] = pack_bf16(ex2(s[k * 4 + 0] - m0), ex2(s[k * 4 + 1] - m0));
                    p[k * 2 + 1] = pack_bf16(ex2(s[k * 4 + 2] - m1), ex2(s[k * 4 + 3] - m1));
                }
                reg_fence(p);
                reg_fence(o);
                wg_fence();
                issue_pv(o, p, d0 + t * K2_TILE);
                wg_commit();
                wg_wait<0>();
            }
            reg_fence(o);
        }
        PROF(19 + pass * 3);
        const float l0 = __shfl_sync(~0u, o[8], (lane & ~3) | 3), l1 = __shfl_sync(~0u, o[10], (lane & ~3) | 3);
        const float i0 = 1.0f / l0, i1 = 1.0f / l1;
#pragma unroll
        for (int i = 0; i < 3; i++) {
            const int pc = head * 9 + (i < 2 ? i * 4 + q : 8);
            uint32_t* op = g_O + ((((row0 >> 6) * 36 + (pc >> 3)) * 128 + wq * 32 + g * 4 + (pc & 3)) * 4 + ((pc >> 2) & 1) * 2);
            if (i < 2 || q == 2) *reinterpret_cast<uint2*>(op) = make_uint2(pack_bf16(o[i * 4] * i0, o[i * 4 + 1] * i0), pack_bf16(o[i * 4 + 2] * i1, o[i * 4 + 3] * i1));
        }
        PROF(20 + pass * 3);
        PROFT(51);
    }
}

constexpr int K3_PIECE = WO_TILE_BYTES / 9;
constexpr int K3_OFF_BAR = WO_TILE_BYTES;
constexpr int K3_SMEM = K3_OFF_BAR + 128;

__global__ void __cluster_dims__(2, 1, 1) __launch_bounds__(128, 1) k3_kernel(__nv_bfloat16* __restrict__ out) {
    extern __shared__ __align__(1024) uint8_t smem[];
    const uint32_t sb = s2u(smem);
    const int tid = threadIdx.x, warp = tid >> 5, lane = tid & 31;
    const int g = lane >> 2, q = lane & 3;
    const uint32_t rank = blockIdx.x & 1;
    const int ct = (blockIdx.x >> 1) & 3, rt = (blockIdx.x >> 3) * 2 + rank;
    const uint32_t bar0 = sb + K3_OFF_BAR;
    PROF(32);
    if (tid == 0) {
        for (int i = 0; i < 9; i++) { mbar_init(bar0 + i * 8, 1); mbar_expect(bar0 + i * 8, K3_PIECE); }
        fence_barrier_init();
    }
    cluster_arrive();
    cluster_wait();
    griddep_wait();
    PROF(33);
    PROFT(52);
    if (tid == 0 && blockIdx.x < 16) g_flag[blockIdx.x] = 0;
    uint4 a[36];
    const uint4* ap = reinterpret_cast<const uint4*>(g_O) + rt * 36 * 128 + tid;
#pragma unroll
    for (int k = 0; k < 4; k++) a[k] = __ldcg(ap + k * 128);
    if (tid < 9) {
        const uint32_t off = tid * K3_PIECE + rank * (K3_PIECE / 2);
        asm volatile("cp.async.bulk.shared::cluster.global.mbarrier::complete_tx::bytes.multicast::cluster [%0], [%1], %2, [%3], %4;"
                     ::"r"(sb + off), "l"(g_Wo + ct * WO_TILE_BYTES + off), "r"(K3_PIECE / 2), "r"(bar0 + tid * 8), "h"((uint16_t)3) : "memory");
    }
    float acc[72];
    {
        const float4* bp = g_base + ((rt >> 1) * 72 + ct * 18) * 256 + (rt & 1) * 128 + tid;
#pragma unroll
        for (int i = 0; i < 18; i++) {
            const float4 v = __ldcg(bp + i * 256);
            acc[i * 4 + 0] = v.x; acc[i * 4 + 1] = v.y; acc[i * 4 + 2] = v.z; acc[i * 4 + 3] = v.w;
        }
#pragma unroll
        for (int k = 4; k < 36; k++) a[k] = __ldcg(ap + k * 128);
#pragma unroll
        for (int i = 0; i < 72; i++) acc[i] *= 0.5f;
    }
    PROF(34);
    const uint32_t db = desc_lo(sb, 2304);
#pragma unroll
    for (int kb = 0; kb < 9; kb++) {
        mbar_wait(bar0 + kb * 8, 0);
        wg_fence();
#pragma unroll
        for (int k = 0; k < 4; k++) {
            const uint4 f = a[kb * 4 + k];
            wgmma_rs_n144<1>(acc, f.x, f.y, f.z, f.w, db + (((kb * 4 + k) * 4608) >> 4), desc_hi(128, 0), 1);
        }
        wg_commit();
    }
    wg_wait<0>();
    reg_fence(acc);
    PROF(35);
    uint32_t* op = reinterpret_cast<uint32_t*>(out + (size_t)(rt * 64 + warp * 16 + g) * DM + ct * 144 + q * 2);
#pragma unroll
    for (int b = 0; b < 18; b++) {
        op[b * 4] = pack_bf16(acc[b * 4], acc[b * 4 + 1]);
        op[b * 4 + 4 * DM] = pack_bf16(acc[b * 4 + 2], acc[b * 4 + 3]);
    }
    cluster_arrive();
    cluster_wait();
    PROF(36);
    PROFT(53);
}

typedef CUresult (*EncodeFn)(CUtensorMap*, CUtensorMapDataType, cuuint32_t, void*, const cuuint64_t*, const cuuint64_t*, const cuuint32_t*,
                             const cuuint32_t*, CUtensorMapInterleave, CUtensorMapSwizzle, CUtensorMapL2promotion, CUtensorMapFloatOOBfill);

void make_map(EncodeFn fn, CUtensorMap* m, const void* base, int rank, const cuuint64_t* dims, const cuuint64_t* strides, const cuuint32_t* box) {
    cuuint32_t es[3] = {1, 1, 1};
    fn(m, CU_TENSOR_MAP_DATA_TYPE_BFLOAT16, rank, const_cast<void*>(base), dims, strides, box, es, CU_TENSOR_MAP_INTERLEAVE_NONE,
       CU_TENSOR_MAP_SWIZZLE_128B, CU_TENSOR_MAP_L2_PROMOTION_L2_256B, CU_TENSOR_MAP_FLOAT_OOB_FILL_NONE);
}

}

extern "C" void kernel_launch(void* const* d_in, const int* in_sizes, int n_in, void* d_out, int out_size) {
    const __nv_bfloat16* x = (const __nv_bfloat16*)d_in[0];
    const __nv_bfloat16* wqkv = (const __nv_bfloat16*)d_in[1];
    const __nv_bfloat16* wo = (const __nv_bfloat16*)d_in[2];
    const __nv_bfloat16* w1 = (const __nv_bfloat16*)d_in[4];
    const __nv_bfloat16* b1 = (const __nv_bfloat16*)d_in[5];
    const __nv_bfloat16* w2 = (const __nv_bfloat16*)d_in[6];
    const __nv_bfloat16* b2 = (const __nv_bfloat16*)d_in[7];
    __nv_bfloat16* out = (__nv_bfloat16*)d_out;

    EncodeFn fn = nullptr;
    cudaDriverEntryPointQueryResult qr;
    cudaGetDriverEntryPoint("cuTensorMapEncodeTiled", (void**)&fn, cudaEnableDefault, &qr);
    CUtensorMap tmX, tmQ3, tmQ1, tm1, tm2;
    {
        cuuint64_t d[3] = {64, SEQ, 9}, s[2] = {DM * 2, 128};
        cuuint32_t b[3] = {64, 8, 9};
        make_map(fn, &tmX, x, 3, d, s, b);
    }
    {
        cuuint64_t d[3] = {3 * DM, DM, 3}, s[2] = {3 * DM * 2, 128};
        cuuint32_t b[3] = {64, 16, 3};
        make_map(fn, &tmQ3, wqkv, 3, d, s, b);
        make_map(fn, &tmQ1, wqkv, 2, d, s, b);
    }
    {
        cuuint64_t d[2] = {FF, DM}, s[1] = {FF * 2};
        cuuint32_t b[2] = {64, 64};
        make_map(fn, &tm1, w1, 2, d, s, b);
        cuuint64_t d2[2] = {DM, FF}, s2[1] = {DM * 2};
        make_map(fn, &tm2, w2, 2, d2, s2, b);
    }
    cudaFuncSetAttribute(k1_kernel, cudaFuncAttributeMaxDynamicSharedMemorySize, K1_SMEM);
    cudaFuncSetAttribute(k2_kernel, cudaFuncAttributeMaxDynamicSharedMemorySize, K2_SMEM);
    cudaFuncSetAttribute(k3_kernel, cudaFuncAttributeMaxDynamicSharedMemorySize, K3_SMEM);

    cudaStream_t st = cudaStreamPerThread;
    cudaLaunchAttribute pdl[1];
    pdl[0].id = cudaLaunchAttributeProgrammaticStreamSerialization;
    pdl[0].val.programmaticStreamSerializationAllowed = 1;
    {
        cudaLaunchConfig_t cfg = {};
        cfg.gridDim = dim3(128); cfg.blockDim = dim3(384); cfg.dynamicSmemBytes = K1_SMEM; cfg.stream = st;
        cudaLaunchKernelEx(&cfg, k1_kernel, tmX, tmQ3, tmQ1, tm1, tm2, b1, wo, x, b2);
    }
    {
        cudaLaunchConfig_t cfg = {};
        cfg.gridDim = dim3(128); cfg.blockDim = dim3(512); cfg.dynamicSmemBytes = K2_SMEM; cfg.stream = st;
        cfg.attrs = pdl; cfg.numAttrs = 1;
        cudaLaunchKernelEx(&cfg, k2_kernel);
    }
    {
        cudaLaunchConfig_t cfg = {};
        cfg.gridDim = dim3(128); cfg.blockDim = dim3(128); cfg.dynamicSmemBytes = K3_SMEM; cfg.stream = st;
        cfg.attrs = pdl; cfg.numAttrs = 1;
        cudaLaunchKernelEx(&cfg, k3_kernel, out);
    }
}
```

```cpp
#include <cuda_runtime.h>
#include <cuda_bf16.h>
#include <cuda.h>
#include <stdint.h>

#define PROF(i) do { } while (0)
#define PROFT(i) do { } while (0)
#define PROFH(i) do { } while (0)
#define PROF_WG 0

namespace {

constexpr int SEQ = 2048, DM = 576, FF = 4608, NH = 32, DH = 18;

constexpr int KV_GROUP_BYTES = 5 * 128;
constexpr int KV_HEAD_BYTES = (SEQ / 8) * KV_GROUP_BYTES;
constexpr int Q_OFFSET = NH * KV_HEAD_BYTES;
#define POLY_MASK 0xB6
__device__ __align__(1024) uint8_t g_QKV[2 * NH * KV_HEAD_BYTES];
__device__ __align__(1024) float g_kmax[NH * 64];
__device__ __align__(1024) float4 g_base[16 * 72 * 256];
__device__ __align__(1024) uint32_t g_O[SEQ * DM / 2];
__device__ unsigned int g_flag[16];
constexpr int WO_TILE_BYTES = DM * 144 * 2;
__device__ __align__(1024) uint8_t g_Wo[4 * WO_TILE_BYTES];

__device__ __forceinline__ uint32_t s2u(const void* p) { return (uint32_t)__cvta_generic_to_shared(p); }
__device__ __forceinline__ void mbar_init(uint32_t b, int c) { asm volatile("mbarrier.init.shared::cta.b64 [%0], %1;" ::"r"(b), "r"(c) : "memory"); }
__device__ __forceinline__ void mbar_expect(uint32_t b, uint32_t bytes) {
    asm volatile("mbarrier.arrive.expect_tx.shared::cta.b64 _, [%0], %1;" ::"r"(b), "r"(bytes) : "memory");
}
__device__ __forceinline__ void mbar_wait(uint32_t b, uint32_t parity) {
    asm volatile(
        "{\n.reg .pred p;\n.reg .u32 c;\n"
        "mbarrier.try_wait.parity.shared::cta.b64 p, [%0], %1;\n"
        "@p bra DONE;\n"
        "mov.u32 c, 0;\n"
        "LOOP:\n"
        "mbarrier.try_wait.parity.shared::cta.b64 p, [%0], %1;\n"
        "@p bra DONE;\n"
        "add.u32 c, c, 1;\n"
        "setp.lt.u32 p, c, 4194304;\n"
        "@p bra LOOP;\n"
        "trap;\n"
        "DONE:\n}\n" ::"r"(b), "r"(parity) : "memory");
}
__device__ __forceinline__ void fence_barrier_init() { asm volatile("fence.mbarrier_init.release.cluster;" ::: "memory"); }
__device__ __forceinline__ void fence_proxy_async() { asm volatile("fence.proxy.async.shared::cta;" ::: "memory"); }
__device__ __forceinline__ void cluster_arrive() { asm volatile("barrier.cluster.arrive.relaxed.aligned;" ::: "memory"); }
__device__ __forceinline__ void cluster_wait() { asm volatile("barrier.cluster.wait.aligned;" ::: "memory"); }
__device__ __forceinline__ void named_bar_sync(int id, int n) { asm volatile("bar.sync %0, %1;" ::"r"(id), "r"(n) : "memory"); }
__device__ __forceinline__ void griddep_wait() { asm volatile("griddepcontrol.wait;" ::: "memory"); }
__device__ __forceinline__ void griddep_launch() { asm volatile("griddepcontrol.launch_dependents;" ::: "memory"); }

__device__ __forceinline__ void tma3d_mc(uint32_t dst, const CUtensorMap* tm, int c0, int c1, int c2, uint32_t bar, uint16_t mask) {
    asm volatile("cp.async.bulk.tensor.3d.shared::cluster.global.mbarrier::complete_tx::bytes.multicast::cluster [%0], [%1, {%3, %4, %5}], [%2], %6;"
                 ::"r"(dst), "l"(tm), "r"(bar), "r"(c0), "r"(c1), "r"(c2), "h"(mask) : "memory");
}
__device__ __forceinline__ void tma2d_mc(uint32_t dst, const CUtensorMap* tm, int c0, int c1, uint32_t bar, uint16_t mask) {
    asm volatile("cp.async.bulk.tensor.2d.shared::cluster.global.mbarrier::complete_tx::bytes.multicast::cluster [%0], [%1, {%3, %4}], [%2], %5;"
                 ::"r"(dst), "l"(tm), "r"(bar), "r"(c0), "r"(c1), "h"(mask) : "memory");
}
__device__ __forceinline__ void tma3d(uint32_t dst, const CUtensorMap* tm, int c0, int c1, int c2, uint32_t bar) {
    asm volatile("cp.async.bulk.tensor.3d.shared::cluster.global.mbarrier::complete_tx::bytes [%0], [%1, {%3, %4, %5}], [%2];"
                 ::"r"(dst), "l"(tm), "r"(bar), "r"(c0), "r"(c1), "r"(c2) : "memory");
}
__device__ __forceinline__ void tma2d(uint32_t dst, const CUtensorMap* tm, int c0, int c1, uint32_t bar) {
    asm volatile("cp.async.bulk.tensor.2d.shared::cluster.global.mbarrier::complete_tx::bytes [%0], [%1, {%3, %4}], [%2];"
                 ::"r"(dst), "l"(tm), "r"(bar), "r"(c0), "r"(c1) : "memory");
}
__device__ __forceinline__ void bulk_load(uint32_t dst, const void* src, uint32_t bytes, uint32_t bar) {
    asm volatile("cp.async.bulk.shared::cluster.global.mbarrier::complete_tx::bytes [%0], [%1], %2, [%3];"
                 ::"r"(dst), "l"(src), "r"(bytes), "r"(bar) : "memory");
}
__device__ __forceinline__ void prefetch_tmap(const CUtensorMap* tm) { asm volatile("prefetch.tensormap [%0];" ::"l"(tm) : "memory"); }

__device__ __forceinline__ void wg_fence() { asm volatile("wgmma.fence.sync.aligned;" ::: "memory"); }
__device__ __forceinline__ void wg_commit() { asm volatile("wgmma.commit_group.sync.aligned;" ::: "memory"); }
template <int N> __device__ __forceinline__ void wg_wait() { asm volatile("wgmma.wait_group.sync.aligned %0;" ::"n"(N) : "memory"); }
template <int N> __device__ __forceinline__ void reg_fence(float (&d)[N]) {
#pragma unroll
    for (int i = 0; i < N; i++) asm volatile("" : "+f"(d[i])::"memory");
}
template <int N> __device__ __forceinline__ void reg_fence(uint32_t (&d)[N]) {
#pragma unroll
    for (int i = 0; i < N; i++) asm volatile("" : "+r"(d[i])::"memory");
}
template <int R> __device__ __forceinline__ void reg_alloc() { asm volatile("setmaxnreg.inc.sync.aligned.u32 %0;" ::"n"(R)); }
template <int R> __device__ __forceinline__ void reg_dealloc() { asm volatile("setmaxnreg.dec.sync.aligned.u32 %0;" ::"n"(R)); }

__device__ __forceinline__ uint32_t desc_lo(uint32_t addr, uint32_t lbo) { return ((addr & 0x3FFFF) >> 4) | ((lbo >> 4) << 16); }
__host__ __device__ constexpr uint32_t desc_hi(uint32_t sbo, uint32_t swz) { return (sbo >> 4) | (swz << 30); }
__device__ __forceinline__ uint32_t pack_bf16(float lo, float hi) {
    uint32_t r;
    asm("cvt.rn.bf16x2.f32 %0, %1, %2;" : "=r"(r) : "f"(hi), "f"(lo));
    return r;
}
__device__ __forceinline__ float bf_lo(uint32_t w) { return __uint_as_float(w << 16); }
__device__ __forceinline__ float bf_hi(uint32_t w) { return __uint_as_float(w & 0xFFFF0000u); }
__device__ __forceinline__ float ex2(float x) {
    float r;
    asm("ex2.approx.ftz.f32 %0, %1;" : "=f"(r) : "f"(x));
    return r;
}
__device__ __forceinline__ float tanh_fast(float x) {
    float r;
    asm("tanh.approx.f32 %0, %1;" : "=f"(r) : "f"(x));
    return r;
}
__device__ __forceinline__ float gelu2(float u) {
    const float w = fmaf(u * u, 0.0356774081f, 0.7978845608f);
    return fmaf(u, tanh_fast(u * w), u);
}

template<int TB> __device__ __forceinline__ void wgmma_ss_n216(float (&d)[108], uint32_t alo, uint32_t ahi, uint32_t blo, uint32_t bhi, int sd) {
    asm volatile("{\n.reg .pred p;\n.reg .b64 da, db;\nsetp.ne.b32 p, %110, 0;\nmov.b64 da, {%108, %112};\nmov.b64 db, {%109, %113};\n"
      "wgmma.mma_async.sync.aligned.m64n216k16.f32.bf16.bf16 {%0, %1, %2, %3, %4, %5, %6, %7, %8, %9, %10, %11, %12, %13, %14, %15, %16, %17, %18, %19, %20, %21, %22, %23, %24, %25, %26, %27, %28, %29, %30, %31, %32, %33, %34, %35, %36, %37, %38, %39, %40, %41, %42, %43, %44, %45, %46, %47, %48, %49, %50, %51, %52, %53, %54, %55, %56, %57, %58, %59, %60, %61, %62, %63, %64, %65, %66, %67, %68, %69, %70, %71, %72, %73, %74, %75, %76, %77, %78, %79, %80, %81, %82, %83, %84, %85, %86, %87, %88, %89, %90, %91, %92, %93, %94, %95, %96, %97, %98, %99, %100, %101, %102, %103, %104, %105, %106, %107}, da, db, p, 1, 1, 0, %111;\n}\n"
      : "+f"(d[0]), "+f"(d[1]), "+f"(d[2]), "+f"(d[3]), "+f"(d[4]), "+f"(d[5]), "+f"(d[6]), "+f"(d[7]), "+f"(d[8]), "+f"(d[9]), "+f"(d[10]), "+f"(d[11]), "+f"(d[12]), "+f"(d[13]), "+f"(d[14]), "+f"(d[15]), "+f"(d[16]), "+f"(d[17]), "+f"(d[18]), "+f"(d[19]), "+f"(d[20]), "+f"(d[21]), "+f"(d[22]), "+f"(d[23]), "+f"(d[24]), "+f"(d[25]), "+f"(d[26]), "+f"(d[27]), "+f"(d[28]), "+f"(d[29]), "+f"(d[30]), "+f"(d[31]), "+f"(d[32]), "+f"(d[33]), "+f"(d[34]), "+f"(d[35]), "+f"(d[36]), "+f"(d[37]), "+f"(d[38]), "+f"(d[39]), "+f"(d[40]), "+f"(d[41]), "+f"(d[42]), "+f"(d[43]), "+f"(d[44]), "+f"(d[45]), "+f"(d[46]), "+f"(d[47]), "+f"(d[48]), "+f"(d[49]), "+f"(d[50]), "+f"(d[51]), "+f"(d[52]), "+f"(d[53]), "+f"(d[54]), "+f"(d[55]), "+f"(d[56]), "+f"(d[57]), "+f"(d[58]), "+f"(d[59]), "+f"(d[60]), "+f"(d[61]), "+f"(d[62]), "+f"(d[63]), "+f"(d[64]), "+f"(d[65]), "+f"(d[66]), "+f"(d[67]), "+f"(d[68]), "+f"(d[69]), "+f"(d[70]), "+f"(d[71]), "+f"(d[72]), "+f"(d[73]), "+f"(d[74]), "+f"(d[75]), "+f"(d[76]), "+f"(d[77]), "+f"(d[78]), "+f"(d[79]), "+f"(d[80]), "+f"(d[81]), "+f"(d[82]), "+f"(d[83]), "+f"(d[84]), "+f"(d[85]), "+f"(d[86]), "+f"(d[87]), "+f"(d[88]), "+f"(d[89]), "+f"(d[90]), "+f"(d[91]), "+f"(d[92]), "+f"(d[93]), "+f"(d[94]), "+f"(d[95]), "+f"(d[96]), "+f"(d[97]), "+f"(d[98]), "+f"(d[99]), "+f"(d[100]), "+f"(d[101]), "+f"(d[102]), "+f"(d[103]), "+f"(d[104]), "+f"(d[105]), "+f"(d[106]), "+f"(d[107])
      : "r"(alo), "r"(blo), "r"(sd), "n"(TB), "r"(ahi), "r"(bhi));
}

template<int TB> __device__ __forceinline__ void wgmma_ss_n64(float (&d)[32], uint32_t alo, uint32_t ahi, uint32_t blo, uint32_t bhi, int sd) {
    asm volatile("{\n.reg .pred p;\n.reg .b64 da, db;\nsetp.ne.b32 p, %34, 0;\nmov.b64 da, {%32, %36};\nmov.b64 db, {%33, %37};\n"
      "wgmma.mma_async.sync.aligned.m64n64k16.f32.bf16.bf16 {%0, %1, %2, %3, %4, %5, %6, %7, %8, %9, %10, %11, %12, %13, %14, %15, %16, %17, %18, %19, %20, %21, %22, %23, %24, %25, %26, %27, %28, %29, %30, %31}, da, db, p, 1, 1, 0, %35;\n}\n"
      : "+f"(d[0]), "+f"(d[1]), "+f"(d[2]), "+f"(d[3]), "+f"(d[4]), "+f"(d[5]), "+f"(d[6]), "+f"(d[7]), "+f"(d[8]), "+f"(d[9]), "+f"(d[10]), "+f"(d[11]), "+f"(d[12]), "+f"(d[13]), "+f"(d[14]), "+f"(d[15]), "+f"(d[16]), "+f"(d[17]), "+f"(d[18]), "+f"(d[19]), "+f"(d[20]), "+f"(d[21]), "+f"(d[22]), "+f"(d[23]), "+f"(d[24]), "+f"(d[25]), "+f"(d[26]), "+f"(d[27]), "+f"(d[28]), "+f"(d[29]), "+f"(d[30]), "+f"(d[31])
      : "r"(alo), "r"(blo), "r"(sd), "n"(TB), "r"(ahi), "r"(bhi));
}

template<int TB> __device__ __forceinline__ void wgmma_rs_n64(float (&d)[32], uint32_t a0, uint32_t a1, uint32_t a2, uint32_t a3, uint32_t blo, uint32_t bhi, int sd) {
    asm volatile("{\n.reg .pred p;\n.reg .b64 db;\nsetp.ne.b32 p, %37, 0;\nmov.b64 db, {%36, %39};\n"
      "wgmma.mma_async.sync.aligned.m64n64k16.f32.bf16.bf16 {%0, %1, %2, %3, %4, %5, %6, %7, %8, %9, %10, %11, %12, %13, %14, %15, %16, %17, %18, %19, %20, %21, %22, %23, %24, %25, %26, %27, %28, %29, %30, %31}, {%32, %33, %34, %35}, db, p, 1, 1, %38;\n}\n"
      : "+f"(d[0]), "+f"(d[1]), "+f"(d[2]), "+f"(d[3]), "+f"(d[4]), "+f"(d[5]), "+f"(d[6]), "+f"(d[7]), "+f"(d[8]), "+f"(d[9]), "+f"(d[10]), "+f"(d[11]), "+f"(d[12]), "+f"(d[13]), "+f"(d[14]), "+f"(d[15]), "+f"(d[16]), "+f"(d[17]), "+f"(d[18]), "+f"(d[19]), "+f"(d[20]), "+f"(d[21]), "+f"(d[22]), "+f"(d[23]), "+f"(d[24]), "+f"(d[25]), "+f"(d[26]), "+f"(d[27]), "+f"(d[28]), "+f"(d[29]), "+f"(d[30]), "+f"(d[31])
      : "r"(a0), "r"(a1), "r"(a2), "r"(a3), "r"(blo), "r"(sd), "n"(TB), "r"(bhi));
}

template<int TB> __device__ __forceinline__ void wgmma_rs_n24(float (&d)[12], uint32_t a0, uint32_t a1, uint32_t a2, uint32_t a3, uint32_t blo, uint32_t bhi, int sd) {
    asm volatile("{\n.reg .pred p;\n.reg .b64 db;\nsetp.ne.b32 p, %17, 0;\nmov.b64 db, {%16, %19};\n"
      "wgmma.mma_async.sync.aligned.m64n24k16.f32.bf16.bf16 {%0, %1, %2, %3, %4, %5, %6, %7, %8, %9, %10, %11}, {%12, %13, %14, %15}, db, p, 1, 1, %18;\n}\n"
      : "+f"(d[0]), "+f"(d[1]), "+f"(d[2]), "+f"(d[3]), "+f"(d[4]), "+f"(d[5]), "+f"(d[6]), "+f"(d[7]), "+f"(d[8]), "+f"(d[9]), "+f"(d[10]), "+f"(d[11])
      : "r"(a0), "r"(a1), "r"(a2), "r"(a3), "r"(blo), "r"(sd), "n"(TB), "r"(bhi));
}

template<int TB> __device__ __forceinline__ void wgmma_rs_n144(float (&d)[72], uint32_t a0, uint32_t a1, uint32_t a2, uint32_t a3, uint32_t blo, uint32_t bhi, int sd) {
    asm volatile("{\n.reg .pred p;\n.reg .b64 db;\nsetp.ne.b32 p, %77, 0;\nmov.b64 db, {%76, %79};\n"
      "wgmma.mma_async.sync.aligned.m64n144k16.f32.bf16.bf16 {%0, %1, %2, %3, %4, %5, %6, %7, %8, %9, %10, %11, %12, %13, %14, %15, %16, %17, %18, %19, %20, %21, %22, %23, %24, %25, %26, %27, %28, %29, %30, %31, %32, %33, %34, %35, %36, %37, %38, %39, %40, %41, %42, %43, %44, %45, %46, %47, %48, %49, %50, %51, %52, %53, %54, %55, %56, %57, %58, %59, %60, %61, %62, %63, %64, %65, %66, %67, %68, %69, %70, %71}, {%72, %73, %74, %75}, db, p, 1, 1, %78;\n}\n"
      : "+f"(d[0]), "+f"(d[1]), "+f"(d[2]), "+f"(d[3]), "+f"(d[4]), "+f"(d[5]), "+f"(d[6]), "+f"(d[7]), "+f"(d[8]), "+f"(d[9]), "+f"(d[10]), "+f"(d[11]), "+f"(d[12]), "+f"(d[13]), "+f"(d[14]), "+f"(d[15]), "+f"(d[16]), "+f"(d[17]), "+f"(d[18]), "+f"(d[19]), "+f"(d[20]), "+f"(d[21]), "+f"(d[22]), "+f"(d[23]), "+f"(d[24]), "+f"(d[25]), "+f"(d[26]), "+f"(d[27]), "+f"(d[28]), "+f"(d[29]), "+f"(d[30]), "+f"(d[31]), "+f"(d[32]), "+f"(d[33]), "+f"(d[34]), "+f"(d[35]), "+f"(d[36]), "+f"(d[37]), "+f"(d[38]), "+f"(d[39]), "+f"(d[40]), "+f"(d[41]), "+f"(d[42]), "+f"(d[43]), "+f"(d[44]), "+f"(d[45]), "+f"(d[46]), "+f"(d[47]), "+f"(d[48]), "+f"(d[49]), "+f"(d[50]), "+f"(d[51]), "+f"(d[52]), "+f"(d[53]), "+f"(d[54]), "+f"(d[55]), "+f"(d[56]), "+f"(d[57]), "+f"(d[58]), "+f"(d[59]), "+f"(d[60]), "+f"(d[61]), "+f"(d[62]), "+f"(d[63]), "+f"(d[64]), "+f"(d[65]), "+f"(d[66]), "+f"(d[67]), "+f"(d[68]), "+f"(d[69]), "+f"(d[70]), "+f"(d[71])
      : "r"(a0), "r"(a1), "r"(a2), "r"(a3), "r"(blo), "r"(sd), "n"(TB), "r"(bhi));
}

constexpr int K1_XN_BYTES = 16 * 9216;
constexpr int K1_SLOT = 16384, K1_NSLOT = 5;
constexpr int K1_OFF_RING = K1_XN_BYTES;
constexpr int K1_OFF_BIAS = K1_OFF_RING + K1_NSLOT * K1_SLOT;
constexpr int K1_OFF_BAR = K1_OFF_BIAS + 576 * 2;
constexpr int K1_SMEM = K1_OFF_BAR + 256 + 128;
constexpr float QSCALE = 0.23570226039551584f * 1.4426950408889634f;

struct Ring {
    uint32_t slot, phase;
    __device__ __forceinline__ void advance() {
        if (++slot == K1_NSLOT) { slot = 0; phase ^= 1; }
    }
};

struct K1Ctx {
    uint32_t full0;
    uint32_t rel_addr;
    uint32_t descA, descB;
    Ring rd;
    uint32_t prev_slot;
    __device__ __forceinline__ uint32_t begin_stage() {
        mbar_wait(full0 + rd.slot * 8, rd.phase);
        wg_fence();
        return descB + rd.slot * (K1_SLOT >> 4);
    }
    __device__ __forceinline__ void end_stage() {
        wg_commit();
        wg_wait<1>();
        if (rel_addr) asm volatile("mbarrier.arrive.shared::cluster.b64 _, [%0];" ::"r"(rel_addr + prev_slot * 8) : "memory");
        prev_slot = rd.slot;
        rd.advance();
    }
};

__device__ __forceinline__ uint32_t descA_step(uint32_t base, int ks) { return base + (((ks >> 2) * 1024 + (ks & 3) * 32) >> 4); }
constexpr uint32_t K1_AHI = desc_hi(9216, 1), K1_BHI = desc_hi(1024, 1);

template <int V> struct IC { static constexpr int value = V; };
template <int I, int N, class F> __device__ __forceinline__ void static_for(F&& f) {
    if constexpr (I < N) { f(IC<I>{}); static_for<I + 1, N>(f); }
}

template <bool A_RS, bool B_RS, class Epi>
__device__ __forceinline__ void tile_pair(K1Ctx& c, float (&accA)[32], float (&accB)[32], uint32_t (&h)[144], Epi&& epi) {
    static_for<0, 9>([&](auto sc) {
        constexpr int s = decltype(sc)::value;
        const uint32_t db = c.begin_stage();
#pragma unroll
        for (int t = 0; t < 8; t++) {
            const int kk = s * 8 + t, ks = kk % 36;
            const uint32_t dbt = db + ((t * 2048) >> 4);
            if (kk < 36) {
                if constexpr (A_RS) wgmma_rs_n64<1>(accA, h[ks * 4], h[ks * 4 + 1], h[ks * 4 + 2], h[ks * 4 + 3], dbt, K1_BHI, ks != 0);
                else wgmma_ss_n64<1>(accA, descA_step(c.descA, ks), K1_AHI, dbt, K1_BHI, ks != 0);
            } else {
                if constexpr (B_RS) wgmma_rs_n64<1>(accB, h[ks * 4], h[ks * 4 + 1], h[ks * 4 + 2], h[ks * 4 + 3], dbt, K1_BHI, ks != 0);
                else wgmma_ss_n64<1>(accB, descA_step(c.descA, ks), K1_AHI, dbt, K1_BHI, ks != 0);
            }
        }
        c.end_stage();
        epi(sc);
    });
}

template <int B0, int NB, int HOFF>
__device__ __forceinline__ void gelu_blocks(const float (&acc)[32], uint32_t (&h)[144], const uint32_t (&bq)[8]) {
#pragma unroll
    for (int b = B0; b < B0 + NB; b++) {
        const float b0 = bf_lo(bq[b]), b1 = bf_hi(bq[b]);
        h[HOFF + b * 2 + 0] = pack_bf16(gelu2(acc[b * 4 + 0] + b0), gelu2(acc[b * 4 + 1] + b1));
        h[HOFF + b * 2 + 1] = pack_bf16(gelu2(acc[b * 4 + 2] + b0), gelu2(acc[b * 4 + 3] + b1));
    }
}
__device__ __forceinline__ void load_bias(uint32_t (&bq)[8], uint32_t addr) {
    asm volatile("ld.shared.v4.u32 {%0, %1, %2, %3}, [%4];" : "=r"(bq[0]), "=r"(bq[1]), "=r"(bq[2]), "=r"(bq[3]) : "r"(addr));
    asm volatile("ld.shared.v4.u32 {%0, %1, %2, %3}, [%4 + 16];" : "=r"(bq[4]), "=r"(bq[5]), "=r"(bq[6]), "=r"(bq[7]) : "r"(addr));
}
template <int S> __device__ __forceinline__ void store_part(const float (&o)[32], float4* p) {
    asm volatile("red.global.add.v4.f32 [%0], {%1, %2, %3, %4};" ::"l"(p + S * 512), "f"(o[S * 8]), "f"(o[S * 8 + 1]), "f"(o[S * 8 + 2]), "f"(o[S * 8 + 3]) : "memory");
    asm volatile("red.global.add.v4.f32 [%0], {%1, %2, %3, %4};" ::"l"(p + S * 512 + 256), "f"(o[S * 8 + 4]), "f"(o[S * 8 + 5]), "f"(o[S * 8 + 6]), "f"(o[S * 8 + 7]) : "memory");
}

__global__ void __cluster_dims__(2, 1, 1) __launch_bounds__(384, 1)
k1_kernel(const __grid_constant__ CUtensorMap tmX, const __grid_constant__ CUtensorMap tmQ3, const __grid_constant__ CUtensorMap tmQ1,
          const __grid_constant__ CUtensorMap tm1, const __grid_constant__ CUtensorMap tm2, const __nv_bfloat16* __restrict__ b1,
          const __nv_bfloat16* __restrict__ wo, const __nv_bfloat16* __restrict__ x, const __nv_bfloat16* __restrict__ b2) {
    extern __shared__ __align__(1024) uint8_t smem[];
    const uint32_t sb = s2u(smem);
    const int tid = threadIdx.x, lane = tid & 31;
    const int warp = __shfl_sync(~0u, tid >> 5, 0);
    const uint32_t rank = blockIdx.x & 1;
    const int cl = blockIdx.x >> 1;
    const int rb = (cl & 7) * 2 + rank;
    const int j = cl >> 3;
    const uint32_t full0 = sb + K1_OFF_BAR, empty0 = full0 + 8 * K1_NSLOT, xbar0 = full0 + 128, ibar = full0 + 256;

    if (warp < 8) {
        PROF(0);
        PROFT(48);
        if (lane == 0) {
            mbar_init(xbar0 + warp * 16, 1);
            mbar_init(xbar0 + warp * 16 + 8, 1);
            fence_barrier_init();
            mbar_expect(xbar0 + warp * 16, 9216);
            tma3d(sb + warp * 2 * 9216, &tmX, 0, rb * 128 + warp * 16, 0, xbar0 + warp * 16);
            mbar_expect(xbar0 + warp * 16 + 8, 9216);
            tma3d(sb + (warp * 2 + 1) * 9216, &tmX, 0, rb * 128 + warp * 16 + 8, 0, xbar0 + warp * 16 + 8);
        }
        __syncwarp();
        cluster_arrive();
        reg_alloc<240>();
#pragma unroll 1
        for (int p = 0; p < 4; p++) {
            mbar_wait(xbar0 + warp * 16 + (p >> 1) * 8, 0);
            uint4* row = reinterpret_cast<uint4*>(smem + (warp * 2 + (p >> 1)) * 9216 + (p & 1) * 512 + lane * 16);
            float f[72];
#pragma unroll
            for (int i = 0; i < 9; i++) {
                const uint4 v = row[i * 64];
                f[i * 8 + 0] = bf_lo(v.x); f[i * 8 + 1] = bf_hi(v.x); f[i * 8 + 2] = bf_lo(v.y); f[i * 8 + 3] = bf_hi(v.y);
                f[i * 8 + 4] = bf_lo(v.z); f[i * 8 + 5] = bf_hi(v.z); f[i * 8 + 6] = bf_lo(v.w); f[i * 8 + 7] = bf_hi(v.w);
            }
            float s0 = 0.f, s1 = 0.f, s2 = 0.f, s3 = 0.f;
#pragma unroll
            for (int i = 0; i < 72; i += 4) { s0 += f[i]; s1 += f[i + 1]; s2 += f[i + 2]; s3 += f[i + 3]; }
            float sm = (s0 + s1) + (s2 + s3);
            sm += __shfl_xor_sync(~0u, sm, 1); sm += __shfl_xor_sync(~0u, sm, 2); sm += __shfl_xor_sync(~0u, sm, 4);
            const float mean = sm * (1.0f / DM);
            s0 = s1 = s2 = s3 = 0.f;
#pragma unroll
            for (int i = 0; i < 72; i += 4) {
                f[i] -= mean; f[i + 1] -= mean; f[i + 2] -= mean; f[i + 3] -= mean;
                s0 = fmaf(f[i], f[i], s0); s1 = fmaf(f[i + 1], f[i + 1], s1);
                s2 = fmaf(f[i + 2], f[i + 2], s2); s3 = fmaf(f[i + 3], f[i + 3], s3);
            }
            float sq = (s0 + s1) + (s2 + s3);
            sq += __shfl_xor_sync(~0u, sq, 1); sq += __shfl_xor_sync(~0u, sq, 2); sq += __shfl_xor_sync(~0u, sq, 4);
            const float rstd = rsqrtf(sq * (1.0f / DM) + 1e-5f);
#pragma unroll
            for (int i = 0; i < 9; i++) {
                uint4 o;
                o.x = pack_bf16(f[i * 8 + 0] * rstd, f[i * 8 + 1] * rstd);
                o.y = pack_bf16(f[i * 8 + 2] * rstd, f[i * 8 + 3] * rstd);
                o.z = pack_bf16(f[i * 8 + 4] * rstd, f[i * 8 + 5] * rstd);
                o.w = pack_bf16(f[i * 8 + 6] * rstd, f[i * 8 + 7] * rstd);
                row[i * 64] = o;
            }
        }
        const int wg = warp >> 2, wq = warp & 3;
        fence_proxy_async();
        named_bar_sync(1 + wg, 128);
        cluster_wait();
        PROF(1);

        const int g = lane >> 2, q = lane & 3;
        K1Ctx c;
        c.full0 = full0;
        c.rel_addr = 0;
        c.descA = desc_lo(sb + wg * 8 * 9216, 16);
        c.descB = desc_lo(sb + K1_OFF_RING, 2048);
        c.rd.slot = 0; c.rd.phase = 0; c.prev_slot = 0;
        uint32_t biasq = sb + K1_OFF_BIAS + q * 32;
        uint32_t bq[8];

        uint32_t h[144];
        float accA[32], accB[32];
        {
            float accQ[108];
            uint32_t rel = 0;
            if (lane == 0 && wq < 2) asm("mapa.shared::cluster.u32 %0, %1, %2;" : "=r"(rel) : "r"(empty0), "r"(wq));
#pragma unroll 1
            for (int s = 0; s < 18; s++) {
                const uint32_t db = c.begin_stage();
                const uint32_t da = c.descA + (s >> 1) * 64 + (s & 1) * 4;
                wgmma_ss_n216<1>(accQ, da, K1_AHI, db, K1_BHI, s != 0);
                wgmma_ss_n216<1>(accQ, da + 2, K1_AHI, db + (8192 >> 4), K1_BHI, 1);
                c.end_stage();
                c.rel_addr = rel;
            }
            PROF(2);
            uint32_t rel9[9];
#pragma unroll
            for (int i9 = 0; i9 < 9; i9++) {
                const int p = 4 * i9 + q, hh = (p * 57) >> 9, r = p - 9 * hh;
                rel9[i9] = hh * KV_HEAD_BYTES + (r < 8 ? (r >> 2) * 128 + (r & 3) * 4 : 0);
            }
            uint32_t gb = 0, o2 = 0;
            float scl0 = 1.f, scl1 = 1.f;
            tile_pair<false, false>(c, accA, accB, h, [&](auto sc) {
                constexpr int s = decltype(sc)::value;
                if constexpr (s == 0) reg_fence(accQ);
                if constexpr (s < 6) {
                    constexpr int grp = s / 2, part = s % 2;
                    if constexpr (part == 0) {
                        const int G = 3 * j + grp, type = G >> 3;
                        gb = (G & 7) * 4 * KV_HEAD_BYTES + (rb * 16 + warp * 2) * KV_GROUP_BYTES + g * 16 + (type == 0 ? Q_OFFSET : (type == 2 ? 256 : 0));
                        o2 = type == 0 ? 256 : (type == 2 ? 264 : 512);
                        scl0 = type == 0 ? QSCALE : ((type == 1 && ((POLY_MASK >> (wq * 2)) & 1)) ? 2.f : 1.f);
                        scl1 = type == 0 ? QSCALE : ((type == 1 && ((POLY_MASK >> (wq * 2 + 1)) & 1)) ? 2.f : 1.f);
                    }
#pragma unroll
                    for (int i9 = part * 5; i9 < (part ? 9 : 5); i9++) {
                        const int b = grp * 9 + i9;
                        uint32_t off = gb + rel9[i9];
                        if (i9 >= 2 && (i9 & 1) == 0) off += (q == i9 / 2 - 1) ? o2 : 0;
                        *reinterpret_cast<uint32_t*>(g_QKV + off) = pack_bf16(accQ[b * 4] * scl0, accQ[b * 4 + 1] * scl0);
                        *reinterpret_cast<uint32_t*>(g_QKV + off + KV_GROUP_BYTES) = pack_bf16(accQ[b * 4 + 2] * scl1, accQ[b * 4 + 3] * scl1);
                    }
                    if constexpr (s == 5) asm volatile("bar.arrive 3, 352;" ::: "memory");
                }
                if constexpr (s == 4) { named_bar_sync(4, 352); load_bias(bq, biasq); }
                if constexpr (s == 5) reg_fence(accA);
                if constexpr (s >= 5) gelu_blocks<(s - 5) * 2, 2, 96>(accA, h, bq);
                if constexpr (s == 8) load_bias(bq, biasq + 128);
            });
        }
        PROF(3);
#pragma unroll
        for (int i = 32; i < 96; i++) asm volatile("mov.u32 %0, 0;" : "=r"(h[i]));
#pragma unroll 1
        for (int p = 1; p < 4; p++) {
            biasq += 256;
            tile_pair<false, false>(c, accA, accB, h, [&](auto sc) {
                constexpr int s = decltype(sc)::value;
                if constexpr (s == 0) {
                    reg_fence(accB);
#pragma unroll
                    for (int i = 0; i < 80; i++) h[i] = h[i + 32];
                }
                if constexpr (s < 4) gelu_blocks<s * 2, 2, 80>(accB, h, bq);
                if constexpr (s == 4) load_bias(bq, biasq);
                if constexpr (s == 5) reg_fence(accA);
                if constexpr (s >= 5) gelu_blocks<(s - 5) * 2, 2, 96>(accA, h, bq);
                if constexpr (s == 8) load_bias(bq, biasq + 128);
            });
        }
        PROF(4);
        tile_pair<false, true>(c, accA, accB, h, [&](auto sc) {
            constexpr int s = decltype(sc)::value;
            if constexpr (s == 0) reg_fence(accB);
            if constexpr (s < 4) gelu_blocks<s * 2, 2, 112>(accB, h, bq);
            if constexpr (s == 4) load_bias(bq, biasq + 256);
            if constexpr (s == 5) reg_fence(accA);
            if constexpr (s == 5 || s == 6) gelu_blocks<(s - 5) * 3, 3, 128>(accA, h, bq);
            if constexpr (s == 7) gelu_blocks<6, 2, 128>(accA, h, bq);
            if constexpr (s == 3 || s == 7) reg_fence(h);
        });
        PROF(5);
        float4* const pbase = g_base + rb * 72 * 256 + tid;
        int tb = j;
        mbar_wait(ibar, 0);
#pragma unroll 1
        for (int p = 0; p < 4; p++) {
            const int ta = tb == 8 ? 0 : tb + 1;
            float4* const pb = pbase + tb * 2048;
            float4* const pa = pbase + ta * 2048;
            tile_pair<true, true>(c, accA, accB, h, [&](auto sc) {
                constexpr int s = decltype(sc)::value;
                if constexpr (s == 0) reg_fence(accB);
                if constexpr (s < 4) store_part<s>(accB, pb);
                if constexpr (s == 5) reg_fence(accA);
                if constexpr (s >= 5) store_part<s - 5>(accA, pa);
            });
            tb = ta == 8 ? 0 : ta + 1;
            PROF(6 + p);
        }
        wg_wait<0>();
        reg_fence(accB);
        {
            float4* const pb = pbase + tb * 2048;
            store_part<0>(accB, pb); store_part<1>(accB, pb); store_part<2>(accB, pb); store_part<3>(accB, pb);
        }
        PROF(10);
        cluster_arrive();
        cluster_wait();
        PROF(11);
        PROFT(49);
    } else {
        reg_dealloc<24>();
        if (warp == 8 && lane == 0) {
            prefetch_tmap(&tmQ3); prefetch_tmap(&tmQ1); prefetch_tmap(&tm1); prefetch_tmap(&tm2);
            for (int i = 0; i < K1_NSLOT; i++) { mbar_init(full0 + i * 8, 1); mbar_init(empty0 + i * 8, 4); }
            mbar_init(ibar, 1);
            fence_barrier_init();
        }
        __syncwarp();
        cluster_arrive();
        cluster_wait();
        if (warp == 8) {
            if (lane == 0) {
                Ring w{0, 1};
                const uint32_t dst0 = sb + K1_OFF_RING + rank * 8192;
#pragma unroll 1
                for (int s = 0; s < 18; s++) {
                    mbar_wait(empty0 + w.slot * 8, w.phase);
                    mbar_expect(full0 + w.slot * 8, 16384);
                    const uint32_t dst = dst0 + w.slot * K1_SLOT;
                    tma3d_mc(dst, &tmQ3, j * 216, s * 32 + rank * 16, 0, full0 + w.slot * 8, 3);
                    tma2d_mc(dst + 6144, &tmQ1, j * 216 + 192, s * 32 + rank * 16, full0 + w.slot * 8, 3);
                    w.advance();
                }
                int tile = 0, kb = rank;
#pragma unroll 1
                for (int s = 0; s < 81; s++) {
                    mbar_wait(empty0 + w.slot * 8, w.phase);
                    mbar_expect(full0 + w.slot * 8, 16384);
                    const uint32_t dst = dst0 + w.slot * K1_SLOT;
                    if (tile < 9) tma2d_mc(dst, &tm1, j * 576 + tile * 64, kb * 64, full0 + w.slot * 8, 3);
                    else tma2d_mc(dst, &tm2, (tile + j >= 18 ? tile + j - 18 : tile + j - 9) * 64, j * 576 + kb * 64, full0 + w.slot * 8, 3);
                    kb += 2;
                    if (kb >= 9) { kb -= 9; tile++; }
                    w.advance();
                }
            }
        } else {
            const int ht = tid - 288;
            if (ht < 72) {
                const uint4 v = __ldg(reinterpret_cast<const uint4*>(b1 + j * 576) + ht);
                uint32_t* sbias = reinterpret_cast<uint32_t*>(smem + K1_OFF_BIAS) + (ht >> 3) * 32 + (ht & 7);
                sbias[0] = v.x; sbias[8] = v.y; sbias[16] = v.z; sbias[24] = v.w;
            }
            asm volatile("bar.arrive 4, 352;" ::: "memory");
#pragma unroll 1
            for (int i = ht; i < 512; i += 96) {
                const int key = i & 127;
                uint8_t* p = g_QKV + (size_t)(j * 4 + (i >> 7)) * KV_HEAD_BYTES + (rb * 16 + (key >> 3)) * KV_GROUP_BYTES + 512 + (key & 7) * 16;
                *reinterpret_cast<uint32_t*>(p + 4) = ((POLY_MASK >> ((key >> 3) & 7)) & 1) ? 0x3F804000u : 0x00003F80u;
                *reinterpret_cast<uint32_t*>(p + 12) = 0x00003F80u;
            }
#pragma unroll 2
            for (int i = blockIdx.x * 324 + ht; i < blockIdx.x * 324 + 324; i += 96) {
                const int k = i / 72, nc = i - k * 72, ct = nc / 18;
                *reinterpret_cast<uint4*>(g_Wo + ct * WO_TILE_BYTES + (k >> 3) * 2304 + (nc - ct * 18) * 128 + (k & 7) * 16) =
                    __ldg(reinterpret_cast<const uint4*>(wo) + i);
            }
            PROFH(37);
#pragma unroll 4
            for (int i = ht; i < 9 * 256; i += 96) {
                const int t = i & 255, nb = j * 9 + (i >> 8);
                const int row = rb * 128 + (t >> 5) * 16 + ((t & 31) >> 2), col = nb * 8 + (t & 3) * 2;
                const uint32_t* xp = reinterpret_cast<const uint32_t*>(x + (size_t)row * DM + col);
                const uint32_t x0 = __ldg(xp), x1 = __ldg(xp + 4 * DM), bb = __ldg(reinterpret_cast<const uint32_t*>(b2 + col));
                g_base[(rb * 72 + nb) * 256 + t] = make_float4(2.f * (bf_lo(x0) + bf_lo(bb)), 2.f * (bf_hi(x0) + bf_hi(bb)),
                                                               2.f * (bf_lo(x1) + bf_lo(bb)), 2.f * (bf_hi(x1) + bf_hi(bb)));
            }
            named_bar_sync(7, 96);
            if (ht == 0) {
                __threadfence();
                atomicAdd(&g_flag[rb], 1u);
                uint32_t v, spins = 0;
                do {
                    __nanosleep(200);
                    asm volatile("ld.acquire.gpu.global.u32 %0, [%1];" : "=r"(v) : "l"(&g_flag[rb]) : "memory");
                    if (++spins > (1u << 20)) __trap();
                } while (v < 8);
                asm volatile("mbarrier.arrive.shared::cta.b64 _, [%0];" ::"r"(ibar) : "memory");
            }
            __syncwarp();
            PROFH(38);
            named_bar_sync(3, 352);
#pragma unroll 1
            for (int i = warp - 9; i < 48; i += 3) {
                const int G = 3 * j + (i >> 4);
                if ((G >> 3) != 1) continue;
                const int head = (G & 7) * 4 + ((i >> 2) & 3), key = (i & 3) * 32 + lane;
                const uint8_t* p = g_QKV + (size_t)head * KV_HEAD_BYTES + (rb * 16 + (key >> 3)) * KV_GROUP_BYTES + (key & 7) * 16;
                const uint4 a = __ldcg(reinterpret_cast<const uint4*>(p)), b = __ldcg(reinterpret_cast<const uint4*>(p + 128));
                const uint32_t e = __ldcg(reinterpret_cast<const uint32_t*>(p + 512));
                float n = bf_lo(e) * bf_lo(e) + bf_hi(e) * bf_hi(e);
                n += bf_lo(a.x) * bf_lo(a.x) + bf_hi(a.x) * bf_hi(a.x) + bf_lo(a.y) * bf_lo(a.y) + bf_hi(a.y) * bf_hi(a.y);
                n += bf_lo(a.z) * bf_lo(a.z) + bf_hi(a.z) * bf_hi(a.z) + bf_lo(a.w) * bf_lo(a.w) + bf_hi(a.w) * bf_hi(a.w);
                n += bf_lo(b.x) * bf_lo(b.x) + bf_hi(b.x) * bf_hi(b.x) + bf_lo(b.y) * bf_lo(b.y) + bf_hi(b.y) * bf_hi(b.y);
                n += bf_lo(b.z) * bf_lo(b.z) + bf_hi(b.z) * bf_hi(b.z) + bf_lo(b.w) * bf_lo(b.w) + bf_hi(b.w) * bf_hi(b.w);
                if ((POLY_MASK >> ((key >> 3) & 7)) & 1) n *= 0.25f;
#pragma unroll
                for (int o = 16; o; o >>= 1) n = fmaxf(n, __shfl_xor_sync(~0u, n, o));
                if (lane == 0) g_kmax[head * 64 + rb * 4 + (i & 3)] = n;
            }
            PROFH(39);
        }
        __syncwarp();
        cluster_arrive();
        cluster_wait();
    }
}

constexpr int K2_NCHUNK = 16;
constexpr int K2_CHUNK_BYTES = KV_HEAD_BYTES / K2_NCHUNK;
constexpr int K2_OFF_BAR = KV_HEAD_BYTES + 8 * KV_GROUP_BYTES;
constexpr int K2_OFF_Q = K2_OFF_BAR + 256;
constexpr int K2_SMEM = K2_OFF_Q + 12 * 512 * 4;

__device__ __forceinline__ float exp2_fixed(float y) {
    const float u = __uint_as_float(__float_as_uint(y) & 0xFF807FFFu) - 512.02545f;
    float t = fmaf(u, 0.019497588f, 0.114550486f);
    t = fmaf(t, u, -0.29839927f);
    return fmaf(t, u, y);
}
__device__ __forceinline__ uint32_t pack_fixed(float lo, float hi) { return __byte_perm(__float_as_uint(lo), __float_as_uint(hi), 0x6521); }

#define POLY_MODE 1
__device__ __forceinline__ uint32_t hfma2_bf16(uint32_t a, uint32_t b, uint32_t c) {
    uint32_t r;
    asm("fma.rn.bf16x2 %0, %1, %2, %3;" : "=r"(r) : "r"(a), "r"(b), "r"(c));
    return r;
}
__device__ __forceinline__ uint32_t exp2_packed(float y0, float y1, uint32_t one2) {
    const uint32_t w = pack_fixed(y0, y1);
    uint32_t m;
    asm("lop3.b32 %0, %1, 0x007F007F, %2, 0xEA;" : "=r"(m) : "r"(w), "r"(one2));
    const uint32_t d = hfma2_bf16(m, 0x3EF93EF9u, 0xBF38BF38u);
    const uint32_t e = hfma2_bf16(d, d, 0xBD71BD71u);
    return hfma2_bf16(w, e, w);
}
__device__ __forceinline__ void softmax_fast(const float (&s)[32], uint32_t (&p)[16], uint32_t one2) {
#pragma unroll
    for (int b = 0; b < 8; b++) {
        if ((POLY_MASK >> b) & 1) {
            p[b * 2 + 0] = exp2_packed(s[b * 4 + 0], s[b * 4 + 1], one2);
            p[b * 2 + 1] = exp2_packed(s[b * 4 + 2], s[b * 4 + 3], one2);
        } else {
            p[b * 2 + 0] = pack_bf16(ex2(s[b * 4 + 0]), ex2(s[b * 4 + 1]));
            p[b * 2 + 1] = pack_bf16(ex2(s[b * 4 + 2]), ex2(s[b * 4 + 3]));
        }
    }
}

constexpr uint32_t K2_TILE = 8 * KV_GROUP_BYTES / 16;
__device__ __forceinline__ void issue_qk(float (&s)[32], const uint32_t (&qa)[8], uint32_t base) {
    wgmma_rs_n64<0>(s, qa[0], qa[1], qa[2], qa[3], base + (8u << 16), desc_hi(KV_GROUP_BYTES, 0), 0);
    wgmma_rs_n64<0>(s, qa[4], qa[5], qa[6], qa[7], base + 32, desc_hi(KV_GROUP_BYTES, 0), 1);
}
__device__ __forceinline__ void issue_pv(float (&o)[12], const uint32_t (&p)[16], uint32_t base) {
#pragma unroll
    for (int k = 0; k < 4; k++)
        wgmma_rs_n24<1>(o, p[k * 4], p[k * 4 + 1], p[k * 4 + 2], p[k * 4 + 3], base + 16 + ((KV_GROUP_BYTES / 16) << 16) + k * (2 * KV_GROUP_BYTES / 16),
                        desc_hi(128, 0), 1);
}

__global__ void __launch_bounds__(512, 1) k2_kernel() {
    extern __shared__ __align__(1024) uint8_t smem[];
    const uint32_t sb = s2u(smem);
    const int tid = threadIdx.x, lane = tid & 31;
    const int warp = __shfl_sync(~0u, tid >> 5, 0);
    const int wg = warp >> 2, wq = warp & 3, g = lane >> 2, q = lane & 3;
    const int head = blockIdx.x >> 2, quarter = blockIdx.x & 3;
    const uint32_t bar0 = sb + K2_OFF_BAR;
    PROF(16);
    if (tid == 0) {
        for (int i = 0; i <= K2_NCHUNK; i++) mbar_init(bar0 + i * 8, 1);
        asm volatile("mbarrier.arrive.shared::cta.b64 _, [%0];" ::"r"(bar0 + K2_NCHUNK * 8) : "memory");
        fence_barrier_init();
    }
    __syncthreads();
    griddep_wait();
    PROF(17);
    PROFT(50);
    uint32_t* qs = reinterpret_cast<uint32_t*>(smem + K2_OFF_Q) + tid;
    const uint8_t* kvsrc = g_QKV + (size_t)head * KV_HEAD_BYTES;
    int next_chunk = ((tid & 127) == 0) ? 4 + wg : K2_NCHUNK;
    float kmax2;
    {
        uint32_t qv[12];
#pragma unroll
        for (int pass = 0; pass < 2; pass++) {
            const int row0 = quarter * 512 + (pass * 4 + wg) * 64 + wq * 16;
            const uint8_t* qp = g_QKV + Q_OFFSET + (size_t)head * KV_HEAD_BYTES + (row0 >> 3) * KV_GROUP_BYTES + g * 16 + q * 4;
            qv[pass * 6 + 0] = __ldcg(reinterpret_cast<const uint32_t*>(qp));
            qv[pass * 6 + 1] = __ldcg(reinterpret_cast<const uint32_t*>(qp + KV_GROUP_BYTES));
            qv[pass * 6 + 2] = __ldcg(reinterpret_cast<const uint32_t*>(qp + 128));
            qv[pass * 6 + 3] = __ldcg(reinterpret_cast<const uint32_t*>(qp + KV_GROUP_BYTES + 128));
            qv[pass * 6 + 4] = (q == 0) ? __ldcg(reinterpret_cast<const uint32_t*>(qp + 256)) : 0u;
            qv[pass * 6 + 5] = (q == 0) ? __ldcg(reinterpret_cast<const uint32_t*>(qp + KV_GROUP_BYTES + 256)) : 0u;
        }
        const float2 v = __ldcg(reinterpret_cast<const float2*>(g_kmax + head * 64 + lane * 2));
        if ((tid & 127) == 32) {
            mbar_expect(bar0 + wg * 8, K2_CHUNK_BYTES);
            bulk_load(sb + wg * K2_CHUNK_BYTES, kvsrc + wg * K2_CHUNK_BYTES, K2_CHUNK_BYTES, bar0 + wg * 8);
        }
        __syncwarp();
#pragma unroll
        for (int i = 0; i < 12; i++) qs[i * 512] = qv[i];
        kmax2 = fmaxf(v.x, v.y);
#pragma unroll
        for (int o = 16; o; o >>= 1) kmax2 = fmaxf(kmax2, __shfl_xor_sync(~0u, kmax2, o));
    }
    const uint32_t d0 = (sb & 0x3FFFF) >> 4;
    const uint32_t one2 = __shfl_sync(~0u, 0x3F803F80u + (uint32_t)(kmax2 < 0.f), 0);

#pragma unroll 1
    for (int pass = 0; pass < 2; pass++) {
        const int row0 = quarter * 512 + (pass * 4 + wg) * 64 + wq * 16;
        uint32_t qa[8];
#pragma unroll
        for (int i = 0; i < 6; i++) qa[i] = qs[(pass * 6 + i) * 512];
        qa[6] = 0u;
        float c0, c1;
        {
            float n0 = bf_lo(qa[0]) * bf_lo(qa[0]) + bf_hi(qa[0]) * bf_hi(qa[0]) + bf_lo(qa[2]) * bf_lo(qa[2]) + bf_hi(qa[2]) * bf_hi(qa[2]) +
                       bf_lo(qa[4]) * bf_lo(qa[4]) + bf_hi(qa[4]) * bf_hi(qa[4]);
            float n1 = bf_lo(qa[1]) * bf_lo(qa[1]) + bf_hi(qa[1]) * bf_hi(qa[1]) + bf_lo(qa[3]) * bf_lo(qa[3]) + bf_hi(qa[3]) * bf_hi(qa[3]) +
                       bf_lo(qa[5]) * bf_lo(qa[5]) + bf_hi(qa[5]) * bf_hi(qa[5]);
            n0 += __shfl_xor_sync(~0u, n0, 1); n1 += __shfl_xor_sync(~0u, n1, 1);
            n0 += __shfl_xor_sync(~0u, n0, 2); n1 += __shfl_xor_sync(~0u, n1, 2);
            c0 = sqrtf(n0 * kmax2) * 1.02f;
            c1 = sqrtf(n1 * kmax2) * 1.02f;
        }
        uint32_t slow;
        {
            const bool bad = !(c0 <= 58.f && c1 <= 58.f);
            asm volatile("{\n.reg .pred p, r;\nsetp.ne.u32 p, %1, 0;\nbarrier.cta.red.or.pred.aligned r, %2, 128, p;\nselp.u32 %0, 1, 0, r;\n}\n"
                         : "=r"(slow) : "r"((uint32_t)bad), "r"(wg + 1) : "memory");
        }
        slow = __any_sync(~0u, slow);
        float o[12];
#pragma unroll
        for (int i = 0; i < 12; i++) o[i] = 0.f;
        if (!slow && q == 1) {
            qa[4] = pack_bf16(-c0, 768.f); qa[5] = pack_bf16(-c1, 768.f);
            qa[6] = 0xBFFF0000u;
        }
        qa[7] = __shfl_sync(~0u, qa[6], lane);
        qa[6] = __shfl_sync(~0u, qa[6], lane ^ 4);

        if (!slow) {
            float s0[32], s1[32];
            uint32_t p[16];
            mbar_wait(bar0, 0);
            PROF(18 + pass * 3);
            reg_fence(qa);
            reg_fence(o);
            wg_fence();
            issue_qk(s0, qa, d0);
            wg_commit();
            uint32_t d = d0, bar = bar0;
#pragma unroll 1
            for (int t = 0; t < 16; t++) {
                wg_fence();
                issue_qk(s1, qa, d + K2_TILE);
                wg_commit();
                wg_wait<1>();
                reg_fence(s0);
                softmax_fast(s0, p, one2);
                reg_fence(p);
                if (next_chunk < K2_NCHUNK) {
                    mbar_expect(bar0 + next_chunk * 8, K2_CHUNK_BYTES);
                    bulk_load(sb + next_chunk * K2_CHUNK_BYTES, kvsrc + next_chunk * K2_CHUNK_BYTES, K2_CHUNK_BYTES, bar0 + next_chunk * 8);
                    next_chunk += 4;
                }
                __syncwarp();
                bar += 8;
                mbar_wait(bar, 0);
                wg_fence();
                issue_pv(o, p, d);
                wg_commit();
                issue_qk(s0, qa, d + 2 * K2_TILE);
                wg_commit();
                wg_wait<1>();
                reg_fence(s1);
                softmax_fast(s1, p, one2);
                reg_fence(p);
                wg_fence();
                issue_pv(o, p, d + K2_TILE);
                wg_commit();
                d += 2 * K2_TILE;
            }
            wg_wait<0>();
            reg_fence(o);
            reg_fence(s0);
        } else {
            float m0 = -INFINITY, m1 = -INFINITY;
            float s[32];
            uint32_t p[16];
            reg_fence(qa);
            for (; next_chunk < K2_NCHUNK; next_chunk += 4) {
                mbar_expect(bar0 + next_chunk * 8, K2_CHUNK_BYTES);
                bulk_load(sb + next_chunk * K2_CHUNK_BYTES, kvsrc + next_chunk * K2_CHUNK_BYTES, K2_CHUNK_BYTES, bar0 + next_chunk * 8);
            }
            __syncwarp();
#pragma unroll 1
            for (int t = 0; t < 32; t++) {
                mbar_wait(bar0 + (t / 2) * 8, 0);
                wg_fence();
                issue_qk(s, qa, d0 + t * K2_TILE);
                wg_commit();
                wg_wait<0>();
                reg_fence(s);
                reg_fence(o);
                float a0 = m0, a1 = m1;
#pragma unroll
                for (int k = 0; k < 8; k++) {
                    if ((POLY_MASK >> k) & 1) {
#pragma unroll
                        for (int i = 0; i < 4; i++) s[k * 4 + i] *= 0.5f;
                    }
                    a0 = fmaxf(a0, fmaxf(s[k * 4 + 0], s[k * 4 + 1]));
                    a1 = fmaxf(a1, fmaxf(s[k * 4 + 2], s[k * 4 + 3]));
                }
                a0 = fmaxf(a0, __shfl_xor_sync(~0u, a0, 1)); a1 = fmaxf(a1, __shfl_xor_sync(~0u, a1, 1));
                a0 = fmaxf(a0, __shfl_xor_sync(~0u, a0, 2)); a1 = fmaxf(a1, __shfl_xor_sync(~0u, a1, 2));
                const float r0 = ex2(m0 - a0), r1 = ex2(m1 - a1);
                m0 = a0; m1 = a1;
#pragma unroll
                for (int i = 0; i < 3; i++) { o[i * 4] *= r0; o[i * 4 + 1] *= r0; o[i * 4 + 2] *= r1; o[i * 4 + 3] *= r1; }
#pragma unroll
                for (int k = 0; k < 8; k++) {
                    p[k * 2 + 0] = pack_bf16(ex2(s[k * 4 + 0] - m0), ex2(s[k * 4 + 1] - m0));
                    p[k * 2 + 1] = pack_bf16(ex2(s[k * 4 + 2] - m1), ex2(s[k * 4 + 3] - m1));
                }
                reg_fence(p);
                reg_fence(o);
                wg_fence();
                issue_pv(o, p, d0 + t * K2_TILE);
                wg_commit();
                wg_wait<0>();
            }
            reg_fence(o);
        }
        PROF(19 + pass * 3);
        const float l0 = __shfl_sync(~0u, o[8], (lane & ~3) | 3), l1 = __shfl_sync(~0u, o[10], (lane & ~3) | 3);
        const float i0 = 1.0f / l0, i1 = 1.0f / l1;
#pragma unroll
        for (int i = 0; i < 3; i++) {
            const int pc = head * 9 + (i < 2 ? i * 4 + q : 8);
            uint32_t* op = g_O + ((((row0 >> 6) * 36 + (pc >> 3)) * 128 + wq * 32 + g * 4 + (pc & 3)) * 4 + ((pc >> 2) & 1) * 2);
            if (i < 2 || q == 2) *reinterpret_cast<uint2*>(op) = make_uint2(pack_bf16(o[i * 4] * i0, o[i * 4 + 1] * i0), pack_bf16(o[i * 4 + 2] * i1, o[i * 4 + 3] * i1));
        }
        PROF(20 + pass * 3);
        PROFT(51);
    }
}

constexpr int K3_PIECE = WO_TILE_BYTES / 9;
constexpr int K3_OFF_BAR = WO_TILE_BYTES;
constexpr int K3_SMEM = K3_OFF_BAR + 128;

__global__ void __cluster_dims__(2, 1, 1) __launch_bounds__(128, 1) k3_kernel(__nv_bfloat16* __restrict__ out) {
    extern __shared__ __align__(1024) uint8_t smem[];
    const uint32_t sb = s2u(smem);
    const int tid = threadIdx.x, warp = tid >> 5, lane = tid & 31;
    const int g = lane >> 2, q = lane & 3;
    const uint32_t rank = blockIdx.x & 1;
    const int ct = (blockIdx.x >> 1) & 3, rt = (blockIdx.x >> 3) * 2 + rank;
    const uint32_t bar0 = sb + K3_OFF_BAR;
    PROF(32);
    if (tid == 0) {
        for (int i = 0; i < 9; i++) { mbar_init(bar0 + i * 8, 1); mbar_expect(bar0 + i * 8, K3_PIECE); }
        fence_barrier_init();
    }
    cluster_arrive();
    cluster_wait();
    griddep_wait();
    PROF(33);
    PROFT(52);
    if (tid == 0 && blockIdx.x < 16) g_flag[blockIdx.x] = 0;
    uint4 a[36];
    const uint4* ap = reinterpret_cast<const uint4*>(g_O) + rt * 36 * 128 + tid;
#pragma unroll
    for (int k = 0; k < 4; k++) a[k] = __ldcg(ap + k * 128);
    if (tid < 9) {
        const uint32_t off = tid * K3_PIECE + rank * (K3_PIECE / 2);
        asm volatile("cp.async.bulk.shared::cluster.global.mbarrier::complete_tx::bytes.multicast::cluster [%0], [%1], %2, [%3], %4;"
                     ::"r"(sb + off), "l"(g_Wo + ct * WO_TILE_BYTES + off), "r"(K3_PIECE / 2), "r"(bar0 + tid * 8), "h"((uint16_t)3) : "memory");
    }
    float acc[72];
    {
        const float4* bp = g_base + ((rt >> 1) * 72 + ct * 18) * 256 + (rt & 1) * 128 + tid;
#pragma unroll
        for (int i = 0; i < 18; i++) {
            const float4 v = __ldcg(bp + i * 256);
            acc[i * 4 + 0] = v.x; acc[i * 4 + 1] = v.y; acc[i * 4 + 2] = v.z; acc[i * 4 + 3] = v.w;
        }
#pragma unroll
        for (int k = 4; k < 36; k++) a[k] = __ldcg(ap + k * 128);
#pragma unroll
        for (int i = 0; i < 72; i++) acc[i] *= 0.5f;
    }
    PROF(34);
    const uint32_t db = desc_lo(sb, 2304);
#pragma unroll
    for (int kb = 0; kb < 9; kb++) {
        mbar_wait(bar0 + kb * 8, 0);
        wg_fence();
#pragma unroll
        for (int k = 0; k < 4; k++) {
            const uint4 f = a[kb * 4 + k];
            wgmma_rs_n144<1>(acc, f.x, f.y, f.z, f.w, db + (((kb * 4 + k) * 4608) >> 4), desc_hi(128, 0), 1);
        }
        wg_commit();
    }
    wg_wait<0>();
    reg_fence(acc);
    PROF(35);
    uint32_t* op = reinterpret_cast<uint32_t*>(out + (size_t)(rt * 64 + warp * 16 + g) * DM + ct * 144 + q * 2);
#pragma unroll
    for (int b = 0; b < 18; b++) {
        op[b * 4] = pack_bf16(acc[b * 4], acc[b * 4 + 1]);
        op[b * 4 + 4 * DM] = pack_bf16(acc[b * 4 + 2], acc[b * 4 + 3]);
    }
    cluster_arrive();
    cluster_wait();
    PROF(36);
    PROFT(53);
}

typedef CUresult (*EncodeFn)(CUtensorMap*, CUtensorMapDataType, cuuint32_t, void*, const cuuint64_t*, const cuuint64_t*, const cuuint32_t*,
                             const cuuint32_t*, CUtensorMapInterleave, CUtensorMapSwizzle, CUtensorMapL2promotion, CUtensorMapFloatOOBfill);

void make_map(EncodeFn fn, CUtensorMap* m, const void* base, int rank, const cuuint64_t* dims, const cuuint64_t* strides, const cuuint32_t* box) {
    cuuint32_t es[3] = {1, 1, 1};
    fn(m, CU_TENSOR_MAP_DATA_TYPE_BFLOAT16, rank, const_cast<void*>(base), dims, strides, box, es, CU_TENSOR_MAP_INTERLEAVE_NONE,
       CU_TENSOR_MAP_SWIZZLE_128B, CU_TENSOR_MAP_L2_PROMOTION_L2_256B, CU_TENSOR_MAP_FLOAT_OOB_FILL_NONE);
}

}

extern "C" void kernel_launch(void* const* d_in, const int* in_sizes, int n_in, void* d_out, int out_size) {
    const __nv_bfloat16* x = (const __nv_bfloat16*)d_in[0];
    const __nv_bfloat16* wqkv = (const __nv_bfloat16*)d_in[1];
    const __nv_bfloat16* wo = (const __nv_bfloat16*)d_in[2];
    const __nv_bfloat16* w1 = (const __nv_bfloat16*)d_in[4];
    const __nv_bfloat16* b1 = (const __nv_bfloat16*)d_in[5];
    const __nv_bfloat16* w2 = (const __nv_bfloat16*)d_in[6];
    const __nv_bfloat16* b2 = (const __nv_bfloat16*)d_in[7];
    __nv_bfloat16* out = (__nv_bfloat16*)d_out;

    EncodeFn fn = nullptr;
    cudaDriverEntryPointQueryResult qr;
    cudaGetDriverEntryPoint("cuTensorMapEncodeTiled", (void**)&fn, cudaEnableDefault, &qr);
    CUtensorMap tmX, tmQ3, tmQ1, tm1, tm2;
    {
        cuuint64_t d[3] = {64, SEQ, 9}, s[2] = {DM * 2, 128};
        cuuint32_t b[3] = {64, 8, 9};
        make_map(fn, &tmX, x, 3, d, s, b);
    }
    {
        cuuint64_t d[3] = {3 * DM, DM, 3}, s[2] = {3 * DM * 2, 128};
        cuuint32_t b[3] = {64, 16, 3};
        make_map(fn, &tmQ3, wqkv, 3, d, s, b);
        make_map(fn, &tmQ1, wqkv, 2, d, s, b);
    }
    {
        cuuint64_t d[2] = {FF, DM}, s[1] = {FF * 2};
        cuuint32_t b[2] = {64, 64};
        make_map(fn, &tm1, w1, 2, d, s, b);
        cuuint64_t d2[2] = {DM, FF}, s2[1] = {DM * 2};
        make_map(fn, &tm2, w2, 2, d2, s2, b);
    }
    cudaFuncSetAttribute(k1_kernel, cudaFuncAttributeMaxDynamicSharedMemorySize, K1_SMEM);
    cudaFuncSetAttribute(k2_kernel, cudaFuncAttributeMaxDynamicSharedMemorySize, K2_SMEM);
    cudaFuncSetAttribute(k3_kernel, cudaFuncAttributeMaxDynamicSharedMemorySize, K3_SMEM);

    cudaStream_t st = cudaStreamPerThread;
    cudaLaunchAttribute pdl[1];
    pdl[0].id = cudaLaunchAttributeProgrammaticStreamSerialization;
    pdl[0].val.programmaticStreamSerializationAllowed = 1;
    {
        cudaLaunchConfig_t cfg = {};
        cfg.gridDim = dim3(128); cfg.blockDim = dim3(384); cfg.dynamicSmemBytes = K1_SMEM; cfg.stream = st;
        cudaLaunchKernelEx(&cfg, k1_kernel, tmX, tmQ3, tmQ1, tm1, tm2, b1, wo, x, b2);
    }
    {
        cudaLaunchConfig_t cfg = {};
        cfg.gridDim = dim3(128); cfg.blockDim = dim3(512); cfg.dynamicSmemBytes = K2_SMEM; cfg.stream = st;
        cfg.attrs = pdl; cfg.numAttrs = 1;
        cudaLaunchKernelEx(&cfg, k2_kernel);
    }
    {
        cudaLaunchConfig_t cfg = {};
        cfg.gridDim = dim3(128); cfg.blockDim = dim3(128); cfg.dynamicSmemBytes = K3_SMEM; cfg.stream = st;
        cfg.attrs = pdl; cfg.numAttrs = 1;
        cudaLaunchKernelEx(&cfg, k3_kernel, out);
    }
}
```

```cpp
#include <cuda_runtime.h>
#include <cuda_bf16.h>
#include <cuda.h>
#include <stdint.h>

#define PROF(i) do { } while (0)
#define PROFT(i) do { } while (0)
#define PROFH(i) do { } while (0)
#define PROF_WG 0

namespace {

constexpr int SEQ = 2048, DM = 576, FF = 4608, NH = 32, DH = 18;

constexpr int KV_GROUP_BYTES = 5 * 128;
constexpr int KV_HEAD_BYTES = (SEQ / 8) * KV_GROUP_BYTES;
constexpr int Q_OFFSET = NH * KV_HEAD_BYTES;
#define POLY_MASK 0xB6
__device__ __align__(1024) uint8_t g_QKV[2 * NH * KV_HEAD_BYTES];
__device__ __align__(1024) float g_kmax[NH * 64];
__device__ __align__(1024) float4 g_base[16 * 72 * 256];
__device__ __align__(1024) uint32_t g_O[SEQ * DM / 2];
struct Flags {
    unsigned int base_init[16];
    unsigned int qkv_stored[16];
    unsigned int ffn_done[16];
    unsigned int o_done[4];
    unsigned int kv_ready;
    unsigned int exited;
};
__device__ Flags g_flags;
constexpr int WO_TILE_BYTES = DM * 144 * 2;
__device__ __align__(1024) uint8_t g_Wo[4 * WO_TILE_BYTES];

__device__ __forceinline__ uint32_t s2u(const void* p) { return (uint32_t)__cvta_generic_to_shared(p); }
__device__ __forceinline__ void mbar_init(uint32_t b, int c) { asm volatile("mbarrier.init.shared::cta.b64 [%0], %1;" ::"r"(b), "r"(c) : "memory"); }
__device__ __forceinline__ void mbar_expect(uint32_t b, uint32_t bytes) {
    asm volatile("mbarrier.arrive.expect_tx.shared::cta.b64 _, [%0], %1;" ::"r"(b), "r"(bytes) : "memory");
}
__device__ __forceinline__ void mbar_wait(uint32_t b, uint32_t parity) {
    asm volatile(
        "{\n.reg .pred p;\n.reg .u32 c;\n"
        "mbarrier.try_wait.parity.shared::cta.b64 p, [%0], %1;\n"
        "@p bra DONE;\n"
        "mov.u32 c, 0;\n"
        "LOOP:\n"
        "mbarrier.try_wait.parity.shared::cta.b64 p, [%0], %1;\n"
        "@p bra DONE;\n"
        "add.u32 c, c, 1;\n"
        "setp.lt.u32 p, c, 4194304;\n"
        "@p bra LOOP;\n"
        "trap;\n"
        "DONE:\n}\n" ::"r"(b), "r"(parity) : "memory");
}
__device__ __forceinline__ void fence_barrier_init() { asm volatile("fence.mbarrier_init.release.cluster;" ::: "memory"); }
__device__ __forceinline__ void fence_proxy_async() { asm volatile("fence.proxy.async.shared::cta;" ::: "memory"); }
__device__ __forceinline__ void cluster_arrive() { asm volatile("barrier.cluster.arrive.relaxed.aligned;" ::: "memory"); }
__device__ __forceinline__ void cluster_wait() { asm volatile("barrier.cluster.wait.aligned;" ::: "memory"); }
__device__ __forceinline__ void named_bar_sync(int id, int n) { asm volatile("bar.sync %0, %1;" ::"r"(id), "r"(n) : "memory"); }
__device__ __forceinline__ void griddep_wait() { asm volatile("griddepcontrol.wait;" ::: "memory"); }
__device__ __forceinline__ void griddep_launch() { asm volatile("griddepcontrol.launch_dependents;" ::: "memory"); }

__device__ __forceinline__ void tma3d_mc(uint32_t dst, const CUtensorMap* tm, int c0, int c1, int c2, uint32_t bar, uint16_t mask) {
    asm volatile("cp.async.bulk.tensor.3d.shared::cluster.global.mbarrier::complete_tx::bytes.multicast::cluster [%0], [%1, {%3, %4, %5}], [%2], %6;"
                 ::"r"(dst), "l"(tm), "r"(bar), "r"(c0), "r"(c1), "r"(c2), "h"(mask) : "memory");
}
__device__ __forceinline__ void tma2d_mc(uint32_t dst, const CUtensorMap* tm, int c0, int c1, uint32_t bar, uint16_t mask) {
    asm volatile("cp.async.bulk.tensor.2d.shared::cluster.global.mbarrier::complete_tx::bytes.multicast::cluster [%0], [%1, {%3, %4}], [%2], %5;"
                 ::"r"(dst), "l"(tm), "r"(bar), "r"(c0), "r"(c1), "h"(mask) : "memory");
}
__device__ __forceinline__ void tma3d(uint32_t dst, const CUtensorMap* tm, int c0, int c1, int c2, uint32_t bar) {
    asm volatile("cp.async.bulk.tensor.3d.shared::cluster.global.mbarrier::complete_tx::bytes [%0], [%1, {%3, %4, %5}], [%2];"
                 ::"r"(dst), "l"(tm), "r"(bar), "r"(c0), "r"(c1), "r"(c2) : "memory");
}
__device__ __forceinline__ void tma2d(uint32_t dst, const CUtensorMap* tm, int c0, int c1, uint32_t bar) {
    asm volatile("cp.async.bulk.tensor.2d.shared::cluster.global.mbarrier::complete_tx::bytes [%0], [%1, {%3, %4}], [%2];"
                 ::"r"(dst), "l"(tm), "r"(bar), "r"(c0), "r"(c1) : "memory");
}
__device__ __forceinline__ void bulk_load(uint32_t dst, const void* src, uint32_t bytes, uint32_t bar) {
    asm volatile("cp.async.bulk.shared::cluster.global.mbarrier::complete_tx::bytes [%0], [%1], %2, [%3];"
                 ::"r"(dst), "l"(src), "r"(bytes), "r"(bar) : "memory");
}
__device__ __forceinline__ void prefetch_tmap(const CUtensorMap* tm) { asm volatile("prefetch.tensormap [%0];" ::"l"(tm) : "memory"); }

__device__ __forceinline__ void wg_fence() { asm volatile("wgmma.fence.sync.aligned;" ::: "memory"); }
__device__ __forceinline__ void wg_commit() { asm volatile("wgmma.commit_group.sync.aligned;" ::: "memory"); }
template <int N> __device__ __forceinline__ void wg_wait() { asm volatile("wgmma.wait_group.sync.aligned %0;" ::"n"(N) : "memory"); }
template <int N> __device__ __forceinline__ void reg_fence(float (&d)[N]) {
#pragma unroll
    for (int i = 0; i < N; i++) asm volatile("" : "+f"(d[i])::"memory");
}
template <int N> __device__ __forceinline__ void reg_fence(uint32_t (&d)[N]) {
#pragma unroll
    for (int i = 0; i < N; i++) asm volatile("" : "+r"(d[i])::"memory");
}
template <int R> __device__ __forceinline__ void reg_alloc() { asm volatile("setmaxnreg.inc.sync.aligned.u32 %0;" ::"n"(R)); }
template <int R> __device__ __forceinline__ void reg_dealloc() { asm volatile("setmaxnreg.dec.sync.aligned.u32 %0;" ::"n"(R)); }

__device__ __forceinline__ uint32_t desc_lo(uint32_t addr, uint32_t lbo) { return ((addr & 0x3FFFF) >> 4) | ((lbo >> 4) << 16); }
__host__ __device__ constexpr uint32_t desc_hi(uint32_t sbo, uint32_t swz) { return (sbo >> 4) | (swz << 30); }
__device__ __forceinline__ uint32_t pack_bf16(float lo, float hi) {
    uint32_t r;
    asm("cvt.rn.bf16x2.f32 %0, %1, %2;" : "=r"(r) : "f"(hi), "f"(lo));
    return r;
}
__device__ __forceinline__ float bf_lo(uint32_t w) { return __uint_as_float(w << 16); }
__device__ __forceinline__ float bf_hi(uint32_t w) { return __uint_as_float(w & 0xFFFF0000u); }
__device__ __forceinline__ float ex2(float x) {
    float r;
    asm("ex2.approx.ftz.f32 %0, %1;" : "=f"(r) : "f"(x));
    return r;
}
__device__ __forceinline__ float tanh_fast(float x) {
    float r;
    asm("tanh.approx.f32 %0, %1;" : "=f"(r) : "f"(x));
    return r;
}
__device__ __forceinline__ float gelu2(float u) {
    const float w = fmaf(u * u, 0.0356774081f, 0.7978845608f);
    return fmaf(u, tanh_fast(u * w), u);
}

template<int TB> __device__ __forceinline__ void wgmma_ss_n216(float (&d)[108], uint32_t alo, uint32_t ahi, uint32_t blo, uint32_t bhi, int sd) {
    asm volatile("{\n.reg .pred p;\n.reg .b64 da, db;\nsetp.ne.b32 p, %110, 0;\nmov.b64 da, {%108, %112};\nmov.b64 db, {%109, %113};\n"
      "wgmma.mma_async.sync.aligned.m64n216k16.f32.bf16.bf16 {%0, %1, %2, %3, %4, %5, %6, %7, %8, %9, %10, %11, %12, %13, %14, %15, %16, %17, %18, %19, %20, %21, %22, %23, %24, %25, %26, %27, %28, %29, %30, %31, %32, %33, %34, %35, %36, %37, %38, %39, %40, %41, %42, %43, %44, %45, %46, %47, %48, %49, %50, %51, %52, %53, %54, %55, %56, %57, %58, %59, %60, %61, %62, %63, %64, %65, %66, %67, %68, %69, %70, %71, %72, %73, %74, %75, %76, %77, %78, %79, %80, %81, %82, %83, %84, %85, %86, %87, %88, %89, %90, %91, %92, %93, %94, %95, %96, %97, %98, %99, %100, %101, %102, %103, %104, %105, %106, %107}, da, db, p, 1, 1, 0, %111;\n}\n"
      : "+f"(d[0]), "+f"(d[1]), "+f"(d[2]), "+f"(d[3]), "+f"(d[4]), "+f"(d[5]), "+f"(d[6]), "+f"(d[7]), "+f"(d[8]), "+f"(d[9]), "+f"(d[10]), "+f"(d[11]), "+f"(d[12]), "+f"(d[13]), "+f"(d[14]), "+f"(d[15]), "+f"(d[16]), "+f"(d[17]), "+f"(d[18]), "+f"(d[19]), "+f"(d[20]), "+f"(d[21]), "+f"(d[22]), "+f"(d[23]), "+f"(d[24]), "+f"(d[25]), "+f"(d[26]), "+f"(d[27]), "+f"(d[28]), "+f"(d[29]), "+f"(d[30]), "+f"(d[31]), "+f"(d[32]), "+f"(d[33]), "+f"(d[34]), "+f"(d[35]), "+f"(d[36]), "+f"(d[37]), "+f"(d[38]), "+f"(d[39]), "+f"(d[40]), "+f"(d[41]), "+f"(d[42]), "+f"(d[43]), "+f"(d[44]), "+f"(d[45]), "+f"(d[46]), "+f"(d[47]), "+f"(d[48]), "+f"(d[49]), "+f"(d[50]), "+f"(d[51]), "+f"(d[52]), "+f"(d[53]), "+f"(d[54]), "+f"(d[55]), "+f"(d[56]), "+f"(d[57]), "+f"(d[58]), "+f"(d[59]), "+f"(d[60]), "+f"(d[61]), "+f"(d[62]), "+f"(d[63]), "+f"(d[64]), "+f"(d[65]), "+f"(d[66]), "+f"(d[67]), "+f"(d[68]), "+f"(d[69]), "+f"(d[70]), "+f"(d[71]), "+f"(d[72]), "+f"(d[73]), "+f"(d[74]), "+f"(d[75]), "+f"(d[76]), "+f"(d[77]), "+f"(d[78]), "+f"(d[79]), "+f"(d[80]), "+f"(d[81]), "+f"(d[82]), "+f"(d[83]), "+f"(d[84]), "+f"(d[85]), "+f"(d[86]), "+f"(d[87]), "+f"(d[88]), "+f"(d[89]), "+f"(d[90]), "+f"(d[91]), "+f"(d[92]), "+f"(d[93]), "+f"(d[94]), "+f"(d[95]), "+f"(d[96]), "+f"(d[97]), "+f"(d[98]), "+f"(d[99]), "+f"(d[100]), "+f"(d[101]), "+f"(d[102]), "+f"(d[103]), "+f"(d[104]), "+f"(d[105]), "+f"(d[106]), "+f"(d[107])
      : "r"(alo), "r"(blo), "r"(sd), "n"(TB), "r"(ahi), "r"(bhi));
}

template<int TB> __device__ __forceinline__ void wgmma_ss_n64(float (&d)[32], uint32_t alo, uint32_t ahi, uint32_t blo, uint32_t bhi, int sd) {
    asm volatile("{\n.reg .pred p;\n.reg .b64 da, db;\nsetp.ne.b32 p, %34, 0;\nmov.b64 da, {%32, %36};\nmov.b64 db, {%33, %37};\n"
      "wgmma.mma_async.sync.aligned.m64n64k16.f32.bf16.bf16 {%0, %1, %2, %3, %4, %5, %6, %7, %8, %9, %10, %11, %12, %13, %14, %15, %16, %17, %18, %19, %20, %21, %22, %23, %24, %25, %26, %27, %28, %29, %30, %31}, da, db, p, 1, 1, 0, %35;\n}\n"
      : "+f"(d[0]), "+f"(d[1]), "+f"(d[2]), "+f"(d[3]), "+f"(d[4]), "+f"(d[5]), "+f"(d[6]), "+f"(d[7]), "+f"(d[8]), "+f"(d[9]), "+f"(d[10]), "+f"(d[11]), "+f"(d[12]), "+f"(d[13]), "+f"(d[14]), "+f"(d[15]), "+f"(d[16]), "+f"(d[17]), "+f"(d[18]), "+f"(d[19]), "+f"(d[20]), "+f"(d[21]), "+f"(d[22]), "+f"(d[23]), "+f"(d[24]), "+f"(d[25]), "+f"(d[26]), "+f"(d[27]), "+f"(d[28]), "+f"(d[29]), "+f"(d[30]), "+f"(d[31])
      : "r"(alo), "r"(blo), "r"(sd), "n"(TB), "r"(ahi), "r"(bhi));
}

template<int TB> __device__ __forceinline__ void wgmma_ss_n128(float (&d)[64], uint32_t alo, uint32_t ahi, uint32_t blo, uint32_t bhi, int sd) {
    asm volatile("{\n.reg .pred p;\n.reg .b64 da, db;\nsetp.ne.b32 p, %66, 0;\nmov.b64 da, {%64, %68};\nmov.b64 db, {%65, %69};\n"
      "wgmma.mma_async.sync.aligned.m64n128k16.f32.bf16.bf16 {%0, %1, %2, %3, %4, %5, %6, %7, %8, %9, %10, %11, %12, %13, %14, %15, %16, %17, %18, %19, %20, %21, %22, %23, %24, %25, %26, %27, %28, %29, %30, %31, %32, %33, %34, %35, %36, %37, %38, %39, %40, %41, %42, %43, %44, %45, %46, %47, %48, %49, %50, %51, %52, %53, %54, %55, %56, %57, %58, %59, %60, %61, %62, %63}, da, db, p, 1, 1, 0, %67;\n}\n"
      : "+f"(d[0]), "+f"(d[1]), "+f"(d[2]), "+f"(d[3]), "+f"(d[4]), "+f"(d[5]), "+f"(d[6]), "+f"(d[7]), "+f"(d[8]), "+f"(d[9]), "+f"(d[10]), "+f"(d[11]), "+f"(d[12]), "+f"(d[13]), "+f"(d[14]), "+f"(d[15]), "+f"(d[16]), "+f"(d[17]), "+f"(d[18]), "+f"(d[19]), "+f"(d[20]), "+f"(d[21]), "+f"(d[22]), "+f"(d[23]), "+f"(d[24]), "+f"(d[25]), "+f"(d[26]), "+f"(d[27]), "+f"(d[28]), "+f"(d[29]), "+f"(d[30]), "+f"(d[31]), "+f"(d[32]), "+f"(d[33]), "+f"(d[34]), "+f"(d[35]), "+f"(d[36]), "+f"(d[37]), "+f"(d[38]), "+f"(d[39]), "+f"(d[40]), "+f"(d[41]), "+f"(d[42]), "+f"(d[43]), "+f"(d[44]), "+f"(d[45]), "+f"(d[46]), "+f"(d[47]), "+f"(d[48]), "+f"(d[49]), "+f"(d[50]), "+f"(d[51]), "+f"(d[52]), "+f"(d[53]), "+f"(d[54]), "+f"(d[55]), "+f"(d[56]), "+f"(d[57]), "+f"(d[58]), "+f"(d[59]), "+f"(d[60]), "+f"(d[61]), "+f"(d[62]), "+f"(d[63])
      : "r"(alo), "r"(blo), "r"(sd), "n"(TB), "r"(ahi), "r"(bhi));
}

template<int TB> __device__ __forceinline__ void wgmma_rs_n64(float (&d)[32], uint32_t a0, uint32_t a1, uint32_t a2, uint32_t a3, uint32_t blo, uint32_t bhi, int sd) {
    asm volatile("{\n.reg .pred p;\n.reg .b64 db;\nsetp.ne.b32 p, %37, 0;\nmov.b64 db, {%36, %39};\n"
      "wgmma.mma_async.sync.aligned.m64n64k16.f32.bf16.bf16 {%0, %1, %2, %3, %4, %5, %6, %7, %8, %9, %10, %11, %12, %13, %14, %15, %16, %17, %18, %19, %20, %21, %22, %23, %24, %25, %26, %27, %28, %29, %30, %31}, {%32, %33, %34, %35}, db, p, 1, 1, %38;\n}\n"
      : "+f"(d[0]), "+f"(d[1]), "+f"(d[2]), "+f"(d[3]), "+f"(d[4]), "+f"(d[5]), "+f"(d[6]), "+f"(d[7]), "+f"(d[8]), "+f"(d[9]), "+f"(d[10]), "+f"(d[11]), "+f"(d[12]), "+f"(d[13]), "+f"(d[14]), "+f"(d[15]), "+f"(d[16]), "+f"(d[17]), "+f"(d[18]), "+f"(d[19]), "+f"(d[20]), "+f"(d[21]), "+f"(d[22]), "+f"(d[23]), "+f"(d[24]), "+f"(d[25]), "+f"(d[26]), "+f"(d[27]), "+f"(d[28]), "+f"(d[29]), "+f"(d[30]), "+f"(d[31])
      : "r"(a0), "r"(a1), "r"(a2), "r"(a3), "r"(blo), "r"(sd), "n"(TB), "r"(bhi));
}

template<int TB> __device__ __forceinline__ void wgmma_rs_n24(float (&d)[12], uint32_t a0, uint32_t a1, uint32_t a2, uint32_t a3, uint32_t blo, uint32_t bhi, int sd) {
    asm volatile("{\n.reg .pred p;\n.reg .b64 db;\nsetp.ne.b32 p, %17, 0;\nmov.b64 db, {%16, %19};\n"
      "wgmma.mma_async.sync.aligned.m64n24k16.f32.bf16.bf16 {%0, %1, %2, %3, %4, %5, %6, %7, %8, %9, %10, %11}, {%12, %13, %14, %15}, db, p, 1, 1, %18;\n}\n"
      : "+f"(d[0]), "+f"(d[1]), "+f"(d[2]), "+f"(d[3]), "+f"(d[4]), "+f"(d[5]), "+f"(d[6]), "+f"(d[7]), "+f"(d[8]), "+f"(d[9]), "+f"(d[10]), "+f"(d[11])
      : "r"(a0), "r"(a1), "r"(a2), "r"(a3), "r"(blo), "r"(sd), "n"(TB), "r"(bhi));
}

template<int TB> __device__ __forceinline__ void wgmma_rs_n144(float (&d)[72], uint32_t a0, uint32_t a1, uint32_t a2, uint32_t a3, uint32_t blo, uint32_t bhi, int sd) {
    asm volatile("{\n.reg .pred p;\n.reg .b64 db;\nsetp.ne.b32 p, %77, 0;\nmov.b64 db, {%76, %79};\n"
      "wgmma.mma_async.sync.aligned.m64n144k16.f32.bf16.bf16 {%0, %1, %2, %3, %4, %5, %6, %7, %8, %9, %10, %11, %12, %13, %14, %15, %16, %17, %18, %19, %20, %21, %22, %23, %24, %25, %26, %27, %28, %29, %30, %31, %32, %33, %34, %35, %36, %37, %38, %39, %40, %41, %42, %43, %44, %45, %46, %47, %48, %49, %50, %51, %52, %53, %54, %55, %56, %57, %58, %59, %60, %61, %62, %63, %64, %65, %66, %67, %68, %69, %70, %71}, {%72, %73, %74, %75}, db, p, 1, 1, %78;\n}\n"
      : "+f"(d[0]), "+f"(d[1]), "+f"(d[2]), "+f"(d[3]), "+f"(d[4]), "+f"(d[5]), "+f"(d[6]), "+f"(d[7]), "+f"(d[8]), "+f"(d[9]), "+f"(d[10]), "+f"(d[11]), "+f"(d[12]), "+f"(d[13]), "+f"(d[14]), "+f"(d[15]), "+f"(d[16]), "+f"(d[17]), "+f"(d[18]), "+f"(d[19]), "+f"(d[20]), "+f"(d[21]), "+f"(d[22]), "+f"(d[23]), "+f"(d[24]), "+f"(d[25]), "+f"(d[26]), "+f"(d[27]), "+f"(d[28]), "+f"(d[29]), "+f"(d[30]), "+f"(d[31]), "+f"(d[32]), "+f"(d[33]), "+f"(d[34]), "+f"(d[35]), "+f"(d[36]), "+f"(d[37]), "+f"(d[38]), "+f"(d[39]), "+f"(d[40]), "+f"(d[41]), "+f"(d[42]), "+f"(d[43]), "+f"(d[44]), "+f"(d[45]), "+f"(d[46]), "+f"(d[47]), "+f"(d[48]), "+f"(d[49]), "+f"(d[50]), "+f"(d[51]), "+f"(d[52]), "+f"(d[53]), "+f"(d[54]), "+f"(d[55]), "+f"(d[56]), "+f"(d[57]), "+f"(d[58]), "+f"(d[59]), "+f"(d[60]), "+f"(d[61]), "+f"(d[62]), "+f"(d[63]), "+f"(d[64]), "+f"(d[65]), "+f"(d[66]), "+f"(d[67]), "+f"(d[68]), "+f"(d[69]), "+f"(d[70]), "+f"(d[71])
      : "r"(a0), "r"(a1), "r"(a2), "r"(a3), "r"(blo), "r"(sd), "n"(TB), "r"(bhi));
}

constexpr int K1_XN_BYTES = 16 * 9216;
constexpr int K1_SLOT = 16384, K1_NSLOT = 5;
constexpr int K1_OFF_RING = K1_XN_BYTES;
constexpr int K1_OFF_BIAS = K1_OFF_RING + K1_NSLOT * K1_SLOT;
constexpr int K1_OFF_BAR = K1_OFF_BIAS + 576 * 2;
constexpr int K1_SMEM = K1_OFF_BAR + 640;
constexpr float QSCALE = 0.23570226039551584f * 1.4426950408889634f;

struct Ring {
    uint32_t slot, phase;
    __device__ __forceinline__ void advance() {
        if (++slot == K1_NSLOT) { slot = 0; phase ^= 1; }
    }
};

struct K1Ctx {
    uint32_t full0;
    uint32_t rel_addr;
    uint32_t descA, descB;
    Ring rd;
    uint32_t prev_slot;
    __device__ __forceinline__ uint32_t begin_stage() {
        mbar_wait(full0 + rd.slot * 8, rd.phase);
        wg_fence();
        return descB + rd.slot * (K1_SLOT >> 4);
    }
    __device__ __forceinline__ void end_stage() {
        wg_commit();
        wg_wait<1>();
        if (rel_addr) asm volatile("mbarrier.arrive.shared::cluster.b64 _, [%0];" ::"r"(rel_addr + prev_slot * 8) : "memory");
        prev_slot = rd.slot;
        rd.advance();
    }
};

__device__ __forceinline__ uint32_t descA_step(uint32_t base, int ks) { return base + (((ks >> 2) * 1024 + (ks & 3) * 32) >> 4); }
constexpr uint32_t K1_AHI = desc_hi(9216, 1), K1_BHI = desc_hi(1024, 1);

template <int V> struct IC { static constexpr int value = V; };
template <int I, int N, class F> __device__ __forceinline__ void static_for(F&& f) {
    if constexpr (I < N) { f(IC<I>{}); static_for<I + 1, N>(f); }
}

template <bool A_RS, bool B_RS, class Epi>
__device__ __forceinline__ void tile_pair(K1Ctx& c, float (&accA)[32], float (&accB)[32], uint32_t (&h)[144], Epi&& epi) {
    static_for<0, 9>([&](auto sc) {
        constexpr int s = decltype(sc)::value;
        const uint32_t db = c.begin_stage();
#pragma unroll
        for (int t = 0; t < 8; t++) {
            const int kk = s * 8 + t, ks = kk % 36;
            const uint32_t dbt = db + ((t * 2048) >> 4);
            if (kk < 36) {
                if constexpr (A_RS) wgmma_rs_n64<1>(accA, h[ks * 4], h[ks * 4 + 1], h[ks * 4 + 2], h[ks * 4 + 3], dbt, K1_BHI, ks != 0);
                else wgmma_ss_n64<1>(accA, descA_step(c.descA, ks), K1_AHI, dbt, K1_BHI, ks != 0);
            } else {
                if constexpr (B_RS) wgmma_rs_n64<1>(accB, h[ks * 4], h[ks * 4 + 1], h[ks * 4 + 2], h[ks * 4 + 3], dbt, K1_BHI, ks != 0);
                else wgmma_ss_n64<1>(accB, descA_step(c.descA, ks), K1_AHI, dbt, K1_BHI, ks != 0);
            }
        }
        c.end_stage();
        epi(sc);
    });
}

template <int B0, int NB, int HOFF>
__device__ __forceinline__ void gelu_blocks(const float (&acc)[32], uint32_t (&h)[144], const uint32_t (&bq)[8]) {
#pragma unroll
    for (int b = B0; b < B0 + NB; b++) {
        const float b0 = bf_lo(bq[b]), b1 = bf_hi(bq[b]);
        h[HOFF + b * 2 + 0] = pack_bf16(gelu2(acc[b * 4 + 0] + b0), gelu2(acc[b * 4 + 1] + b1));
        h[HOFF + b * 2 + 1] = pack_bf16(gelu2(acc[b * 4 + 2] + b0), gelu2(acc[b * 4 + 3] + b1));
    }
}
__device__ __forceinline__ void load_bias(uint32_t (&bq)[8], uint32_t addr) {
    asm volatile("ld.shared.v4.u32 {%0, %1, %2, %3}, [%4];" : "=r"(bq[0]), "=r"(bq[1]), "=r"(bq[2]), "=r"(bq[3]) : "r"(addr));
    asm volatile("ld.shared.v4.u32 {%0, %1, %2, %3}, [%4 + 16];" : "=r"(bq[4]), "=r"(bq[5]), "=r"(bq[6]), "=r"(bq[7]) : "r"(addr));
}
template <int S> __device__ __forceinline__ void store_part(const float (&o)[32], float4* p) {
    asm volatile("red.global.add.v4.f32 [%0], {%1, %2, %3, %4};" ::"l"(p + S * 512), "f"(o[S * 8]), "f"(o[S * 8 + 1]), "f"(o[S * 8 + 2]), "f"(o[S * 8 + 3]) : "memory");
    asm volatile("red.global.add.v4.f32 [%0], {%1, %2, %3, %4};" ::"l"(p + S * 512 + 256), "f"(o[S * 8 + 4]), "f"(o[S * 8 + 5]), "f"(o[S * 8 + 6]), "f"(o[S * 8 + 7]) : "memory");
}

constexpr int NCHUNK = 16;
constexpr int CHUNK_BYTES = KV_HEAD_BYTES / NCHUNK;
constexpr int SM_Q = 0;
constexpr int SM_KV = 32768;
constexpr int WO_PIECE = WO_TILE_BYTES / 9;
__host__ __device__ constexpr int sm_wo(int i) { return i == 0 ? 210944 : (i == 1 ? 0 : SM_KV + (i - 2) * WO_PIECE); }
constexpr int SM_EXCH = SM_KV + 7 * WO_PIECE;

__device__ __forceinline__ float exp2_fixed(float y) {
    const float u = __uint_as_float(__float_as_uint(y) & 0xFF807FFFu) - 512.02545f;
    float t = fmaf(u, 0.019497588f, 0.114550486f);
    t = fmaf(t, u, -0.29839927f);
    return fmaf(t, u, y);
}
__device__ __forceinline__ uint32_t pack_fixed(float lo, float hi) { return __byte_perm(__float_as_uint(lo), __float_as_uint(hi), 0x6521); }

#define POLY_MODE 1
__device__ __forceinline__ uint32_t hfma2_bf16(uint32_t a, uint32_t b, uint32_t c) {
    uint32_t r;
    asm("fma.rn.bf16x2 %0, %1, %2, %3;" : "=r"(r) : "r"(a), "r"(b), "r"(c));
    return r;
}
__device__ __forceinline__ uint32_t exp2_packed(float y0, float y1, uint32_t one2) {
    const uint32_t w = pack_fixed(y0, y1);
    uint32_t m;
    asm("lop3.b32 %0, %1, 0x007F007F, %2, 0xEA;" : "=r"(m) : "r"(w), "r"(one2));
    const uint32_t d = hfma2_bf16(m, 0x3EF93EF9u, 0xBF38BF38u);
    const uint32_t e = hfma2_bf16(d, d, 0xBD71BD71u);
    return hfma2_bf16(w, e, w);
}
template <int NB>
__device__ __forceinline__ void softmax_fast(const float (&s)[NB * 4], uint32_t (&p)[NB * 2], uint32_t one2) {
#pragma unroll
    for (int b = 0; b < NB; b++) {
        if ((POLY_MASK >> (b & 7)) & 1) {
            p[b * 2 + 0] = exp2_packed(s[b * 4 + 0], s[b * 4 + 1], one2);
            p[b * 2 + 1] = exp2_packed(s[b * 4 + 2], s[b * 4 + 3], one2);
        } else {
            p[b * 2 + 0] = pack_bf16(ex2(s[b * 4 + 0]), ex2(s[b * 4 + 1]));
            p[b * 2 + 1] = pack_bf16(ex2(s[b * 4 + 2]), ex2(s[b * 4 + 3]));
        }
    }
}

constexpr uint32_t KV_TILE = CHUNK_BYTES / 16;
__device__ __forceinline__ void issue_qk(float (&s)[64], uint32_t qd, uint32_t kd) {
    wgmma_ss_n128<0>(s, qd, desc_hi(512, 0), kd + (8u << 16), desc_hi(KV_GROUP_BYTES, 0), 0);
    wgmma_ss_n128<0>(s, qd + 16, desc_hi(512, 0), kd + 32, desc_hi(KV_GROUP_BYTES, 0), 1);
}
__device__ __forceinline__ void issue_pv(float (&o)[12], const uint32_t (&p)[32], uint32_t kd) {
#pragma unroll
    for (int k = 0; k < 8; k++)
        wgmma_rs_n24<1>(o, p[k * 4], p[k * 4 + 1], p[k * 4 + 2], p[k * 4 + 3], kd + 16 + ((KV_GROUP_BYTES / 16) << 16) + k * (2 * KV_GROUP_BYTES / 16),
                        desc_hi(128, 0), 1);
}
__device__ __forceinline__ void store_o(float (&o)[12], int rt, int head, int wq, int lane) {
    const int g = lane >> 2, q = lane & 3;
    const float i0 = __fdividef(1.0f, __shfl_sync(~0u, o[8], lane | 3)), i1 = __fdividef(1.0f, __shfl_sync(~0u, o[10], lane | 3));
#pragma unroll
    for (int i = 0; i < 3; i++) {
        const int pc = head * 9 + (i < 2 ? i * 4 + q : 8);
        uint32_t* op = g_O + (((rt * 36 + (pc >> 3)) * 128 + wq * 32 + g * 4 + (pc & 3)) * 4 + ((pc >> 2) & 1) * 2);
        if (i < 2 || q == 2) *reinterpret_cast<uint2*>(op) = make_uint2(pack_bf16(o[i * 4] * i0, o[i * 4 + 1] * i0), pack_bf16(o[i * 4 + 2] * i1, o[i * 4 + 3] * i1));
    }
#pragma unroll
    for (int i = 0; i < 12; i++) o[i] = 0.f;
}
__device__ __forceinline__ void mbar_arrive(uint32_t b) { asm volatile("mbarrier.arrive.shared::cta.b64 _, [%0];" ::"r"(b) : "memory"); }
__device__ __forceinline__ void mbar_wait_sleep(uint32_t b, uint32_t ns) {
    uint32_t ok, spins = 0;
    while (true) {
        asm volatile("{\n.reg .pred p;\nmbarrier.try_wait.parity.shared::cta.b64 p, [%1], 0;\nselp.u32 %0, 1, 0, p;\n}\n" : "=r"(ok) : "r"(b) : "memory");
        if (ok) break;
        __nanosleep(ns);
        if (++spins > (1u << 21)) __trap();
    }
}
__device__ __forceinline__ void flag_signal(unsigned int* f) {
    __threadfence();
    atomicAdd(f, 1u);
}
__device__ __forceinline__ void flag_wait(const unsigned int* f, unsigned int target, unsigned int sleep_ns) {
    uint32_t v, spins = 0;
    while (true) {
        asm volatile("ld.acquire.gpu.global.u32 %0, [%1];" : "=r"(v) : "l"(f) : "memory");
        if (v >= target) break;
        if (sleep_ns) __nanosleep(sleep_ns);
        if (++spins > (1u << 21)) __trap();
    }
}
__device__ __forceinline__ float sumsq2(uint32_t w) { return fmaf(bf_lo(w), bf_lo(w), bf_hi(w) * bf_hi(w)); }
__device__ __forceinline__ float sumsq8(const uint4 v) { return (sumsq2(v.x) + sumsq2(v.y)) + (sumsq2(v.z) + sumsq2(v.w)); }

enum { B_FULL = 0, B_EMPTY = 5, B_INIT = 10, B_XNDEAD = 11, B_QRDY = 12, B_FFN = 13, B_X = 16, B_KV = 32, B_FREE = 48, B_WO = 64, B_END = 73 };

__global__ void __cluster_dims__(2, 1, 1) __launch_bounds__(384, 1)
fused_kernel(const __grid_constant__ CUtensorMap tmX, const __grid_constant__ CUtensorMap tmQ3, const __grid_constant__ CUtensorMap tmQ1,
          const __grid_constant__ CUtensorMap tm1, const __grid_constant__ CUtensorMap tm2, const __nv_bfloat16* __restrict__ b1,
          const __nv_bfloat16* __restrict__ wo, const __nv_bfloat16* __restrict__ x, const __nv_bfloat16* __restrict__ b2,
          __nv_bfloat16* __restrict__ out) {
    extern __shared__ __align__(1024) uint8_t smem[];
    const uint32_t sb = s2u(smem);
    const int tid = threadIdx.x, lane = tid & 31;
    const int warp = __shfl_sync(~0u, tid >> 5, 0);
    const uint32_t rank = blockIdx.x & 1;
    const int cl = blockIdx.x >> 1;
    const int rb = (cl & 7) * 2 + rank;
    const int j = cl >> 3;
    const uint32_t bar0 = sb + K1_OFF_BAR;
    const uint32_t full0 = bar0 + B_FULL * 8, empty0 = bar0 + B_EMPTY * 8, xbar0 = bar0 + B_X * 8;
    const int head = blockIdx.x >> 2, quarter = blockIdx.x & 3;
    const int rt = quarter * 8 + (head >> 2), ct = head & 3;
    volatile uint32_t* slow_flag = reinterpret_cast<volatile uint32_t*>(smem + K1_OFF_BAR + B_END * 8);

    if (warp < 8) {
        PROF(0);
        PROFT(48);
        if (lane == 0) {
            mbar_init(xbar0 + warp * 16, 1);
            mbar_init(xbar0 + warp * 16 + 8, 1);
            fence_barrier_init();
            mbar_expect(xbar0 + warp * 16, 9216);
            tma3d(sb + warp * 2 * 9216, &tmX, 0, rb * 128 + warp * 16, 0, xbar0 + warp * 16);
            mbar_expect(xbar0 + warp * 16 + 8, 9216);
            tma3d(sb + (warp * 2 + 1) * 9216, &tmX, 0, rb * 128 + warp * 16 + 8, 0, xbar0 + warp * 16 + 8);
        }
        __syncwarp();
        cluster_arrive();
        reg_alloc<240>();
#pragma unroll 1
        for (int p = 0; p < 4; p++) {
            mbar_wait(xbar0 + warp * 16 + (p >> 1) * 8, 0);
            uint4* row = reinterpret_cast<uint4*>(smem + (warp * 2 + (p >> 1)) * 9216 + (p & 1) * 512 + lane * 16);
            float f[72];
#pragma unroll
            for (int i = 0; i < 9; i++) {
                const uint4 v = row[i * 64];
                f[i * 8 + 0] = bf_lo(v.x); f[i * 8 + 1] = bf_hi(v.x); f[i * 8 + 2] = bf_lo(v.y); f[i * 8 + 3] = bf_hi(v.y);
                f[i * 8 + 4] = bf_lo(v.z); f[i * 8 + 5] = bf_hi(v.z); f[i * 8 + 6] = bf_lo(v.w); f[i * 8 + 7] = bf_hi(v.w);
            }
            float s0 = 0.f, s1 = 0.f, s2 = 0.f, s3 = 0.f;
#pragma unroll
            for (int i = 0; i < 72; i += 4) { s0 += f[i]; s1 += f[i + 1]; s2 += f[i + 2]; s3 += f[i + 3]; }
            float sm = (s0 + s1) + (s2 + s3);
            sm += __shfl_xor_sync(~0u, sm, 1); sm += __shfl_xor_sync(~0u, sm, 2); sm += __shfl_xor_sync(~0u, sm, 4);
            const float mean = sm * (1.0f / DM);
            s0 = s1 = s2 = s3 = 0.f;
#pragma unroll
            for (int i = 0; i < 72; i += 4) {
                f[i] -= mean; f[i + 1] -= mean; f[i + 2] -= mean; f[i + 3] -= mean;
                s0 = fmaf(f[i], f[i], s0); s1 = fmaf(f[i + 1], f[i + 1], s1);
                s2 = fmaf(f[i + 2], f[i + 2], s2); s3 = fmaf(f[i + 3], f[i + 3], s3);
            }
            float sq = (s0 + s1) + (s2 + s3);
            sq += __shfl_xor_sync(~0u, sq, 1); sq += __shfl_xor_sync(~0u, sq, 2); sq += __shfl_xor_sync(~0u, sq, 4);
            const float rstd = rsqrtf(sq * (1.0f / DM) + 1e-5f);
#pragma unroll
            for (int i = 0; i < 9; i++) {
                uint4 o;
                o.x = pack_bf16(f[i * 8 + 0] * rstd, f[i * 8 + 1] * rstd);
                o.y = pack_bf16(f[i * 8 + 2] * rstd, f[i * 8 + 3] * rstd);
                o.z = pack_bf16(f[i * 8 + 4] * rstd, f[i * 8 + 5] * rstd);
                o.w = pack_bf16(f[i * 8 + 6] * rstd, f[i * 8 + 7] * rstd);
                row[i * 64] = o;
            }
        }
        const int wg = warp >> 2, wq = warp & 3;
        fence_proxy_async();
        named_bar_sync(1 + wg, 128);
        cluster_wait();
        PROF(1);

        const int g = lane >> 2, q = lane & 3;
        K1Ctx c;
        c.full0 = full0;
        c.rel_addr = 0;
        c.descA = desc_lo(sb + wg * 8 * 9216, 16);
        c.descB = desc_lo(sb + K1_OFF_RING, 2048);
        c.rd.slot = 0; c.rd.phase = 0; c.prev_slot = 0;
        uint32_t biasq = sb + K1_OFF_BIAS + q * 32;
        uint32_t bq[8];

        uint32_t h[144];
        float accA[32], accB[32];
        {
            float accQ[108];
            uint32_t rel = 0;
            if (lane == 0 && wq < 2) asm("mapa.shared::cluster.u32 %0, %1, %2;" : "=r"(rel) : "r"(empty0), "r"(wq));
#pragma unroll 1
            for (int s = 0; s < 18; s++) {
                const uint32_t db = c.begin_stage();
                const uint32_t da = c.descA + (s >> 1) * 64 + (s & 1) * 4;
                wgmma_ss_n216<1>(accQ, da, K1_AHI, db, K1_BHI, s != 0);
                wgmma_ss_n216<1>(accQ, da + 2, K1_AHI, db + (8192 >> 4), K1_BHI, 1);
                c.end_stage();
                c.rel_addr = rel;
            }
            PROF(2);
            uint32_t rel9[9];
#pragma unroll
            for (int i9 = 0; i9 < 9; i9++) {
                const int p = 4 * i9 + q, hh = (p * 57) >> 9, r = p - 9 * hh;
                rel9[i9] = hh * KV_HEAD_BYTES + (r < 8 ? (r >> 2) * 128 + (r & 3) * 4 : 0);
            }
            uint32_t gb = 0, o2 = 0;
            float scl0 = 1.f, scl1 = 1.f;
            tile_pair<false, false>(c, accA, accB, h, [&](auto sc) {
                constexpr int s = decltype(sc)::value;
                if constexpr (s == 0) reg_fence(accQ);
                if constexpr (s < 6) {
                    constexpr int grp = s / 2, part = s % 2;
                    if constexpr (part == 0) {
                        const int G = 3 * j + grp, type = G >> 3;
                        gb = (G & 7) * 4 * KV_HEAD_BYTES + (rb * 16 + warp * 2) * KV_GROUP_BYTES + g * 16 + (type == 0 ? Q_OFFSET : (type == 2 ? 256 : 0));
                        o2 = type == 0 ? 256 : (type == 2 ? 264 : 512);
                        scl0 = type == 0 ? QSCALE : ((type == 1 && ((POLY_MASK >> (wq * 2)) & 1)) ? 2.f : 1.f);
                        scl1 = type == 0 ? QSCALE : ((type == 1 && ((POLY_MASK >> (wq * 2 + 1)) & 1)) ? 2.f : 1.f);
                    }
#pragma unroll
                    for (int i9 = part * 5; i9 < (part ? 9 : 5); i9++) {
                        const int b = grp * 9 + i9;
                        uint32_t off = gb + rel9[i9];
                        if (i9 >= 2 && (i9 & 1) == 0) off += (q == i9 / 2 - 1) ? o2 : 0;
                        *reinterpret_cast<uint32_t*>(g_QKV + off) = pack_bf16(accQ[b * 4] * scl0, accQ[b * 4 + 1] * scl0);
                        *reinterpret_cast<uint32_t*>(g_QKV + off + KV_GROUP_BYTES) = pack_bf16(accQ[b * 4 + 2] * scl1, accQ[b * 4 + 3] * scl1);
                    }
                    if constexpr (s == 5) asm volatile("bar.arrive 3, 352;" ::: "memory");
                }
                if constexpr (s == 4) { named_bar_sync(4, 352); load_bias(bq, biasq); }
                if constexpr (s == 5) reg_fence(accA);
                if constexpr (s >= 5) gelu_blocks<(s - 5) * 2, 2, 96>(accA, h, bq);
                if constexpr (s == 8) load_bias(bq, biasq + 128);
            });
        }
        PROF(3);
#pragma unroll
        for (int i = 32; i < 96; i++) asm volatile("mov.u32 %0, 0;" : "=r"(h[i]));
#pragma unroll 1
        for (int p = 1; p < 4; p++) {
            biasq += 256;
            tile_pair<false, false>(c, accA, accB, h, [&](auto sc) {
                constexpr int s = decltype(sc)::value;
                if constexpr (s == 0) {
                    reg_fence(accB);
#pragma unroll
                    for (int i = 0; i < 80; i++) h[i] = h[i + 32];
                }
                if constexpr (s < 4) gelu_blocks<s * 2, 2, 80>(accB, h, bq);
                if constexpr (s == 4) load_bias(bq, biasq);
                if constexpr (s == 5) reg_fence(accA);
                if constexpr (s >= 5) gelu_blocks<(s - 5) * 2, 2, 96>(accA, h, bq);
                if constexpr (s == 8) load_bias(bq, biasq + 128);
            });
        }
        PROF(4);
        tile_pair<false, true>(c, accA, accB, h, [&](auto sc) {
            constexpr int s = decltype(sc)::value;
            if constexpr (s == 0) reg_fence(accB);
            if constexpr (s < 4) gelu_blocks<s * 2, 2, 112>(accB, h, bq);
            if constexpr (s == 4) load_bias(bq, biasq + 256);
            if constexpr (s == 5) { reg_fence(accA); if (tid == wg * 128) mbar_arrive(bar0 + B_XNDEAD * 8); }
            if constexpr (s == 5 || s == 6) gelu_blocks<(s - 5) * 3, 3, 128>(accA, h, bq);
            if constexpr (s == 7) gelu_blocks<6, 2, 128>(accA, h, bq);
            if constexpr (s == 3 || s == 7) reg_fence(h);
        });
        PROF(5);
        float4* const pbase = g_base + rb * 72 * 256 + tid;
        int tb = j;
        mbar_wait(bar0 + B_INIT * 8, 0);
#pragma unroll 1
        for (int p = 0; p < 4; p++) {
            const int ta = tb == 8 ? 0 : tb + 1;
            float4* const pb = pbase + tb * 2048;
            float4* const pa = pbase + ta * 2048;
            tile_pair<true, true>(c, accA, accB, h, [&](auto sc) {
                constexpr int s = decltype(sc)::value;
                if constexpr (s == 0) reg_fence(accB);
                if constexpr (s < 4) store_part<s>(accB, pb);
                if constexpr (s == 5) reg_fence(accA);
                if constexpr (s >= 5) store_part<s - 5>(accA, pa);
            });
            tb = ta == 8 ? 0 : ta + 1;
            PROF(6 + p);
        }
        wg_wait<0>();
        if (c.rel_addr) asm volatile("mbarrier.arrive.shared::cluster.b64 _, [%0];" ::"r"(c.rel_addr + c.prev_slot * 8) : "memory");
        reg_fence(accB);
        {
            float4* const pb = pbase + tb * 2048;
            store_part<0>(accB, pb); store_part<1>(accB, pb); store_part<2>(accB, pb); store_part<3>(accB, pb);
        }
        __syncwarp();
        if (lane == 0) mbar_arrive(bar0 + B_FFN * 8);
        PROF(10);
        PROFT(49);

        mbar_wait(bar0 + B_QRDY * 8, 0);
        const uint32_t slow = __any_sync(~0u, *slow_flag != 0);
        const uint32_t kd0 = ((sb + SM_KV) & 0x3FFFF) >> 4;
        const uint32_t qd0 = desc_lo(sb + SM_Q + wg * 4096, 128);
        const uint32_t kvbar = bar0 + B_KV * 8;
        float o[12];
#pragma unroll
        for (int i = 0; i < 12; i++) o[i] = 0.f;
        PROF(16);
        PROFT(50);
        if (!slow) {
            const uint32_t one2 = __shfl_sync(~0u, 0x3F803F80u + slow, 0);
            float s0[64], s1[64];
            uint32_t p0[32], p1[32];
            mbar_wait(kvbar, 0);
            reg_fence(o);
            wg_fence();
            issue_qk(s0, qd0, kd0);
            wg_commit();
            mbar_wait(kvbar + 8, 0);
            wg_fence();
            issue_qk(s1, qd0, kd0 + KV_TILE);
            wg_commit();
#pragma unroll 1
            for (int n = 0; n < 64; n += 2) {
                const uint32_t t = n & 15, tn = (n + 2) & 15;
                const uint32_t qd = qd0 + (((n + 2) >> 4) & 3) * 512, kd = kd0 + t * KV_TILE, kdn = kd0 + tn * KV_TILE;
                wg_wait<1>();
                reg_fence(s0);
                if (n >= 50 && tid == wg * 128) mbar_arrive(bar0 + (B_FREE + ((n - 50) >> 1)) * 8);
                softmax_fast<16>(s0, p0, one2);
                reg_fence(p0);
                if (t == 0 && n != 0) {
                    wg_wait<0>();
                    reg_fence(o);
                    store_o(o, quarter * 8 + (n >> 4) * 2 - 2 + wg, head, wq, lane);
                    reg_fence(o);
                    if (n == 16) PROF(17);
                }
                mbar_wait(kvbar + tn * 8, 0);
                wg_fence();
                issue_pv(o, p0, kd);
                issue_qk(s0, qd, kdn);
                wg_commit();
                wg_wait<1>();
                reg_fence(s1);
                softmax_fast<16>(s1, p1, one2);
                reg_fence(p1);
                mbar_wait(kvbar + tn * 8 + 8, 0);
                wg_fence();
                issue_pv(o, p1, kd + KV_TILE);
                issue_qk(s1, qd, kdn + KV_TILE);
                wg_commit();
            }
            wg_wait<0>();
            reg_fence(o);
            reg_fence(s0);
            reg_fence(s1);
            store_o(o, quarter * 8 + 6 + wg, head, wq, lane);
        } else {
#pragma unroll 1
            for (int pass = 0; pass < 4; pass++) {
                float m0 = -INFINITY, m1 = -INFINITY;
                float s[64];
                uint32_t p[32];
#pragma unroll 1
                for (int t = 0; t < 16; t++) {
                    mbar_wait(kvbar + t * 8, 0);
                    wg_fence();
                    issue_qk(s, qd0 + pass * 512, kd0 + t * KV_TILE);
                    wg_commit();
                    wg_wait<0>();
                    reg_fence(s);
                    float a0 = m0, a1 = m1;
#pragma unroll
                    for (int k = 0; k < 16; k++) {
                        if ((POLY_MASK >> (k & 7)) & 1) {
#pragma unroll
                            for (int i = 0; i < 4; i++) s[k * 4 + i] *= 0.5f;
                        }
                        a0 = fmaxf(a0, fmaxf(s[k * 4 + 0], s[k * 4 + 1]));
                        a1 = fmaxf(a1, fmaxf(s[k * 4 + 2], s[k * 4 + 3]));
                    }
                    a0 = fmaxf(a0, __shfl_xor_sync(~0u, a0, 1)); a1 = fmaxf(a1, __shfl_xor_sync(~0u, a1, 1));
                    a0 = fmaxf(a0, __shfl_xor_sync(~0u, a0, 2)); a1 = fmaxf(a1, __shfl_xor_sync(~0u, a1, 2));
                    const float r0 = ex2(m0 - a0), r1 = ex2(m1 - a1);
                    m0 = a0; m1 = a1;
#pragma unroll
                    for (int i = 0; i < 3; i++) { o[i * 4] *= r0; o[i * 4 + 1] *= r0; o[i * 4 + 2] *= r1; o[i * 4 + 3] *= r1; }
#pragma unroll
                    for (int k = 0; k < 16; k++) {
                        p[k * 2 + 0] = pack_bf16(ex2(s[k * 4 + 0] - m0), ex2(s[k * 4 + 1] - m0));
                        p[k * 2 + 1] = pack_bf16(ex2(s[k * 4 + 2] - m1), ex2(s[k * 4 + 3] - m1));
                    }
                    reg_fence(p);
                    reg_fence(o);
                    wg_fence();
                    issue_pv(o, p, kd0 + t * KV_TILE);
                    wg_commit();
                    wg_wait<0>();
                    reg_fence(o);
                }
                store_o(o, quarter * 8 + pass * 2 + wg, head, wq, lane);
            }
            if (tid == wg * 128)
                for (int i = 0; i < 7; i++) mbar_arrive(bar0 + (B_FREE + i) * 8);
        }
        PROF(18);
        PROFT(51);

        named_bar_sync(5, 256);
        if (tid == 0) {
            flag_signal(&g_flags.o_done[quarter]);
            flag_wait(&g_flags.ffn_done[rt >> 1], 8, 0);
        }
        named_bar_sync(5, 256);
        const int t128 = tid & 127;
        float4 bs[9];
        {
            const float4* bp = g_base + ((rt >> 1) * 72 + ct * 18 + wg * 9) * 256 + (rt & 1) * 128 + t128;
#pragma unroll
            for (int i = 0; i < 9; i++) bs[i] = __ldcg(bp + i * 256);
        }
        if (tid == 0) flag_wait(&g_flags.o_done[quarter], 32, 0);
        named_bar_sync(5, 256);
        PROF(19);
        uint4 af[18];
        {
            const uint4* ap = reinterpret_cast<const uint4*>(g_O) + (rt * 36 + wg * 18) * 128 + t128;
#pragma unroll
            for (int k = 0; k < 18; k++) af[k] = __ldcg(ap + k * 128);
        }
        float acc[72];
        const uint32_t wd0 = desc_lo(sb, 2304);
#pragma unroll
        for (int i = 0; i < 5; i++) mbar_wait(bar0 + (B_WO + wg * 4 + i) * 8, 0);
        wg_fence();
#pragma unroll
        for (int k = 0; k < 18; k++) {
            const uint32_t off = wg ? sm_wo((k + 18) >> 2) + ((k + 18) & 3) * 4608 : sm_wo(k >> 2) + (k & 3) * 4608;
            wgmma_rs_n144<1>(acc, af[k].x, af[k].y, af[k].z, af[k].w, wd0 + (off >> 4), desc_hi(128, 0), k != 0);
        }
        wg_commit();
        wg_wait<0>();
        reg_fence(acc);
        PROF(20);
        {
            float4* ex = reinterpret_cast<float4*>(smem + SM_EXCH) + t128;
#pragma unroll
            for (int i = 0; i < 9; i++) {
                const float4 lo = make_float4(acc[i * 4], acc[i * 4 + 1], acc[i * 4 + 2], acc[i * 4 + 3]);
                const float4 hi = make_float4(acc[36 + i * 4], acc[36 + i * 4 + 1], acc[36 + i * 4 + 2], acc[36 + i * 4 + 3]);
                ex[(wg * 9 + i) * 128] = wg ? lo : hi;
                const float4 own = wg ? hi : lo;
                bs[i].x = fmaf(bs[i].x, 0.5f, own.x); bs[i].y = fmaf(bs[i].y, 0.5f, own.y);
                bs[i].z = fmaf(bs[i].z, 0.5f, own.z); bs[i].w = fmaf(bs[i].w, 0.5f, own.w);
            }
            named_bar_sync(5, 256);
            uint32_t* op = reinterpret_cast<uint32_t*>(out + (size_t)(rt * 64 + wq * 16 + g) * DM + ct * 144 + wg * 72 + q * 2);
#pragma unroll
            for (int i = 0; i < 9; i++) {
                const float4 v = ex[((wg ^ 1) * 9 + i) * 128];
                op[i * 4] = pack_bf16(bs[i].x + v.x, bs[i].y + v.y);
                op[i * 4 + 4 * DM] = pack_bf16(bs[i].z + v.z, bs[i].w + v.w);
            }
        }
        if (tid == 0) {
            if (atomicAdd(&g_flags.exited, 1u) == gridDim.x - 1) {
                unsigned int* f = reinterpret_cast<unsigned int*>(&g_flags);
#pragma unroll 1
                for (int i = 0; i < (int)(sizeof(Flags) / 4); i++) f[i] = 0;
            }
        }
        PROF(21);
        PROFT(52);
    } else {
        reg_dealloc<24>();
        if (warp == 8 && lane == 0) {
            prefetch_tmap(&tmQ3); prefetch_tmap(&tmQ1); prefetch_tmap(&tm1); prefetch_tmap(&tm2);
            for (int i = 0; i < K1_NSLOT; i++) { mbar_init(full0 + i * 8, 1); mbar_init(empty0 + i * 8, 4); }
            mbar_init(bar0 + B_INIT * 8, 1); mbar_init(bar0 + B_XNDEAD * 8, 2); mbar_init(bar0 + B_QRDY * 8, 3); mbar_init(bar0 + B_FFN * 8, 8);
#pragma unroll 1
            for (int i = 0; i < 16; i++) { mbar_init(bar0 + (B_KV + i) * 8, 1); mbar_init(bar0 + (B_FREE + i) * 8, 2); }
#pragma unroll 1
            for (int i = 0; i < 9; i++) mbar_init(bar0 + (B_WO + i) * 8, 1);
            *slow_flag = 0;
            fence_barrier_init();
        }
        __syncwarp();
        cluster_arrive();
        cluster_wait();
        const uint8_t* kvsrc = g_QKV + (size_t)head * KV_HEAD_BYTES;
        if (warp == 8) {
            if (lane == 0) {
                Ring w{0, 1};
                const uint32_t dst0 = sb + K1_OFF_RING + rank * 8192;
#pragma unroll 1
                for (int s = 0; s < 18; s++) {
                    mbar_wait(empty0 + w.slot * 8, w.phase);
                    mbar_expect(full0 + w.slot * 8, 16384);
                    const uint32_t dst = dst0 + w.slot * K1_SLOT;
                    tma3d_mc(dst, &tmQ3, j * 216, s * 32 + rank * 16, 0, full0 + w.slot * 8, 3);
                    tma2d_mc(dst + 6144, &tmQ1, j * 216 + 192, s * 32 + rank * 16, full0 + w.slot * 8, 3);
                    w.advance();
                }
                int tile = 0, kb = rank;
#pragma unroll 1
                for (int s = 0; s < 81; s++) {
                    mbar_wait(empty0 + w.slot * 8, w.phase);
                    mbar_expect(full0 + w.slot * 8, 16384);
                    const uint32_t dst = dst0 + w.slot * K1_SLOT;
                    if (tile < 9) tma2d_mc(dst, &tm1, j * 576 + tile * 64, kb * 64, full0 + w.slot * 8, 3);
                    else tma2d_mc(dst, &tm2, (tile + j >= 18 ? tile + j - 18 : tile + j - 9) * 64, j * 576 + kb * 64, full0 + w.slot * 8, 3);
                    kb += 2;
                    if (kb >= 9) { kb -= 9; tile++; }
                    w.advance();
                }
#pragma unroll 1
                for (int s = 0; s < K1_NSLOT; s++) { mbar_wait(empty0 + w.slot * 8, w.phase); w.advance(); }
                mbar_wait(bar0 + B_QRDY * 8, 0);
                asm volatile("fence.proxy.async;" ::: "memory");
#pragma unroll 1
                for (int i = 11; i < NCHUNK; i++) {
                    mbar_expect(bar0 + (B_KV + i) * 8, CHUNK_BYTES);
                    bulk_load(sb + SM_KV + i * CHUNK_BYTES, kvsrc + i * CHUNK_BYTES, CHUNK_BYTES, bar0 + (B_KV + i) * 8);
                }
#pragma unroll 1
                for (int i = 0; i < 9; i++) {
                    if (i > 0) {
                        const int f = i == 1 ? 0 : ((i - 1) * 9 + 4) / 10;
                        mbar_wait_sleep(bar0 + (B_FREE + f) * 8, i == 1 ? 500 : 50);
                    }
                    mbar_expect(bar0 + (B_WO + i) * 8, WO_PIECE);
                    bulk_load(sb + (i == 0 ? sm_wo(0) : (i == 1 ? sm_wo(1) : SM_KV + (i - 2) * WO_PIECE)), g_Wo + ct * WO_TILE_BYTES + i * WO_PIECE, WO_PIECE,
                              bar0 + (B_WO + i) * 8);
                }
            }
        } else {
            const int ht = tid - 288;
            if (ht < 72) {
                const uint4 v = __ldg(reinterpret_cast<const uint4*>(b1 + j * 576) + ht);
                uint32_t* sbias = reinterpret_cast<uint32_t*>(smem + K1_OFF_BIAS) + (ht >> 3) * 32 + (ht & 7);
                sbias[0] = v.x; sbias[8] = v.y; sbias[16] = v.z; sbias[24] = v.w;
            }
            asm volatile("bar.arrive 4, 352;" ::: "memory");
#pragma unroll 4
            for (int i = ht; i < 9 * 256; i += 96) {
                const int t = i & 255, nb = j * 9 + (i >> 8);
                const int row = rb * 128 + (t >> 5) * 16 + ((t & 31) >> 2), col = nb * 8 + (t & 3) * 2;
                const uint32_t* xp = reinterpret_cast<const uint32_t*>(x + (size_t)row * DM + col);
                const uint32_t x0 = __ldg(xp), x1 = __ldg(xp + 4 * DM), bb = __ldg(reinterpret_cast<const uint32_t*>(b2 + col));
                g_base[(rb * 72 + nb) * 256 + t] = make_float4(2.f * (bf_lo(x0) + bf_lo(bb)), 2.f * (bf_hi(x0) + bf_hi(bb)),
                                                               2.f * (bf_lo(x1) + bf_lo(bb)), 2.f * (bf_hi(x1) + bf_hi(bb)));
            }
            named_bar_sync(7, 96);
            if (ht == 0) flag_signal(&g_flags.base_init[rb]);
            PROFH(37);
#pragma unroll 1
            for (int i = ht; i < 512; i += 96) {
                const int key = i & 127;
                uint8_t* p = g_QKV + (size_t)(j * 4 + (i >> 7)) * KV_HEAD_BYTES + (rb * 16 + (key >> 3)) * KV_GROUP_BYTES + 512 + (key & 7) * 16;
                *reinterpret_cast<uint32_t*>(p + 4) = ((POLY_MASK >> ((key >> 3) & 7)) & 1) ? 0x3F804000u : 0x00003F80u;
                *reinterpret_cast<uint32_t*>(p + 12) = 0x00003F80u;
            }
#pragma unroll 2
            for (int i = blockIdx.x * 324 + ht; i < blockIdx.x * 324 + 324; i += 96) {
                const int k = i / 72, nc = i - k * 72, c4 = nc / 18;
                *reinterpret_cast<uint4*>(g_Wo + c4 * WO_TILE_BYTES + (k >> 3) * 2304 + (nc - c4 * 18) * 128 + (k & 7) * 16) =
                    __ldg(reinterpret_cast<const uint4*>(wo) + i);
            }
            PROFH(38);
            named_bar_sync(3, 352);
            if (ht == 0) {
                flag_signal(&g_flags.qkv_stored[rb]);
                flag_wait(&g_flags.base_init[rb], 8, 200);
                mbar_arrive(bar0 + B_INIT * 8);
                flag_wait(&g_flags.qkv_stored[rb], 8, 200);
            }
            named_bar_sync(7, 96);
            PROFH(39);
#pragma unroll 1
            for (int i = warp - 9; i < 16; i += 3) {
                const int hd = j * 4 + (i >> 2), key = (i & 3) * 32 + lane;
                const uint8_t* p = g_QKV + (size_t)hd * KV_HEAD_BYTES + (rb * 16 + (key >> 3)) * KV_GROUP_BYTES + (key & 7) * 16;
                const uint4 a = __ldcg(reinterpret_cast<const uint4*>(p)), b = __ldcg(reinterpret_cast<const uint4*>(p + 128));
                float n = sumsq2(__ldcg(reinterpret_cast<const uint32_t*>(p + 512))) + sumsq8(a) + sumsq8(b);
                if ((POLY_MASK >> ((key >> 3) & 7)) & 1) n *= 0.25f;
#pragma unroll
                for (int o = 16; o; o >>= 1) n = fmaxf(n, __shfl_xor_sync(~0u, n, o));
                if (lane == 0) g_kmax[hd * 64 + rb * 4 + (i & 3)] = n;
            }
            named_bar_sync(7, 96);
            PROFH(40);
            if (ht == 0) {
                flag_signal(&g_flags.kv_ready);
                flag_wait(&g_flags.kv_ready, 128, 300);
                mbar_wait_sleep(bar0 + B_XNDEAD * 8, 300);
            }
            named_bar_sync(7, 96);
            PROFH(41);
            if (lane == 0) {
                asm volatile("fence.proxy.async;" ::: "memory");
#pragma unroll 1
                for (int i = warp - 9; i < 11; i += 3) {
                    mbar_expect(bar0 + (B_KV + i) * 8, CHUNK_BYTES);
                    bulk_load(sb + SM_KV + i * CHUNK_BYTES, kvsrc + i * CHUNK_BYTES, CHUNK_BYTES, bar0 + (B_KV + i) * 8);
                }
            }
            __syncwarp();
            float kmax2;
            {
                const float2 v = __ldcg(reinterpret_cast<const float2*>(g_kmax + head * 64 + lane * 2));
                kmax2 = fmaxf(v.x, v.y);
#pragma unroll
                for (int o = 16; o; o >>= 1) kmax2 = fmaxf(kmax2, __shfl_xor_sync(~0u, kmax2, o));
            }
#pragma unroll 1
            for (int r = ht; r < 512; r += 96) {
                const uint8_t* p = kvsrc + Q_OFFSET + (quarter * 64 + (r >> 3)) * KV_GROUP_BYTES + (r & 7) * 16;
                const uint4 a = __ldcg(reinterpret_cast<const uint4*>(p)), b = __ldcg(reinterpret_cast<const uint4*>(p + 128));
                const uint32_t e = __ldcg(reinterpret_cast<const uint32_t*>(p + 256));
                const float cc = sqrtf((sumsq2(e) + sumsq8(a) + sumsq8(b)) * kmax2) * 1.02f;
                if (!(cc <= 58.f)) *slow_flag = 1;
                uint4* dst = reinterpret_cast<uint4*>(smem + SM_Q + (r >> 3) * 512 + (r & 7) * 16);
                dst[0] = a;
                dst[8] = b;
                dst[16] = make_uint4(e, pack_bf16(-cc, 768.f), 0u, 0u);
                dst[24] = make_uint4(0u, POLY_MODE ? 0xBFFF0000u : 0xC0000000u, 0u, 0u);
            }
            named_bar_sync(7, 96);
            if (*slow_flag) {
#pragma unroll 1
                for (int r = ht; r < 512; r += 96) {
                    uint32_t* dst = reinterpret_cast<uint32_t*>(smem + SM_Q + (r >> 3) * 512 + (r & 7) * 16);
                    dst[65] = 0u;
                    dst[97] = 0u;
                }
            }
            fence_proxy_async();
            __syncwarp();
            if (lane == 0) mbar_arrive(bar0 + B_QRDY * 8);
            PROFH(42);
            if (ht == 0) {
                mbar_wait_sleep(bar0 + B_FFN * 8, 300);
                flag_signal(&g_flags.ffn_done[rb]);
            }
        }
    }
}

typedef CUresult (*EncodeFn)(CUtensorMap*, CUtensorMapDataType, cuuint32_t, void*, const cuuint64_t*, const cuuint64_t*, const cuuint32_t*,
                             const cuuint32_t*, CUtensorMapInterleave, CUtensorMapSwizzle, CUtensorMapL2promotion, CUtensorMapFloatOOBfill);

void make_map(EncodeFn fn, CUtensorMap* m, const void* base, int rank, const cuuint64_t* dims, const cuuint64_t* strides, const cuuint32_t* box) {
    cuuint32_t es[3] = {1, 1, 1};
    fn(m, CU_TENSOR_MAP_DATA_TYPE_BFLOAT16, rank, const_cast<void*>(base), dims, strides, box, es, CU_TENSOR_MAP_INTERLEAVE_NONE,
       CU_TENSOR_MAP_SWIZZLE_128B, CU_TENSOR_MAP_L2_PROMOTION_L2_256B, CU_TENSOR_MAP_FLOAT_OOB_FILL_NONE);
}

}

extern "C" void kernel_launch(void* const* d_in, const int* in_sizes, int n_in, void* d_out, int out_size) {
    const __nv_bfloat16* x = (const __nv_bfloat16*)d_in[0];
    const __nv_bfloat16* wqkv = (const __nv_bfloat16*)d_in[1];
    const __nv_bfloat16* wo = (const __nv_bfloat16*)d_in[2];
    const __nv_bfloat16* w1 = (const __nv_bfloat16*)d_in[4];
    const __nv_bfloat16* b1 = (const __nv_bfloat16*)d_in[5];
    const __nv_bfloat16* w2 = (const __nv_bfloat16*)d_in[6];
    const __nv_bfloat16* b2 = (const __nv_bfloat16*)d_in[7];
    __nv_bfloat16* out = (__nv_bfloat16*)d_out;

    EncodeFn fn = nullptr;
    cudaDriverEntryPointQueryResult qr;
    cudaGetDriverEntryPoint("cuTensorMapEncodeTiled", (void**)&fn, cudaEnableDefault, &qr);
    CUtensorMap tmX, tmQ3, tmQ1, tm1, tm2;
    {
        cuuint64_t d[3] = {64, SEQ, 9}, s[2] = {DM * 2, 128};
        cuuint32_t b[3] = {64, 8, 9};
        make_map(fn, &tmX, x, 3, d, s, b);
    }
    {
        cuuint64_t d[3] = {3 * DM, DM, 3}, s[2] = {3 * DM * 2, 128};
        cuuint32_t b[3] = {64, 16, 3};
        make_map(fn, &tmQ3, wqkv, 3, d, s, b);
        make_map(fn, &tmQ1, wqkv, 2, d, s, b);
    }
    {
        cuuint64_t d[2] = {FF, DM}, s[1] = {FF * 2};
        cuuint32_t b[2] = {64, 64};
        make_map(fn, &tm1, w1, 2, d, s, b);
        cuuint64_t d2[2] = {DM, FF}, s2[1] = {DM * 2};
        make_map(fn, &tm2, w2, 2, d2, s2, b);
    }
    cudaFuncSetAttribute(fused_kernel, cudaFuncAttributeMaxDynamicSharedMemorySize, K1_SMEM);
    fused_kernel<<<128, 384, K1_SMEM, cudaStreamPerThread>>>(tmX, tmQ3, tmQ1, tm1, tm2, b1, wo, x, b2, out);
}
```

```cpp
#include <cuda_runtime.h>
#include <cuda_bf16.h>
#include <cuda.h>
#include <stdint.h>

#define PROF(i) do { } while (0)
#define PROFT(i) do { } while (0)
#define PROFH(i) do { } while (0)
#define PROF_WG 0

namespace {

constexpr int SEQ = 2048, DM = 576, FF = 4608, NH = 32, DH = 18;

constexpr int KV_GROUP_BYTES = 5 * 128;
constexpr int KV_HEAD_BYTES = (SEQ / 8) * KV_GROUP_BYTES;
constexpr int Q_OFFSET = NH * KV_HEAD_BYTES;
#define POLY_MASK 0xB6
__device__ __align__(1024) uint8_t g_QKV[2 * NH * KV_HEAD_BYTES];
__device__ __align__(1024) float g_kmax[NH * 64];
__device__ __align__(1024) float4 g_base[16 * 72 * 256];
__device__ __align__(1024) uint32_t g_O[SEQ * DM / 2];
struct Flags {
    unsigned int base_init[16];
    unsigned int qkv_stored[16];
    unsigned int ffn_done[16];
    unsigned int o_done[4];
    unsigned int kv_ready;
    unsigned int exited;
};
__device__ Flags g_flags;
constexpr int WO_TILE_BYTES = DM * 144 * 2;
__device__ __align__(1024) uint8_t g_Wo[4 * WO_TILE_BYTES];

__device__ __forceinline__ uint32_t s2u(const void* p) { return (uint32_t)__cvta_generic_to_shared(p); }
__device__ __forceinline__ void mbar_init(uint32_t b, int c) { asm volatile("mbarrier.init.shared::cta.b64 [%0], %1;" ::"r"(b), "r"(c) : "memory"); }
__device__ __forceinline__ void mbar_expect(uint32_t b, uint32_t bytes) {
    asm volatile("mbarrier.arrive.expect_tx.shared::cta.b64 _, [%0], %1;" ::"r"(b), "r"(bytes) : "memory");
}
__device__ __forceinline__ void mbar_wait(uint32_t b, uint32_t parity) {
    asm volatile(
        "{\n.reg .pred p;\n.reg .u32 c;\n"
        "mbarrier.try_wait.parity.shared::cta.b64 p, [%0], %1;\n"
        "@p bra DONE;\n"
        "mov.u32 c, 0;\n"
        "LOOP:\n"
        "mbarrier.try_wait.parity.shared::cta.b64 p, [%0], %1;\n"
        "@p bra DONE;\n"
        "add.u32 c, c, 1;\n"
        "setp.lt.u32 p, c, 4194304;\n"
        "@p bra LOOP;\n"
        "trap;\n"
        "DONE:\n}\n" ::"r"(b), "r"(parity) : "memory");
}
__device__ __forceinline__ void fence_barrier_init() { asm volatile("fence.mbarrier_init.release.cluster;" ::: "memory"); }
__device__ __forceinline__ void fence_proxy_async() { asm volatile("fence.proxy.async.shared::cta;" ::: "memory"); }
__device__ __forceinline__ void cluster_arrive() { asm volatile("barrier.cluster.arrive.relaxed.aligned;" ::: "memory"); }
__device__ __forceinline__ void cluster_wait() { asm volatile("barrier.cluster.wait.aligned;" ::: "memory"); }
__device__ __forceinline__ void named_bar_sync(int id, int n) { asm volatile("bar.sync %0, %1;" ::"r"(id), "r"(n) : "memory"); }
__device__ __forceinline__ void griddep_wait() { asm volatile("griddepcontrol.wait;" ::: "memory"); }
__device__ __forceinline__ void griddep_launch() { asm volatile("griddepcontrol.launch_dependents;" ::: "memory"); }

__device__ __forceinline__ void tma3d_mc(uint32_t dst, const CUtensorMap* tm, int c0, int c1, int c2, uint32_t bar, uint16_t mask) {
    asm volatile("cp.async.bulk.tensor.3d.shared::cluster.global.mbarrier::complete_tx::bytes.multicast::cluster [%0], [%1, {%3, %4, %5}], [%2], %6;"
                 ::"r"(dst), "l"(tm), "r"(bar), "r"(c0), "r"(c1), "r"(c2), "h"(mask) : "memory");
}
__device__ __forceinline__ void tma2d_mc(uint32_t dst, const CUtensorMap* tm, int c0, int c1, uint32_t bar, uint16_t mask) {
    asm volatile("cp.async.bulk.tensor.2d.shared::cluster.global.mbarrier::complete_tx::bytes.multicast::cluster [%0], [%1, {%3, %4}], [%2], %5;"
                 ::"r"(dst), "l"(tm), "r"(bar), "r"(c0), "r"(c1), "h"(mask) : "memory");
}
__device__ __forceinline__ void tma3d(uint32_t dst, const CUtensorMap* tm, int c0, int c1, int c2, uint32_t bar) {
    asm volatile("cp.async.bulk.tensor.3d.shared::cluster.global.mbarrier::complete_tx::bytes [%0], [%1, {%3, %4, %5}], [%2];"
                 ::"r"(dst), "l"(tm), "r"(bar), "r"(c0), "r"(c1), "r"(c2) : "memory");
}
__device__ __forceinline__ void tma2d(uint32_t dst, const CUtensorMap* tm, int c0, int c1, uint32_t bar) {
    asm volatile("cp.async.bulk.tensor.2d.shared::cluster.global.mbarrier::complete_tx::bytes [%0], [%1, {%3, %4}], [%2];"
                 ::"r"(dst), "l"(tm), "r"(bar), "r"(c0), "r"(c1) : "memory");
}
__device__ __forceinline__ void bulk_load(uint32_t dst, const void* src, uint32_t bytes, uint32_t bar) {
    asm volatile("cp.async.bulk.shared::cluster.global.mbarrier::complete_tx::bytes [%0], [%1], %2, [%3];"
                 ::"r"(dst), "l"(src), "r"(bytes), "r"(bar) : "memory");
}
__device__ __forceinline__ void prefetch_tmap(const CUtensorMap* tm) { asm volatile("prefetch.tensormap [%0];" ::"l"(tm) : "memory"); }

__device__ __forceinline__ void wg_fence() { asm volatile("wgmma.fence.sync.aligned;" ::: "memory"); }
__device__ __forceinline__ void wg_commit() { asm volatile("wgmma.commit_group.sync.aligned;" ::: "memory"); }
template <int N> __device__ __forceinline__ void wg_wait() { asm volatile("wgmma.wait_group.sync.aligned %0;" ::"n"(N) : "memory"); }
template <int N> __device__ __forceinline__ void reg_fence(float (&d)[N]) {
#pragma unroll
    for (int i = 0; i < N; i++) asm volatile("" : "+f"(d[i])::"memory");
}
template <int N> __device__ __forceinline__ void reg_fence(uint32_t (&d)[N]) {
#pragma unroll
    for (int i = 0; i < N; i++) asm volatile("" : "+r"(d[i])::"memory");
}
template <int R> __device__ __forceinline__ void reg_alloc() { asm volatile("setmaxnreg.inc.sync.aligned.u32 %0;" ::"n"(R)); }
template <int R> __device__ __forceinline__ void reg_dealloc() { asm volatile("setmaxnreg.dec.sync.aligned.u32 %0;" ::"n"(R)); }

__device__ __forceinline__ uint64_t mk_desc(uint64_t z, uint32_t addr, uint32_t lbo, uint32_t sbo, uint32_t swz) {
    return z + ((uint64_t)(((addr & 0x3FFFF) >> 4) | ((lbo >> 4) << 16)) | ((uint64_t)((sbo >> 4) | (swz << 30)) << 32));
}
__device__ __forceinline__ uint32_t pack_bf16(float lo, float hi) {
    uint32_t r;
    asm("cvt.rn.bf16x2.f32 %0, %1, %2;" : "=r"(r) : "f"(hi), "f"(lo));
    return r;
}
__device__ __forceinline__ float bf_lo(uint32_t w) { return __uint_as_float(w << 16); }
__device__ __forceinline__ float bf_hi(uint32_t w) { return __uint_as_float(w & 0xFFFF0000u); }
__device__ __forceinline__ float ex2(float x) {
    float r;
    asm("ex2.approx.ftz.f32 %0, %1;" : "=f"(r) : "f"(x));
    return r;
}
__device__ __forceinline__ float tanh_fast(float x) {
    float r;
    asm("tanh.approx.f32 %0, %1;" : "=f"(r) : "f"(x));
    return r;
}
__device__ __forceinline__ float gelu2(float u) {
    const float w = fmaf(u * u, 0.0356774081f, 0.7978845608f);
    return fmaf(u, tanh_fast(u * w), u);
}

template<int TB, int AOFF, int BOFF> __device__ __forceinline__ void wgmma_ss_n216(float (&d)[108], uint64_t da, uint64_t db, int sd) {
    asm volatile("{\n.reg .pred p;\n.reg .b64 ta, tb;\nsetp.ne.b32 p, %110, 0;\nadd.s64 ta, %108, %112;\nadd.s64 tb, %109, %113;\n"
      "wgmma.mma_async.sync.aligned.m64n216k16.f32.bf16.bf16 {%0, %1, %2, %3, %4, %5, %6, %7, %8, %9, %10, %11, %12, %13, %14, %15, %16, %17, %18, %19, %20, %21, %22, %23, %24, %25, %26, %27, %28, %29, %30, %31, %32, %33, %34, %35, %36, %37, %38, %39, %40, %41, %42, %43, %44, %45, %46, %47, %48, %49, %50, %51, %52, %53, %54, %55, %56, %57, %58, %59, %60, %61, %62, %63, %64, %65, %66, %67, %68, %69, %70, %71, %72, %73, %74, %75, %76, %77, %78, %79, %80, %81, %82, %83, %84, %85, %86, %87, %88, %89, %90, %91, %92, %93, %94, %95, %96, %97, %98, %99, %100, %101, %102, %103, %104, %105, %106, %107}, ta, tb, p, 1, 1, 0, %111;\n}\n"
      : "+f"(d[0]), "+f"(d[1]), "+f"(d[2]), "+f"(d[3]), "+f"(d[4]), "+f"(d[5]), "+f"(d[6]), "+f"(d[7]), "+f"(d[8]), "+f"(d[9]), "+f"(d[10]), "+f"(d[11]), "+f"(d[12]), "+f"(d[13]), "+f"(d[14]), "+f"(d[15]), "+f"(d[16]), "+f"(d[17]), "+f"(d[18]), "+f"(d[19]), "+f"(d[20]), "+f"(d[21]), "+f"(d[22]), "+f"(d[23]), "+f"(d[24]), "+f"(d[25]), "+f"(d[26]), "+f"(d[27]), "+f"(d[28]), "+f"(d[29]), "+f"(d[30]), "+f"(d[31]), "+f"(d[32]), "+f"(d[33]), "+f"(d[34]), "+f"(d[35]), "+f"(d[36]), "+f"(d[37]), "+f"(d[38]), "+f"(d[39]), "+f"(d[40]), "+f"(d[41]), "+f"(d[42]), "+f"(d[43]), "+f"(d[44]), "+f"(d[45]), "+f"(d[46]), "+f"(d[47]), "+f"(d[48]), "+f"(d[49]), "+f"(d[50]), "+f"(d[51]), "+f"(d[52]), "+f"(d[53]), "+f"(d[54]), "+f"(d[55]), "+f"(d[56]), "+f"(d[57]), "+f"(d[58]), "+f"(d[59]), "+f"(d[60]), "+f"(d[61]), "+f"(d[62]), "+f"(d[63]), "+f"(d[64]), "+f"(d[65]), "+f"(d[66]), "+f"(d[67]), "+f"(d[68]), "+f"(d[69]), "+f"(d[70]), "+f"(d[71]), "+f"(d[72]), "+f"(d[73]), "+f"(d[74]), "+f"(d[75]), "+f"(d[76]), "+f"(d[77]), "+f"(d[78]), "+f"(d[79]), "+f"(d[80]), "+f"(d[81]), "+f"(d[82]), "+f"(d[83]), "+f"(d[84]), "+f"(d[85]), "+f"(d[86]), "+f"(d[87]), "+f"(d[88]), "+f"(d[89]), "+f"(d[90]), "+f"(d[91]), "+f"(d[92]), "+f"(d[93]), "+f"(d[94]), "+f"(d[95]), "+f"(d[96]), "+f"(d[97]), "+f"(d[98]), "+f"(d[99]), "+f"(d[100]), "+f"(d[101]), "+f"(d[102]), "+f"(d[103]), "+f"(d[104]), "+f"(d[105]), "+f"(d[106]), "+f"(d[107])
      : "l"(da), "l"(db), "r"(sd), "n"(TB), "n"(AOFF), "n"(BOFF));
}

template<int TB, int AOFF, int BOFF> __device__ __forceinline__ void wgmma_ss_n64(float (&d)[32], uint64_t da, uint64_t db, int sd) {
    asm volatile("{\n.reg .pred p;\n.reg .b64 ta, tb;\nsetp.ne.b32 p, %34, 0;\nadd.s64 ta, %32, %36;\nadd.s64 tb, %33, %37;\n"
      "wgmma.mma_async.sync.aligned.m64n64k16.f32.bf16.bf16 {%0, %1, %2, %3, %4, %5, %6, %7, %8, %9, %10, %11, %12, %13, %14, %15, %16, %17, %18, %19, %20, %21, %22, %23, %24, %25, %26, %27, %28, %29, %30, %31}, ta, tb, p, 1, 1, 0, %35;\n}\n"
      : "+f"(d[0]), "+f"(d[1]), "+f"(d[2]), "+f"(d[3]), "+f"(d[4]), "+f"(d[5]), "+f"(d[6]), "+f"(d[7]), "+f"(d[8]), "+f"(d[9]), "+f"(d[10]), "+f"(d[11]), "+f"(d[12]), "+f"(d[13]), "+f"(d[14]), "+f"(d[15]), "+f"(d[16]), "+f"(d[17]), "+f"(d[18]), "+f"(d[19]), "+f"(d[20]), "+f"(d[21]), "+f"(d[22]), "+f"(d[23]), "+f"(d[24]), "+f"(d[25]), "+f"(d[26]), "+f"(d[27]), "+f"(d[28]), "+f"(d[29]), "+f"(d[30]), "+f"(d[31])
      : "l"(da), "l"(db), "r"(sd), "n"(TB), "n"(AOFF), "n"(BOFF));
}

template<int TB, int AOFF, int BOFF> __device__ __forceinline__ void wgmma_ss_n128(float (&d)[64], uint64_t da, uint64_t db, int sd) {
    asm volatile("{\n.reg .pred p;\n.reg .b64 ta, tb;\nsetp.ne.b32 p, %66, 0;\nadd.s64 ta, %64, %68;\nadd.s64 tb, %65, %69;\n"
      "wgmma.mma_async.sync.aligned.m64n128k16.f32.bf16.bf16 {%0, %1, %2, %3, %4, %5, %6, %7, %8, %9, %10, %11, %12, %13, %14, %15, %16, %17, %18, %19, %20, %21, %22, %23, %24, %25, %26, %27, %28, %29, %30, %31, %32, %33, %34, %35, %36, %37, %38, %39, %40, %41, %42, %43, %44, %45, %46, %47, %48, %49, %50, %51, %52, %53, %54, %55, %56, %57, %58, %59, %60, %61, %62, %63}, ta, tb, p, 1, 1, 0, %67;\n}\n"
      : "+f"(d[0]), "+f"(d[1]), "+f"(d[2]), "+f"(d[3]), "+f"(d[4]), "+f"(d[5]), "+f"(d[6]), "+f"(d[7]), "+f"(d[8]), "+f"(d[9]), "+f"(d[10]), "+f"(d[11]), "+f"(d[12]), "+f"(d[13]), "+f"(d[14]), "+f"(d[15]), "+f"(d[16]), "+f"(d[17]), "+f"(d[18]), "+f"(d[19]), "+f"(d[20]), "+f"(d[21]), "+f"(d[22]), "+f"(d[23]), "+f"(d[24]), "+f"(d[25]), "+f"(d[26]), "+f"(d[27]), "+f"(d[28]), "+f"(d[29]), "+f"(d[30]), "+f"(d[31]), "+f"(d[32]), "+f"(d[33]), "+f"(d[34]), "+f"(d[35]), "+f"(d[36]), "+f"(d[37]), "+f"(d[38]), "+f"(d[39]), "+f"(d[40]), "+f"(d[41]), "+f"(d[42]), "+f"(d[43]), "+f"(d[44]), "+f"(d[45]), "+f"(d[46]), "+f"(d[47]), "+f"(d[48]), "+f"(d[49]), "+f"(d[50]), "+f"(d[51]), "+f"(d[52]), "+f"(d[53]), "+f"(d[54]), "+f"(d[55]), "+f"(d[56]), "+f"(d[57]), "+f"(d[58]), "+f"(d[59]), "+f"(d[60]), "+f"(d[61]), "+f"(d[62]), "+f"(d[63])
      : "l"(da), "l"(db), "r"(sd), "n"(TB), "n"(AOFF), "n"(BOFF));
}

template<int TB, int BOFF> __device__ __forceinline__ void wgmma_rs_n64(float (&d)[32], uint32_t a0, uint32_t a1, uint32_t a2, uint32_t a3, uint64_t db, int sd) {
    asm volatile("{\n.reg .pred p;\n.reg .b64 tb;\nsetp.ne.b32 p, %37, 0;\nadd.s64 tb, %36, %39;\n"
      "wgmma.mma_async.sync.aligned.m64n64k16.f32.bf16.bf16 {%0, %1, %2, %3, %4, %5, %6, %7, %8, %9, %10, %11, %12, %13, %14, %15, %16, %17, %18, %19, %20, %21, %22, %23, %24, %25, %26, %27, %28, %29, %30, %31}, {%32, %33, %34, %35}, tb, p, 1, 1, %38;\n}\n"
      : "+f"(d[0]), "+f"(d[1]), "+f"(d[2]), "+f"(d[3]), "+f"(d[4]), "+f"(d[5]), "+f"(d[6]), "+f"(d[7]), "+f"(d[8]), "+f"(d[9]), "+f"(d[10]), "+f"(d[11]), "+f"(d[12]), "+f"(d[13]), "+f"(d[14]), "+f"(d[15]), "+f"(d[16]), "+f"(d[17]), "+f"(d[18]), "+f"(d[19]), "+f"(d[20]), "+f"(d[21]), "+f"(d[22]), "+f"(d[23]), "+f"(d[24]), "+f"(d[25]), "+f"(d[26]), "+f"(d[27]), "+f"(d[28]), "+f"(d[29]), "+f"(d[30]), "+f"(d[31])
      : "r"(a0), "r"(a1), "r"(a2), "r"(a3), "l"(db), "r"(sd), "n"(TB), "n"(BOFF));
}

template<int TB, int BOFF> __device__ __forceinline__ void wgmma_rs_n24(float (&d)[12], uint32_t a0, uint32_t a1, uint32_t a2, uint32_t a3, uint64_t db, int sd) {
    asm volatile("{\n.reg .pred p;\n.reg .b64 tb;\nsetp.ne.b32 p, %17, 0;\nadd.s64 tb, %16, %19;\n"
      "wgmma.mma_async.sync.aligned.m64n24k16.f32.bf16.bf16 {%0, %1, %2, %3, %4, %5, %6, %7, %8, %9, %10, %11}, {%12, %13, %14, %15}, tb, p, 1, 1, %18;\n}\n"
      : "+f"(d[0]), "+f"(d[1]), "+f"(d[2]), "+f"(d[3]), "+f"(d[4]), "+f"(d[5]), "+f"(d[6]), "+f"(d[7]), "+f"(d[8]), "+f"(d[9]), "+f"(d[10]), "+f"(d[11])
      : "r"(a0), "r"(a1), "r"(a2), "r"(a3), "l"(db), "r"(sd), "n"(TB), "n"(BOFF));
}

template<int TB, int BOFF> __device__ __forceinline__ void wgmma_rs_n144(float (&d)[72], uint32_t a0, uint32_t a1, uint32_t a2, uint32_t a3, uint64_t db, int sd) {
    asm volatile("{\n.reg .pred p;\n.reg .b64 tb;\nsetp.ne.b32 p, %77, 0;\nadd.s64 tb, %76, %79;\n"
      "wgmma.mma_async.sync.aligned.m64n144k16.f32.bf16.bf16 {%0, %1, %2, %3, %4, %5, %6, %7, %8, %9, %10, %11, %12, %13, %14, %15, %16, %17, %18, %19, %20, %21, %22, %23, %24, %25, %26, %27, %28, %29, %30, %31, %32, %33, %34, %35, %36, %37, %38, %39, %40, %41, %42, %43, %44, %45, %46, %47, %48, %49, %50, %51, %52, %53, %54, %55, %56, %57, %58, %59, %60, %61, %62, %63, %64, %65, %66, %67, %68, %69, %70, %71}, {%72, %73, %74, %75}, tb, p, 1, 1, %78;\n}\n"
      : "+f"(d[0]), "+f"(d[1]), "+f"(d[2]), "+f"(d[3]), "+f"(d[4]), "+f"(d[5]), "+f"(d[6]), "+f"(d[7]), "+f"(d[8]), "+f"(d[9]), "+f"(d[10]), "+f"(d[11]), "+f"(d[12]), "+f"(d[13]), "+f"(d[14]), "+f"(d[15]), "+f"(d[16]), "+f"(d[17]), "+f"(d[18]), "+f"(d[19]), "+f"(d[20]), "+f"(d[21]), "+f"(d[22]), "+f"(d[23]), "+f"(d[24]), "+f"(d[25]), "+f"(d[26]), "+f"(d[27]), "+f"(d[28]), "+f"(d[29]), "+f"(d[30]), "+f"(d[31]), "+f"(d[32]), "+f"(d[33]), "+f"(d[34]), "+f"(d[35]), "+f"(d[36]), "+f"(d[37]), "+f"(d[38]), "+f"(d[39]), "+f"(d[40]), "+f"(d[41]), "+f"(d[42]), "+f"(d[43]), "+f"(d[44]), "+f"(d[45]), "+f"(d[46]), "+f"(d[47]), "+f"(d[48]), "+f"(d[49]), "+f"(d[50]), "+f"(d[51]), "+f"(d[52]), "+f"(d[53]), "+f"(d[54]), "+f"(d[55]), "+f"(d[56]), "+f"(d[57]), "+f"(d[58]), "+f"(d[59]), "+f"(d[60]), "+f"(d[61]), "+f"(d[62]), "+f"(d[63]), "+f"(d[64]), "+f"(d[65]), "+f"(d[66]), "+f"(d[67]), "+f"(d[68]), "+f"(d[69]), "+f"(d[70]), "+f"(d[71])
      : "r"(a0), "r"(a1), "r"(a2), "r"(a3), "l"(db), "r"(sd), "n"(TB), "n"(BOFF));
}

constexpr int K1_XN_BYTES = 16 * 9216;
constexpr int K1_OFF_RING = K1_XN_BYTES;
constexpr int K1_OFF_BIAS = K1_OFF_RING + 10 * 8192;
constexpr int K1_OFF_BAR = K1_OFF_BIAS + 576 * 2;
constexpr int K1_SMEM = K1_OFF_BAR + 768;
constexpr float QSCALE = 0.23570226039551584f * 1.4426950408889634f;

struct K1Ctx {
    uint32_t full0;
    uint32_t rel_addr;
    uint64_t descA, descB;
    uint32_t phase;
    __device__ __forceinline__ void begin_stage(int s) {
        mbar_wait(full0 + s * 8, phase);
        wg_fence();
    }
    __device__ __forceinline__ void release(int s) {
        if (rel_addr) asm volatile("mbarrier.arrive.shared::cluster.b64 _, [%0];" ::"r"(rel_addr + s * 8) : "memory");
    }
    __device__ __forceinline__ void end_stage(int s) {
        wg_commit();
        wg_wait<1>();
        release(s == 0 ? 8 : s - 1);
    }
};

__host__ __device__ constexpr int a_off(int ks) { return ((ks >> 2) * 1024 + (ks & 3) * 32) >> 4; }

template <int V> struct IC { static constexpr int value = V; };
template <int I, int N, class F> __device__ __forceinline__ void static_for(F&& f) {
    if constexpr (I < N) { f(IC<I>{}); static_for<I + 1, N>(f); }
}

template <bool A_RS, bool B_RS, class Epi>
__device__ __forceinline__ void tile_pair(K1Ctx& c, float (&accA)[32], float (&accB)[32], uint32_t (&h)[144], Epi&& epi) {
    static_for<0, 9>([&](auto sc) {
        constexpr int s = decltype(sc)::value;
        c.begin_stage(s);
        static_for<0, 8>([&](auto tc) {
            constexpr int kk = s * 8 + decltype(tc)::value, ks = kk % 36;
            constexpr int bo = (ks * 2048) >> 4;
            if constexpr (kk < 36) {
                if constexpr (A_RS) wgmma_rs_n64<1, bo>(accA, h[ks * 4], h[ks * 4 + 1], h[ks * 4 + 2], h[ks * 4 + 3], c.descB, ks != 0);
                else wgmma_ss_n64<1, a_off(ks), bo>(accA, c.descA, c.descB, ks != 0);
            } else {
                if constexpr (B_RS) wgmma_rs_n64<1, bo>(accB, h[ks * 4], h[ks * 4 + 1], h[ks * 4 + 2], h[ks * 4 + 3], c.descB, ks != 0);
                else wgmma_ss_n64<1, a_off(ks), bo>(accB, c.descA, c.descB, ks != 0);
            }
        });
        c.end_stage(s);
        epi(sc);
    });
    c.phase ^= 1;
}

template <int B0, int NB, int HOFF>
__device__ __forceinline__ void gelu_blocks(const float (&acc)[32], uint32_t (&h)[144], const uint32_t (&bq)[8]) {
#pragma unroll
    for (int b = B0; b < B0 + NB; b++) {
        const float b0 = bf_lo(bq[b]), b1 = bf_hi(bq[b]);
        h[HOFF + b * 2 + 0] = pack_bf16(gelu2(acc[b * 4 + 0] + b0), gelu2(acc[b * 4 + 1] + b1));
        h[HOFF + b * 2 + 1] = pack_bf16(gelu2(acc[b * 4 + 2] + b0), gelu2(acc[b * 4 + 3] + b1));
    }
}
__device__ __forceinline__ void load_bias(uint32_t (&bq)[8], uint32_t addr) {
    asm volatile("ld.shared.v4.u32 {%0, %1, %2, %3}, [%4];" : "=r"(bq[0]), "=r"(bq[1]), "=r"(bq[2]), "=r"(bq[3]) : "r"(addr));
    asm volatile("ld.shared.v4.u32 {%0, %1, %2, %3}, [%4 + 16];" : "=r"(bq[4]), "=r"(bq[5]), "=r"(bq[6]), "=r"(bq[7]) : "r"(addr));
}
template <int S> __device__ __forceinline__ void store_part(const float (&o)[32], float4* p) {
    asm volatile("red.global.add.v4.f32 [%0], {%1, %2, %3, %4};" ::"l"(p + S * 512), "f"(o[S * 8]), "f"(o[S * 8 + 1]), "f"(o[S * 8 + 2]), "f"(o[S * 8 + 3]) : "memory");
    asm volatile("red.global.add.v4.f32 [%0], {%1, %2, %3, %4};" ::"l"(p + S * 512 + 256), "f"(o[S * 8 + 4]), "f"(o[S * 8 + 5]), "f"(o[S * 8 + 6]), "f"(o[S * 8 + 7]) : "memory");
}

constexpr int NCHUNK = 16;
constexpr int CHUNK_BYTES = KV_HEAD_BYTES / NCHUNK;
constexpr int SM_Q = 0;
constexpr int SM_KV = 32768;
constexpr int WO_PIECE = WO_TILE_BYTES / 9;
__host__ __device__ constexpr int sm_wo(int i) { return i == 0 ? 210944 : (i == 1 ? 0 : SM_KV + (i - 2) * WO_PIECE); }
constexpr int SM_EXCH = SM_KV + 7 * WO_PIECE;

__device__ __forceinline__ float exp2_fixed(float y) {
    const float u = __uint_as_float(__float_as_uint(y) & 0xFF807FFFu) - 512.02545f;
    float t = fmaf(u, 0.019497588f, 0.114550486f);
    t = fmaf(t, u, -0.29839927f);
    return fmaf(t, u, y);
}
__device__ __forceinline__ uint32_t pack_fixed(float lo, float hi) { return __byte_perm(__float_as_uint(lo), __float_as_uint(hi), 0x6521); }

#define POLY_MODE 1
__device__ __forceinline__ uint32_t hfma2_bf16(uint32_t a, uint32_t b, uint32_t c) {
    uint32_t r;
    asm("fma.rn.bf16x2 %0, %1, %2, %3;" : "=r"(r) : "r"(a), "r"(b), "r"(c));
    return r;
}
__device__ __forceinline__ uint32_t exp2_packed(float y0, float y1, uint32_t one2) {
    const uint32_t w = pack_fixed(y0, y1);
    uint32_t m;
    asm("lop3.b32 %0, %1, 0x007F007F, %2, 0xEA;" : "=r"(m) : "r"(w), "r"(one2));
    const uint32_t d = hfma2_bf16(m, 0x3EF93EF9u, 0xBF38BF38u);
    const uint32_t e = hfma2_bf16(d, d, 0xBD71BD71u);
    return hfma2_bf16(w, e, w);
}
template <int NB>
__device__ __forceinline__ void softmax_fast(const float (&s)[NB * 4], uint32_t (&p)[NB * 2], uint32_t one2) {
#pragma unroll
    for (int b = 0; b < NB; b++) {
        if ((POLY_MASK >> (b & 7)) & 1) {
            p[b * 2 + 0] = exp2_packed(s[b * 4 + 0], s[b * 4 + 1], one2);
            p[b * 2 + 1] = exp2_packed(s[b * 4 + 2], s[b * 4 + 3], one2);
        } else {
            p[b * 2 + 0] = pack_bf16(ex2(s[b * 4 + 0]), ex2(s[b * 4 + 1]));
            p[b * 2 + 1] = pack_bf16(ex2(s[b * 4 + 2]), ex2(s[b * 4 + 3]));
        }
    }
}

constexpr int KV_TILE = CHUNK_BYTES / 16;
template <int OFF> __device__ __forceinline__ void issue_qk(float (&s)[64], uint64_t qd, uint64_t kd) {
    wgmma_ss_n128<0, 0, OFF + (8 << 16)>(s, qd, kd, 0);
    wgmma_ss_n128<0, 16, OFF + 32>(s, qd, kd, 1);
}
template <int OFF> __device__ __forceinline__ void issue_pv(float (&o)[12], const uint32_t (&p)[32], uint64_t vd) {
    static_for<0, 8>([&](auto kc) {
        constexpr int k = decltype(kc)::value;
        wgmma_rs_n24<1, OFF + k * (2 * KV_GROUP_BYTES / 16)>(o, p[k * 4], p[k * 4 + 1], p[k * 4 + 2], p[k * 4 + 3], vd, 1);
    });
}
__device__ __forceinline__ void store_o(float (&o)[12], int rt, int head, int wq, int lane) {
    const int g = lane >> 2, q = lane & 3;
    const float i0 = __fdividef(1.0f, __shfl_sync(~0u, o[8], lane | 3)), i1 = __fdividef(1.0f, __shfl_sync(~0u, o[10], lane | 3));
#pragma unroll
    for (int i = 0; i < 3; i++) {
        const int pc = head * 9 + (i < 2 ? i * 4 + q : 8);
        uint32_t* op = g_O + (((rt * 36 + (pc >> 3)) * 128 + wq * 32 + g * 4 + (pc & 3)) * 4 + ((pc >> 2) & 1) * 2);
        if (i < 2 || q == 2) *reinterpret_cast<uint2*>(op) = make_uint2(pack_bf16(o[i * 4] * i0, o[i * 4 + 1] * i0), pack_bf16(o[i * 4 + 2] * i1, o[i * 4 + 3] * i1));
    }
#pragma unroll
    for (int i = 0; i < 12; i++) o[i] = 0.f;
}
__device__ __forceinline__ void mbar_arrive(uint32_t b) { asm volatile("mbarrier.arrive.shared::cta.b64 _, [%0];" ::"r"(b) : "memory"); }
__device__ __forceinline__ void mbar_wait_sleep(uint32_t b, uint32_t ns) {
    uint32_t ok, spins = 0;
    while (true) {
        asm volatile("{\n.reg .pred p;\nmbarrier.try_wait.parity.shared::cta.b64 p, [%1], 0;\nselp.u32 %0, 1, 0, p;\n}\n" : "=r"(ok) : "r"(b) : "memory");
        if (ok) break;
        __nanosleep(ns);
        if (++spins > (1u << 21)) __trap();
    }
}
__device__ __forceinline__ void flag_signal(unsigned int* f) {
    __threadfence();
    atomicAdd(f, 1u);
}
__device__ __forceinline__ void flag_wait(const unsigned int* f, unsigned int target, unsigned int sleep_ns) {
    uint32_t v, spins = 0;
    while (true) {
        asm volatile("ld.acquire.gpu.global.u32 %0, [%1];" : "=r"(v) : "l"(f) : "memory");
        if (v >= target) break;
        if (sleep_ns) __nanosleep(sleep_ns);
        if (++spins > (1u << 21)) __trap();
    }
}
__device__ __forceinline__ float sumsq2(uint32_t w) { return fmaf(bf_lo(w), bf_lo(w), bf_hi(w) * bf_hi(w)); }
__device__ __forceinline__ float sumsq8(const uint4 v) { return (sumsq2(v.x) + sumsq2(v.y)) + (sumsq2(v.z) + sumsq2(v.w)); }

enum { B_FULL = 0, B_EMPTY = 9, B_INIT = 18, B_XNDEAD = 19, B_QRDY = 20, B_FFN = 21, B_X = 22, B_KV = 38, B_FREE = 54, B_WO = 62, B_END = 71 };

__global__ void __cluster_dims__(2, 1, 1) __launch_bounds__(384, 1)
fused_kernel(const __grid_constant__ CUtensorMap tmX, const __grid_constant__ CUtensorMap tmQ3, const __grid_constant__ CUtensorMap tmQ1,
          const __grid_constant__ CUtensorMap tm1, const __grid_constant__ CUtensorMap tm2, const __nv_bfloat16* __restrict__ b1,
          const __nv_bfloat16* __restrict__ wo, const __nv_bfloat16* __restrict__ x, const __nv_bfloat16* __restrict__ b2,
          __nv_bfloat16* __restrict__ out, const uint64_t zero) {
    extern __shared__ __align__(1024) uint8_t smem[];
    const uint32_t sb = s2u(smem);
    const int tid = threadIdx.x, lane = tid & 31;
    const int warp = __shfl_sync(~0u, tid >> 5, 0);
    const uint32_t rank = blockIdx.x & 1;
    const int cl = blockIdx.x >> 1;
    const int rb = (cl & 7) * 2 + rank;
    const int j = cl >> 3;
    const uint32_t bar0 = sb + K1_OFF_BAR;
    const uint32_t full0 = bar0 + B_FULL * 8, empty0 = bar0 + B_EMPTY * 8, xbar0 = bar0 + B_X * 8;
    const int head = blockIdx.x >> 2, quarter = blockIdx.x & 3;
    const int rt = quarter * 8 + (head >> 2), ct = head & 3;
    volatile uint32_t* slow_flag = reinterpret_cast<volatile uint32_t*>(smem + K1_OFF_BAR + B_END * 8);

    if (warp < 8) {
        PROF(0);
        PROFT(48);
        if (lane == 0) {
            mbar_init(xbar0 + warp * 16, 1);
            mbar_init(xbar0 + warp * 16 + 8, 1);
            fence_barrier_init();
            mbar_expect(xbar0 + warp * 16, 9216);
            tma3d(sb + warp * 2 * 9216, &tmX, 0, rb * 128 + warp * 16, 0, xbar0 + warp * 16);
            mbar_expect(xbar0 + warp * 16 + 8, 9216);
            tma3d(sb + (warp * 2 + 1) * 9216, &tmX, 0, rb * 128 + warp * 16 + 8, 0, xbar0 + warp * 16 + 8);
        }
        __syncwarp();
        cluster_arrive();
        reg_alloc<240>();
#pragma unroll 1
        for (int p = 0; p < 4; p++) {
            mbar_wait(xbar0 + warp * 16 + (p >> 1) * 8, 0);
            uint4* row = reinterpret_cast<uint4*>(smem + (warp * 2 + (p >> 1)) * 9216 + (p & 1) * 512 + lane * 16);
            float f[72];
#pragma unroll
            for (int i = 0; i < 9; i++) {
                const uint4 v = row[i * 64];
                f[i * 8 + 0] = bf_lo(v.x); f[i * 8 + 1] = bf_hi(v.x); f[i * 8 + 2] = bf_lo(v.y); f[i * 8 + 3] = bf_hi(v.y);
                f[i * 8 + 4] = bf_lo(v.z); f[i * 8 + 5] = bf_hi(v.z); f[i * 8 + 6] = bf_lo(v.w); f[i * 8 + 7] = bf_hi(v.w);
            }
            float s0 = 0.f, s1 = 0.f, s2 = 0.f, s3 = 0.f;
#pragma unroll
            for (int i = 0; i < 72; i += 4) { s0 += f[i]; s1 += f[i + 1]; s2 += f[i + 2]; s3 += f[i + 3]; }
            float sm = (s0 + s1) + (s2 + s3);
            sm += __shfl_xor_sync(~0u, sm, 1); sm += __shfl_xor_sync(~0u, sm, 2); sm += __shfl_xor_sync(~0u, sm, 4);
            const float mean = sm * (1.0f / DM);
            s0 = s1 = s2 = s3 = 0.f;
#pragma unroll
            for (int i = 0; i < 72; i += 4) {
                f[i] -= mean; f[i + 1] -= mean; f[i + 2] -= mean; f[i + 3] -= mean;
                s0 = fmaf(f[i], f[i], s0); s1 = fmaf(f[i + 1], f[i + 1], s1);
                s2 = fmaf(f[i + 2], f[i + 2], s2); s3 = fmaf(f[i + 3], f[i + 3], s3);
            }
            float sq = (s0 + s1) + (s2 + s3);
            sq += __shfl_xor_sync(~0u, sq, 1); sq += __shfl_xor_sync(~0u, sq, 2); sq += __shfl_xor_sync(~0u, sq, 4);
            const float rstd = rsqrtf(sq * (1.0f / DM) + 1e-5f);
#pragma unroll
            for (int i = 0; i < 9; i++) {
                uint4 o;
                o.x = pack_bf16(f[i * 8 + 0] * rstd, f[i * 8 + 1] * rstd);
                o.y = pack_bf16(f[i * 8 + 2] * rstd, f[i * 8 + 3] * rstd);
                o.z = pack_bf16(f[i * 8 + 4] * rstd, f[i * 8 + 5] * rstd);
                o.w = pack_bf16(f[i * 8 + 6] * rstd, f[i * 8 + 7] * rstd);
                row[i * 64] = o;
            }
        }
        const int wg = warp >> 2, wq = warp & 3;
        fence_proxy_async();
        named_bar_sync(1 + wg, 128);
        cluster_wait();
        PROF(1);

        const int g = lane >> 2, q = lane & 3;
        K1Ctx c;
        c.full0 = full0;
        c.rel_addr = 0;
        c.descA = mk_desc(zero, sb + wg * 8 * 9216, 16, 9216, 1);
        c.descB = mk_desc(zero, sb + K1_OFF_RING, 2048, 1024, 1);
        c.phase = 0;
        uint32_t biasq = sb + K1_OFF_BIAS + q * 32;
        uint32_t bq[8];

        uint32_t h[144];
        float accA[32], accB[32];
        {
            float accQ[108];
            uint32_t rel = 0;
            if (lane == 0 && wq < 2) asm("mapa.shared::cluster.u32 %0, %1, %2;" : "=r"(rel) : "r"(empty0), "r"(wq));
#pragma unroll 1
            for (int r = 0; r < 2; r++) {
                const uint64_t dae = c.descA + (r ? a_off(18) : 0), dao = c.descA + (r ? a_off(20) : a_off(2));
                static_for<0, 9>([&](auto sc) {
                    constexpr int s = decltype(sc)::value;
                    c.begin_stage(s);
                    wgmma_ss_n216<1, (s >> 1) * 64, ((2 * s) % 9) * 512>(accQ, (s & 1) ? dao : dae, c.descB, (r | s) != 0);
                    wgmma_ss_n216<1, (s >> 1) * 64 + 2, ((2 * s + 1) % 9) * 512>(accQ, (s & 1) ? dao : dae, c.descB, 1);
                    c.end_stage(s);
                    c.rel_addr = rel;
                });
                c.phase ^= 1;
            }
            PROF(2);
            uint32_t rel9[9];
#pragma unroll
            for (int i9 = 0; i9 < 9; i9++) {
                const int p = 4 * i9 + q, hh = (p * 57) >> 9, r = p - 9 * hh;
                rel9[i9] = hh * KV_HEAD_BYTES + (r < 8 ? (r >> 2) * 128 + (r & 3) * 4 : 0);
            }
            uint32_t gb = 0, o2 = 0;
            float scl0 = 1.f, scl1 = 1.f;
            tile_pair<false, false>(c, accA, accB, h, [&](auto sc) {
                constexpr int s = decltype(sc)::value;
                if constexpr (s == 0) reg_fence(accQ);
                if constexpr (s < 6) {
                    constexpr int grp = s / 2, part = s % 2;
                    if constexpr (part == 0) {
                        const int G = 3 * j + grp, type = G >> 3;
                        gb = (G & 7) * 4 * KV_HEAD_BYTES + (rb * 16 + warp * 2) * KV_GROUP_BYTES + g * 16 + (type == 0 ? Q_OFFSET : (type == 2 ? 256 : 0));
                        o2 = type == 0 ? 256 : (type == 2 ? 264 : 512);
                        scl0 = type == 0 ? QSCALE : ((type == 1 && ((POLY_MASK >> (wq * 2)) & 1)) ? 2.f : 1.f);
                        scl1 = type == 0 ? QSCALE : ((type == 1 && ((POLY_MASK >> (wq * 2 + 1)) & 1)) ? 2.f : 1.f);
                    }
#pragma unroll
                    for (int i9 = part * 5; i9 < (part ? 9 : 5); i9++) {
                        const int b = grp * 9 + i9;
                        uint32_t off = gb + rel9[i9];
                        if (i9 >= 2 && (i9 & 1) == 0) off += (q == i9 / 2 - 1) ? o2 : 0;
                        *reinterpret_cast<uint32_t*>(g_QKV + off) = pack_bf16(accQ[b * 4] * scl0, accQ[b * 4 + 1] * scl0);
                        *reinterpret_cast<uint32_t*>(g_QKV + off + KV_GROUP_BYTES) = pack_bf16(accQ[b * 4 + 2] * scl1, accQ[b * 4 + 3] * scl1);
                    }
                    if constexpr (s == 5) asm volatile("bar.arrive 3, 352;" ::: "memory");
                }
                if constexpr (s == 4) { named_bar_sync(4, 352); load_bias(bq, biasq); }
                if constexpr (s == 5) reg_fence(accA);
                if constexpr (s >= 5) gelu_blocks<(s - 5) * 2, 2, 96>(accA, h, bq);
                if constexpr (s == 8) load_bias(bq, biasq + 128);
            });
        }
        PROF(3);
#pragma unroll
        for (int i = 32; i < 96; i++) asm volatile("mov.u32 %0, 0;" : "=r"(h[i]));
#pragma unroll 1
        for (int p = 1; p < 4; p++) {
            biasq += 256;
            tile_pair<false, false>(c, accA, accB, h, [&](auto sc) {
                constexpr int s = decltype(sc)::value;
                if constexpr (s == 0) {
                    reg_fence(accB);
#pragma unroll
                    for (int i = 0; i < 80; i++) h[i] = h[i + 32];
                }
                if constexpr (s < 4) gelu_blocks<s * 2, 2, 80>(accB, h, bq);
                if constexpr (s == 4) load_bias(bq, biasq);
                if constexpr (s == 5) reg_fence(accA);
                if constexpr (s >= 5) gelu_blocks<(s - 5) * 2, 2, 96>(accA, h, bq);
                if constexpr (s == 8) load_bias(bq, biasq + 128);
            });
        }
        PROF(4);
        tile_pair<false, true>(c, accA, accB, h, [&](auto sc) {
            constexpr int s = decltype(sc)::value;
            if constexpr (s == 0) reg_fence(accB);
            if constexpr (s < 4) gelu_blocks<s * 2, 2, 112>(accB, h, bq);
            if constexpr (s == 4) load_bias(bq, biasq + 256);
            if constexpr (s == 5) { reg_fence(accA); if (tid == wg * 128) mbar_arrive(bar0 + B_XNDEAD * 8); }
            if constexpr (s == 5 || s == 6) gelu_blocks<(s - 5) * 3, 3, 128>(accA, h, bq);
            if constexpr (s == 7) gelu_blocks<6, 2, 128>(accA, h, bq);
            if constexpr (s == 3 || s == 7) reg_fence(h);
        });
        PROF(5);
        float4* const pbase = g_base + rb * 72 * 256 + tid;
        int tb = j;
        mbar_wait(bar0 + B_INIT * 8, 0);
#pragma unroll 1
        for (int p = 0; p < 4; p++) {
            const int ta = tb == 8 ? 0 : tb + 1;
            float4* const pb = pbase + tb * 2048;
            float4* const pa = pbase + ta * 2048;
            tile_pair<true, true>(c, accA, accB, h, [&](auto sc) {
                constexpr int s = decltype(sc)::value;
                if constexpr (s == 0) reg_fence(accB);
                if constexpr (s < 4) store_part<s>(accB, pb);
                if constexpr (s == 5) reg_fence(accA);
                if constexpr (s >= 5) store_part<s - 5>(accA, pa);
            });
            tb = ta == 8 ? 0 : ta + 1;
            PROF(6 + p);
        }
        wg_wait<0>();
        c.release(8);
        reg_fence(accB);
        {
            float4* const pb = pbase + tb * 2048;
            store_part<0>(accB, pb); store_part<1>(accB, pb); store_part<2>(accB, pb); store_part<3>(accB, pb);
        }
        __syncwarp();
        if (lane == 0) mbar_arrive(bar0 + B_FFN * 8);
        PROF(10);
        PROFT(49);

        mbar_wait(bar0 + B_QRDY * 8, 0);
        const uint32_t slow = __any_sync(~0u, *slow_flag != 0);
        const uint64_t kd0 = mk_desc(zero, sb + SM_KV, 0, KV_GROUP_BYTES, 0);
        const uint64_t vd0 = mk_desc(zero, sb + SM_KV + 256, KV_GROUP_BYTES, 128, 0);
        const uint64_t qd0 = mk_desc(zero, sb + SM_Q + wg * 4096, 128, 512, 0);
        const uint32_t kvbar = bar0 + B_KV * 8;
        float o[12];
#pragma unroll
        for (int i = 0; i < 12; i++) o[i] = 0.f;
        PROF(16);
        PROFT(50);
        if (!slow) {
            const uint32_t one2 = 0x3F803F80u + (uint32_t)zero;
            float s0[64], s1[64];
            uint32_t p0[32], p1[32];
            mbar_wait(kvbar, 0);
            reg_fence(o);
            wg_fence();
            issue_qk<0>(s0, qd0, kd0);
            wg_commit();
            mbar_wait(kvbar + 8, 0);
            wg_fence();
            issue_qk<KV_TILE>(s1, qd0, kd0);
            wg_commit();
            uint64_t qd = qd0;
            const uint32_t fre = (tid == wg * 128) ? bar0 + B_FREE * 8 - 8 : 0;
#pragma unroll 1
            for (int pass = 0; pass < 4; pass++) {
                uint64_t vd = vd0, kdn = kd0 + 2 * KV_TILE;
                uint32_t bn = kvbar + 16;
#pragma unroll 1
                for (int it = 0; it < 8; it++) {
                    if (it == 7) { kdn = kd0; bn = kvbar; qd += 512; }
                    wg_wait<1>();
                    reg_fence(s0);
                    if (pass == 3 && it > 0 && fre) mbar_arrive(fre + it * 8);
                    softmax_fast<16>(s0, p0, one2);
                    reg_fence(p0);
                    if (it == 0 && pass != 0) {
                        wg_wait<0>();
                        reg_fence(o);
                        store_o(o, quarter * 8 + pass * 2 - 2 + wg, head, wq, lane);
                        reg_fence(o);
                    }
                    mbar_wait(bn, 0);
                    wg_fence();
                    issue_pv<0>(o, p0, vd);
                    issue_qk<0>(s0, qd, kdn);
                    wg_commit();
                    wg_wait<1>();
                    reg_fence(s1);
                    softmax_fast<16>(s1, p1, one2);
                    reg_fence(p1);
                    mbar_wait(bn + 8, 0);
                    wg_fence();
                    issue_pv<KV_TILE>(o, p1, vd);
                    issue_qk<KV_TILE>(s1, qd, kdn);
                    wg_commit();
                    vd += 2 * KV_TILE; kdn += 2 * KV_TILE; bn += 16;
                }
                if (pass == 0) PROF(17);
            }
            wg_wait<0>();
            reg_fence(o);
            reg_fence(s0);
            reg_fence(s1);
            store_o(o, quarter * 8 + 6 + wg, head, wq, lane);
        } else {
#pragma unroll 1
            for (int pass = 0; pass < 4; pass++) {
                float m0 = -INFINITY, m1 = -INFINITY;
                float s[64];
                uint32_t p[32];
#pragma unroll 1
                for (int t = 0; t < 16; t++) {
                    mbar_wait(kvbar + t * 8, 0);
                    wg_fence();
                    issue_qk<0>(s, qd0 + pass * 512, kd0 + t * KV_TILE);
                    wg_commit();
                    wg_wait<0>();
                    reg_fence(s);
                    float a0 = m0, a1 = m1;
#pragma unroll
                    for (int k = 0; k < 16; k++) {
                        if ((POLY_MASK >> (k & 7)) & 1) {
#pragma unroll
                            for (int i = 0; i < 4; i++) s[k * 4 + i] *= 0.5f;
                        }
                        a0 = fmaxf(a0, fmaxf(s[k * 4 + 0], s[k * 4 + 1]));
                        a1 = fmaxf(a1, fmaxf(s[k * 4 + 2], s[k * 4 + 3]));
                    }
                    a0 = fmaxf(a0, __shfl_xor_sync(~0u, a0, 1)); a1 = fmaxf(a1, __shfl_xor_sync(~0u, a1, 1));
                    a0 = fmaxf(a0, __shfl_xor_sync(~0u, a0, 2)); a1 = fmaxf(a1, __shfl_xor_sync(~0u, a1, 2));
                    const float r0 = ex2(m0 - a0), r1 = ex2(m1 - a1);
                    m0 = a0; m1 = a1;
#pragma unroll
                    for (int i = 0; i < 3; i++) { o[i * 4] *= r0; o[i * 4 + 1] *= r0; o[i * 4 + 2] *= r1; o[i * 4 + 3] *= r1; }
#pragma unroll
                    for (int k = 0; k < 16; k++) {
                        p[k * 2 + 0] = pack_bf16(ex2(s[k * 4 + 0] - m0), ex2(s[k * 4 + 1] - m0));
                        p[k * 2 + 1] = pack_bf16(ex2(s[k * 4 + 2] - m1), ex2(s[k * 4 + 3] - m1));
                    }
                    reg_fence(p);
                    reg_fence(o);
                    wg_fence();
                    issue_pv<0>(o, p, vd0 + t * KV_TILE);
                    wg_commit();
                    wg_wait<0>();
                    reg_fence(o);
                }
                store_o(o, quarter * 8 + pass * 2 + wg, head, wq, lane);
            }
            if (tid == wg * 128)
                for (int i = 0; i < 7; i++) mbar_arrive(bar0 + (B_FREE + i) * 8);
        }
        PROF(18);
        PROFT(51);

        named_bar_sync(5, 256);
        if (tid == 0) {
            flag_signal(&g_flags.o_done[quarter]);
            flag_wait(&g_flags.ffn_done[rt >> 1], 8, 0);
        }
        named_bar_sync(5, 256);
        const int t128 = tid & 127;
        float4 bs[9];
        {
            const float4* bp = g_base + ((rt >> 1) * 72 + ct * 18 + wg * 9) * 256 + (rt & 1) * 128 + t128;
#pragma unroll
            for (int i = 0; i < 9; i++) bs[i] = __ldcg(bp + i * 256);
        }
        if (tid == 0) flag_wait(&g_flags.o_done[quarter], 32, 0);
        named_bar_sync(5, 256);
        PROF(19);
        uint4 af[18];
        {
            const uint4* ap = reinterpret_cast<const uint4*>(g_O) + (rt * 36 + wg * 18) * 128 + t128;
#pragma unroll
            for (int k = 0; k < 18; k++) af[k] = __ldcg(ap + k * 128);
        }
        float acc[72];
        const uint64_t wd0 = mk_desc(zero, sb, 2304, 128, 0), wd1 = wd0 + wg * ((18 * 4608) >> 4);
#pragma unroll
        for (int i = 0; i < 5; i++) mbar_wait(bar0 + (B_WO + wg * 4 + i) * 8, 0);
        wg_fence();
        static_for<0, 18>([&](auto kc) {
            constexpr int k = decltype(kc)::value;
            if constexpr (k < 8) {
                constexpr int o0 = (sm_wo(k >> 2) + (k & 3) * 4608) >> 4, o1 = (SM_KV + (k + 10) * 4608) >> 4;
                wgmma_rs_n144<1, 0>(acc, af[k].x, af[k].y, af[k].z, af[k].w, wd0 + (wg ? o1 : o0), k != 0);
            } else {
                wgmma_rs_n144<1, (SM_KV + (k - 8) * 4608) / 16>(acc, af[k].x, af[k].y, af[k].z, af[k].w, wd1, 1);
            }
        });
        wg_commit();
        wg_wait<0>();
        reg_fence(acc);
        PROF(20);
        {
            float4* ex = reinterpret_cast<float4*>(smem + SM_EXCH) + t128;
#pragma unroll
            for (int i = 0; i < 9; i++) {
                const float4 lo = make_float4(acc[i * 4], acc[i * 4 + 1], acc[i * 4 + 2], acc[i * 4 + 3]);
                const float4 hi = make_float4(acc[36 + i * 4], acc[36 + i * 4 + 1], acc[36 + i * 4 + 2], acc[36 + i * 4 + 3]);
                ex[(wg * 9 + i) * 128] = wg ? lo : hi;
                const float4 own = wg ? hi : lo;
                bs[i].x = fmaf(bs[i].x, 0.5f, own.x); bs[i].y = fmaf(bs[i].y, 0.5f, own.y);
                bs[i].z = fmaf(bs[i].z, 0.5f, own.z); bs[i].w = fmaf(bs[i].w, 0.5f, own.w);
            }
            named_bar_sync(5, 256);
            uint32_t* op = reinterpret_cast<uint32_t*>(out + (size_t)(rt * 64 + wq * 16 + g) * DM + ct * 144 + wg * 72 + q * 2);
#pragma unroll
            for (int i = 0; i < 9; i++) {
                const float4 v = ex[((wg ^ 1) * 9 + i) * 128];
                op[i * 4] = pack_bf16(bs[i].x + v.x, bs[i].y + v.y);
                op[i * 4 + 4 * DM] = pack_bf16(bs[i].z + v.z, bs[i].w + v.w);
            }
        }
        if (tid == 0) {
            if (atomicAdd(&g_flags.exited, 1u) == gridDim.x - 1) {
                unsigned int* f = reinterpret_cast<unsigned int*>(&g_flags);
#pragma unroll 1
                for (int i = 0; i < (int)(sizeof(Flags) / 4); i++) f[i] = 0;
            }
        }
        PROF(21);
        PROFT(52);
    } else {
        reg_dealloc<24>();
        if (warp == 8 && lane == 0) {
            prefetch_tmap(&tmQ3); prefetch_tmap(&tmQ1); prefetch_tmap(&tm1); prefetch_tmap(&tm2);
            #pragma unroll 1
            for (int i = 0; i < 9; i++) { mbar_init(full0 + i * 8, 1); mbar_init(empty0 + i * 8, 4); mbar_init(bar0 + (B_WO + i) * 8, 1); }
            mbar_init(bar0 + B_INIT * 8, 1); mbar_init(bar0 + B_XNDEAD * 8, 2); mbar_init(bar0 + B_QRDY * 8, 3); mbar_init(bar0 + B_FFN * 8, 8);
#pragma unroll 1
            for (int i = 0; i < 16; i++) { mbar_init(bar0 + (B_KV + i) * 8, 1); mbar_init(bar0 + (B_FREE + (i & 7)) * 8, 2); }
            *slow_flag = 0;
            fence_barrier_init();
        }
        __syncwarp();
        cluster_arrive();
        cluster_wait();
        const uint8_t* kvsrc = g_QKV + (size_t)head * KV_HEAD_BYTES;
        if (warp == 8) {
            if (lane == 0) {
                int st = 0, u = rank, tile = -4;
                int es = 5;
                uint32_t eph = 1;
#pragma unroll 1
                for (int n = 0; n < 99; n++) {
                    mbar_wait(empty0 + es * 8, eph);
                    const uint32_t fb = full0 + st * 8, dst = sb + K1_OFF_RING + u * 8192;
                    mbar_expect(fb, 16384);
                    if (tile < 0) {
                        tma3d_mc(dst, &tmQ3, j * 216, n * 32 + rank * 16, 0, fb, 3);
                        tma2d_mc(dst + 6144, &tmQ1, j * 216 + 192, n * 32 + rank * 16, fb, 3);
                    } else if (tile < 9) {
                        tma2d_mc(dst, &tm1, j * 576 + tile * 64, u * 64, fb, 3);
                    } else {
                        tma2d_mc(dst, &tm2, (tile + j >= 18 ? tile + j - 18 : tile + j - 9) * 64, j * 576 + u * 64, fb, 3);
                    }
                    u += 2;
                    if (u >= 9) { u -= 9; tile++; }
                    if (++st == 9) st = 0;
                    if (++es == 9) { es = 0; eph ^= 1; }
                }
                mbar_wait(empty0 + 8 * 8, 0);
                mbar_wait(bar0 + B_QRDY * 8, 0);
                asm volatile("fence.proxy.async;" ::: "memory");
#pragma unroll 1
                for (int i = 11; i < NCHUNK; i++) {
                    mbar_expect(bar0 + (B_KV + i) * 8, CHUNK_BYTES);
                    bulk_load(sb + SM_KV + i * CHUNK_BYTES, kvsrc + i * CHUNK_BYTES, CHUNK_BYTES, bar0 + (B_KV + i) * 8);
                }
#pragma unroll 1
                for (int i = 0; i < 9; i++) {
                    if (i > 0) {
                        const int f = i == 1 ? 0 : ((i - 1) * 9 + 4) / 10;
                        mbar_wait_sleep(bar0 + (B_FREE + f) * 8, i == 1 ? 500 : 50);
                    }
                    mbar_expect(bar0 + (B_WO + i) * 8, WO_PIECE);
                    bulk_load(sb + (i == 0 ? sm_wo(0) : (i == 1 ? sm_wo(1) : SM_KV + (i - 2) * WO_PIECE)), g_Wo + ct * WO_TILE_BYTES + i * WO_PIECE, WO_PIECE,
                              bar0 + (B_WO + i) * 8);
                }
            }
        } else {
            const int ht = tid - 288;
            if (ht < 72) {
                const uint4 v = __ldg(reinterpret_cast<const uint4*>(b1 + j * 576) + ht);
                uint32_t* sbias = reinterpret_cast<uint32_t*>(smem + K1_OFF_BIAS) + (ht >> 3) * 32 + (ht & 7);
                sbias[0] = v.x; sbias[8] = v.y; sbias[16] = v.z; sbias[24] = v.w;
            }
            asm volatile("bar.arrive 4, 352;" ::: "memory");
#pragma unroll 4
            for (int i = ht; i < 9 * 256; i += 96) {
                const int t = i & 255, nb = j * 9 + (i >> 8);
                const int row = rb * 128 + (t >> 5) * 16 + ((t & 31) >> 2), col = nb * 8 + (t & 3) * 2;
                const uint32_t* xp = reinterpret_cast<const uint32_t*>(x + (size_t)row * DM + col);
                const uint32_t x0 = __ldg(xp), x1 = __ldg(xp + 4 * DM), bb = __ldg(reinterpret_cast<const uint32_t*>(b2 + col));
                g_base[(rb * 72 + nb) * 256 + t] = make_float4(2.f * (bf_lo(x0) + bf_lo(bb)), 2.f * (bf_hi(x0) + bf_hi(bb)),
                                                               2.f * (bf_lo(x1) + bf_lo(bb)), 2.f * (bf_hi(x1) + bf_hi(bb)));
            }
            named_bar_sync(7, 96);
            if (ht == 0) flag_signal(&g_flags.base_init[rb]);
            PROFH(37);
#pragma unroll 1
            for (int i = ht; i < 512; i += 96) {
                const int key = i & 127;
                uint8_t* p = g_QKV + (size_t)(j * 4 + (i >> 7)) * KV_HEAD_BYTES + (rb * 16 + (key >> 3)) * KV_GROUP_BYTES + 512 + (key & 7) * 16;
                *reinterpret_cast<uint32_t*>(p + 4) = ((POLY_MASK >> ((key >> 3) & 7)) & 1) ? 0x3F804000u : 0x00003F80u;
                *reinterpret_cast<uint32_t*>(p + 12) = 0x00003F80u;
            }
#pragma unroll 2
            for (int i = blockIdx.x * 324 + ht; i < blockIdx.x * 324 + 324; i += 96) {
                const int k = i / 72, nc = i - k * 72, c4 = nc / 18;
                *reinterpret_cast<uint4*>(g_Wo + c4 * WO_TILE_BYTES + (k >> 3) * 2304 + (nc - c4 * 18) * 128 + (k & 7) * 16) =
                    __ldg(reinterpret_cast<const uint4*>(wo) + i);
            }
            PROFH(38);
            named_bar_sync(3, 352);
            if (ht == 0) {
                flag_signal(&g_flags.qkv_stored[rb]);
                flag_wait(&g_flags.base_init[rb], 8, 200);
                mbar_arrive(bar0 + B_INIT * 8);
                flag_wait(&g_flags.qkv_stored[rb], 8, 200);
            }
            named_bar_sync(7, 96);
            PROFH(39);
#pragma unroll 1
            for (int i = warp - 9; i < 16; i += 3) {
                const int hd = j * 4 + (i >> 2), key = (i & 3) * 32 + lane;
                const uint8_t* p = g_QKV + (size_t)hd * KV_HEAD_BYTES + (rb * 16 + (key >> 3)) * KV_GROUP_BYTES + (key & 7) * 16;
                const uint4 a = __ldcg(reinterpret_cast<const uint4*>(p)), b = __ldcg(reinterpret_cast<const uint4*>(p + 128));
                float n = sumsq2(__ldcg(reinterpret_cast<const uint32_t*>(p + 512))) + sumsq8(a) + sumsq8(b);
                if ((POLY_MASK >> ((key >> 3) & 7)) & 1) n *= 0.25f;
#pragma unroll
                for (int o = 16; o; o >>= 1) n = fmaxf(n, __shfl_xor_sync(~0u, n, o));
                if (lane == 0) g_kmax[hd * 64 + rb * 4 + (i & 3)] = n;
            }
            named_bar_sync(7, 96);
            PROFH(40);
            if (ht == 0) {
                flag_signal(&g_flags.kv_ready);
                flag_wait(&g_flags.kv_ready, 128, 300);
                mbar_wait_sleep(bar0 + B_XNDEAD * 8, 300);
            }
            named_bar_sync(7, 96);
            PROFH(41);
            if (lane == 0) {
                asm volatile("fence.proxy.async;" ::: "memory");
#pragma unroll 1
                for (int i = warp - 9; i < 11; i += 3) {
                    mbar_expect(bar0 + (B_KV + i) * 8, CHUNK_BYTES);
                    bulk_load(sb + SM_KV + i * CHUNK_BYTES, kvsrc + i * CHUNK_BYTES, CHUNK_BYTES, bar0 + (B_KV + i) * 8);
                }
            }
            __syncwarp();
            float kmax2;
            {
                const float2 v = __ldcg(reinterpret_cast<const float2*>(g_kmax + head * 64 + lane * 2));
                kmax2 = fmaxf(v.x, v.y);
#pragma unroll
                for (int o = 16; o; o >>= 1) kmax2 = fmaxf(kmax2, __shfl_xor_sync(~0u, kmax2, o));
            }
#pragma unroll 1
            for (int r = ht; r < 512; r += 96) {
                const uint8_t* p = kvsrc + Q_OFFSET + (quarter * 64 + (r >> 3)) * KV_GROUP_BYTES + (r & 7) * 16;
                const uint4 a = __ldcg(reinterpret_cast<const uint4*>(p)), b = __ldcg(reinterpret_cast<const uint4*>(p + 128));
                const uint32_t e = __ldcg(reinterpret_cast<const uint32_t*>(p + 256));
                const float cc = sqrtf((sumsq2(e) + sumsq8(a) + sumsq8(b)) * kmax2) * 1.02f;
                if (!(cc <= 58.f)) *slow_flag = 1;
                uint4* dst = reinterpret_cast<uint4*>(smem + SM_Q + (r >> 3) * 512 + (r & 7) * 16);
                dst[0] = a;
                dst[8] = b;
                dst[16] = make_uint4(e, pack_bf16(-cc, 768.f), 0u, 0u);
                dst[24] = make_uint4(0u, POLY_MODE ? 0xBFFF0000u : 0xC0000000u, 0u, 0u);
            }
            named_bar_sync(7, 96);
            if (*slow_flag) {
#pragma unroll 1
                for (int r = ht; r < 512; r += 96) {
                    uint32_t* dst = reinterpret_cast<uint32_t*>(smem + SM_Q + (r >> 3) * 512 + (r & 7) * 16);
                    dst[65] = 0u;
                    dst[97] = 0u;
                }
            }
            fence_proxy_async();
            __syncwarp();
            if (lane == 0) mbar_arrive(bar0 + B_QRDY * 8);
            PROFH(42);
            if (ht == 0) {
                mbar_wait_sleep(bar0 + B_FFN * 8, 300);
                flag_signal(&g_flags.ffn_done[rb]);
            }
        }
    }
}

typedef CUresult (*EncodeFn)(CUtensorMap*, CUtensorMapDataType, cuuint32_t, void*, const cuuint64_t*, const cuuint64_t*, const cuuint32_t*,
                             const cuuint32_t*, CUtensorMapInterleave, CUtensorMapSwizzle, CUtensorMapL2promotion, CUtensorMapFloatOOBfill);

void make_map(EncodeFn fn, CUtensorMap* m, const void* base, int rank, const cuuint64_t* dims, const cuuint64_t* strides, const cuuint32_t* box) {
    cuuint32_t es[3] = {1, 1, 1};
    fn(m, CU_TENSOR_MAP_DATA_TYPE_BFLOAT16, rank, const_cast<void*>(base), dims, strides, box, es, CU_TENSOR_MAP_INTERLEAVE_NONE,
       CU_TENSOR_MAP_SWIZZLE_128B, CU_TENSOR_MAP_L2_PROMOTION_L2_256B, CU_TENSOR_MAP_FLOAT_OOB_FILL_NONE);
}

}

extern "C" void kernel_launch(void* const* d_in, const int* in_sizes, int n_in, void* d_out, int out_size) {
    const __nv_bfloat16* x = (const __nv_bfloat16*)d_in[0];
    const __nv_bfloat16* wqkv = (const __nv_bfloat16*)d_in[1];
    const __nv_bfloat16* wo = (const __nv_bfloat16*)d_in[2];
    const __nv_bfloat16* w1 = (const __nv_bfloat16*)d_in[4];
    const __nv_bfloat16* b1 = (const __nv_bfloat16*)d_in[5];
    const __nv_bfloat16* w2 = (const __nv_bfloat16*)d_in[6];
    const __nv_bfloat16* b2 = (const __nv_bfloat16*)d_in[7];
    __nv_bfloat16* out = (__nv_bfloat16*)d_out;

    EncodeFn fn = nullptr;
    cudaDriverEntryPointQueryResult qr;
    cudaGetDriverEntryPoint("cuTensorMapEncodeTiled", (void**)&fn, cudaEnableDefault, &qr);
    CUtensorMap tmX, tmQ3, tmQ1, tm1, tm2;
    {
        cuuint64_t d[3] = {64, SEQ, 9}, s[2] = {DM * 2, 128};
        cuuint32_t b[3] = {64, 8, 9};
        make_map(fn, &tmX, x, 3, d, s, b);
    }
    {
        cuuint64_t d[3] = {3 * DM, DM, 3}, s[2] = {3 * DM * 2, 128};
        cuuint32_t b[3] = {64, 16, 3};
        make_map(fn, &tmQ3, wqkv, 3, d, s, b);
        make_map(fn, &tmQ1, wqkv, 2, d, s, b);
    }
    {
        cuuint64_t d[2] = {FF, DM}, s[1] = {FF * 2};
        cuuint32_t b[2] = {64, 64};
        make_map(fn, &tm1, w1, 2, d, s, b);
        cuuint64_t d2[2] = {DM, FF}, s2[1] = {DM * 2};
        make_map(fn, &tm2, w2, 2, d2, s2, b);
    }
    cudaFuncSetAttribute(fused_kernel, cudaFuncAttributeMaxDynamicSharedMemorySize, K1_SMEM);
    fused_kernel<<<128, 384, K1_SMEM, cudaStreamPerThread>>>(tmX, tmQ3, tmQ1, tm1, tm2, b1, wo, x, b2, out, 0ull);
}
```

```cpp
#include <cuda_runtime.h>
#include <cuda_bf16.h>
#include <cuda.h>
#include <stdint.h>

#define PROF(i) do { } while (0)
#define PROFT(i) do { } while (0)
#define PROFH(i) do { } while (0)
#define PROF_WG 0

namespace {

constexpr int SEQ = 2048, DM = 576, FF = 4608, NH = 32, DH = 18;

constexpr int KV_GROUP_BYTES = 5 * 128;
constexpr int KV_HEAD_BYTES = (SEQ / 8) * KV_GROUP_BYTES;
constexpr int Q_OFFSET = NH * KV_HEAD_BYTES;
#define POLY_MASK 0xB6
__device__ __align__(1024) uint8_t g_QKV[2 * NH * KV_HEAD_BYTES];
__device__ __align__(1024) float g_kmax[NH * 64];
constexpr int SLAB = 16 * 36 * 256;
__device__ __align__(1024) uint4 g_part[8 * SLAB];
__device__ __align__(1024) float4 g_base[2 * SLAB];
__device__ __align__(1024) uint32_t g_O[SEQ * DM / 2];
struct Flags {
    unsigned int qkv_stored[16];
    unsigned int ffn_done[16];
    unsigned int o_done[4];
    unsigned int kv_ready;
    unsigned int exited;
};
__device__ Flags g_flags;
constexpr int WO_TILE_BYTES = DM * 144 * 2;
__device__ __align__(1024) uint8_t g_Wo[4 * WO_TILE_BYTES];

__device__ __forceinline__ uint32_t s2u(const void* p) { return (uint32_t)__cvta_generic_to_shared(p); }
__device__ __forceinline__ void mbar_init(uint32_t b, int c) { asm volatile("mbarrier.init.shared::cta.b64 [%0], %1;" ::"r"(b), "r"(c) : "memory"); }
__device__ __forceinline__ void mbar_expect(uint32_t b, uint32_t bytes) {
    asm volatile("mbarrier.arrive.expect_tx.shared::cta.b64 _, [%0], %1;" ::"r"(b), "r"(bytes) : "memory");
}
__device__ __forceinline__ void mbar_wait(uint32_t b, uint32_t parity) {
    asm volatile(
        "{\n.reg .pred p;\n.reg .u32 c;\n"
        "mbarrier.try_wait.parity.shared::cta.b64 p, [%0], %1;\n"
        "@p bra DONE;\n"
        "mov.u32 c, 0;\n"
        "LOOP:\n"
        "mbarrier.try_wait.parity.shared::cta.b64 p, [%0], %1;\n"
        "@p bra DONE;\n"
        "add.u32 c, c, 1;\n"
        "setp.lt.u32 p, c, 4194304;\n"
        "@p bra LOOP;\n"
        "trap;\n"
        "DONE:\n}\n" ::"r"(b), "r"(parity) : "memory");
}
__device__ __forceinline__ void fence_barrier_init() { asm volatile("fence.mbarrier_init.release.cluster;" ::: "memory"); }
__device__ __forceinline__ void fence_proxy_async() { asm volatile("fence.proxy.async.shared::cta;" ::: "memory"); }
__device__ __forceinline__ void cluster_arrive() { asm volatile("barrier.cluster.arrive.relaxed.aligned;" ::: "memory"); }
__device__ __forceinline__ void cluster_wait() { asm volatile("barrier.cluster.wait.aligned;" ::: "memory"); }
__device__ __forceinline__ void named_bar_sync(int id, int n) { asm volatile("bar.sync %0, %1;" ::"r"(id), "r"(n) : "memory"); }
__device__ __forceinline__ void griddep_wait() { asm volatile("griddepcontrol.wait;" ::: "memory"); }
__device__ __forceinline__ void griddep_launch() { asm volatile("griddepcontrol.launch_dependents;" ::: "memory"); }

__device__ __forceinline__ void tma3d_mc(uint32_t dst, const CUtensorMap* tm, int c0, int c1, int c2, uint32_t bar, uint16_t mask) {
    asm volatile("cp.async.bulk.tensor.3d.shared::cluster.global.mbarrier::complete_tx::bytes.multicast::cluster [%0], [%1, {%3, %4, %5}], [%2], %6;"
                 ::"r"(dst), "l"(tm), "r"(bar), "r"(c0), "r"(c1), "r"(c2), "h"(mask) : "memory");
}
__device__ __forceinline__ void tma2d_mc(uint32_t dst, const CUtensorMap* tm, int c0, int c1, uint32_t bar, uint16_t mask) {
    asm volatile("cp.async.bulk.tensor.2d.shared::cluster.global.mbarrier::complete_tx::bytes.multicast::cluster [%0], [%1, {%3, %4}], [%2], %5;"
                 ::"r"(dst), "l"(tm), "r"(bar), "r"(c0), "r"(c1), "h"(mask) : "memory");
}
__device__ __forceinline__ void tma3d(uint32_t dst, const CUtensorMap* tm, int c0, int c1, int c2, uint32_t bar) {
    asm volatile("cp.async.bulk.tensor.3d.shared::cluster.global.mbarrier::complete_tx::bytes [%0], [%1, {%3, %4, %5}], [%2];"
                 ::"r"(dst), "l"(tm), "r"(bar), "r"(c0), "r"(c1), "r"(c2) : "memory");
}
__device__ __forceinline__ void tma2d(uint32_t dst, const CUtensorMap* tm, int c0, int c1, uint32_t bar) {
    asm volatile("cp.async.bulk.tensor.2d.shared::cluster.global.mbarrier::complete_tx::bytes [%0], [%1, {%3, %4}], [%2];"
                 ::"r"(dst), "l"(tm), "r"(bar), "r"(c0), "r"(c1) : "memory");
}
__device__ __forceinline__ void bulk_load(uint32_t dst, const void* src, uint32_t bytes, uint32_t bar) {
    asm volatile("cp.async.bulk.shared::cluster.global.mbarrier::complete_tx::bytes [%0], [%1], %2, [%3];"
                 ::"r"(dst), "l"(src), "r"(bytes), "r"(bar) : "memory");
}
__device__ __forceinline__ void prefetch_tmap(const CUtensorMap* tm) { asm volatile("prefetch.tensormap [%0];" ::"l"(tm) : "memory"); }

__device__ __forceinline__ void wg_fence() { asm volatile("wgmma.fence.sync.aligned;" ::: "memory"); }
__device__ __forceinline__ void wg_commit() { asm volatile("wgmma.commit_group.sync.aligned;" ::: "memory"); }
template <int N> __device__ __forceinline__ void wg_wait() { asm volatile("wgmma.wait_group.sync.aligned %0;" ::"n"(N) : "memory"); }
template <int N> __device__ __forceinline__ void reg_fence(float (&d)[N]) {
#pragma unroll
    for (int i = 0; i < N; i++) asm volatile("" : "+f"(d[i])::"memory");
}
template <int N> __device__ __forceinline__ void reg_fence(uint32_t (&d)[N]) {
#pragma unroll
    for (int i = 0; i < N; i++) asm volatile("" : "+r"(d[i])::"memory");
}
template <int R> __device__ __forceinline__ void reg_alloc() { asm volatile("setmaxnreg.inc.sync.aligned.u32 %0;" ::"n"(R)); }
template <int R> __device__ __forceinline__ void reg_dealloc() { asm volatile("setmaxnreg.dec.sync.aligned.u32 %0;" ::"n"(R)); }

__device__ __forceinline__ uint64_t mk_desc(uint64_t z, uint32_t addr, uint32_t lbo, uint32_t sbo, uint32_t swz) {
    return z + ((uint64_t)(((addr & 0x3FFFF) >> 4) | ((lbo >> 4) << 16)) | ((uint64_t)((sbo >> 4) | (swz << 30)) << 32));
}
__device__ __forceinline__ uint32_t pack_bf16(float lo, float hi) {
    uint32_t r;
    asm("cvt.rn.bf16x2.f32 %0, %1, %2;" : "=r"(r) : "f"(hi), "f"(lo));
    return r;
}
__device__ __forceinline__ float bf_lo(uint32_t w) { return __uint_as_float(w << 16); }
__device__ __forceinline__ float bf_hi(uint32_t w) { return __uint_as_float(w & 0xFFFF0000u); }
__device__ __forceinline__ float ex2(float x) {
    float r;
    asm("ex2.approx.ftz.f32 %0, %1;" : "=f"(r) : "f"(x));
    return r;
}
__device__ __forceinline__ float tanh_fast(float x) {
    float r;
    asm("tanh.approx.f32 %0, %1;" : "=f"(r) : "f"(x));
    return r;
}
__device__ __forceinline__ float gelu2(float u) {
    const float w = fmaf(u * u, 0.0356774081f, 0.7978845608f);
    return fmaf(u, tanh_fast(u * w), u);
}

template<int TB, int AOFF, int BOFF> __device__ __forceinline__ void wgmma_ss_n216(float (&d)[108], uint64_t da, uint64_t db, int sd) {
    asm volatile("{\n.reg .pred p;\n.reg .b64 ta, tb;\nsetp.ne.b32 p, %110, 0;\nadd.s64 ta, %108, %112;\nadd.s64 tb, %109, %113;\n"
      "wgmma.mma_async.sync.aligned.m64n216k16.f32.bf16.bf16 {%0, %1, %2, %3, %4, %5, %6, %7, %8, %9, %10, %11, %12, %13, %14, %15, %16, %17, %18, %19, %20, %21, %22, %23, %24, %25, %26, %27, %28, %29, %30, %31, %32, %33, %34, %35, %36, %37, %38, %39, %40, %41, %42, %43, %44, %45, %46, %47, %48, %49, %50, %51, %52, %53, %54, %55, %56, %57, %58, %59, %60, %61, %62, %63, %64, %65, %66, %67, %68, %69, %70, %71, %72, %73, %74, %75, %76, %77, %78, %79, %80, %81, %82, %83, %84, %85, %86, %87, %88, %89, %90, %91, %92, %93, %94, %95, %96, %97, %98, %99, %100, %101, %102, %103, %104, %105, %106, %107}, ta, tb, p, 1, 1, 0, %111;\n}\n"
      : "+f"(d[0]), "+f"(d[1]), "+f"(d[2]), "+f"(d[3]), "+f"(d[4]), "+f"(d[5]), "+f"(d[6]), "+f"(d[7]), "+f"(d[8]), "+f"(d[9]), "+f"(d[10]), "+f"(d[11]), "+f"(d[12]), "+f"(d[13]), "+f"(d[14]), "+f"(d[15]), "+f"(d[16]), "+f"(d[17]), "+f"(d[18]), "+f"(d[19]), "+f"(d[20]), "+f"(d[21]), "+f"(d[22]), "+f"(d[23]), "+f"(d[24]), "+f"(d[25]), "+f"(d[26]), "+f"(d[27]), "+f"(d[28]), "+f"(d[29]), "+f"(d[30]), "+f"(d[31]), "+f"(d[32]), "+f"(d[33]), "+f"(d[34]), "+f"(d[35]), "+f"(d[36]), "+f"(d[37]), "+f"(d[38]), "+f"(d[39]), "+f"(d[40]), "+f"(d[41]), "+f"(d[42]), "+f"(d[43]), "+f"(d[44]), "+f"(d[45]), "+f"(d[46]), "+f"(d[47]), "+f"(d[48]), "+f"(d[49]), "+f"(d[50]), "+f"(d[51]), "+f"(d[52]), "+f"(d[53]), "+f"(d[54]), "+f"(d[55]), "+f"(d[56]), "+f"(d[57]), "+f"(d[58]), "+f"(d[59]), "+f"(d[60]), "+f"(d[61]), "+f"(d[62]), "+f"(d[63]), "+f"(d[64]), "+f"(d[65]), "+f"(d[66]), "+f"(d[67]), "+f"(d[68]), "+f"(d[69]), "+f"(d[70]), "+f"(d[71]), "+f"(d[72]), "+f"(d[73]), "+f"(d[74]), "+f"(d[75]), "+f"(d[76]), "+f"(d[77]), "+f"(d[78]), "+f"(d[79]), "+f"(d[80]), "+f"(d[81]), "+f"(d[82]), "+f"(d[83]), "+f"(d[84]), "+f"(d[85]), "+f"(d[86]), "+f"(d[87]), "+f"(d[88]), "+f"(d[89]), "+f"(d[90]), "+f"(d[91]), "+f"(d[92]), "+f"(d[93]), "+f"(d[94]), "+f"(d[95]), "+f"(d[96]), "+f"(d[97]), "+f"(d[98]), "+f"(d[99]), "+f"(d[100]), "+f"(d[101]), "+f"(d[102]), "+f"(d[103]), "+f"(d[104]), "+f"(d[105]), "+f"(d[106]), "+f"(d[107])
      : "l"(da), "l"(db), "r"(sd), "n"(TB), "n"(AOFF), "n"(BOFF));
}

template<int TB, int AOFF, int BOFF> __device__ __forceinline__ void wgmma_ss_n64(float (&d)[32], uint64_t da, uint64_t db, int sd) {
    asm volatile("{\n.reg .pred p;\n.reg .b64 ta, tb;\nsetp.ne.b32 p, %34, 0;\nadd.s64 ta, %32, %36;\nadd.s64 tb, %33, %37;\n"
      "wgmma.mma_async.sync.aligned.m64n64k16.f32.bf16.bf16 {%0, %1, %2, %3, %4, %5, %6, %7, %8, %9, %10, %11, %12, %13, %14, %15, %16, %17, %18, %19, %20, %21, %22, %23, %24, %25, %26, %27, %28, %29, %30, %31}, ta, tb, p, 1, 1, 0, %35;\n}\n"
      : "+f"(d[0]), "+f"(d[1]), "+f"(d[2]), "+f"(d[3]), "+f"(d[4]), "+f"(d[5]), "+f"(d[6]), "+f"(d[7]), "+f"(d[8]), "+f"(d[9]), "+f"(d[10]), "+f"(d[11]), "+f"(d[12]), "+f"(d[13]), "+f"(d[14]), "+f"(d[15]), "+f"(d[16]), "+f"(d[17]), "+f"(d[18]), "+f"(d[19]), "+f"(d[20]), "+f"(d[21]), "+f"(d[22]), "+f"(d[23]), "+f"(d[24]), "+f"(d[25]), "+f"(d[26]), "+f"(d[27]), "+f"(d[28]), "+f"(d[29]), "+f"(d[30]), "+f"(d[31])
      : "l"(da), "l"(db), "r"(sd), "n"(TB), "n"(AOFF), "n"(BOFF));
}

template<int TB, int AOFF, int BOFF> __device__ __forceinline__ void wgmma_ss_n128(float (&d)[64], uint64_t da, uint64_t db, int sd) {
    asm volatile("{\n.reg .pred p;\n.reg .b64 ta, tb;\nsetp.ne.b32 p, %66, 0;\nadd.s64 ta, %64, %68;\nadd.s64 tb, %65, %69;\n"
      "wgmma.mma_async.sync.aligned.m64n128k16.f32.bf16.bf16 {%0, %1, %2, %3, %4, %5, %6, %7, %8, %9, %10, %11, %12, %13, %14, %15, %16, %17, %18, %19, %20, %21, %22, %23, %24, %25, %26, %27, %28, %29, %30, %31, %32, %33, %34, %35, %36, %37, %38, %39, %40, %41, %42, %43, %44, %45, %46, %47, %48, %49, %50, %51, %52, %53, %54, %55, %56, %57, %58, %59, %60, %61, %62, %63}, ta, tb, p, 1, 1, 0, %67;\n}\n"
      : "+f"(d[0]), "+f"(d[1]), "+f"(d[2]), "+f"(d[3]), "+f"(d[4]), "+f"(d[5]), "+f"(d[6]), "+f"(d[7]), "+f"(d[8]), "+f"(d[9]), "+f"(d[10]), "+f"(d[11]), "+f"(d[12]), "+f"(d[13]), "+f"(d[14]), "+f"(d[15]), "+f"(d[16]), "+f"(d[17]), "+f"(d[18]), "+f"(d[19]), "+f"(d[20]), "+f"(d[21]), "+f"(d[22]), "+f"(d[23]), "+f"(d[24]), "+f"(d[25]), "+f"(d[26]), "+f"(d[27]), "+f"(d[28]), "+f"(d[29]), "+f"(d[30]), "+f"(d[31]), "+f"(d[32]), "+f"(d[33]), "+f"(d[34]), "+f"(d[35]), "+f"(d[36]), "+f"(d[37]), "+f"(d[38]), "+f"(d[39]), "+f"(d[40]), "+f"(d[41]), "+f"(d[42]), "+f"(d[43]), "+f"(d[44]), "+f"(d[45]), "+f"(d[46]), "+f"(d[47]), "+f"(d[48]), "+f"(d[49]), "+f"(d[50]), "+f"(d[51]), "+f"(d[52]), "+f"(d[53]), "+f"(d[54]), "+f"(d[55]), "+f"(d[56]), "+f"(d[57]), "+f"(d[58]), "+f"(d[59]), "+f"(d[60]), "+f"(d[61]), "+f"(d[62]), "+f"(d[63])
      : "l"(da), "l"(db), "r"(sd), "n"(TB), "n"(AOFF), "n"(BOFF));
}

template<int TB, int BOFF> __device__ __forceinline__ void wgmma_rs_n64(float (&d)[32], uint32_t a0, uint32_t a1, uint32_t a2, uint32_t a3, uint64_t db, int sd) {
    asm volatile("{\n.reg .pred p;\n.reg .b64 tb;\nsetp.ne.b32 p, %37, 0;\nadd.s64 tb, %36, %39;\n"
      "wgmma.mma_async.sync.aligned.m64n64k16.f32.bf16.bf16 {%0, %1, %2, %3, %4, %5, %6, %7, %8, %9, %10, %11, %12, %13, %14, %15, %16, %17, %18, %19, %20, %21, %22, %23, %24, %25, %26, %27, %28, %29, %30, %31}, {%32, %33, %34, %35}, tb, p, 1, 1, %38;\n}\n"
      : "+f"(d[0]), "+f"(d[1]), "+f"(d[2]), "+f"(d[3]), "+f"(d[4]), "+f"(d[5]), "+f"(d[6]), "+f"(d[7]), "+f"(d[8]), "+f"(d[9]), "+f"(d[10]), "+f"(d[11]), "+f"(d[12]), "+f"(d[13]), "+f"(d[14]), "+f"(d[15]), "+f"(d[16]), "+f"(d[17]), "+f"(d[18]), "+f"(d[19]), "+f"(d[20]), "+f"(d[21]), "+f"(d[22]), "+f"(d[23]), "+f"(d[24]), "+f"(d[25]), "+f"(d[26]), "+f"(d[27]), "+f"(d[28]), "+f"(d[29]), "+f"(d[30]), "+f"(d[31])
      : "r"(a0), "r"(a1), "r"(a2), "r"(a3), "l"(db), "r"(sd), "n"(TB), "n"(BOFF));
}

template<int TB, int BOFF> __device__ __forceinline__ void wgmma_rs_n24(float (&d)[12], uint32_t a0, uint32_t a1, uint32_t a2, uint32_t a3, uint64_t db, int sd) {
    asm volatile("{\n.reg .pred p;\n.reg .b64 tb;\nsetp.ne.b32 p, %17, 0;\nadd.s64 tb, %16, %19;\n"
      "wgmma.mma_async.sync.aligned.m64n24k16.f32.bf16.bf16 {%0, %1, %2, %3, %4, %5, %6, %7, %8, %9, %10, %11}, {%12, %13, %14, %15}, tb, p, 1, 1, %18;\n}\n"
      : "+f"(d[0]), "+f"(d[1]), "+f"(d[2]), "+f"(d[3]), "+f"(d[4]), "+f"(d[5]), "+f"(d[6]), "+f"(d[7]), "+f"(d[8]), "+f"(d[9]), "+f"(d[10]), "+f"(d[11])
      : "r"(a0), "r"(a1), "r"(a2), "r"(a3), "l"(db), "r"(sd), "n"(TB), "n"(BOFF));
}

template<int TB, int BOFF> __device__ __forceinline__ void wgmma_rs_n144(float (&d)[72], uint32_t a0, uint32_t a1, uint32_t a2, uint32_t a3, uint64_t db, int sd) {
    asm volatile("{\n.reg .pred p;\n.reg .b64 tb;\nsetp.ne.b32 p, %77, 0;\nadd.s64 tb, %76, %79;\n"
      "wgmma.mma_async.sync.aligned.m64n144k16.f32.bf16.bf16 {%0, %1, %2, %3, %4, %5, %6, %7, %8, %9, %10, %11, %12, %13, %14, %15, %16, %17, %18, %19, %20, %21, %22, %23, %24, %25, %26, %27, %28, %29, %30, %31, %32, %33, %34, %35, %36, %37, %38, %39, %40, %41, %42, %43, %44, %45, %46, %47, %48, %49, %50, %51, %52, %53, %54, %55, %56, %57, %58, %59, %60, %61, %62, %63, %64, %65, %66, %67, %68, %69, %70, %71}, {%72, %73, %74, %75}, tb, p, 1, 1, %78;\n}\n"
      : "+f"(d[0]), "+f"(d[1]), "+f"(d[2]), "+f"(d[3]), "+f"(d[4]), "+f"(d[5]), "+f"(d[6]), "+f"(d[7]), "+f"(d[8]), "+f"(d[9]), "+f"(d[10]), "+f"(d[11]), "+f"(d[12]), "+f"(d[13]), "+f"(d[14]), "+f"(d[15]), "+f"(d[16]), "+f"(d[17]), "+f"(d[18]), "+f"(d[19]), "+f"(d[20]), "+f"(d[21]), "+f"(d[22]), "+f"(d[23]), "+f"(d[24]), "+f"(d[25]), "+f"(d[26]), "+f"(d[27]), "+f"(d[28]), "+f"(d[29]), "+f"(d[30]), "+f"(d[31]), "+f"(d[32]), "+f"(d[33]), "+f"(d[34]), "+f"(d[35]), "+f"(d[36]), "+f"(d[37]), "+f"(d[38]), "+f"(d[39]), "+f"(d[40]), "+f"(d[41]), "+f"(d[42]), "+f"(d[43]), "+f"(d[44]), "+f"(d[45]), "+f"(d[46]), "+f"(d[47]), "+f"(d[48]), "+f"(d[49]), "+f"(d[50]), "+f"(d[51]), "+f"(d[52]), "+f"(d[53]), "+f"(d[54]), "+f"(d[55]), "+f"(d[56]), "+f"(d[57]), "+f"(d[58]), "+f"(d[59]), "+f"(d[60]), "+f"(d[61]), "+f"(d[62]), "+f"(d[63]), "+f"(d[64]), "+f"(d[65]), "+f"(d[66]), "+f"(d[67]), "+f"(d[68]), "+f"(d[69]), "+f"(d[70]), "+f"(d[71])
      : "r"(a0), "r"(a1), "r"(a2), "r"(a3), "l"(db), "r"(sd), "n"(TB), "n"(BOFF));
}

constexpr int K1_XN_BYTES = 16 * 9216;
constexpr int K1_OFF_RING = K1_XN_BYTES;
constexpr int K1_OFF_BIAS = K1_OFF_RING + 10 * 8192;
constexpr int K1_OFF_BAR = K1_OFF_BIAS + 576 * 2;
constexpr int K1_SMEM = K1_OFF_BAR + 768;
constexpr float QSCALE = 0.23570226039551584f * 1.4426950408889634f;

struct K1Ctx {
    uint32_t full0;
    uint32_t rel_addr;
    uint64_t descA, descB;
    uint32_t phase;
    __device__ __forceinline__ void begin_stage(int s) {
        mbar_wait(full0 + s * 8, phase);
        wg_fence();
    }
    __device__ __forceinline__ void release(int s) {
        if (rel_addr) asm volatile("mbarrier.arrive.shared::cluster.b64 _, [%0];" ::"r"(rel_addr + s * 8) : "memory");
    }
    __device__ __forceinline__ void end_stage(int s) {
        wg_commit();
        wg_wait<1>();
        release(s == 0 ? 8 : s - 1);
    }
};

__host__ __device__ constexpr int a_off(int ks) { return ((ks >> 2) * 1024 + (ks & 3) * 32) >> 4; }

template <int V> struct IC { static constexpr int value = V; };
template <int I, int N, class F> __device__ __forceinline__ void static_for(F&& f) {
    if constexpr (I < N) { f(IC<I>{}); static_for<I + 1, N>(f); }
}

template <bool A_RS, bool B_RS, class Epi>
__device__ __forceinline__ void tile_pair(K1Ctx& c, float (&accA)[32], float (&accB)[32], uint32_t (&h)[144], Epi&& epi) {
    static_for<0, 9>([&](auto sc) {
        constexpr int s = decltype(sc)::value;
        c.begin_stage(s);
        static_for<0, 8>([&](auto tc) {
            constexpr int kk = s * 8 + decltype(tc)::value, ks = kk % 36;
            constexpr int bo = (ks * 2048) >> 4;
            if constexpr (kk < 36) {
                if constexpr (A_RS) wgmma_rs_n64<1, bo>(accA, h[ks * 4], h[ks * 4 + 1], h[ks * 4 + 2], h[ks * 4 + 3], c.descB, ks != 0);
                else wgmma_ss_n64<1, a_off(ks), bo>(accA, c.descA, c.descB, ks != 0);
            } else {
                if constexpr (B_RS) wgmma_rs_n64<1, bo>(accB, h[ks * 4], h[ks * 4 + 1], h[ks * 4 + 2], h[ks * 4 + 3], c.descB, ks != 0);
                else wgmma_ss_n64<1, a_off(ks), bo>(accB, c.descA, c.descB, ks != 0);
            }
        });
        c.end_stage(s);
        epi(sc);
    });
    c.phase ^= 1;
}

template <int B0, int NB, int HOFF>
__device__ __forceinline__ void gelu_blocks(const float (&acc)[32], uint32_t (&h)[144], const uint32_t (&bq)[8]) {
#pragma unroll
    for (int b = B0; b < B0 + NB; b++) {
        const float b0 = bf_lo(bq[b]), b1 = bf_hi(bq[b]);
        h[HOFF + b * 2 + 0] = pack_bf16(gelu2(acc[b * 4 + 0] + b0), gelu2(acc[b * 4 + 1] + b1));
        h[HOFF + b * 2 + 1] = pack_bf16(gelu2(acc[b * 4 + 2] + b0), gelu2(acc[b * 4 + 3] + b1));
    }
}
__device__ __forceinline__ void load_bias(uint32_t (&bq)[8], uint32_t addr) {
    asm volatile("ld.shared.v4.u32 {%0, %1, %2, %3}, [%4];" : "=r"(bq[0]), "=r"(bq[1]), "=r"(bq[2]), "=r"(bq[3]) : "r"(addr));
    asm volatile("ld.shared.v4.u32 {%0, %1, %2, %3}, [%4 + 16];" : "=r"(bq[4]), "=r"(bq[5]), "=r"(bq[6]), "=r"(bq[7]) : "r"(addr));
}
template <int S> __device__ __forceinline__ void store_part(const float (&o)[32], uint4* p) {
    uint4 v;
    v.x = pack_bf16(o[S * 8 + 0], o[S * 8 + 1]); v.y = pack_bf16(o[S * 8 + 2], o[S * 8 + 3]);
    v.z = pack_bf16(o[S * 8 + 4], o[S * 8 + 5]); v.w = pack_bf16(o[S * 8 + 6], o[S * 8 + 7]);
    p[S * 256] = v;
}

constexpr int NCHUNK = 16;
constexpr int CHUNK_BYTES = KV_HEAD_BYTES / NCHUNK;
constexpr int SM_Q = 0;
constexpr int SM_KV = 32768;
constexpr int WO_PIECE = WO_TILE_BYTES / 9;
__host__ __device__ constexpr int sm_wo(int i) { return i == 0 ? 210944 : (i == 1 ? 0 : SM_KV + (i - 2) * WO_PIECE); }
constexpr int SM_EXCH = SM_KV + 7 * WO_PIECE;

__device__ __forceinline__ float exp2_fixed(float y) {
    const float u = __uint_as_float(__float_as_uint(y) & 0xFF807FFFu) - 512.02545f;
    float t = fmaf(u, 0.019497588f, 0.114550486f);
    t = fmaf(t, u, -0.29839927f);
    return fmaf(t, u, y);
}
__device__ __forceinline__ uint32_t pack_fixed(float lo, float hi) { return __byte_perm(__float_as_uint(lo), __float_as_uint(hi), 0x6521); }

#define POLY_MODE 1
__device__ __forceinline__ uint32_t hfma2_bf16(uint32_t a, uint32_t b, uint32_t c) {
    uint32_t r;
    asm("fma.rn.bf16x2 %0, %1, %2, %3;" : "=r"(r) : "r"(a), "r"(b), "r"(c));
    return r;
}
__device__ __forceinline__ uint32_t exp2_packed(float y0, float y1, uint32_t one2) {
    const uint32_t w = pack_fixed(y0, y1);
    uint32_t m;
    asm("lop3.b32 %0, %1, 0x007F007F, %2, 0xEA;" : "=r"(m) : "r"(w), "r"(one2));
    const uint32_t d = hfma2_bf16(m, 0x3EF93EF9u, 0xBF38BF38u);
    const uint32_t e = hfma2_bf16(d, d, 0xBD71BD71u);
    return hfma2_bf16(w, e, w);
}
template <int NB>
__device__ __forceinline__ void softmax_fast(const float (&s)[NB * 4], uint32_t (&p)[NB * 2], uint32_t one2) {
#pragma unroll
    for (int b = 0; b < NB; b++) {
        if ((POLY_MASK >> (b & 7)) & 1) {
            p[b * 2 + 0] = exp2_packed(s[b * 4 + 0], s[b * 4 + 1], one2);
            p[b * 2 + 1] = exp2_packed(s[b * 4 + 2], s[b * 4 + 3], one2);
        } else {
            p[b * 2 + 0] = pack_bf16(ex2(s[b * 4 + 0]), ex2(s[b * 4 + 1]));
            p[b * 2 + 1] = pack_bf16(ex2(s[b * 4 + 2]), ex2(s[b * 4 + 3]));
        }
    }
}

constexpr int KV_TILE = CHUNK_BYTES / 16;
template <int OFF> __device__ __forceinline__ void issue_qk(float (&s)[64], uint64_t qd, uint64_t kd) {
    wgmma_ss_n128<0, 0, OFF + (8 << 16)>(s, qd, kd, 0);
    wgmma_ss_n128<0, 16, OFF + 32>(s, qd, kd, 1);
}
template <int OFF> __device__ __forceinline__ void issue_pv(float (&o)[12], const uint32_t (&p)[32], uint64_t vd) {
    static_for<0, 8>([&](auto kc) {
        constexpr int k = decltype(kc)::value;
        wgmma_rs_n24<1, OFF + k * (2 * KV_GROUP_BYTES / 16)>(o, p[k * 4], p[k * 4 + 1], p[k * 4 + 2], p[k * 4 + 3], vd, 1);
    });
}
__device__ __forceinline__ void store_o(float (&o)[12], int rt, int head, int wq, int lane) {
    const int g = lane >> 2, q = lane & 3;
    const float i0 = __fdividef(1.0f, __shfl_sync(~0u, o[8], lane | 3)), i1 = __fdividef(1.0f, __shfl_sync(~0u, o[10], lane | 3));
#pragma unroll
    for (int i = 0; i < 3; i++) {
        const int pc = head * 9 + (i < 2 ? i * 4 + q : 8);
        uint32_t* op = g_O + (((rt * 36 + (pc >> 3)) * 128 + wq * 32 + g * 4 + (pc & 3)) * 4 + ((pc >> 2) & 1) * 2);
        if (i < 2 || q == 2) *reinterpret_cast<uint2*>(op) = make_uint2(pack_bf16(o[i * 4] * i0, o[i * 4 + 1] * i0), pack_bf16(o[i * 4 + 2] * i1, o[i * 4 + 3] * i1));
    }
#pragma unroll
    for (int i = 0; i < 12; i++) o[i] = 0.f;
}
__device__ __forceinline__ void mbar_arrive(uint32_t b) { asm volatile("mbarrier.arrive.shared::cta.b64 _, [%0];" ::"r"(b) : "memory"); }
__device__ __forceinline__ void mbar_wait_sleep(uint32_t b, uint32_t ns) {
    uint32_t ok, spins = 0;
    while (true) {
        asm volatile("{\n.reg .pred p;\nmbarrier.try_wait.parity.shared::cta.b64 p, [%1], 0;\nselp.u32 %0, 1, 0, p;\n}\n" : "=r"(ok) : "r"(b) : "memory");
        if (ok) break;
        __nanosleep(ns);
        if (++spins > (1u << 21)) __trap();
    }
}
__device__ __forceinline__ void flag_signal(unsigned int* f) {
    __threadfence();
    atomicAdd(f, 1u);
}
__device__ __forceinline__ void flag_wait(const unsigned int* f, unsigned int target, unsigned int sleep_ns) {
    uint32_t v, spins = 0;
    while (true) {
        asm volatile("ld.acquire.gpu.global.u32 %0, [%1];" : "=r"(v) : "l"(f) : "memory");
        if (v >= target) break;
        if (sleep_ns) __nanosleep(sleep_ns);
        if (++spins > (1u << 21)) __trap();
    }
}
__device__ __forceinline__ float sumsq2(uint32_t w) { return fmaf(bf_lo(w), bf_lo(w), bf_hi(w) * bf_hi(w)); }
__device__ __forceinline__ float sumsq8(const uint4 v) { return (sumsq2(v.x) + sumsq2(v.y)) + (sumsq2(v.z) + sumsq2(v.w)); }

enum { B_FULL = 0, B_EMPTY = 9, B_BASE = 18, B_XNDEAD = 19, B_QRDY = 20, B_FFN = 21, B_X = 22, B_KV = 38, B_FREE = 54, B_WO = 62, B_END = 71 };

__global__ void __cluster_dims__(2, 1, 1) __launch_bounds__(384, 1)
fused_kernel(const __grid_constant__ CUtensorMap tmX, const __grid_constant__ CUtensorMap tmQ3, const __grid_constant__ CUtensorMap tmQ1,
          const __grid_constant__ CUtensorMap tm1, const __grid_constant__ CUtensorMap tm2, const __nv_bfloat16* __restrict__ b1,
          const __nv_bfloat16* __restrict__ wo, const __nv_bfloat16* __restrict__ x, const __nv_bfloat16* __restrict__ b2,
          __nv_bfloat16* __restrict__ out, const uint64_t zero) {
    extern __shared__ __align__(1024) uint8_t smem[];
    const uint32_t sb = s2u(smem);
    const int tid = threadIdx.x, lane = tid & 31;
    const int warp = __shfl_sync(~0u, tid >> 5, 0);
    const uint32_t rank = blockIdx.x & 1;
    const int cl = blockIdx.x >> 1;
    const int rb = (cl & 7) * 2 + rank;
    const int j = cl >> 3;
    const uint32_t bar0 = sb + K1_OFF_BAR;
    const uint32_t full0 = bar0 + B_FULL * 8, empty0 = bar0 + B_EMPTY * 8, xbar0 = bar0 + B_X * 8;
    const int head = blockIdx.x >> 2, quarter = blockIdx.x & 3;
    const int rt = quarter * 8 + (head >> 2), ct = head & 3;
    volatile uint32_t* slow_flag = reinterpret_cast<volatile uint32_t*>(smem + K1_OFF_BAR + B_END * 8);

    if (warp < 8) {
        PROF(0);
        PROFT(48);
        if (lane == 0) {
            mbar_init(xbar0 + warp * 16, 1);
            mbar_init(xbar0 + warp * 16 + 8, 1);
            fence_barrier_init();
            mbar_expect(xbar0 + warp * 16, 9216);
            tma3d(sb + warp * 2 * 9216, &tmX, 0, rb * 128 + warp * 16, 0, xbar0 + warp * 16);
            mbar_expect(xbar0 + warp * 16 + 8, 9216);
            tma3d(sb + (warp * 2 + 1) * 9216, &tmX, 0, rb * 128 + warp * 16 + 8, 0, xbar0 + warp * 16 + 8);
        }
        __syncwarp();
        cluster_arrive();
        PROF(22);
        reg_alloc<240>();
        PROF(23);
#pragma unroll 1
        for (int p = 0; p < 4; p++) {
            mbar_wait(xbar0 + warp * 16 + (p >> 1) * 8, 0);
            PROF(24 + p);
            uint4* row = reinterpret_cast<uint4*>(smem + (warp * 2 + (p >> 1)) * 9216 + (p & 1) * 512 + lane * 16);
            float f[72];
#pragma unroll
            for (int i = 0; i < 9; i++) {
                const uint4 v = row[i * 64];
                f[i * 8 + 0] = bf_lo(v.x); f[i * 8 + 1] = bf_hi(v.x); f[i * 8 + 2] = bf_lo(v.y); f[i * 8 + 3] = bf_hi(v.y);
                f[i * 8 + 4] = bf_lo(v.z); f[i * 8 + 5] = bf_hi(v.z); f[i * 8 + 6] = bf_lo(v.w); f[i * 8 + 7] = bf_hi(v.w);
            }
            float s0 = 0.f, s1 = 0.f, s2 = 0.f, s3 = 0.f;
#pragma unroll
            for (int i = 0; i < 72; i += 4) { s0 += f[i]; s1 += f[i + 1]; s2 += f[i + 2]; s3 += f[i + 3]; }
            float sm = (s0 + s1) + (s2 + s3);
            sm += __shfl_xor_sync(~0u, sm, 1); sm += __shfl_xor_sync(~0u, sm, 2); sm += __shfl_xor_sync(~0u, sm, 4);
            const float mean = sm * (1.0f / DM);
            s0 = s1 = s2 = s3 = 0.f;
#pragma unroll
            for (int i = 0; i < 72; i += 4) {
                f[i] -= mean; f[i + 1] -= mean; f[i + 2] -= mean; f[i + 3] -= mean;
                s0 = fmaf(f[i], f[i], s0); s1 = fmaf(f[i + 1], f[i + 1], s1);
                s2 = fmaf(f[i + 2], f[i + 2], s2); s3 = fmaf(f[i + 3], f[i + 3], s3);
            }
            float sq = (s0 + s1) + (s2 + s3);
            sq += __shfl_xor_sync(~0u, sq, 1); sq += __shfl_xor_sync(~0u, sq, 2); sq += __shfl_xor_sync(~0u, sq, 4);
            const float rstd = rsqrtf(sq * (1.0f / DM) + 1e-5f);
#pragma unroll
            for (int i = 0; i < 9; i++) {
                uint4 o;
                o.x = pack_bf16(f[i * 8 + 0] * rstd, f[i * 8 + 1] * rstd);
                o.y = pack_bf16(f[i * 8 + 2] * rstd, f[i * 8 + 3] * rstd);
                o.z = pack_bf16(f[i * 8 + 4] * rstd, f[i * 8 + 5] * rstd);
                o.w = pack_bf16(f[i * 8 + 6] * rstd, f[i * 8 + 7] * rstd);
                row[i * 64] = o;
            }
        }
        PROF(28);
        const int wg = warp >> 2, wq = warp & 3;
        fence_proxy_async();
        named_bar_sync(1 + wg, 128);
        cluster_wait();
        PROF(1);

        const int g = lane >> 2, q = lane & 3;
        K1Ctx c;
        c.full0 = full0;
        c.rel_addr = 0;
        c.descA = mk_desc(zero, sb + wg * 8 * 9216, 16, 9216, 1);
        c.descB = mk_desc(zero, sb + K1_OFF_RING, 2048, 1024, 1);
        c.phase = 0;
        uint32_t biasq = sb + K1_OFF_BIAS + q * 32;
        uint32_t bq[8];

        uint32_t h[144];
        float accA[32], accB[32];
        {
            float accQ[108];
            uint32_t rel = 0;
            if (lane == 0 && wq < 2) asm("mapa.shared::cluster.u32 %0, %1, %2;" : "=r"(rel) : "r"(empty0), "r"(wq));
#pragma unroll 1
            for (int r = 0; r < 2; r++) {
                const uint64_t dae = c.descA + (r ? a_off(18) : 0), dao = c.descA + (r ? a_off(20) : a_off(2));
                static_for<0, 9>([&](auto sc) {
                    constexpr int s = decltype(sc)::value;
                    c.begin_stage(s);
                    wgmma_ss_n216<1, (s >> 1) * 64, ((2 * s) % 9) * 512>(accQ, (s & 1) ? dao : dae, c.descB, (r | s) != 0);
                    wgmma_ss_n216<1, (s >> 1) * 64 + 2, ((2 * s + 1) % 9) * 512>(accQ, (s & 1) ? dao : dae, c.descB, 1);
                    c.end_stage(s);
                    c.rel_addr = rel;
                });
                c.phase ^= 1;
            }
            PROF(2);
            uint32_t rel9[9];
#pragma unroll
            for (int i9 = 0; i9 < 9; i9++) {
                const int p = 4 * i9 + q, hh = (p * 57) >> 9, r = p - 9 * hh;
                rel9[i9] = hh * KV_HEAD_BYTES + (r < 8 ? (r >> 2) * 128 + (r & 3) * 4 : 0);
            }
            uint32_t gb = 0, o2 = 0;
            float scl0 = 1.f, scl1 = 1.f;
            tile_pair<false, false>(c, accA, accB, h, [&](auto sc) {
                constexpr int s = decltype(sc)::value;
                if constexpr (s == 0) reg_fence(accQ);
                if constexpr (s < 6) {
                    constexpr int grp = s / 2, part = s % 2;
                    if constexpr (part == 0) {
                        const int G = 3 * j + grp, type = G >> 3;
                        gb = (G & 7) * 4 * KV_HEAD_BYTES + (rb * 16 + warp * 2) * KV_GROUP_BYTES + g * 16 + (type == 0 ? Q_OFFSET : (type == 2 ? 256 : 0));
                        o2 = type == 0 ? 256 : (type == 2 ? 264 : 512);
                        scl0 = type == 0 ? QSCALE : ((type == 1 && ((POLY_MASK >> (wq * 2)) & 1)) ? 2.f : 1.f);
                        scl1 = type == 0 ? QSCALE : ((type == 1 && ((POLY_MASK >> (wq * 2 + 1)) & 1)) ? 2.f : 1.f);
                    }
#pragma unroll
                    for (int i9 = part * 5; i9 < (part ? 9 : 5); i9++) {
                        const int b = grp * 9 + i9;
                        uint32_t off = gb + rel9[i9];
                        if (i9 >= 2 && (i9 & 1) == 0) off += (q == i9 / 2 - 1) ? o2 : 0;
                        *reinterpret_cast<uint32_t*>(g_QKV + off) = pack_bf16(accQ[b * 4] * scl0, accQ[b * 4 + 1] * scl0);
                        *reinterpret_cast<uint32_t*>(g_QKV + off + KV_GROUP_BYTES) = pack_bf16(accQ[b * 4 + 2] * scl1, accQ[b * 4 + 3] * scl1);
                    }
                    if constexpr (s == 5) asm volatile("bar.arrive 3, 352;" ::: "memory");
                }
                if constexpr (s == 4) { named_bar_sync(4, 352); load_bias(bq, biasq); }
                if constexpr (s == 5) reg_fence(accA);
                if constexpr (s >= 5) gelu_blocks<(s - 5) * 2, 2, 96>(accA, h, bq);
                if constexpr (s == 8) load_bias(bq, biasq + 128);
            });
        }
        PROF(3);
#pragma unroll
        for (int i = 32; i < 96; i++) asm volatile("mov.u32 %0, 0;" : "=r"(h[i]));
#pragma unroll 1
        for (int p = 1; p < 4; p++) {
            biasq += 256;
            tile_pair<false, false>(c, accA, accB, h, [&](auto sc) {
                constexpr int s = decltype(sc)::value;
                if constexpr (s == 0) {
                    reg_fence(accB);
#pragma unroll
                    for (int i = 0; i < 80; i++) h[i] = h[i + 32];
                }
                if constexpr (s < 4) gelu_blocks<s * 2, 2, 80>(accB, h, bq);
                if constexpr (s == 4) load_bias(bq, biasq);
                if constexpr (s == 5) reg_fence(accA);
                if constexpr (s >= 5) gelu_blocks<(s - 5) * 2, 2, 96>(accA, h, bq);
                if constexpr (s == 8) load_bias(bq, biasq + 128);
            });
        }
        PROF(4);
        tile_pair<false, true>(c, accA, accB, h, [&](auto sc) {
            constexpr int s = decltype(sc)::value;
            if constexpr (s == 0) reg_fence(accB);
            if constexpr (s < 4) gelu_blocks<s * 2, 2, 112>(accB, h, bq);
            if constexpr (s == 4) load_bias(bq, biasq + 256);
            if constexpr (s == 5) { reg_fence(accA); if (tid == wg * 128) mbar_arrive(bar0 + B_XNDEAD * 8); }
            if constexpr (s == 5 || s == 6) gelu_blocks<(s - 5) * 3, 3, 128>(accA, h, bq);
            if constexpr (s == 7) gelu_blocks<6, 2, 128>(accA, h, bq);
            if constexpr (s == 3 || s == 7) reg_fence(h);
        });
        PROF(5);
        uint4* pout = g_part + j * SLAB + rb * 36 * 256 + tid;
#pragma unroll 1
        for (int p = 0; p < 4; p++) {
            tile_pair<true, true>(c, accA, accB, h, [&](auto sc) {
                constexpr int s = decltype(sc)::value;
                if constexpr (s == 0) reg_fence(accB);
                if constexpr (s < 4) store_part<s>(accB, pout);
                if constexpr (s == 5) reg_fence(accA);
                if constexpr (s >= 5) store_part<s - 5>(accA, pout + 1024);
            });
            pout += 2048;
            PROF(6 + p);
        }
        wg_wait<0>();
        c.release(8);
        reg_fence(accB);
        store_part<0>(accB, pout); store_part<1>(accB, pout); store_part<2>(accB, pout); store_part<3>(accB, pout);
        __syncwarp();
        if (lane == 0) mbar_arrive(bar0 + B_FFN * 8);
        PROF(10);
        PROFT(49);

        mbar_wait(bar0 + B_QRDY * 8, 0);
        const uint32_t slow = __any_sync(~0u, *slow_flag != 0);
        const uint64_t kd0 = mk_desc(zero, sb + SM_KV, 0, KV_GROUP_BYTES, 0);
        const uint64_t vd0 = mk_desc(zero, sb + SM_KV + 256, KV_GROUP_BYTES, 128, 0);
        const uint64_t qd0 = mk_desc(zero, sb + SM_Q + wg * 4096, 128, 512, 0);
        const uint32_t kvbar = bar0 + B_KV * 8;
        float o[12];
#pragma unroll
        for (int i = 0; i < 12; i++) o[i] = 0.f;
        PROF(16);
        PROFT(50);
        if (!slow) {
            const uint32_t one2 = 0x3F803F80u + (uint32_t)zero;
            float s0[64], s1[64];
            uint32_t p0[32], p1[32];
            mbar_wait(kvbar, 0);
            reg_fence(o);
            wg_fence();
            issue_qk<0>(s0, qd0, kd0);
            wg_commit();
            mbar_wait(kvbar + 8, 0);
            wg_fence();
            issue_qk<KV_TILE>(s1, qd0, kd0);
            wg_commit();
            uint64_t qd = qd0;
            const uint32_t fre = (tid == wg * 128) ? bar0 + B_FREE * 8 - 8 : 0;
#pragma unroll 1
            for (int pass = 0; pass < 4; pass++) {
                uint64_t vd = vd0, kdn = kd0 + 2 * KV_TILE;
                uint32_t bn = kvbar + 16;
#pragma unroll 1
                for (int it = 0; it < 8; it++) {
                    if (it == 7) { kdn = kd0; bn = kvbar; qd += 512; }
                    wg_wait<1>();
                    reg_fence(s0);
                    if (pass == 3 && it > 0 && fre) mbar_arrive(fre + it * 8);
                    softmax_fast<16>(s0, p0, one2);
                    reg_fence(p0);
                    if (it == 0 && pass != 0) {
                        wg_wait<0>();
                        reg_fence(o);
                        store_o(o, quarter * 8 + pass * 2 - 2 + wg, head, wq, lane);
                        reg_fence(o);
                    }
                    mbar_wait(bn, 0);
                    wg_fence();
                    issue_pv<0>(o, p0, vd);
                    issue_qk<0>(s0, qd, kdn);
                    wg_commit();
                    wg_wait<1>();
                    reg_fence(s1);
                    softmax_fast<16>(s1, p1, one2);
                    reg_fence(p1);
                    mbar_wait(bn + 8, 0);
                    wg_fence();
                    issue_pv<KV_TILE>(o, p1, vd);
                    issue_qk<KV_TILE>(s1, qd, kdn);
                    wg_commit();
                    vd += 2 * KV_TILE; kdn += 2 * KV_TILE; bn += 16;
                }
                if (pass == 0) PROF(17);
            }
            wg_wait<0>();
            reg_fence(o);
            reg_fence(s0);
            reg_fence(s1);
            store_o(o, quarter * 8 + 6 + wg, head, wq, lane);
        } else {
#pragma unroll 1
            for (int pass = 0; pass < 4; pass++) {
                float m0 = -INFINITY, m1 = -INFINITY;
                float s[64];
                uint32_t p[32];
#pragma unroll 1
                for (int t = 0; t < 16; t++) {
                    mbar_wait(kvbar + t * 8, 0);
                    wg_fence();
                    issue_qk<0>(s, qd0 + pass * 512, kd0 + t * KV_TILE);
                    wg_commit();
                    wg_wait<0>();
                    reg_fence(s);
                    float a0 = m0, a1 = m1;
#pragma unroll
                    for (int k = 0; k < 16; k++) {
                        if ((POLY_MASK >> (k & 7)) & 1) {
#pragma unroll
                            for (int i = 0; i < 4; i++) s[k * 4 + i] *= 0.5f;
                        }
                        a0 = fmaxf(a0, fmaxf(s[k * 4 + 0], s[k * 4 + 1]));
                        a1 = fmaxf(a1, fmaxf(s[k * 4 + 2], s[k * 4 + 3]));
                    }
                    a0 = fmaxf(a0, __shfl_xor_sync(~0u, a0, 1)); a1 = fmaxf(a1, __shfl_xor_sync(~0u, a1, 1));
                    a0 = fmaxf(a0, __shfl_xor_sync(~0u, a0, 2)); a1 = fmaxf(a1, __shfl_xor_sync(~0u, a1, 2));
                    const float r0 = ex2(m0 - a0), r1 = ex2(m1 - a1);
                    m0 = a0; m1 = a1;
#pragma unroll
                    for (int i = 0; i < 3; i++) { o[i * 4] *= r0; o[i * 4 + 1] *= r0; o[i * 4 + 2] *= r1; o[i * 4 + 3] *= r1; }
#pragma unroll
                    for (int k = 0; k < 16; k++) {
                        p[k * 2 + 0] = pack_bf16(ex2(s[k * 4 + 0] - m0), ex2(s[k * 4 + 1] - m0));
                        p[k * 2 + 1] = pack_bf16(ex2(s[k * 4 + 2] - m1), ex2(s[k * 4 + 3] - m1));
                    }
                    reg_fence(p);
                    reg_fence(o);
                    wg_fence();
                    issue_pv<0>(o, p, vd0 + t * KV_TILE);
                    wg_commit();
                    wg_wait<0>();
                    reg_fence(o);
                }
                store_o(o, quarter * 8 + pass * 2 + wg, head, wq, lane);
            }
            if (tid == wg * 128)
                for (int i = 0; i < 7; i++) mbar_arrive(bar0 + (B_FREE + i) * 8);
        }
        PROF(18);
        PROFT(51);

        named_bar_sync(5, 256);
        if (tid == 0) flag_signal(&g_flags.o_done[quarter]);
        mbar_wait(bar0 + B_BASE * 8, 0);
        const int t128 = tid & 127;
        float4 bs[9];
        {
            const float4* bp = g_base + ((rt >> 1) * 72 + ct * 18 + wg * 9) * 256 + (rt & 1) * 128 + t128;
#pragma unroll
            for (int i = 0; i < 9; i++) bs[i] = __ldcg(bp + i * 256);
        }
        if (tid == 0) flag_wait(&g_flags.o_done[quarter], 32, 0);
        named_bar_sync(5, 256);
        PROF(19);
        uint4 af[18];
        {
            const uint4* ap = reinterpret_cast<const uint4*>(g_O) + (rt * 36 + wg * 18) * 128 + t128;
#pragma unroll
            for (int k = 0; k < 18; k++) af[k] = __ldcg(ap + k * 128);
        }
        float acc[72];
        const uint64_t wd0 = mk_desc(zero, sb, 2304, 128, 0), wd1 = wd0 + wg * ((18 * 4608) >> 4);
#pragma unroll
        for (int i = 0; i < 5; i++) mbar_wait(bar0 + (B_WO + wg * 4 + i) * 8, 0);
        wg_fence();
        static_for<0, 18>([&](auto kc) {
            constexpr int k = decltype(kc)::value;
            if constexpr (k < 8) {
                constexpr int o0 = (sm_wo(k >> 2) + (k & 3) * 4608) >> 4, o1 = (SM_KV + (k + 10) * 4608) >> 4;
                wgmma_rs_n144<1, 0>(acc, af[k].x, af[k].y, af[k].z, af[k].w, wd0 + (wg ? o1 : o0), k != 0);
            } else {
                wgmma_rs_n144<1, (SM_KV + (k - 8) * 4608) / 16>(acc, af[k].x, af[k].y, af[k].z, af[k].w, wd1, 1);
            }
        });
        wg_commit();
        wg_wait<0>();
        reg_fence(acc);
        PROF(20);
        {
            float4* ex = reinterpret_cast<float4*>(smem + SM_EXCH) + t128;
#pragma unroll
            for (int i = 0; i < 9; i++) {
                const float4 lo = make_float4(acc[i * 4], acc[i * 4 + 1], acc[i * 4 + 2], acc[i * 4 + 3]);
                const float4 hi = make_float4(acc[36 + i * 4], acc[36 + i * 4 + 1], acc[36 + i * 4 + 2], acc[36 + i * 4 + 3]);
                ex[(wg * 9 + i) * 128] = wg ? lo : hi;
                const float4 own = wg ? hi : lo;
                bs[i].x += own.x; bs[i].y += own.y;
                bs[i].z += own.z; bs[i].w += own.w;
            }
            named_bar_sync(5, 256);
            uint32_t* op = reinterpret_cast<uint32_t*>(out + (size_t)(rt * 64 + wq * 16 + g) * DM + ct * 144 + wg * 72 + q * 2);
#pragma unroll
            for (int i = 0; i < 9; i++) {
                const float4 v = ex[((wg ^ 1) * 9 + i) * 128];
                op[i * 4] = pack_bf16(bs[i].x + v.x, bs[i].y + v.y);
                op[i * 4 + 4 * DM] = pack_bf16(bs[i].z + v.z, bs[i].w + v.w);
            }
        }
        if (tid == 0) {
            if (atomicAdd(&g_flags.exited, 1u) == gridDim.x - 1) {
                unsigned int* f = reinterpret_cast<unsigned int*>(&g_flags);
#pragma unroll 1
                for (int i = 0; i < (int)(sizeof(Flags) / 4); i++) f[i] = 0;
            }
        }
        PROF(21);
        PROFT(52);
    } else {
        reg_dealloc<24>();
        if (warp == 8 && lane == 0) {
            prefetch_tmap(&tmQ3); prefetch_tmap(&tmQ1); prefetch_tmap(&tm1); prefetch_tmap(&tm2);
            #pragma unroll 1
            for (int i = 0; i < 9; i++) { mbar_init(full0 + i * 8, 1); mbar_init(empty0 + i * 8, 4); mbar_init(bar0 + (B_WO + i) * 8, 1); }
            mbar_init(bar0 + B_BASE * 8, 3); mbar_init(bar0 + B_XNDEAD * 8, 2); mbar_init(bar0 + B_QRDY * 8, 3); mbar_init(bar0 + B_FFN * 8, 8);
#pragma unroll 1
            for (int i = 0; i < 16; i++) { mbar_init(bar0 + (B_KV + i) * 8, 1); mbar_init(bar0 + (B_FREE + (i & 7)) * 8, 2); }
            *slow_flag = 0;
            fence_barrier_init();
        }
        __syncwarp();
        cluster_arrive();
        cluster_wait();
        const uint8_t* kvsrc = g_QKV + (size_t)head * KV_HEAD_BYTES;
        if (warp == 8) {
            if (lane == 0) {
                int st = 0, u = rank, tile = -4;
                int es = 5;
                uint32_t eph = 1;
#pragma unroll 1
                for (int n = 0; n < 99; n++) {
                    mbar_wait(empty0 + es * 8, eph);
                    const uint32_t fb = full0 + st * 8, dst = sb + K1_OFF_RING + u * 8192;
                    mbar_expect(fb, 16384);
                    if (tile < 0) {
                        tma3d_mc(dst, &tmQ3, j * 216, n * 32 + rank * 16, 0, fb, 3);
                        tma2d_mc(dst + 6144, &tmQ1, j * 216 + 192, n * 32 + rank * 16, fb, 3);
                    } else if (tile < 9) {
                        tma2d_mc(dst, &tm1, j * 576 + tile * 64, u * 64, fb, 3);
                    } else {
                        tma2d_mc(dst, &tm2, (tile - 9) * 64, j * 576 + u * 64, fb, 3);
                    }
                    u += 2;
                    if (u >= 9) { u -= 9; tile++; }
                    if (++st == 9) st = 0;
                    if (++es == 9) { es = 0; eph ^= 1; }
                }
                mbar_wait(empty0 + 8 * 8, 0);
                mbar_wait(bar0 + B_QRDY * 8, 0);
                asm volatile("fence.proxy.async;" ::: "memory");
#pragma unroll 1
                for (int i = 11; i < NCHUNK; i++) {
                    mbar_expect(bar0 + (B_KV + i) * 8, CHUNK_BYTES);
                    bulk_load(sb + SM_KV + i * CHUNK_BYTES, kvsrc + i * CHUNK_BYTES, CHUNK_BYTES, bar0 + (B_KV + i) * 8);
                }
#pragma unroll 1
                for (int i = 0; i < 9; i++) {
                    if (i > 0) {
                        const int f = i == 1 ? 0 : ((i - 1) * 9 + 4) / 10;
                        mbar_wait_sleep(bar0 + (B_FREE + f) * 8, i == 1 ? 500 : 50);
                    }
                    mbar_expect(bar0 + (B_WO + i) * 8, WO_PIECE);
                    bulk_load(sb + (i == 0 ? sm_wo(0) : (i == 1 ? sm_wo(1) : SM_KV + (i - 2) * WO_PIECE)), g_Wo + ct * WO_TILE_BYTES + i * WO_PIECE, WO_PIECE,
                              bar0 + (B_WO + i) * 8);
                }
            }
        } else {
            const int ht = tid - 288;
            if (ht < 72) {
                const uint4 v = __ldg(reinterpret_cast<const uint4*>(b1 + j * 576) + ht);
                uint32_t* sbias = reinterpret_cast<uint32_t*>(smem + K1_OFF_BIAS) + (ht >> 3) * 32 + (ht & 7);
                sbias[0] = v.x; sbias[8] = v.y; sbias[16] = v.z; sbias[24] = v.w;
            }
            asm volatile("bar.arrive 4, 352;" ::: "memory");
            PROFH(37);
#pragma unroll 1
            for (int i = ht; i < 512; i += 96) {
                const int key = i & 127;
                uint8_t* p = g_QKV + (size_t)(j * 4 + (i >> 7)) * KV_HEAD_BYTES + (rb * 16 + (key >> 3)) * KV_GROUP_BYTES + 512 + (key & 7) * 16;
                *reinterpret_cast<uint32_t*>(p + 4) = ((POLY_MASK >> ((key >> 3) & 7)) & 1) ? 0x3F804000u : 0x00003F80u;
                *reinterpret_cast<uint32_t*>(p + 12) = 0x00003F80u;
            }
#pragma unroll 2
            for (int i = blockIdx.x * 324 + ht; i < blockIdx.x * 324 + 324; i += 96) {
                const int k = i / 72, nc = i - k * 72, c4 = nc / 18;
                *reinterpret_cast<uint4*>(g_Wo + c4 * WO_TILE_BYTES + (k >> 3) * 2304 + (nc - c4 * 18) * 128 + (k & 7) * 16) =
                    __ldg(reinterpret_cast<const uint4*>(wo) + i);
            }
            PROFH(38);
            named_bar_sync(3, 352);
            if (ht == 0) {
                flag_signal(&g_flags.qkv_stored[rb]);
                flag_wait(&g_flags.qkv_stored[rb], 8, 200);
            }
            named_bar_sync(7, 96);
            PROFH(39);
#pragma unroll 1
            for (int i = warp - 9; i < 16; i += 3) {
                const int hd = j * 4 + (i >> 2), key = (i & 3) * 32 + lane;
                const uint8_t* p = g_QKV + (size_t)hd * KV_HEAD_BYTES + (rb * 16 + (key >> 3)) * KV_GROUP_BYTES + (key & 7) * 16;
                const uint4 a = __ldcg(reinterpret_cast<const uint4*>(p)), b = __ldcg(reinterpret_cast<const uint4*>(p + 128));
                float n = sumsq2(__ldcg(reinterpret_cast<const uint32_t*>(p + 512))) + sumsq8(a) + sumsq8(b);
                if ((POLY_MASK >> ((key >> 3) & 7)) & 1) n *= 0.25f;
#pragma unroll
                for (int o = 16; o; o >>= 1) n = fmaxf(n, __shfl_xor_sync(~0u, n, o));
                if (lane == 0) g_kmax[hd * 64 + rb * 4 + (i & 3)] = n;
            }
            named_bar_sync(7, 96);
            PROFH(40);
            if (ht == 0) {
                flag_signal(&g_flags.kv_ready);
                flag_wait(&g_flags.kv_ready, 128, 300);
                mbar_wait_sleep(bar0 + B_XNDEAD * 8, 300);
            }
            named_bar_sync(7, 96);
            PROFH(41);
            float kmax2;
            {
                const float2 v = __ldcg(reinterpret_cast<const float2*>(g_kmax + head * 64 + lane * 2));
                kmax2 = fmaxf(v.x, v.y);
#pragma unroll
                for (int o = 16; o; o >>= 1) kmax2 = fmaxf(kmax2, __shfl_xor_sync(~0u, kmax2, o));
            }
            asm volatile("fence.proxy.async;" ::: "memory");
            int chunk = warp - 9;
#pragma unroll 1
            for (int r = ht; r < 512; r += 96) {
                if (lane == 0 && chunk < 11) {
                    mbar_expect(bar0 + (B_KV + chunk) * 8, CHUNK_BYTES);
                    bulk_load(sb + SM_KV + chunk * CHUNK_BYTES, kvsrc + chunk * CHUNK_BYTES, CHUNK_BYTES, bar0 + (B_KV + chunk) * 8);
                }
                chunk += 3;
                const uint8_t* p = kvsrc + Q_OFFSET + (quarter * 64 + (r >> 3)) * KV_GROUP_BYTES + (r & 7) * 16;
                const uint4 a = __ldcg(reinterpret_cast<const uint4*>(p)), b = __ldcg(reinterpret_cast<const uint4*>(p + 128));
                const uint32_t e = __ldcg(reinterpret_cast<const uint32_t*>(p + 256));
                const float cc = sqrtf((sumsq2(e) + sumsq8(a) + sumsq8(b)) * kmax2) * 1.02f;
                if (!(cc <= 58.f)) *slow_flag = 1;
                uint4* dst = reinterpret_cast<uint4*>(smem + SM_Q + (r >> 3) * 512 + (r & 7) * 16);
                dst[0] = a;
                dst[8] = b;
                dst[16] = make_uint4(e, pack_bf16(-cc, 768.f), 0u, 0u);
                dst[24] = make_uint4(0u, POLY_MODE ? 0xBFFF0000u : 0xC0000000u, 0u, 0u);
            }
            named_bar_sync(7, 96);
            if (*slow_flag) {
#pragma unroll 1
                for (int r = ht; r < 512; r += 96) {
                    uint32_t* dst = reinterpret_cast<uint32_t*>(smem + SM_Q + (r >> 3) * 512 + (r & 7) * 16);
                    dst[65] = 0u;
                    dst[97] = 0u;
                }
            }
            fence_proxy_async();
            __syncwarp();
            if (lane == 0) mbar_arrive(bar0 + B_QRDY * 8);
            PROFH(42);
            if (ht == 0) {
                mbar_wait_sleep(bar0 + B_FFN * 8, 300);
                flag_signal(&g_flags.ffn_done[rb]);
                flag_wait(&g_flags.ffn_done[rt >> 1], 8, 300);
            }
            named_bar_sync(7, 96);
#pragma unroll 1
            for (int i = ht; i < 9 * 128; i += 96) {
                const int t = (rt & 1) * 128 + (i & 127), pb = ct * 9 + (i >> 7);
                const int u = ((rt >> 1) * 36 + pb) * 256 + t;
                const int col = pb * 16 + (t & 3) * 2;
                const uint32_t* xp = reinterpret_cast<const uint32_t*>(x + (size_t)((rt >> 1) * 128 + (t >> 5) * 16 + ((t & 31) >> 2)) * DM + col);
                float a[8];
                {
                    const uint32_t x0 = __ldg(xp), x1 = __ldg(xp + 4 * DM), x2 = __ldg(xp + 4), x3 = __ldg(xp + 4 * DM + 4);
                    const uint32_t ba = __ldg(reinterpret_cast<const uint32_t*>(b2 + col)), bb = __ldg(reinterpret_cast<const uint32_t*>(b2 + col + 8));
                    a[0] = bf_lo(x0) + bf_lo(ba); a[1] = bf_hi(x0) + bf_hi(ba); a[2] = bf_lo(x1) + bf_lo(ba); a[3] = bf_hi(x1) + bf_hi(ba);
                    a[4] = bf_lo(x2) + bf_lo(bb); a[5] = bf_hi(x2) + bf_hi(bb); a[6] = bf_lo(x3) + bf_lo(bb); a[7] = bf_hi(x3) + bf_hi(bb);
                }
#pragma unroll 2
                for (int jj = 0; jj < 8; jj++) {
                    const uint4 v = __ldcg(g_part + jj * SLAB + u);
                    a[0] = fmaf(bf_lo(v.x), 0.5f, a[0]); a[1] = fmaf(bf_hi(v.x), 0.5f, a[1]); a[2] = fmaf(bf_lo(v.y), 0.5f, a[2]); a[3] = fmaf(bf_hi(v.y), 0.5f, a[3]);
                    a[4] = fmaf(bf_lo(v.z), 0.5f, a[4]); a[5] = fmaf(bf_hi(v.z), 0.5f, a[5]); a[6] = fmaf(bf_lo(v.w), 0.5f, a[6]); a[7] = fmaf(bf_hi(v.w), 0.5f, a[7]);
                }
                float4* bp = g_base + ((rt >> 1) * 72 + pb * 2) * 256 + t;
                bp[0] = make_float4(a[0], a[1], a[2], a[3]);
                bp[256] = make_float4(a[4], a[5], a[6], a[7]);
            }
            __syncwarp();
            if (lane == 0) mbar_arrive(bar0 + B_BASE * 8);
            PROFH(43);
        }
    }
}

typedef CUresult (*EncodeFn)(CUtensorMap*, CUtensorMapDataType, cuuint32_t, void*, const cuuint64_t*, const cuuint64_t*, const cuuint32_t*,
                             const cuuint32_t*, CUtensorMapInterleave, CUtensorMapSwizzle, CUtensorMapL2promotion, CUtensorMapFloatOOBfill);

void make_map(EncodeFn fn, CUtensorMap* m, const void* base, int rank, const cuuint64_t* dims, const cuuint64_t* strides, const cuuint32_t* box) {
    cuuint32_t es[3] = {1, 1, 1};
    fn(m, CU_TENSOR_MAP_DATA_TYPE_BFLOAT16, rank, const_cast<void*>(base), dims, strides, box, es, CU_TENSOR_MAP_INTERLEAVE_NONE,
       CU_TENSOR_MAP_SWIZZLE_128B, CU_TENSOR_MAP_L2_PROMOTION_L2_256B, CU_TENSOR_MAP_FLOAT_OOB_FILL_NONE);
}

}

extern "C" void kernel_launch(void* const* d_in, const int* in_sizes, int n_in, void* d_out, int out_size) {
    const __nv_bfloat16* x = (const __nv_bfloat16*)d_in[0];
    const __nv_bfloat16* wqkv = (const __nv_bfloat16*)d_in[1];
    const __nv_bfloat16* wo = (const __nv_bfloat16*)d_in[2];
    const __nv_bfloat16* w1 = (const __nv_bfloat16*)d_in[4];
    const __nv_bfloat16* b1 = (const __nv_bfloat16*)d_in[5];
    const __nv_bfloat16* w2 = (const __nv_bfloat16*)d_in[6];
    const __nv_bfloat16* b2 = (const __nv_bfloat16*)d_in[7];
    __nv_bfloat16* out = (__nv_bfloat16*)d_out;

    EncodeFn fn = nullptr;
    cudaDriverEntryPointQueryResult qr;
    cudaGetDriverEntryPoint("cuTensorMapEncodeTiled", (void**)&fn, cudaEnableDefault, &qr);
    CUtensorMap tmX, tmQ3, tmQ1, tm1, tm2;
    {
        cuuint64_t d[3] = {64, SEQ, 9}, s[2] = {DM * 2, 128};
        cuuint32_t b[3] = {64, 8, 9};
        make_map(fn, &tmX, x, 3, d, s, b);
    }
    {
        cuuint64_t d[3] = {3 * DM, DM, 3}, s[2] = {3 * DM * 2, 128};
        cuuint32_t b[3] = {64, 16, 3};
        make_map(fn, &tmQ3, wqkv, 3, d, s, b);
        make_map(fn, &tmQ1, wqkv, 2, d, s, b);
    }
    {
        cuuint64_t d[2] = {FF, DM}, s[1] = {FF * 2};
        cuuint32_t b[2] = {64, 64};
        make_map(fn, &tm1, w1, 2, d, s, b);
        cuuint64_t d2[2] = {DM, FF}, s2[1] = {DM * 2};
        make_map(fn, &tm2, w2, 2, d2, s2, b);
    }
    cudaFuncSetAttribute(fused_kernel, cudaFuncAttributeMaxDynamicSharedMemorySize, K1_SMEM);
    fused_kernel<<<128, 384, K1_SMEM, cudaStreamPerThread>>>(tmX, tmQ3, tmQ1, tm1, tm2, b1, wo, x, b2, out, 0ull);
}
```

```cpp
#include <cuda_runtime.h>
#include <cuda_bf16.h>
#include <cuda.h>
#include <stdint.h>

#define PROF(i) do { } while (0)
#define PROFT(i) do { } while (0)
#define PROFH(i) do { } while (0)
#define PROF_WG 0

namespace {

constexpr int SEQ = 2048, DM = 576, FF = 4608, NH = 32, DH = 18;

constexpr int KV_GROUP_BYTES = 5 * 128;
constexpr int KV_HEAD_BYTES = (SEQ / 8) * KV_GROUP_BYTES;
constexpr int Q_OFFSET = NH * KV_HEAD_BYTES;
#define POLY_MASK 0xB6
__device__ __align__(1024) uint8_t g_QKV[2 * NH * KV_HEAD_BYTES];
__device__ __align__(1024) float g_kmax[NH * 64];
constexpr int SLAB = 16 * 36 * 256;
__device__ __align__(1024) uint4 g_part[8 * SLAB];
__device__ __align__(1024) float4 g_base[2 * SLAB];
__device__ __align__(1024) uint32_t g_O[SEQ * DM / 2];
struct Flags {
    unsigned int qkv_stored[16];
    unsigned int ffn_done[16];
    unsigned int o_done[4];
    unsigned int kv_ready;
    unsigned int exited;
};
__device__ Flags g_flags;
constexpr int WO_TILE_BYTES = DM * 144 * 2;
__device__ __align__(1024) uint8_t g_Wo[4 * WO_TILE_BYTES];

__device__ __forceinline__ uint32_t s2u(const void* p) { return (uint32_t)__cvta_generic_to_shared(p); }
__device__ __forceinline__ void mbar_init(uint32_t b, int c) { asm volatile("mbarrier.init.shared::cta.b64 [%0], %1;" ::"r"(b), "r"(c) : "memory"); }
__device__ __forceinline__ void mbar_expect(uint32_t b, uint32_t bytes) {
    asm volatile("mbarrier.arrive.expect_tx.shared::cta.b64 _, [%0], %1;" ::"r"(b), "r"(bytes) : "memory");
}
__device__ __forceinline__ void mbar_wait(uint32_t b, uint32_t parity) {
    asm volatile(
        "{\n.reg .pred p;\n.reg .u32 c;\n"
        "mbarrier.try_wait.parity.shared::cta.b64 p, [%0], %1;\n"
        "@p bra DONE;\n"
        "mov.u32 c, 0;\n"
        "LOOP:\n"
        "mbarrier.try_wait.parity.shared::cta.b64 p, [%0], %1;\n"
        "@p bra DONE;\n"
        "add.u32 c, c, 1;\n"
        "setp.lt.u32 p, c, 4194304;\n"
        "@p bra LOOP;\n"
        "trap;\n"
        "DONE:\n}\n" ::"r"(b), "r"(parity) : "memory");
}
__device__ __forceinline__ void fence_barrier_init() { asm volatile("fence.mbarrier_init.release.cluster;" ::: "memory"); }
__device__ __forceinline__ void fence_proxy_async() { asm volatile("fence.proxy.async.shared::cta;" ::: "memory"); }
__device__ __forceinline__ void cluster_arrive() { asm volatile("barrier.cluster.arrive.relaxed.aligned;" ::: "memory"); }
__device__ __forceinline__ void cluster_wait() { asm volatile("barrier.cluster.wait.aligned;" ::: "memory"); }
__device__ __forceinline__ void named_bar_sync(int id, int n) { asm volatile("bar.sync %0, %1;" ::"r"(id), "r"(n) : "memory"); }
__device__ __forceinline__ void griddep_wait() { asm volatile("griddepcontrol.wait;" ::: "memory"); }
__device__ __forceinline__ void griddep_launch() { asm volatile("griddepcontrol.launch_dependents;" ::: "memory"); }

__device__ __forceinline__ void tma3d_mc(uint32_t dst, const CUtensorMap* tm, int c0, int c1, int c2, uint32_t bar, uint16_t mask) {
    asm volatile("cp.async.bulk.tensor.3d.shared::cluster.global.mbarrier::complete_tx::bytes.multicast::cluster [%0], [%1, {%3, %4, %5}], [%2], %6;"
                 ::"r"(dst), "l"(tm), "r"(bar), "r"(c0), "r"(c1), "r"(c2), "h"(mask) : "memory");
}
__device__ __forceinline__ void tma2d_mc(uint32_t dst, const CUtensorMap* tm, int c0, int c1, uint32_t bar, uint16_t mask) {
    asm volatile("cp.async.bulk.tensor.2d.shared::cluster.global.mbarrier::complete_tx::bytes.multicast::cluster [%0], [%1, {%3, %4}], [%2], %5;"
                 ::"r"(dst), "l"(tm), "r"(bar), "r"(c0), "r"(c1), "h"(mask) : "memory");
}
__device__ __forceinline__ void tma3d(uint32_t dst, const CUtensorMap* tm, int c0, int c1, int c2, uint32_t bar) {
    asm volatile("cp.async.bulk.tensor.3d.shared::cluster.global.mbarrier::complete_tx::bytes [%0], [%1, {%3, %4, %5}], [%2];"
                 ::"r"(dst), "l"(tm), "r"(bar), "r"(c0), "r"(c1), "r"(c2) : "memory");
}
__device__ __forceinline__ void tma2d(uint32_t dst, const CUtensorMap* tm, int c0, int c1, uint32_t bar) {
    asm volatile("cp.async.bulk.tensor.2d.shared::cluster.global.mbarrier::complete_tx::bytes [%0], [%1, {%3, %4}], [%2];"
                 ::"r"(dst), "l"(tm), "r"(bar), "r"(c0), "r"(c1) : "memory");
}
__device__ __forceinline__ void bulk_load(uint32_t dst, const void* src, uint32_t bytes, uint32_t bar) {
    asm volatile("cp.async.bulk.shared::cluster.global.mbarrier::complete_tx::bytes [%0], [%1], %2, [%3];"
                 ::"r"(dst), "l"(src), "r"(bytes), "r"(bar) : "memory");
}
__device__ __forceinline__ void prefetch_tmap(const CUtensorMap* tm) { asm volatile("prefetch.tensormap [%0];" ::"l"(tm) : "memory"); }

__device__ __forceinline__ void wg_fence() { asm volatile("wgmma.fence.sync.aligned;" ::: "memory"); }
__device__ __forceinline__ void wg_commit() { asm volatile("wgmma.commit_group.sync.aligned;" ::: "memory"); }
template <int N> __device__ __forceinline__ void wg_wait() { asm volatile("wgmma.wait_group.sync.aligned %0;" ::"n"(N) : "memory"); }
template <int N> __device__ __forceinline__ void reg_fence(float (&d)[N]) {
#pragma unroll
    for (int i = 0; i < N; i++) asm volatile("" : "+f"(d[i])::"memory");
}
template <int N> __device__ __forceinline__ void reg_fence(uint32_t (&d)[N]) {
#pragma unroll
    for (int i = 0; i < N; i++) asm volatile("" : "+r"(d[i])::"memory");
}
template <int R> __device__ __forceinline__ void reg_alloc() { asm volatile("setmaxnreg.inc.sync.aligned.u32 %0;" ::"n"(R)); }
template <int R> __device__ __forceinline__ void reg_dealloc() { asm volatile("setmaxnreg.dec.sync.aligned.u32 %0;" ::"n"(R)); }

__device__ __forceinline__ uint64_t mk_desc(uint64_t z, uint32_t addr, uint32_t lbo, uint32_t sbo, uint32_t swz) {
    return z + ((uint64_t)(((addr & 0x3FFFF) >> 4) | ((lbo >> 4) << 16)) | ((uint64_t)((sbo >> 4) | (swz << 30)) << 32));
}
__device__ __forceinline__ uint32_t pack_bf16(float lo, float hi) {
    uint32_t r;
    asm("cvt.rn.bf16x2.f32 %0, %1, %2;" : "=r"(r) : "f"(hi), "f"(lo));
    return r;
}
__device__ __forceinline__ float bf_lo(uint32_t w) { return __uint_as_float(w << 16); }
__device__ __forceinline__ float bf_hi(uint32_t w) { return __uint_as_float(w & 0xFFFF0000u); }
__device__ __forceinline__ float ex2(float x) {
    float r;
    asm("ex2.approx.ftz.f32 %0, %1;" : "=f"(r) : "f"(x));
    return r;
}
__device__ __forceinline__ float tanh_fast(float x) {
    float r;
    asm("tanh.approx.f32 %0, %1;" : "=f"(r) : "f"(x));
    return r;
}
__device__ __forceinline__ float gelu2(float u) {
    const float w = fmaf(u * u, 0.0356774081f, 0.7978845608f);
    return fmaf(u, tanh_fast(u * w), u);
}

template<int TB, int AOFF, int BOFF> __device__ __forceinline__ void wgmma_ss_n216(float (&d)[108], uint64_t da, uint64_t db, int sd) {
    asm volatile("{\n.reg .pred p;\n.reg .b64 ta, tb;\nsetp.ne.b32 p, %110, 0;\nadd.s64 ta, %108, %112;\nadd.s64 tb, %109, %113;\n"
      "wgmma.mma_async.sync.aligned.m64n216k16.f32.bf16.bf16 {%0, %1, %2, %3, %4, %5, %6, %7, %8, %9, %10, %11, %12, %13, %14, %15, %16, %17, %18, %19, %20, %21, %22, %23, %24, %25, %26, %27, %28, %29, %30, %31, %32, %33, %34, %35, %36, %37, %38, %39, %40, %41, %42, %43, %44, %45, %46, %47, %48, %49, %50, %51, %52, %53, %54, %55, %56, %57, %58, %59, %60, %61, %62, %63, %64, %65, %66, %67, %68, %69, %70, %71, %72, %73, %74, %75, %76, %77, %78, %79, %80, %81, %82, %83, %84, %85, %86, %87, %88, %89, %90, %91, %92, %93, %94, %95, %96, %97, %98, %99, %100, %101, %102, %103, %104, %105, %106, %107}, ta, tb, p, 1, 1, 0, %111;\n}\n"
      : "+f"(d[0]), "+f"(d[1]), "+f"(d[2]), "+f"(d[3]), "+f"(d[4]), "+f"(d[5]), "+f"(d[6]), "+f"(d[7]), "+f"(d[8]), "+f"(d[9]), "+f"(d[10]), "+f"(d[11]), "+f"(d[12]), "+f"(d[13]), "+f"(d[14]), "+f"(d[15]), "+f"(d[16]), "+f"(d[17]), "+f"(d[18]), "+f"(d[19]), "+f"(d[20]), "+f"(d[21]), "+f"(d[22]), "+f"(d[23]), "+f"(d[24]), "+f"(d[25]), "+f"(d[26]), "+f"(d[27]), "+f"(d[28]), "+f"(d[29]), "+f"(d[30]), "+f"(d[31]), "+f"(d[32]), "+f"(d[33]), "+f"(d[34]), "+f"(d[35]), "+f"(d[36]), "+f"(d[37]), "+f"(d[38]), "+f"(d[39]), "+f"(d[40]), "+f"(d[41]), "+f"(d[42]), "+f"(d[43]), "+f"(d[44]), "+f"(d[45]), "+f"(d[46]), "+f"(d[47]), "+f"(d[48]), "+f"(d[49]), "+f"(d[50]), "+f"(d[51]), "+f"(d[52]), "+f"(d[53]), "+f"(d[54]), "+f"(d[55]), "+f"(d[56]), "+f"(d[57]), "+f"(d[58]), "+f"(d[59]), "+f"(d[60]), "+f"(d[61]), "+f"(d[62]), "+f"(d[63]), "+f"(d[64]), "+f"(d[65]), "+f"(d[66]), "+f"(d[67]), "+f"(d[68]), "+f"(d[69]), "+f"(d[70]), "+f"(d[71]), "+f"(d[72]), "+f"(d[73]), "+f"(d[74]), "+f"(d[75]), "+f"(d[76]), "+f"(d[77]), "+f"(d[78]), "+f"(d[79]), "+f"(d[80]), "+f"(d[81]), "+f"(d[82]), "+f"(d[83]), "+f"(d[84]), "+f"(d[85]), "+f"(d[86]), "+f"(d[87]), "+f"(d[88]), "+f"(d[89]), "+f"(d[90]), "+f"(d[91]), "+f"(d[92]), "+f"(d[93]), "+f"(d[94]), "+f"(d[95]), "+f"(d[96]), "+f"(d[97]), "+f"(d[98]), "+f"(d[99]), "+f"(d[100]), "+f"(d[101]), "+f"(d[102]), "+f"(d[103]), "+f"(d[104]), "+f"(d[105]), "+f"(d[106]), "+f"(d[107])
      : "l"(da), "l"(db), "r"(sd), "n"(TB), "n"(AOFF), "n"(BOFF));
}

template<int TB, int AOFF, int BOFF> __device__ __forceinline__ void wgmma_ss_n64(float (&d)[32], uint64_t da, uint64_t db, int sd) {
    asm volatile("{\n.reg .pred p;\n.reg .b64 ta, tb;\nsetp.ne.b32 p, %34, 0;\nadd.s64 ta, %32, %36;\nadd.s64 tb, %33, %37;\n"
      "wgmma.mma_async.sync.aligned.m64n64k16.f32.bf16.bf16 {%0, %1, %2, %3, %4, %5, %6, %7, %8, %9, %10, %11, %12, %13, %14, %15, %16, %17, %18, %19, %20, %21, %22, %23, %24, %25, %26, %27, %28, %29, %30, %31}, ta, tb, p, 1, 1, 0, %35;\n}\n"
      : "+f"(d[0]), "+f"(d[1]), "+f"(d[2]), "+f"(d[3]), "+f"(d[4]), "+f"(d[5]), "+f"(d[6]), "+f"(d[7]), "+f"(d[8]), "+f"(d[9]), "+f"(d[10]), "+f"(d[11]), "+f"(d[12]), "+f"(d[13]), "+f"(d[14]), "+f"(d[15]), "+f"(d[16]), "+f"(d[17]), "+f"(d[18]), "+f"(d[19]), "+f"(d[20]), "+f"(d[21]), "+f"(d[22]), "+f"(d[23]), "+f"(d[24]), "+f"(d[25]), "+f"(d[26]), "+f"(d[27]), "+f"(d[28]), "+f"(d[29]), "+f"(d[30]), "+f"(d[31])
      : "l"(da), "l"(db), "r"(sd), "n"(TB), "n"(AOFF), "n"(BOFF));
}

template<int TB, int AOFF, int BOFF> __device__ __forceinline__ void wgmma_ss_n128(float (&d)[64], uint64_t da, uint64_t db, int sd) {
    asm volatile("{\n.reg .pred p;\n.reg .b64 ta, tb;\nsetp.ne.b32 p, %66, 0;\nadd.s64 ta, %64, %68;\nadd.s64 tb, %65, %69;\n"
      "wgmma.mma_async.sync.aligned.m64n128k16.f32.bf16.bf16 {%0, %1, %2, %3, %4, %5, %6, %7, %8, %9, %10, %11, %12, %13, %14, %15, %16, %17, %18, %19, %20, %21, %22, %23, %24, %25, %26, %27, %28, %29, %30, %31, %32, %33, %34, %35, %36, %37, %38, %39, %40, %41, %42, %43, %44, %45, %46, %47, %48, %49, %50, %51, %52, %53, %54, %55, %56, %57, %58, %59, %60, %61, %62, %63}, ta, tb, p, 1, 1, 0, %67;\n}\n"
      : "+f"(d[0]), "+f"(d[1]), "+f"(d[2]), "+f"(d[3]), "+f"(d[4]), "+f"(d[5]), "+f"(d[6]), "+f"(d[7]), "+f"(d[8]), "+f"(d[9]), "+f"(d[10]), "+f"(d[11]), "+f"(d[12]), "+f"(d[13]), "+f"(d[14]), "+f"(d[15]), "+f"(d[16]), "+f"(d[17]), "+f"(d[18]), "+f"(d[19]), "+f"(d[20]), "+f"(d[21]), "+f"(d[22]), "+f"(d[23]), "+f"(d[24]), "+f"(d[25]), "+f"(d[26]), "+f"(d[27]), "+f"(d[28]), "+f"(d[29]), "+f"(d[30]), "+f"(d[31]), "+f"(d[32]), "+f"(d[33]), "+f"(d[34]), "+f"(d[35]), "+f"(d[36]), "+f"(d[37]), "+f"(d[38]), "+f"(d[39]), "+f"(d[40]), "+f"(d[41]), "+f"(d[42]), "+f"(d[43]), "+f"(d[44]), "+f"(d[45]), "+f"(d[46]), "+f"(d[47]), "+f"(d[48]), "+f"(d[49]), "+f"(d[50]), "+f"(d[51]), "+f"(d[52]), "+f"(d[53]), "+f"(d[54]), "+f"(d[55]), "+f"(d[56]), "+f"(d[57]), "+f"(d[58]), "+f"(d[59]), "+f"(d[60]), "+f"(d[61]), "+f"(d[62]), "+f"(d[63])
      : "l"(da), "l"(db), "r"(sd), "n"(TB), "n"(AOFF), "n"(BOFF));
}

template<int TB, int BOFF> __device__ __forceinline__ void wgmma_rs_n64(float (&d)[32], uint32_t a0, uint32_t a1, uint32_t a2, uint32_t a3, uint64_t db, int sd) {
    asm volatile("{\n.reg .pred p;\n.reg .b64 tb;\nsetp.ne.b32 p, %37, 0;\nadd.s64 tb, %36, %39;\n"
      "wgmma.mma_async.sync.aligned.m64n64k16.f32.bf16.bf16 {%0, %1, %2, %3, %4, %5, %6, %7, %8, %9, %10, %11, %12, %13, %14, %15, %16, %17, %18, %19, %20, %21, %22, %23, %24, %25, %26, %27, %28, %29, %30, %31}, {%32, %33, %34, %35}, tb, p, 1, 1, %38;\n}\n"
      : "+f"(d[0]), "+f"(d[1]), "+f"(d[2]), "+f"(d[3]), "+f"(d[4]), "+f"(d[5]), "+f"(d[6]), "+f"(d[7]), "+f"(d[8]), "+f"(d[9]), "+f"(d[10]), "+f"(d[11]), "+f"(d[12]), "+f"(d[13]), "+f"(d[14]), "+f"(d[15]), "+f"(d[16]), "+f"(d[17]), "+f"(d[18]), "+f"(d[19]), "+f"(d[20]), "+f"(d[21]), "+f"(d[22]), "+f"(d[23]), "+f"(d[24]), "+f"(d[25]), "+f"(d[26]), "+f"(d[27]), "+f"(d[28]), "+f"(d[29]), "+f"(d[30]), "+f"(d[31])
      : "r"(a0), "r"(a1), "r"(a2), "r"(a3), "l"(db), "r"(sd), "n"(TB), "n"(BOFF));
}

template<int TB, int BOFF> __device__ __forceinline__ void wgmma_rs_n24(float (&d)[12], uint32_t a0, uint32_t a1, uint32_t a2, uint32_t a3, uint64_t db, int sd) {
    asm volatile("{\n.reg .pred p;\n.reg .b64 tb;\nsetp.ne.b32 p, %17, 0;\nadd.s64 tb, %16, %19;\n"
      "wgmma.mma_async.sync.aligned.m64n24k16.f32.bf16.bf16 {%0, %1, %2, %3, %4, %5, %6, %7, %8, %9, %10, %11}, {%12, %13, %14, %15}, tb, p, 1, 1, %18;\n}\n"
      : "+f"(d[0]), "+f"(d[1]), "+f"(d[2]), "+f"(d[3]), "+f"(d[4]), "+f"(d[5]), "+f"(d[6]), "+f"(d[7]), "+f"(d[8]), "+f"(d[9]), "+f"(d[10]), "+f"(d[11])
      : "r"(a0), "r"(a1), "r"(a2), "r"(a3), "l"(db), "r"(sd), "n"(TB), "n"(BOFF));
}

template<int TB, int BOFF> __device__ __forceinline__ void wgmma_rs_n144(float (&d)[72], uint32_t a0, uint32_t a1, uint32_t a2, uint32_t a3, uint64_t db, int sd) {
    asm volatile("{\n.reg .pred p;\n.reg .b64 tb;\nsetp.ne.b32 p, %77, 0;\nadd.s64 tb, %76, %79;\n"
      "wgmma.mma_async.sync.aligned.m64n144k16.f32.bf16.bf16 {%0, %1, %2, %3, %4, %5, %6, %7, %8, %9, %10, %11, %12, %13, %14, %15, %16, %17, %18, %19, %20, %21, %22, %23, %24, %25, %26, %27, %28, %29, %30, %31, %32, %33, %34, %35, %36, %37, %38, %39, %40, %41, %42, %43, %44, %45, %46, %47, %48, %49, %50, %51, %52, %53, %54, %55, %56, %57, %58, %59, %60, %61, %62, %63, %64, %65, %66, %67, %68, %69, %70, %71}, {%72, %73, %74, %75}, tb, p, 1, 1, %78;\n}\n"
      : "+f"(d[0]), "+f"(d[1]), "+f"(d[2]), "+f"(d[3]), "+f"(d[4]), "+f"(d[5]), "+f"(d[6]), "+f"(d[7]), "+f"(d[8]), "+f"(d[9]), "+f"(d[10]), "+f"(d[11]), "+f"(d[12]), "+f"(d[13]), "+f"(d[14]), "+f"(d[15]), "+f"(d[16]), "+f"(d[17]), "+f"(d[18]), "+f"(d[19]), "+f"(d[20]), "+f"(d[21]), "+f"(d[22]), "+f"(d[23]), "+f"(d[24]), "+f"(d[25]), "+f"(d[26]), "+f"(d[27]), "+f"(d[28]), "+f"(d[29]), "+f"(d[30]), "+f"(d[31]), "+f"(d[32]), "+f"(d[33]), "+f"(d[34]), "+f"(d[35]), "+f"(d[36]), "+f"(d[37]), "+f"(d[38]), "+f"(d[39]), "+f"(d[40]), "+f"(d[41]), "+f"(d[42]), "+f"(d[43]), "+f"(d[44]), "+f"(d[45]), "+f"(d[46]), "+f"(d[47]), "+f"(d[48]), "+f"(d[49]), "+f"(d[50]), "+f"(d[51]), "+f"(d[52]), "+f"(d[53]), "+f"(d[54]), "+f"(d[55]), "+f"(d[56]), "+f"(d[57]), "+f"(d[58]), "+f"(d[59]), "+f"(d[60]), "+f"(d[61]), "+f"(d[62]), "+f"(d[63]), "+f"(d[64]), "+f"(d[65]), "+f"(d[66]), "+f"(d[67]), "+f"(d[68]), "+f"(d[69]), "+f"(d[70]), "+f"(d[71])
      : "r"(a0), "r"(a1), "r"(a2), "r"(a3), "l"(db), "r"(sd), "n"(TB), "n"(BOFF));
}

constexpr int K1_XN_BYTES = 16 * 9216;
constexpr int K1_OFF_RING = K1_XN_BYTES;
constexpr int K1_OFF_BIAS = K1_OFF_RING + 10 * 8192;
constexpr int K1_OFF_BAR = K1_OFF_BIAS + 576 * 2;
constexpr int K1_SMEM = K1_OFF_BAR + 768;
constexpr float QSCALE = 0.23570226039551584f * 1.4426950408889634f;

struct K1Ctx {
    uint32_t full0;
    uint32_t rel_addr;
    uint64_t descA, descB;
    uint32_t phase;
    __device__ __forceinline__ void begin_stage(int s) {
        mbar_wait(full0 + s * 8, phase);
        wg_fence();
    }
    __device__ __forceinline__ void release(int s) {
        if (rel_addr) asm volatile("mbarrier.arrive.shared::cluster.b64 _, [%0];" ::"r"(rel_addr + s * 8) : "memory");
    }
    __device__ __forceinline__ void end_stage(int s) {
        wg_commit();
        wg_wait<1>();
        release(s == 0 ? 8 : s - 1);
    }
};

__host__ __device__ constexpr int a_off(int ks) { return ((ks >> 2) * 1024 + (ks & 3) * 32) >> 4; }

template <int V> struct IC { static constexpr int value = V; };
template <int I, int N, class F> __device__ __forceinline__ void static_for(F&& f) {
    if constexpr (I < N) { f(IC<I>{}); static_for<I + 1, N>(f); }
}

template <bool A_RS, bool B_RS, class Epi>
__device__ __forceinline__ void tile_pair(K1Ctx& c, float (&accA)[32], float (&accB)[32], uint32_t (&h)[144], Epi&& epi) {
    static_for<0, 9>([&](auto sc) {
        constexpr int s = decltype(sc)::value;
        c.begin_stage(s);
        static_for<0, 8>([&](auto tc) {
            constexpr int kk = s * 8 + decltype(tc)::value, ks = kk % 36;
            constexpr int bo = (ks * 2048) >> 4;
            if constexpr (kk < 36) {
                if constexpr (A_RS) wgmma_rs_n64<1, bo>(accA, h[ks * 4], h[ks * 4 + 1], h[ks * 4 + 2], h[ks * 4 + 3], c.descB, ks != 0);
                else wgmma_ss_n64<1, a_off(ks), bo>(accA, c.descA, c.descB, ks != 0);
            } else {
                if constexpr (B_RS) wgmma_rs_n64<1, bo>(accB, h[ks * 4], h[ks * 4 + 1], h[ks * 4 + 2], h[ks * 4 + 3], c.descB, ks != 0);
                else wgmma_ss_n64<1, a_off(ks), bo>(accB, c.descA, c.descB, ks != 0);
            }
        });
        c.end_stage(s);
        epi(sc);
    });
    c.phase ^= 1;
}

template <int B0, int NB, int HOFF>
__device__ __forceinline__ void gelu_blocks(const float (&acc)[32], uint32_t (&h)[144], const uint32_t (&bq)[8]) {
#pragma unroll
    for (int b = B0; b < B0 + NB; b++) {
        const float b0 = bf_lo(bq[b]), b1 = bf_hi(bq[b]);
        h[HOFF + b * 2 + 0] = pack_bf16(gelu2(acc[b * 4 + 0] + b0), gelu2(acc[b * 4 + 1] + b1));
        h[HOFF + b * 2 + 1] = pack_bf16(gelu2(acc[b * 4 + 2] + b0), gelu2(acc[b * 4 + 3] + b1));
    }
}
__device__ __forceinline__ void load_bias(uint32_t (&bq)[8], uint32_t addr) {
    asm volatile("ld.shared.v4.u32 {%0, %1, %2, %3}, [%4];" : "=r"(bq[0]), "=r"(bq[1]), "=r"(bq[2]), "=r"(bq[3]) : "r"(addr));
    asm volatile("ld.shared.v4.u32 {%0, %1, %2, %3}, [%4 + 16];" : "=r"(bq[4]), "=r"(bq[5]), "=r"(bq[6]), "=r"(bq[7]) : "r"(addr));
}
template <int S> __device__ __forceinline__ void store_part(const float (&o)[32], uint4* p) {
    uint4 v;
    v.x = pack_bf16(o[S * 8 + 0], o[S * 8 + 1]); v.y = pack_bf16(o[S * 8 + 2], o[S * 8 + 3]);
    v.z = pack_bf16(o[S * 8 + 4], o[S * 8 + 5]); v.w = pack_bf16(o[S * 8 + 6], o[S * 8 + 7]);
    p[S * 256] = v;
}

constexpr int NCHUNK = 16;
constexpr int CHUNK_BYTES = KV_HEAD_BYTES / NCHUNK;
constexpr int SM_Q = 0;
constexpr int SM_KV = 32768;
constexpr int WO_PIECE = WO_TILE_BYTES / 9;
__host__ __device__ constexpr int sm_wo(int i) { return i == 0 ? 210944 : (i == 1 ? 0 : SM_KV + (i - 2) * WO_PIECE); }
constexpr int SM_EXCH = SM_KV + 7 * WO_PIECE;
constexpr int SM_RED = SM_KV + KV_HEAD_BYTES;

__device__ __forceinline__ float exp2_fixed(float y) {
    const float u = __uint_as_float(__float_as_uint(y) & 0xFF807FFFu) - 512.02545f;
    float t = fmaf(u, 0.019497588f, 0.114550486f);
    t = fmaf(t, u, -0.29839927f);
    return fmaf(t, u, y);
}
__device__ __forceinline__ uint32_t pack_fixed(float lo, float hi) { return __byte_perm(__float_as_uint(lo), __float_as_uint(hi), 0x6521); }

#define POLY_MODE 1
__device__ __forceinline__ uint32_t hfma2_bf16(uint32_t a, uint32_t b, uint32_t c) {
    uint32_t r;
    asm("fma.rn.bf16x2 %0, %1, %2, %3;" : "=r"(r) : "r"(a), "r"(b), "r"(c));
    return r;
}
__device__ __forceinline__ uint32_t exp2_packed(float y0, float y1, uint32_t one2) {
    const uint32_t w = pack_fixed(y0, y1);
    uint32_t m;
    asm("lop3.b32 %0, %1, 0x007F007F, %2, 0xEA;" : "=r"(m) : "r"(w), "r"(one2));
    const uint32_t d = hfma2_bf16(m, 0x3EF93EF9u, 0xBF38BF38u);
    const uint32_t e = hfma2_bf16(d, d, 0xBD71BD71u);
    return hfma2_bf16(w, e, w);
}
template <int NB>
__device__ __forceinline__ void softmax_fast(const float (&s)[NB * 4], uint32_t (&p)[NB * 2], uint32_t one2) {
#pragma unroll
    for (int b = 0; b < NB; b++) {
        if ((POLY_MASK >> (b & 7)) & 1) {
            p[b * 2 + 0] = exp2_packed(s[b * 4 + 0], s[b * 4 + 1], one2);
            p[b * 2 + 1] = exp2_packed(s[b * 4 + 2], s[b * 4 + 3], one2);
        } else {
            p[b * 2 + 0] = pack_bf16(ex2(s[b * 4 + 0]), ex2(s[b * 4 + 1]));
            p[b * 2 + 1] = pack_bf16(ex2(s[b * 4 + 2]), ex2(s[b * 4 + 3]));
        }
    }
}

constexpr int KV_TILE = CHUNK_BYTES / 16;
template <int OFF> __device__ __forceinline__ void issue_qk(float (&s)[64], uint64_t qd, uint64_t kd) {
    wgmma_ss_n128<0, 0, OFF + (8 << 16)>(s, qd, kd, 0);
    wgmma_ss_n128<0, 16, OFF + 32>(s, qd, kd, 1);
}
template <int OFF> __device__ __forceinline__ void issue_pv(float (&o)[12], const uint32_t (&p)[32], uint64_t vd) {
    static_for<0, 8>([&](auto kc) {
        constexpr int k = decltype(kc)::value;
        wgmma_rs_n24<1, OFF + k * (2 * KV_GROUP_BYTES / 16)>(o, p[k * 4], p[k * 4 + 1], p[k * 4 + 2], p[k * 4 + 3], vd, 1);
    });
}
__device__ __forceinline__ void store_o(float (&o)[12], int rt, int head, int wq, int lane) {
    const int g = lane >> 2, q = lane & 3;
    const float i0 = __fdividef(1.0f, __shfl_sync(~0u, o[8], lane | 3)), i1 = __fdividef(1.0f, __shfl_sync(~0u, o[10], lane | 3));
#pragma unroll
    for (int i = 0; i < 3; i++) {
        const int pc = head * 9 + (i < 2 ? i * 4 + q : 8);
        uint32_t* op = g_O + (((rt * 36 + (pc >> 3)) * 128 + wq * 32 + g * 4 + (pc & 3)) * 4 + ((pc >> 2) & 1) * 2);
        if (i < 2 || q == 2) *reinterpret_cast<uint2*>(op) = make_uint2(pack_bf16(o[i * 4] * i0, o[i * 4 + 1] * i0), pack_bf16(o[i * 4 + 2] * i1, o[i * 4 + 3] * i1));
    }
#pragma unroll
    for (int i = 0; i < 12; i++) o[i] = 0.f;
}
__device__ __forceinline__ void mbar_arrive(uint32_t b) { asm volatile("mbarrier.arrive.shared::cta.b64 _, [%0];" ::"r"(b) : "memory"); }
__device__ __forceinline__ void mbar_wait_sleep(uint32_t b, uint32_t ns) {
    uint32_t ok, spins = 0;
    while (true) {
        asm volatile("{\n.reg .pred p;\nmbarrier.try_wait.parity.shared::cta.b64 p, [%1], 0;\nselp.u32 %0, 1, 0, p;\n}\n" : "=r"(ok) : "r"(b) : "memory");
        if (ok) break;
        __nanosleep(ns);
        if (++spins > (1u << 21)) __trap();
    }
}
__device__ __forceinline__ void flag_signal(unsigned int* f) {
    __threadfence();
    atomicAdd(f, 1u);
}
__device__ __forceinline__ void flag_wait(const unsigned int* f, unsigned int target, unsigned int sleep_ns) {
    uint32_t v, spins = 0;
    while (true) {
        asm volatile("ld.acquire.gpu.global.u32 %0, [%1];" : "=r"(v) : "l"(f) : "memory");
        if (v >= target) break;
        if (sleep_ns) __nanosleep(sleep_ns);
        if (++spins > (1u << 21)) __trap();
    }
}
__device__ __forceinline__ uint32_t hadd2_bf16(uint32_t a, uint32_t b) {
    uint32_t r;
    asm("add.rn.bf16x2 %0, %1, %2;" : "=r"(r) : "r"(a), "r"(b));
    return r;
}
__device__ __forceinline__ uint4 hadd8_bf16(const uint4 a, const uint4 b) {
    return make_uint4(hadd2_bf16(a.x, b.x), hadd2_bf16(a.y, b.y), hadd2_bf16(a.z, b.z), hadd2_bf16(a.w, b.w));
}
__device__ __forceinline__ float sumsq2(uint32_t w) { return fmaf(bf_lo(w), bf_lo(w), bf_hi(w) * bf_hi(w)); }
__device__ __forceinline__ float sumsq8(const uint4 v) { return (sumsq2(v.x) + sumsq2(v.y)) + (sumsq2(v.z) + sumsq2(v.w)); }

enum { B_FULL = 0, B_EMPTY = 9, B_BASE = 18, B_XNDEAD = 19, B_QRDY = 20, B_FFN = 21, B_X = 22, B_KV = 38, B_FREE = 54, B_WO = 62, B_RED = 71, B_END = 77 };

__global__ void __cluster_dims__(2, 1, 1) __launch_bounds__(384, 1)
fused_kernel(const __grid_constant__ CUtensorMap tmX, const __grid_constant__ CUtensorMap tmQ3, const __grid_constant__ CUtensorMap tmQ1,
          const __grid_constant__ CUtensorMap tm1, const __grid_constant__ CUtensorMap tm2, const __grid_constant__ CUtensorMap tmP, const __nv_bfloat16* __restrict__ b1,
          const __nv_bfloat16* __restrict__ wo, const __nv_bfloat16* __restrict__ x, const __nv_bfloat16* __restrict__ b2,
          __nv_bfloat16* __restrict__ out, const uint64_t zero) {
    extern __shared__ __align__(1024) uint8_t smem[];
    const uint32_t sb = s2u(smem);
    const int tid = threadIdx.x, lane = tid & 31;
    const int warp = __shfl_sync(~0u, tid >> 5, 0);
    const uint32_t rank = blockIdx.x & 1;
    const int cl = blockIdx.x >> 1;
    const int rb = (cl & 7) * 2 + rank;
    const int j = cl >> 3;
    const uint32_t bar0 = sb + K1_OFF_BAR;
    const uint32_t full0 = bar0 + B_FULL * 8, empty0 = bar0 + B_EMPTY * 8, xbar0 = bar0 + B_X * 8;
    const int head = blockIdx.x >> 2, quarter = blockIdx.x & 3;
    const int rt = quarter * 8 + (head >> 2), ct = head & 3;
    volatile uint32_t* slow_flag = reinterpret_cast<volatile uint32_t*>(smem + K1_OFF_BAR + B_END * 8);

    if (warp < 8) {
        PROF(0);
        PROFT(48);
        if (lane == 0) {
            mbar_init(xbar0 + warp * 16, 1);
            mbar_init(xbar0 + warp * 16 + 8, 1);
            fence_barrier_init();
            mbar_expect(xbar0 + warp * 16, 9216);
            tma3d(sb + warp * 2 * 9216, &tmX, 0, rb * 128 + warp * 16, 0, xbar0 + warp * 16);
            mbar_expect(xbar0 + warp * 16 + 8, 9216);
            tma3d(sb + (warp * 2 + 1) * 9216, &tmX, 0, rb * 128 + warp * 16 + 8, 0, xbar0 + warp * 16 + 8);
        }
        __syncwarp();
        cluster_arrive();
        PROF(22);
        reg_alloc<240>();
        PROF(23);
#pragma unroll 1
        for (int p = 0; p < 4; p++) {
            mbar_wait(xbar0 + warp * 16 + (p >> 1) * 8, 0);
            PROF(24 + p);
            uint4* row = reinterpret_cast<uint4*>(smem + (warp * 2 + (p >> 1)) * 9216 + (p & 1) * 512 + lane * 16);
            float f[72];
#pragma unroll
            for (int i = 0; i < 9; i++) {
                const uint4 v = row[i * 64];
                f[i * 8 + 0] = bf_lo(v.x); f[i * 8 + 1] = bf_hi(v.x); f[i * 8 + 2] = bf_lo(v.y); f[i * 8 + 3] = bf_hi(v.y);
                f[i * 8 + 4] = bf_lo(v.z); f[i * 8 + 5] = bf_hi(v.z); f[i * 8 + 6] = bf_lo(v.w); f[i * 8 + 7] = bf_hi(v.w);
            }
            float s0 = 0.f, s1 = 0.f, s2 = 0.f, s3 = 0.f;
#pragma unroll
            for (int i = 0; i < 72; i += 4) { s0 += f[i]; s1 += f[i + 1]; s2 += f[i + 2]; s3 += f[i + 3]; }
            float sm = (s0 + s1) + (s2 + s3);
            sm += __shfl_xor_sync(~0u, sm, 1); sm += __shfl_xor_sync(~0u, sm, 2); sm += __shfl_xor_sync(~0u, sm, 4);
            const float mean = sm * (1.0f / DM);
            s0 = s1 = s2 = s3 = 0.f;
#pragma unroll
            for (int i = 0; i < 72; i += 4) {
                f[i] -= mean; f[i + 1] -= mean; f[i + 2] -= mean; f[i + 3] -= mean;
                s0 = fmaf(f[i], f[i], s0); s1 = fmaf(f[i + 1], f[i + 1], s1);
                s2 = fmaf(f[i + 2], f[i + 2], s2); s3 = fmaf(f[i + 3], f[i + 3], s3);
            }
            float sq = (s0 + s1) + (s2 + s3);
            sq += __shfl_xor_sync(~0u, sq, 1); sq += __shfl_xor_sync(~0u, sq, 2); sq += __shfl_xor_sync(~0u, sq, 4);
            const float rstd = rsqrtf(sq * (1.0f / DM) + 1e-5f);
#pragma unroll
            for (int i = 0; i < 9; i++) {
                uint4 o;
                o.x = pack_bf16(f[i * 8 + 0] * rstd, f[i * 8 + 1] * rstd);
                o.y = pack_bf16(f[i * 8 + 2] * rstd, f[i * 8 + 3] * rstd);
                o.z = pack_bf16(f[i * 8 + 4] * rstd, f[i * 8 + 5] * rstd);
                o.w = pack_bf16(f[i * 8 + 6] * rstd, f[i * 8 + 7] * rstd);
                row[i * 64] = o;
            }
        }
        PROF(28);
        const int wg = warp >> 2, wq = warp & 3;
        fence_proxy_async();
        named_bar_sync(1 + wg, 128);
        cluster_wait();
        PROF(1);

        const int g = lane >> 2, q = lane & 3;
        K1Ctx c;
        c.full0 = full0;
        c.rel_addr = 0;
        c.descA = mk_desc(zero, sb + wg * 8 * 9216, 16, 9216, 1);
        c.descB = mk_desc(zero, sb + K1_OFF_RING, 2048, 1024, 1);
        c.phase = 0;
        uint32_t biasq = sb + K1_OFF_BIAS + q * 32;
        uint32_t bq[8];

        uint32_t h[144];
        float accA[32], accB[32];
        {
            float accQ[108];
            uint32_t rel = 0;
            if (lane == 0 && wq < 2) asm("mapa.shared::cluster.u32 %0, %1, %2;" : "=r"(rel) : "r"(empty0), "r"(wq));
#pragma unroll 1
            for (int r = 0; r < 2; r++) {
                const uint64_t dae = c.descA + (r ? a_off(18) : 0), dao = c.descA + (r ? a_off(20) : a_off(2));
                static_for<0, 9>([&](auto sc) {
                    constexpr int s = decltype(sc)::value;
                    c.begin_stage(s);
                    wgmma_ss_n216<1, (s >> 1) * 64, ((2 * s) % 9) * 512>(accQ, (s & 1) ? dao : dae, c.descB, (r | s) != 0);
                    wgmma_ss_n216<1, (s >> 1) * 64 + 2, ((2 * s + 1) % 9) * 512>(accQ, (s & 1) ? dao : dae, c.descB, 1);
                    c.end_stage(s);
                    c.rel_addr = rel;
                });
                c.phase ^= 1;
            }
            PROF(2);
            uint32_t rel9[9];
#pragma unroll
            for (int i9 = 0; i9 < 9; i9++) {
                const int p = 4 * i9 + q, hh = (p * 57) >> 9, r = p - 9 * hh;
                rel9[i9] = hh * KV_HEAD_BYTES + (r < 8 ? (r >> 2) * 128 + (r & 3) * 4 : 0);
            }
            uint32_t gb = 0, o2 = 0;
            float scl0 = 1.f, scl1 = 1.f;
            tile_pair<false, false>(c, accA, accB, h, [&](auto sc) {
                constexpr int s = decltype(sc)::value;
                if constexpr (s == 0) reg_fence(accQ);
                if constexpr (s < 6) {
                    constexpr int grp = s / 2, part = s % 2;
                    if constexpr (part == 0) {
                        const int G = 3 * j + grp, type = G >> 3;
                        gb = (G & 7) * 4 * KV_HEAD_BYTES + (rb * 16 + warp * 2) * KV_GROUP_BYTES + g * 16 + (type == 0 ? Q_OFFSET : (type == 2 ? 256 : 0));
                        o2 = type == 0 ? 256 : (type == 2 ? 264 : 512);
                        scl0 = type == 0 ? QSCALE : ((type == 1 && ((POLY_MASK >> (wq * 2)) & 1)) ? 2.f : 1.f);
                        scl1 = type == 0 ? QSCALE : ((type == 1 && ((POLY_MASK >> (wq * 2 + 1)) & 1)) ? 2.f : 1.f);
                    }
#pragma unroll
                    for (int i9 = part * 5; i9 < (part ? 9 : 5); i9++) {
                        const int b = grp * 9 + i9;
                        uint32_t off = gb + rel9[i9];
                        if (i9 >= 2 && (i9 & 1) == 0) off += (q == i9 / 2 - 1) ? o2 : 0;
                        *reinterpret_cast<uint32_t*>(g_QKV + off) = pack_bf16(accQ[b * 4] * scl0, accQ[b * 4 + 1] * scl0);
                        *reinterpret_cast<uint32_t*>(g_QKV + off + KV_GROUP_BYTES) = pack_bf16(accQ[b * 4 + 2] * scl1, accQ[b * 4 + 3] * scl1);
                    }
                    if constexpr (s == 5) asm volatile("bar.arrive 3, 352;" ::: "memory");
                }
                if constexpr (s == 4) { named_bar_sync(4, 352); load_bias(bq, biasq); }
                if constexpr (s == 5) reg_fence(accA);
                if constexpr (s >= 5) gelu_blocks<(s - 5) * 2, 2, 96>(accA, h, bq);
                if constexpr (s == 8) load_bias(bq, biasq + 128);
            });
        }
        PROF(3);
#pragma unroll
        for (int i = 32; i < 96; i++) asm volatile("mov.u32 %0, 0;" : "=r"(h[i]));
#pragma unroll 1
        for (int p = 1; p < 4; p++) {
            biasq += 256;
            tile_pair<false, false>(c, accA, accB, h, [&](auto sc) {
                constexpr int s = decltype(sc)::value;
                if constexpr (s == 0) {
                    reg_fence(accB);
#pragma unroll
                    for (int i = 0; i < 80; i++) h[i] = h[i + 32];
                }
                if constexpr (s < 4) gelu_blocks<s * 2, 2, 80>(accB, h, bq);
                if constexpr (s == 4) load_bias(bq, biasq);
                if constexpr (s == 5) reg_fence(accA);
                if constexpr (s >= 5) gelu_blocks<(s - 5) * 2, 2, 96>(accA, h, bq);
                if constexpr (s == 8) load_bias(bq, biasq + 128);
            });
        }
        PROF(4);
        tile_pair<false, true>(c, accA, accB, h, [&](auto sc) {
            constexpr int s = decltype(sc)::value;
            if constexpr (s == 0) reg_fence(accB);
            if constexpr (s < 4) gelu_blocks<s * 2, 2, 112>(accB, h, bq);
            if constexpr (s == 4) load_bias(bq, biasq + 256);
            if constexpr (s == 5) { reg_fence(accA); if (tid == wg * 128) mbar_arrive(bar0 + B_XNDEAD * 8); }
            if constexpr (s == 5 || s == 6) gelu_blocks<(s - 5) * 3, 3, 128>(accA, h, bq);
            if constexpr (s == 7) gelu_blocks<6, 2, 128>(accA, h, bq);
            if constexpr (s == 3 || s == 7) reg_fence(h);
        });
        PROF(5);
        uint4* pout = g_part + j * SLAB + rb * 36 * 256 + tid;
#pragma unroll 1
        for (int p = 0; p < 4; p++) {
            tile_pair<true, true>(c, accA, accB, h, [&](auto sc) {
                constexpr int s = decltype(sc)::value;
                if constexpr (s == 0) reg_fence(accB);
                if constexpr (s < 4) store_part<s>(accB, pout);
                if constexpr (s == 5) reg_fence(accA);
                if constexpr (s >= 5) store_part<s - 5>(accA, pout + 1024);
            });
            pout += 2048;
            PROF(6 + p);
        }
        wg_wait<0>();
        c.release(8);
        reg_fence(accB);
        store_part<0>(accB, pout); store_part<1>(accB, pout); store_part<2>(accB, pout); store_part<3>(accB, pout);
        __syncwarp();
        if (lane == 0) mbar_arrive(bar0 + B_FFN * 8);
        PROF(10);
        PROFT(49);

        mbar_wait(bar0 + B_QRDY * 8, 0);
        const uint32_t slow = __any_sync(~0u, *slow_flag != 0);
        const uint64_t kd0 = mk_desc(zero, sb + SM_KV, 0, KV_GROUP_BYTES, 0);
        const uint64_t vd0 = mk_desc(zero, sb + SM_KV + 256, KV_GROUP_BYTES, 128, 0);
        const uint64_t qd0 = mk_desc(zero, sb + SM_Q + wg * 4096, 128, 512, 0);
        const uint32_t kvbar = bar0 + B_KV * 8;
        float o[12];
#pragma unroll
        for (int i = 0; i < 12; i++) o[i] = 0.f;
        PROF(16);
        PROFT(50);
        if (!slow) {
            const uint32_t one2 = 0x3F803F80u + (uint32_t)zero;
            float s0[64], s1[64];
            uint32_t p0[32], p1[32];
            mbar_wait(kvbar, 0);
            reg_fence(o);
            wg_fence();
            issue_qk<0>(s0, qd0, kd0);
            wg_commit();
            mbar_wait(kvbar + 8, 0);
            wg_fence();
            issue_qk<KV_TILE>(s1, qd0, kd0);
            wg_commit();
            uint64_t qd = qd0;
            const uint32_t fre = (tid == wg * 128) ? bar0 + B_FREE * 8 - 8 : 0;
#pragma unroll 1
            for (int pass = 0; pass < 4; pass++) {
                uint64_t vd = vd0, kdn = kd0 + 2 * KV_TILE;
                uint32_t bn = kvbar + 16;
#pragma unroll 1
                for (int it = 0; it < 8; it++) {
                    if (it == 7) { kdn = kd0; bn = kvbar; qd += 512; }
                    wg_wait<1>();
                    reg_fence(s0);
                    if (pass == 3 && it > 0 && fre) mbar_arrive(fre + it * 8);
                    softmax_fast<16>(s0, p0, one2);
                    reg_fence(p0);
                    if (it == 0 && pass != 0) {
                        wg_wait<0>();
                        reg_fence(o);
                        store_o(o, quarter * 8 + pass * 2 - 2 + wg, head, wq, lane);
                        reg_fence(o);
                    }
                    mbar_wait(bn, 0);
                    wg_fence();
                    issue_pv<0>(o, p0, vd);
                    issue_qk<0>(s0, qd, kdn);
                    wg_commit();
                    wg_wait<1>();
                    reg_fence(s1);
                    softmax_fast<16>(s1, p1, one2);
                    reg_fence(p1);
                    mbar_wait(bn + 8, 0);
                    wg_fence();
                    issue_pv<KV_TILE>(o, p1, vd);
                    issue_qk<KV_TILE>(s1, qd, kdn);
                    wg_commit();
                    vd += 2 * KV_TILE; kdn += 2 * KV_TILE; bn += 16;
                }
                if (pass == 0) PROF(17);
            }
            wg_wait<0>();
            reg_fence(o);
            reg_fence(s0);
            reg_fence(s1);
            store_o(o, quarter * 8 + 6 + wg, head, wq, lane);
        } else {
#pragma unroll 1
            for (int pass = 0; pass < 4; pass++) {
                float m0 = -INFINITY, m1 = -INFINITY;
                float s[64];
                uint32_t p[32];
#pragma unroll 1
                for (int t = 0; t < 16; t++) {
                    mbar_wait(kvbar + t * 8, 0);
                    wg_fence();
                    issue_qk<0>(s, qd0 + pass * 512, kd0 + t * KV_TILE);
                    wg_commit();
                    wg_wait<0>();
                    reg_fence(s);
                    float a0 = m0, a1 = m1;
#pragma unroll
                    for (int k = 0; k < 16; k++) {
                        if ((POLY_MASK >> (k & 7)) & 1) {
#pragma unroll
                            for (int i = 0; i < 4; i++) s[k * 4 + i] *= 0.5f;
                        }
                        a0 = fmaxf(a0, fmaxf(s[k * 4 + 0], s[k * 4 + 1]));
                        a1 = fmaxf(a1, fmaxf(s[k * 4 + 2], s[k * 4 + 3]));
                    }
                    a0 = fmaxf(a0, __shfl_xor_sync(~0u, a0, 1)); a1 = fmaxf(a1, __shfl_xor_sync(~0u, a1, 1));
                    a0 = fmaxf(a0, __shfl_xor_sync(~0u, a0, 2)); a1 = fmaxf(a1, __shfl_xor_sync(~0u, a1, 2));
                    const float r0 = ex2(m0 - a0), r1 = ex2(m1 - a1);
                    m0 = a0; m1 = a1;
#pragma unroll
                    for (int i = 0; i < 3; i++) { o[i * 4] *= r0; o[i * 4 + 1] *= r0; o[i * 4 + 2] *= r1; o[i * 4 + 3] *= r1; }
#pragma unroll
                    for (int k = 0; k < 16; k++) {
                        p[k * 2 + 0] = pack_bf16(ex2(s[k * 4 + 0] - m0), ex2(s[k * 4 + 1] - m0));
                        p[k * 2 + 1] = pack_bf16(ex2(s[k * 4 + 2] - m1), ex2(s[k * 4 + 3] - m1));
                    }
                    reg_fence(p);
                    reg_fence(o);
                    wg_fence();
                    issue_pv<0>(o, p, vd0 + t * KV_TILE);
                    wg_commit();
                    wg_wait<0>();
                    reg_fence(o);
                }
                store_o(o, quarter * 8 + pass * 2 + wg, head, wq, lane);
            }
            if (tid == wg * 128)
                for (int i = 0; i < 7; i++) mbar_arrive(bar0 + (B_FREE + i) * 8);
        }
        PROF(18);
        PROFT(51);

        named_bar_sync(5, 256);
        if (tid == 0) flag_signal(&g_flags.o_done[quarter]);
        mbar_wait(bar0 + B_BASE * 8, 0);
        const int t128 = tid & 127;
        float4 bs[9];
        {
            const float4* bp = g_base + ((rt >> 1) * 72 + ct * 18 + wg * 9) * 256 + (rt & 1) * 128 + t128;
#pragma unroll
            for (int i = 0; i < 9; i++) bs[i] = __ldcg(bp + i * 256);
        }
        if (tid == 0) flag_wait(&g_flags.o_done[quarter], 32, 0);
        named_bar_sync(5, 256);
        PROF(19);
        uint4 af[18];
        {
            const uint4* ap = reinterpret_cast<const uint4*>(g_O) + (rt * 36 + wg * 18) * 128 + t128;
#pragma unroll
            for (int k = 0; k < 18; k++) af[k] = __ldcg(ap + k * 128);
        }
        float acc[72];
        const uint64_t wd0 = mk_desc(zero, sb, 2304, 128, 0), wd1 = wd0 + wg * ((18 * 4608) >> 4);
#pragma unroll
        for (int i = 0; i < 5; i++) mbar_wait(bar0 + (B_WO + wg * 4 + i) * 8, 0);
        wg_fence();
        static_for<0, 18>([&](auto kc) {
            constexpr int k = decltype(kc)::value;
            if constexpr (k < 8) {
                constexpr int o0 = (sm_wo(k >> 2) + (k & 3) * 4608) >> 4, o1 = (SM_KV + (k + 10) * 4608) >> 4;
                wgmma_rs_n144<1, 0>(acc, af[k].x, af[k].y, af[k].z, af[k].w, wd0 + (wg ? o1 : o0), k != 0);
            } else {
                wgmma_rs_n144<1, (SM_KV + (k - 8) * 4608) / 16>(acc, af[k].x, af[k].y, af[k].z, af[k].w, wd1, 1);
            }
        });
        wg_commit();
        wg_wait<0>();
        reg_fence(acc);
        PROF(20);
        {
            float4* ex = reinterpret_cast<float4*>(smem + SM_EXCH) + t128;
#pragma unroll
            for (int i = 0; i < 9; i++) {
                const float4 lo = make_float4(acc[i * 4], acc[i * 4 + 1], acc[i * 4 + 2], acc[i * 4 + 3]);
                const float4 hi = make_float4(acc[36 + i * 4], acc[36 + i * 4 + 1], acc[36 + i * 4 + 2], acc[36 + i * 4 + 3]);
                ex[(wg * 9 + i) * 128] = wg ? lo : hi;
                const float4 own = wg ? hi : lo;
                bs[i].x += own.x; bs[i].y += own.y;
                bs[i].z += own.z; bs[i].w += own.w;
            }
            named_bar_sync(5, 256);
            uint32_t* op = reinterpret_cast<uint32_t*>(out + (size_t)(rt * 64 + wq * 16 + g) * DM + ct * 144 + wg * 72 + q * 2);
#pragma unroll
            for (int i = 0; i < 9; i++) {
                const float4 v = ex[((wg ^ 1) * 9 + i) * 128];
                op[i * 4] = pack_bf16(bs[i].x + v.x, bs[i].y + v.y);
                op[i * 4 + 4 * DM] = pack_bf16(bs[i].z + v.z, bs[i].w + v.w);
            }
        }
        if (tid == 0) {
            if (atomicAdd(&g_flags.exited, 1u) == gridDim.x - 1) {
                unsigned int* f = reinterpret_cast<unsigned int*>(&g_flags);
#pragma unroll 1
                for (int i = 0; i < (int)(sizeof(Flags) / 4); i++) f[i] = 0;
            }
        }
        PROF(21);
        PROFT(52);
    } else {
        reg_dealloc<24>();
        if (warp == 8 && lane == 0) {
            prefetch_tmap(&tmQ3); prefetch_tmap(&tmQ1); prefetch_tmap(&tm1); prefetch_tmap(&tm2);
            #pragma unroll 1
            for (int i = 0; i < 9; i++) { mbar_init(full0 + i * 8, 1); mbar_init(empty0 + i * 8, 4); mbar_init(bar0 + (B_WO + i) * 8, 1); }
            mbar_init(bar0 + B_BASE * 8, 3); mbar_init(bar0 + B_XNDEAD * 8, 2); mbar_init(bar0 + B_QRDY * 8, 3); mbar_init(bar0 + B_FFN * 8, 8);
#pragma unroll 1
            for (int i = 0; i < 16; i++) { mbar_init(bar0 + (B_KV + i) * 8, 1); mbar_init(bar0 + (B_FREE + (i & 7)) * 8, 2); if (i < 6) mbar_init(bar0 + (B_RED + i) * 8, 1); }
            *slow_flag = 0;
            fence_barrier_init();
        }
        __syncwarp();
        cluster_arrive();
        cluster_wait();
        const uint8_t* kvsrc = g_QKV + (size_t)head * KV_HEAD_BYTES;
        if (warp == 8) {
            if (lane == 0) {
                int st = 0, u = rank, tile = -4;
                int es = 5;
                uint32_t eph = 1;
#pragma unroll 1
                for (int n = 0; n < 99; n++) {
                    mbar_wait(empty0 + es * 8, eph);
                    const uint32_t fb = full0 + st * 8, dst = sb + K1_OFF_RING + u * 8192;
                    mbar_expect(fb, 16384);
                    if (tile < 0) {
                        tma3d_mc(dst, &tmQ3, j * 216, n * 32 + rank * 16, 0, fb, 3);
                        tma2d_mc(dst + 6144, &tmQ1, j * 216 + 192, n * 32 + rank * 16, fb, 3);
                    } else if (tile < 9) {
                        tma2d_mc(dst, &tm1, j * 576 + tile * 64, u * 64, fb, 3);
                    } else {
                        tma2d_mc(dst, &tm2, (tile - 9) * 64, j * 576 + u * 64, fb, 3);
                    }
                    u += 2;
                    if (u >= 9) { u -= 9; tile++; }
                    if (++st == 9) st = 0;
                    if (++es == 9) { es = 0; eph ^= 1; }
                }
                mbar_wait(empty0 + 8 * 8, 0);
                mbar_wait(bar0 + B_QRDY * 8, 0);
                asm volatile("fence.proxy.async;" ::: "memory");
#pragma unroll 1
                for (int i = 11; i < NCHUNK; i++) {
                    mbar_expect(bar0 + (B_KV + i) * 8, CHUNK_BYTES);
                    bulk_load(sb + SM_KV + i * CHUNK_BYTES, kvsrc + i * CHUNK_BYTES, CHUNK_BYTES, bar0 + (B_KV + i) * 8);
                }
#pragma unroll 1
                for (int i = 0; i < 9; i++) {
                    if (i == 0) mbar_wait_sleep(bar0 + B_BASE * 8, 500);
                    if (i > 0) {
                        const int f = i == 1 ? 0 : ((i - 1) * 9 + 4) / 10;
                        mbar_wait_sleep(bar0 + (B_FREE + f) * 8, i == 1 ? 500 : 50);
                    }
                    mbar_expect(bar0 + (B_WO + i) * 8, WO_PIECE);
                    bulk_load(sb + (i == 0 ? sm_wo(0) : (i == 1 ? sm_wo(1) : SM_KV + (i - 2) * WO_PIECE)), g_Wo + ct * WO_TILE_BYTES + i * WO_PIECE, WO_PIECE,
                              bar0 + (B_WO + i) * 8);
                }
            }
        } else {
            const int ht = tid - 288;
            if (ht < 72) {
                const uint4 v = __ldg(reinterpret_cast<const uint4*>(b1 + j * 576) + ht);
                uint32_t* sbias = reinterpret_cast<uint32_t*>(smem + K1_OFF_BIAS) + (ht >> 3) * 32 + (ht & 7);
                sbias[0] = v.x; sbias[8] = v.y; sbias[16] = v.z; sbias[24] = v.w;
            }
            asm volatile("bar.arrive 4, 352;" ::: "memory");
            PROFH(37);
#pragma unroll 1
            for (int i = ht; i < 512; i += 96) {
                const int key = i & 127;
                uint8_t* p = g_QKV + (size_t)(j * 4 + (i >> 7)) * KV_HEAD_BYTES + (rb * 16 + (key >> 3)) * KV_GROUP_BYTES + 512 + (key & 7) * 16;
                *reinterpret_cast<uint32_t*>(p + 4) = ((POLY_MASK >> ((key >> 3) & 7)) & 1) ? 0x3F804000u : 0x00003F80u;
                *reinterpret_cast<uint32_t*>(p + 12) = 0x00003F80u;
            }
#pragma unroll 2
            for (int i = blockIdx.x * 324 + ht; i < blockIdx.x * 324 + 324; i += 96) {
                const int k = i / 72, nc = i - k * 72, c4 = nc / 18;
                *reinterpret_cast<uint4*>(g_Wo + c4 * WO_TILE_BYTES + (k >> 3) * 2304 + (nc - c4 * 18) * 128 + (k & 7) * 16) =
                    __ldg(reinterpret_cast<const uint4*>(wo) + i);
            }
            PROFH(38);
            named_bar_sync(3, 352);
            if (ht == 0) {
                flag_signal(&g_flags.qkv_stored[rb]);
                flag_wait(&g_flags.qkv_stored[rb], 8, 200);
            }
            named_bar_sync(7, 96);
            PROFH(39);
#pragma unroll 1
            for (int i = warp - 9; i < 16; i += 3) {
                const int hd = j * 4 + (i >> 2), key = (i & 3) * 32 + lane;
                const uint8_t* p = g_QKV + (size_t)hd * KV_HEAD_BYTES + (rb * 16 + (key >> 3)) * KV_GROUP_BYTES + (key & 7) * 16;
                const uint4 a = __ldcg(reinterpret_cast<const uint4*>(p)), b = __ldcg(reinterpret_cast<const uint4*>(p + 128));
                float n = sumsq2(__ldcg(reinterpret_cast<const uint32_t*>(p + 512))) + sumsq8(a) + sumsq8(b);
                if ((POLY_MASK >> ((key >> 3) & 7)) & 1) n *= 0.25f;
#pragma unroll
                for (int o = 16; o; o >>= 1) n = fmaxf(n, __shfl_xor_sync(~0u, n, o));
                if (lane == 0) g_kmax[hd * 64 + rb * 4 + (i & 3)] = n;
            }
            named_bar_sync(7, 96);
            PROFH(40);
            if (ht == 0) {
                flag_signal(&g_flags.kv_ready);
                flag_wait(&g_flags.kv_ready, 128, 300);
                mbar_wait_sleep(bar0 + B_XNDEAD * 8, 300);
            }
            named_bar_sync(7, 96);
            PROFH(41);
            float kmax2;
            {
                const float2 v = __ldcg(reinterpret_cast<const float2*>(g_kmax + head * 64 + lane * 2));
                kmax2 = fmaxf(v.x, v.y);
#pragma unroll
                for (int o = 16; o; o >>= 1) kmax2 = fmaxf(kmax2, __shfl_xor_sync(~0u, kmax2, o));
            }
            asm volatile("fence.proxy.async;" ::: "memory");
            int chunk = warp - 9;
#pragma unroll 1
            for (int r = ht; r < 512; r += 96) {
                if (lane == 0 && chunk < 11) {
                    mbar_expect(bar0 + (B_KV + chunk) * 8, CHUNK_BYTES);
                    bulk_load(sb + SM_KV + chunk * CHUNK_BYTES, kvsrc + chunk * CHUNK_BYTES, CHUNK_BYTES, bar0 + (B_KV + chunk) * 8);
                }
                chunk += 3;
                const uint8_t* p = kvsrc + Q_OFFSET + (quarter * 64 + (r >> 3)) * KV_GROUP_BYTES + (r & 7) * 16;
                const uint4 a = __ldcg(reinterpret_cast<const uint4*>(p)), b = __ldcg(reinterpret_cast<const uint4*>(p + 128));
                const uint32_t e = __ldcg(reinterpret_cast<const uint32_t*>(p + 256));
                const float cc = sqrtf((sumsq2(e) + sumsq8(a) + sumsq8(b)) * kmax2) * 1.02f;
                if (!(cc <= 58.f)) *slow_flag = 1;
                uint4* dst = reinterpret_cast<uint4*>(smem + SM_Q + (r >> 3) * 512 + (r & 7) * 16);
                dst[0] = a;
                dst[8] = b;
                dst[16] = make_uint4(e, pack_bf16(-cc, 768.f), 0u, 0u);
                dst[24] = make_uint4(0u, POLY_MODE ? 0xBFFF0000u : 0xC0000000u, 0u, 0u);
            }
            named_bar_sync(7, 96);
            if (*slow_flag) {
#pragma unroll 1
                for (int r = ht; r < 512; r += 96) {
                    uint32_t* dst = reinterpret_cast<uint32_t*>(smem + SM_Q + (r >> 3) * 512 + (r & 7) * 16);
                    dst[65] = 0u;
                    dst[97] = 0u;
                }
            }
            fence_proxy_async();
            __syncwarp();
            if (lane == 0) mbar_arrive(bar0 + B_QRDY * 8);
            PROFH(42);
            if (ht == 0) {
                mbar_wait_sleep(bar0 + B_FFN * 8, 300);
                flag_signal(&g_flags.ffn_done[rb]);
                flag_wait(&g_flags.ffn_done[rt >> 1], 8, 300);
            }
            named_bar_sync(7, 96);
            {
                const int w3 = warp - 9;
                const uint32_t rbar = bar0 + (B_RED + w3 * 2) * 8, rbuf = SM_RED + w3 * 8192;
                const int u0 = ((rt >> 1) * 36 + ct * 9) * 256 + (rt & 1) * 128;
                mbar_wait_sleep(empty0 + 8 * 8, 100);
                asm volatile("fence.proxy.async;" ::: "memory");
#pragma unroll 1
                for (int i = -2; i < 12; i++) {
                    float a[8];
                    int t = 0, pb = 0;
                    if (i >= 0) {
                        const int bx = i * 3 + w3;
                        t = (rt & 1) * 128 + (bx & 3) * 32 + lane;
                        pb = ct * 9 + (bx >> 2);
                        const int col = pb * 16 + (t & 3) * 2;
                        const uint32_t* xp = reinterpret_cast<const uint32_t*>(x + (size_t)((rt >> 1) * 128 + (t >> 5) * 16 + ((t & 31) >> 2)) * DM + col);
                        const uint32_t x0 = __ldg(xp), x1 = __ldg(xp + 4 * DM), x2 = __ldg(xp + 4), x3 = __ldg(xp + 4 * DM + 4);
                        const uint32_t ba = __ldg(reinterpret_cast<const uint32_t*>(b2 + col)), bb = __ldg(reinterpret_cast<const uint32_t*>(b2 + col + 8));
                        mbar_wait(rbar + (i & 1) * 8, (i >> 1) & 1);
                        const uint4* sp = reinterpret_cast<const uint4*>(smem + rbuf + (i & 1) * 4096) + lane;
                        const uint4 v = hadd8_bf16(hadd8_bf16(sp[0], sp[32]), hadd8_bf16(sp[64], sp[96]));
                        a[0] = fmaf(bf_lo(v.x), 0.5f, bf_lo(x0) + bf_lo(ba)); a[1] = fmaf(bf_hi(v.x), 0.5f, bf_hi(x0) + bf_hi(ba));
                        a[2] = fmaf(bf_lo(v.y), 0.5f, bf_lo(x1) + bf_lo(ba)); a[3] = fmaf(bf_hi(v.y), 0.5f, bf_hi(x1) + bf_hi(ba));
                        a[4] = fmaf(bf_lo(v.z), 0.5f, bf_lo(x2) + bf_lo(bb)); a[5] = fmaf(bf_hi(v.z), 0.5f, bf_hi(x2) + bf_hi(bb));
                        a[6] = fmaf(bf_lo(v.w), 0.5f, bf_lo(x3) + bf_lo(bb)); a[7] = fmaf(bf_hi(v.w), 0.5f, bf_hi(x3) + bf_hi(bb));
                        const uint4 w = hadd8_bf16(hadd8_bf16(sp[128], sp[160]), hadd8_bf16(sp[192], sp[224]));
                        a[0] = fmaf(bf_lo(w.x), 0.5f, a[0]); a[1] = fmaf(bf_hi(w.x), 0.5f, a[1]); a[2] = fmaf(bf_lo(w.y), 0.5f, a[2]); a[3] = fmaf(bf_hi(w.y), 0.5f, a[3]);
                        a[4] = fmaf(bf_lo(w.z), 0.5f, a[4]); a[5] = fmaf(bf_hi(w.z), 0.5f, a[5]); a[6] = fmaf(bf_lo(w.w), 0.5f, a[6]); a[7] = fmaf(bf_hi(w.w), 0.5f, a[7]);
                        float4* bp = g_base + ((rt >> 1) * 72 + pb * 2) * 256 + t;
                        bp[0] = make_float4(a[0], a[1], a[2], a[3]);
                        bp[256] = make_float4(a[4], a[5], a[6], a[7]);
                    }
                    __syncwarp();
                    if (lane == 0 && i < 10) {
                        const int bx = (i + 2) * 3 + w3;
                        mbar_expect(rbar + (i & 1) * 8, 4096);
                        tma2d(sb + rbuf + (i & 1) * 4096, &tmP, (u0 + (bx >> 2) * 256 + (bx & 3) * 32) * 2, 0, rbar + (i & 1) * 8);
                    }
                }
            }
            __syncwarp();
            if (lane == 0) mbar_arrive(bar0 + B_BASE * 8);
            PROFH(43);
        }
    }
}

typedef CUresult (*EncodeFn)(CUtensorMap*, CUtensorMapDataType, cuuint32_t, void*, const cuuint64_t*, const cuuint64_t*, const cuuint32_t*,
                             const cuuint32_t*, CUtensorMapInterleave, CUtensorMapSwizzle, CUtensorMapL2promotion, CUtensorMapFloatOOBfill);

void make_map(EncodeFn fn, CUtensorMap* m, const void* base, int rank, const cuuint64_t* dims, const cuuint64_t* strides, const cuuint32_t* box) {
    cuuint32_t es[3] = {1, 1, 1};
    fn(m, CU_TENSOR_MAP_DATA_TYPE_BFLOAT16, rank, const_cast<void*>(base), dims, strides, box, es, CU_TENSOR_MAP_INTERLEAVE_NONE,
       CU_TENSOR_MAP_SWIZZLE_128B, CU_TENSOR_MAP_L2_PROMOTION_L2_256B, CU_TENSOR_MAP_FLOAT_OOB_FILL_NONE);
}

}

extern "C" void kernel_launch(void* const* d_in, const int* in_sizes, int n_in, void* d_out, int out_size) {
    const __nv_bfloat16* x = (const __nv_bfloat16*)d_in[0];
    const __nv_bfloat16* wqkv = (const __nv_bfloat16*)d_in[1];
    const __nv_bfloat16* wo = (const __nv_bfloat16*)d_in[2];
    const __nv_bfloat16* w1 = (const __nv_bfloat16*)d_in[4];
    const __nv_bfloat16* b1 = (const __nv_bfloat16*)d_in[5];
    const __nv_bfloat16* w2 = (const __nv_bfloat16*)d_in[6];
    const __nv_bfloat16* b2 = (const __nv_bfloat16*)d_in[7];
    __nv_bfloat16* out = (__nv_bfloat16*)d_out;

    EncodeFn fn = nullptr;
    cudaDriverEntryPointQueryResult qr;
    cudaGetDriverEntryPoint("cuTensorMapEncodeTiled", (void**)&fn, cudaEnableDefault, &qr);
    CUtensorMap tmX, tmQ3, tmQ1, tm1, tm2, tmP;
    {
        void* gp = nullptr;
        cudaGetSymbolAddress(&gp, g_part);
        cuuint64_t d[2] = {SLAB * 2, 8}, s[1] = {SLAB * 16};
        cuuint32_t b[2] = {64, 8}, es[2] = {1, 1};
        fn(&tmP, CU_TENSOR_MAP_DATA_TYPE_INT64, 2, gp, d, s, b, es, CU_TENSOR_MAP_INTERLEAVE_NONE, CU_TENSOR_MAP_SWIZZLE_NONE,
           CU_TENSOR_MAP_L2_PROMOTION_NONE, CU_TENSOR_MAP_FLOAT_OOB_FILL_NONE);
    }
    {
        cuuint64_t d[3] = {64, SEQ, 9}, s[2] = {DM * 2, 128};
        cuuint32_t b[3] = {64, 8, 9};
        make_map(fn, &tmX, x, 3, d, s, b);
    }
    {
        cuuint64_t d[3] = {3 * DM, DM, 3}, s[2] = {3 * DM * 2, 128};
        cuuint32_t b[3] = {64, 16, 3};
        make_map(fn, &tmQ3, wqkv, 3, d, s, b);
        make_map(fn, &tmQ1, wqkv, 2, d, s, b);
    }
    {
        cuuint64_t d[2] = {FF, DM}, s[1] = {FF * 2};
        cuuint32_t b[2] = {64, 64};
        make_map(fn, &tm1, w1, 2, d, s, b);
        cuuint64_t d2[2] = {DM, FF}, s2[1] = {DM * 2};
        make_map(fn, &tm2, w2, 2, d2, s2, b);
    }
    cudaFuncSetAttribute(fused_kernel, cudaFuncAttributeMaxDynamicSharedMemorySize, K1_SMEM);
    fused_kernel<<<128, 384, K1_SMEM, cudaStreamPerThread>>>(tmX, tmQ3, tmQ1, tm1, tm2, tmP, b1, wo, x, b2, out, 0ull);
}
```

```cpp
#include <cuda_runtime.h>
#include <cuda_bf16.h>
#include <cuda.h>
#include <stdint.h>

#define PROF(i) do { } while (0)
#define PROFT(i) do { } while (0)
#define PROFH(i) do { } while (0)
#define PROF_WG 0

namespace {

constexpr int SEQ = 2048, DM = 576, FF = 4608, NH = 32, DH = 18;

constexpr int KV_GROUP_BYTES = 5 * 128;
constexpr int KV_HEAD_BYTES = (SEQ / 8) * KV_GROUP_BYTES;
constexpr int Q_OFFSET = NH * KV_HEAD_BYTES;
#define POLY_MASK 0xB6
__device__ __align__(1024) uint8_t g_QKV[2 * NH * KV_HEAD_BYTES];
__device__ __align__(1024) float g_kmax[NH * 64];
constexpr int SLAB = 16 * 36 * 256;
__device__ __align__(1024) uint4 g_part[8 * SLAB];
__device__ __align__(1024) uint2 g_ffn[128 * 2 * 9 * 128];
__device__ __align__(1024) uint32_t g_O[SEQ * DM / 2];
struct Flags {
    unsigned int qkv_stored[16];
    unsigned int ffn_done[16];
    unsigned int o_done[4];
    unsigned int kv_ready;
    unsigned int exited;
};
__device__ Flags g_flags;
constexpr int WO_TILE_BYTES = DM * 144 * 2;
__device__ __align__(1024) uint8_t g_Wo[4 * WO_TILE_BYTES];

__device__ __forceinline__ uint32_t s2u(const void* p) { return (uint32_t)__cvta_generic_to_shared(p); }
__device__ __forceinline__ void mbar_init(uint32_t b, int c) { asm volatile("mbarrier.init.shared::cta.b64 [%0], %1;" ::"r"(b), "r"(c) : "memory"); }
__device__ __forceinline__ void mbar_expect(uint32_t b, uint32_t bytes) {
    asm volatile("mbarrier.arrive.expect_tx.shared::cta.b64 _, [%0], %1;" ::"r"(b), "r"(bytes) : "memory");
}
__device__ __forceinline__ bool mbar_try(uint32_t b, uint32_t parity) {
    uint32_t ok;
    asm volatile("{\n.reg .pred p;\nmbarrier.try_wait.parity.shared::cta.b64 p, [%1], %2;\nselp.u32 %0, 1, 0, p;\n}\n" : "=r"(ok) : "r"(b), "r"(parity) : "memory");
    return ok != 0;
}
__device__ __forceinline__ void mbar_wait(uint32_t b, uint32_t parity) {
    if (__builtin_expect(!mbar_try(b, parity), 0)) {
        uint32_t spins = 0;
        while (!mbar_try(b, parity))
            if (++spins > (1u << 22)) __trap();
    }
}
__device__ __forceinline__ void fence_barrier_init() { asm volatile("fence.mbarrier_init.release.cluster;" ::: "memory"); }
__device__ __forceinline__ void fence_proxy_async() { asm volatile("fence.proxy.async.shared::cta;" ::: "memory"); }
__device__ __forceinline__ void cluster_arrive() { asm volatile("barrier.cluster.arrive.relaxed.aligned;" ::: "memory"); }
__device__ __forceinline__ void cluster_wait() { asm volatile("barrier.cluster.wait.aligned;" ::: "memory"); }
__device__ __forceinline__ void named_bar_sync(int id, int n) { asm volatile("bar.sync %0, %1;" ::"r"(id), "r"(n) : "memory"); }
__device__ __forceinline__ void griddep_wait() { asm volatile("griddepcontrol.wait;" ::: "memory"); }
__device__ __forceinline__ void griddep_launch() { asm volatile("griddepcontrol.launch_dependents;" ::: "memory"); }

__device__ __forceinline__ void tma3d_mc(uint32_t dst, const CUtensorMap* tm, int c0, int c1, int c2, uint32_t bar, uint16_t mask) {
    asm volatile("cp.async.bulk.tensor.3d.shared::cluster.global.mbarrier::complete_tx::bytes.multicast::cluster [%0], [%1, {%3, %4, %5}], [%2], %6;"
                 ::"r"(dst), "l"(tm), "r"(bar), "r"(c0), "r"(c1), "r"(c2), "h"(mask) : "memory");
}
__device__ __forceinline__ void tma2d_mc(uint32_t dst, const CUtensorMap* tm, int c0, int c1, uint32_t bar, uint16_t mask) {
    asm volatile("cp.async.bulk.tensor.2d.shared::cluster.global.mbarrier::complete_tx::bytes.multicast::cluster [%0], [%1, {%3, %4}], [%2], %5;"
                 ::"r"(dst), "l"(tm), "r"(bar), "r"(c0), "r"(c1), "h"(mask) : "memory");
}
__device__ __forceinline__ void tma3d(uint32_t dst, const CUtensorMap* tm, int c0, int c1, int c2, uint32_t bar) {
    asm volatile("cp.async.bulk.tensor.3d.shared::cluster.global.mbarrier::complete_tx::bytes [%0], [%1, {%3, %4, %5}], [%2];"
                 ::"r"(dst), "l"(tm), "r"(bar), "r"(c0), "r"(c1), "r"(c2) : "memory");
}
__device__ __forceinline__ void tma2d(uint32_t dst, const CUtensorMap* tm, int c0, int c1, uint32_t bar) {
    asm volatile("cp.async.bulk.tensor.2d.shared::cluster.global.mbarrier::complete_tx::bytes [%0], [%1, {%3, %4}], [%2];"
                 ::"r"(dst), "l"(tm), "r"(bar), "r"(c0), "r"(c1) : "memory");
}
__device__ __forceinline__ void bulk_load(uint32_t dst, const void* src, uint32_t bytes, uint32_t bar) {
    asm volatile("cp.async.bulk.shared::cluster.global.mbarrier::complete_tx::bytes [%0], [%1], %2, [%3];"
                 ::"r"(dst), "l"(src), "r"(bytes), "r"(bar) : "memory");
}
__device__ __forceinline__ void prefetch_tmap(const CUtensorMap* tm) { asm volatile("prefetch.tensormap [%0];" ::"l"(tm) : "memory"); }

__device__ __forceinline__ void wg_fence() { asm volatile("wgmma.fence.sync.aligned;" ::: "memory"); }
__device__ __forceinline__ void wg_commit() { asm volatile("wgmma.commit_group.sync.aligned;" ::: "memory"); }
template <int N> __device__ __forceinline__ void wg_wait() { asm volatile("wgmma.wait_group.sync.aligned %0;" ::"n"(N) : "memory"); }
template <int N> __device__ __forceinline__ void reg_fence(float (&d)[N]) {
#pragma unroll
    for (int i = 0; i < N; i++) asm volatile("" : "+f"(d[i])::"memory");
}
template <int N> __device__ __forceinline__ void reg_fence(uint32_t (&d)[N]) {
#pragma unroll
    for (int i = 0; i < N; i++) asm volatile("" : "+r"(d[i])::"memory");
}
template <int R> __device__ __forceinline__ void reg_alloc() { asm volatile("setmaxnreg.inc.sync.aligned.u32 %0;" ::"n"(R)); }
template <int R> __device__ __forceinline__ void reg_dealloc() { asm volatile("setmaxnreg.dec.sync.aligned.u32 %0;" ::"n"(R)); }

__device__ __forceinline__ uint64_t mk_desc(uint64_t z, uint32_t addr, uint32_t lbo, uint32_t sbo, uint32_t swz) {
    return z + ((uint64_t)(((addr & 0x3FFFF) >> 4) | ((lbo >> 4) << 16)) | ((uint64_t)((sbo >> 4) | (swz << 30)) << 32));
}
__device__ __forceinline__ uint32_t pack_bf16(float lo, float hi) {
    uint32_t r;
    asm("cvt.rn.bf16x2.f32 %0, %1, %2;" : "=r"(r) : "f"(hi), "f"(lo));
    return r;
}
__device__ __forceinline__ float bf_lo(uint32_t w) { return __uint_as_float(w << 16); }
__device__ __forceinline__ float bf_hi(uint32_t w) { return __uint_as_float(w & 0xFFFF0000u); }
__device__ __forceinline__ float ex2(float x) {
    float r;
    asm("ex2.approx.ftz.f32 %0, %1;" : "=f"(r) : "f"(x));
    return r;
}
__device__ __forceinline__ float tanh_fast(float x) {
    float r;
    asm("tanh.approx.f32 %0, %1;" : "=f"(r) : "f"(x));
    return r;
}
__device__ __forceinline__ float gelu2(float u) {
    const float w = fmaf(u * u, 0.0356774081f, 0.7978845608f);
    return fmaf(u, tanh_fast(u * w), u);
}

template<int TB, int AOFF, int BOFF> __device__ __forceinline__ void wgmma_ss_n216(float (&d)[108], uint64_t da, uint64_t db, int sd) {
    asm volatile("{\n.reg .pred p;\n.reg .b64 ta, tb;\nsetp.ne.b32 p, %110, 0;\nadd.s64 ta, %108, %112;\nadd.s64 tb, %109, %113;\n"
      "wgmma.mma_async.sync.aligned.m64n216k16.f32.bf16.bf16 {%0, %1, %2, %3, %4, %5, %6, %7, %8, %9, %10, %11, %12, %13, %14, %15, %16, %17, %18, %19, %20, %21, %22, %23, %24, %25, %26, %27, %28, %29, %30, %31, %32, %33, %34, %35, %36, %37, %38, %39, %40, %41, %42, %43, %44, %45, %46, %47, %48, %49, %50, %51, %52, %53, %54, %55, %56, %57, %58, %59, %60, %61, %62, %63, %64, %65, %66, %67, %68, %69, %70, %71, %72, %73, %74, %75, %76, %77, %78, %79, %80, %81, %82, %83, %84, %85, %86, %87, %88, %89, %90, %91, %92, %93, %94, %95, %96, %97, %98, %99, %100, %101, %102, %103, %104, %105, %106, %107}, ta, tb, p, 1, 1, 0, %111;\n}\n"
      : "+f"(d[0]), "+f"(d[1]), "+f"(d[2]), "+f"(d[3]), "+f"(d[4]), "+f"(d[5]), "+f"(d[6]), "+f"(d[7]), "+f"(d[8]), "+f"(d[9]), "+f"(d[10]), "+f"(d[11]), "+f"(d[12]), "+f"(d[13]), "+f"(d[14]), "+f"(d[15]), "+f"(d[16]), "+f"(d[17]), "+f"(d[18]), "+f"(d[19]), "+f"(d[20]), "+f"(d[21]), "+f"(d[22]), "+f"(d[23]), "+f"(d[24]), "+f"(d[25]), "+f"(d[26]), "+f"(d[27]), "+f"(d[28]), "+f"(d[29]), "+f"(d[30]), "+f"(d[31]), "+f"(d[32]), "+f"(d[33]), "+f"(d[34]), "+f"(d[35]), "+f"(d[36]), "+f"(d[37]), "+f"(d[38]), "+f"(d[39]), "+f"(d[40]), "+f"(d[41]), "+f"(d[42]), "+f"(d[43]), "+f"(d[44]), "+f"(d[45]), "+f"(d[46]), "+f"(d[47]), "+f"(d[48]), "+f"(d[49]), "+f"(d[50]), "+f"(d[51]), "+f"(d[52]), "+f"(d[53]), "+f"(d[54]), "+f"(d[55]), "+f"(d[56]), "+f"(d[57]), "+f"(d[58]), "+f"(d[59]), "+f"(d[60]), "+f"(d[61]), "+f"(d[62]), "+f"(d[63]), "+f"(d[64]), "+f"(d[65]), "+f"(d[66]), "+f"(d[67]), "+f"(d[68]), "+f"(d[69]), "+f"(d[70]), "+f"(d[71]), "+f"(d[72]), "+f"(d[73]), "+f"(d[74]), "+f"(d[75]), "+f"(d[76]), "+f"(d[77]), "+f"(d[78]), "+f"(d[79]), "+f"(d[80]), "+f"(d[81]), "+f"(d[82]), "+f"(d[83]), "+f"(d[84]), "+f"(d[85]), "+f"(d[86]), "+f"(d[87]), "+f"(d[88]), "+f"(d[89]), "+f"(d[90]), "+f"(d[91]), "+f"(d[92]), "+f"(d[93]), "+f"(d[94]), "+f"(d[95]), "+f"(d[96]), "+f"(d[97]), "+f"(d[98]), "+f"(d[99]), "+f"(d[100]), "+f"(d[101]), "+f"(d[102]), "+f"(d[103]), "+f"(d[104]), "+f"(d[105]), "+f"(d[106]), "+f"(d[107])
      : "l"(da), "l"(db), "r"(sd), "n"(TB), "n"(AOFF), "n"(BOFF));
}

template<int TB, int AOFF, int BOFF> __device__ __forceinline__ void wgmma_ss_n64(float (&d)[32], uint64_t da, uint64_t db, int sd) {
    asm volatile("{\n.reg .pred p;\n.reg .b64 ta, tb;\nsetp.ne.b32 p, %34, 0;\nadd.s64 ta, %32, %36;\nadd.s64 tb, %33, %37;\n"
      "wgmma.mma_async.sync.aligned.m64n64k16.f32.bf16.bf16 {%0, %1, %2, %3, %4, %5, %6, %7, %8, %9, %10, %11, %12, %13, %14, %15, %16, %17, %18, %19, %20, %21, %22, %23, %24, %25, %26, %27, %28, %29, %30, %31}, ta, tb, p, 1, 1, 0, %35;\n}\n"
      : "+f"(d[0]), "+f"(d[1]), "+f"(d[2]), "+f"(d[3]), "+f"(d[4]), "+f"(d[5]), "+f"(d[6]), "+f"(d[7]), "+f"(d[8]), "+f"(d[9]), "+f"(d[10]), "+f"(d[11]), "+f"(d[12]), "+f"(d[13]), "+f"(d[14]), "+f"(d[15]), "+f"(d[16]), "+f"(d[17]), "+f"(d[18]), "+f"(d[19]), "+f"(d[20]), "+f"(d[21]), "+f"(d[22]), "+f"(d[23]), "+f"(d[24]), "+f"(d[25]), "+f"(d[26]), "+f"(d[27]), "+f"(d[28]), "+f"(d[29]), "+f"(d[30]), "+f"(d[31])
      : "l"(da), "l"(db), "r"(sd), "n"(TB), "n"(AOFF), "n"(BOFF));
}

template<int TB, int AOFF, int BOFF> __device__ __forceinline__ void wgmma_ss_n128(float (&d)[64], uint64_t da, uint64_t db, int sd) {
    asm volatile("{\n.reg .pred p;\n.reg .b64 ta, tb;\nsetp.ne.b32 p, %66, 0;\nadd.s64 ta, %64, %68;\nadd.s64 tb, %65, %69;\n"
      "wgmma.mma_async.sync.aligned.m64n128k16.f32.bf16.bf16 {%0, %1, %2, %3, %4, %5, %6, %7, %8, %9, %10, %11, %12, %13, %14, %15, %16, %17, %18, %19, %20, %21, %22, %23, %24, %25, %26, %27, %28, %29, %30, %31, %32, %33, %34, %35, %36, %37, %38, %39, %40, %41, %42, %43, %44, %45, %46, %47, %48, %49, %50, %51, %52, %53, %54, %55, %56, %57, %58, %59, %60, %61, %62, %63}, ta, tb, p, 1, 1, 0, %67;\n}\n"
      : "+f"(d[0]), "+f"(d[1]), "+f"(d[2]), "+f"(d[3]), "+f"(d[4]), "+f"(d[5]), "+f"(d[6]), "+f"(d[7]), "+f"(d[8]), "+f"(d[9]), "+f"(d[10]), "+f"(d[11]), "+f"(d[12]), "+f"(d[13]), "+f"(d[14]), "+f"(d[15]), "+f"(d[16]), "+f"(d[17]), "+f"(d[18]), "+f"(d[19]), "+f"(d[20]), "+f"(d[21]), "+f"(d[22]), "+f"(d[23]), "+f"(d[24]), "+f"(d[25]), "+f"(d[26]), "+f"(d[27]), "+f"(d[28]), "+f"(d[29]), "+f"(d[30]), "+f"(d[31]), "+f"(d[32]), "+f"(d[33]), "+f"(d[34]), "+f"(d[35]), "+f"(d[36]), "+f"(d[37]), "+f"(d[38]), "+f"(d[39]), "+f"(d[40]), "+f"(d[41]), "+f"(d[42]), "+f"(d[43]), "+f"(d[44]), "+f"(d[45]), "+f"(d[46]), "+f"(d[47]), "+f"(d[48]), "+f"(d[49]), "+f"(d[50]), "+f"(d[51]), "+f"(d[52]), "+f"(d[53]), "+f"(d[54]), "+f"(d[55]), "+f"(d[56]), "+f"(d[57]), "+f"(d[58]), "+f"(d[59]), "+f"(d[60]), "+f"(d[61]), "+f"(d[62]), "+f"(d[63])
      : "l"(da), "l"(db), "r"(sd), "n"(TB), "n"(AOFF), "n"(BOFF));
}

template<int TB, int BOFF> __device__ __forceinline__ void wgmma_rs_n64(float (&d)[32], uint32_t a0, uint32_t a1, uint32_t a2, uint32_t a3, uint64_t db, int sd) {
    asm volatile("{\n.reg .pred p;\n.reg .b64 tb;\nsetp.ne.b32 p, %37, 0;\nadd.s64 tb, %36, %39;\n"
      "wgmma.mma_async.sync.aligned.m64n64k16.f32.bf16.bf16 {%0, %1, %2, %3, %4, %5, %6, %7, %8, %9, %10, %11, %12, %13, %14, %15, %16, %17, %18, %19, %20, %21, %22, %23, %24, %25, %26, %27, %28, %29, %30, %31}, {%32, %33, %34, %35}, tb, p, 1, 1, %38;\n}\n"
      : "+f"(d[0]), "+f"(d[1]), "+f"(d[2]), "+f"(d[3]), "+f"(d[4]), "+f"(d[5]), "+f"(d[6]), "+f"(d[7]), "+f"(d[8]), "+f"(d[9]), "+f"(d[10]), "+f"(d[11]), "+f"(d[12]), "+f"(d[13]), "+f"(d[14]), "+f"(d[15]), "+f"(d[16]), "+f"(d[17]), "+f"(d[18]), "+f"(d[19]), "+f"(d[20]), "+f"(d[21]), "+f"(d[22]), "+f"(d[23]), "+f"(d[24]), "+f"(d[25]), "+f"(d[26]), "+f"(d[27]), "+f"(d[28]), "+f"(d[29]), "+f"(d[30]), "+f"(d[31])
      : "r"(a0), "r"(a1), "r"(a2), "r"(a3), "l"(db), "r"(sd), "n"(TB), "n"(BOFF));
}

template<int TB, int BOFF> __device__ __forceinline__ void wgmma_rs_n24(float (&d)[12], uint32_t a0, uint32_t a1, uint32_t a2, uint32_t a3, uint64_t db, int sd) {
    asm volatile("{\n.reg .pred p;\n.reg .b64 tb;\nsetp.ne.b32 p, %17, 0;\nadd.s64 tb, %16, %19;\n"
      "wgmma.mma_async.sync.aligned.m64n24k16.f32.bf16.bf16 {%0, %1, %2, %3, %4, %5, %6, %7, %8, %9, %10, %11}, {%12, %13, %14, %15}, tb, p, 1, 1, %18;\n}\n"
      : "+f"(d[0]), "+f"(d[1]), "+f"(d[2]), "+f"(d[3]), "+f"(d[4]), "+f"(d[5]), "+f"(d[6]), "+f"(d[7]), "+f"(d[8]), "+f"(d[9]), "+f"(d[10]), "+f"(d[11])
      : "r"(a0), "r"(a1), "r"(a2), "r"(a3), "l"(db), "r"(sd), "n"(TB), "n"(BOFF));
}

template<int TB, int BOFF> __device__ __forceinline__ void wgmma_rs_n144(float (&d)[72], uint32_t a0, uint32_t a1, uint32_t a2, uint32_t a3, uint64_t db, int sd) {
    asm volatile("{\n.reg .pred p;\n.reg .b64 tb;\nsetp.ne.b32 p, %77, 0;\nadd.s64 tb, %76, %79;\n"
      "wgmma.mma_async.sync.aligned.m64n144k16.f32.bf16.bf16 {%0, %1, %2, %3, %4, %5, %6, %7, %8, %9, %10, %11, %12, %13, %14, %15, %16, %17, %18, %19, %20, %21, %22, %23, %24, %25, %26, %27, %28, %29, %30, %31, %32, %33, %34, %35, %36, %37, %38, %39, %40, %41, %42, %43, %44, %45, %46, %47, %48, %49, %50, %51, %52, %53, %54, %55, %56, %57, %58, %59, %60, %61, %62, %63, %64, %65, %66, %67, %68, %69, %70, %71}, {%72, %73, %74, %75}, tb, p, 1, 1, %78;\n}\n"
      : "+f"(d[0]), "+f"(d[1]), "+f"(d[2]), "+f"(d[3]), "+f"(d[4]), "+f"(d[5]), "+f"(d[6]), "+f"(d[7]), "+f"(d[8]), "+f"(d[9]), "+f"(d[10]), "+f"(d[11]), "+f"(d[12]), "+f"(d[13]), "+f"(d[14]), "+f"(d[15]), "+f"(d[16]), "+f"(d[17]), "+f"(d[18]), "+f"(d[19]), "+f"(d[20]), "+f"(d[21]), "+f"(d[22]), "+f"(d[23]), "+f"(d[24]), "+f"(d[25]), "+f"(d[26]), "+f"(d[27]), "+f"(d[28]), "+f"(d[29]), "+f"(d[30]), "+f"(d[31]), "+f"(d[32]), "+f"(d[33]), "+f"(d[34]), "+f"(d[35]), "+f"(d[36]), "+f"(d[37]), "+f"(d[38]), "+f"(d[39]), "+f"(d[40]), "+f"(d[41]), "+f"(d[42]), "+f"(d[43]), "+f"(d[44]), "+f"(d[45]), "+f"(d[46]), "+f"(d[47]), "+f"(d[48]), "+f"(d[49]), "+f"(d[50]), "+f"(d[51]), "+f"(d[52]), "+f"(d[53]), "+f"(d[54]), "+f"(d[55]), "+f"(d[56]), "+f"(d[57]), "+f"(d[58]), "+f"(d[59]), "+f"(d[60]), "+f"(d[61]), "+f"(d[62]), "+f"(d[63]), "+f"(d[64]), "+f"(d[65]), "+f"(d[66]), "+f"(d[67]), "+f"(d[68]), "+f"(d[69]), "+f"(d[70]), "+f"(d[71])
      : "r"(a0), "r"(a1), "r"(a2), "r"(a3), "l"(db), "r"(sd), "n"(TB), "n"(BOFF));
}

constexpr int K1_XN_BYTES = 16 * 9216;
constexpr int K1_OFF_RING = K1_XN_BYTES;
constexpr int K1_OFF_BIAS = K1_OFF_RING + 10 * 8192;
constexpr int K1_OFF_BAR = K1_OFF_BIAS + 576 * 2;
constexpr int K1_SMEM = K1_OFF_BAR + 768;
constexpr float QSCALE = 0.23570226039551584f * 1.4426950408889634f;

struct K1Ctx {
    uint32_t full0;
    uint32_t rel_addr;
    uint64_t descA, descB;
    uint32_t phase;
    __device__ __forceinline__ void begin_stage(int s) {
        mbar_wait(full0 + s * 8, phase);
        wg_fence();
    }
    __device__ __forceinline__ void release(int s) {
        if (rel_addr) asm volatile("mbarrier.arrive.shared::cluster.b64 _, [%0];" ::"r"(rel_addr + s * 8) : "memory");
    }
    __device__ __forceinline__ void end_stage(int s) {
        wg_commit();
        wg_wait<1>();
        release(s == 0 ? 8 : s - 1);
    }
};

__host__ __device__ constexpr int a_off(int ks) { return ((ks >> 2) * 1024 + (ks & 3) * 32) >> 4; }

template <int V> struct IC { static constexpr int value = V; };
template <int I, int N, class F> __device__ __forceinline__ void static_for(F&& f) {
    if constexpr (I < N) { f(IC<I>{}); static_for<I + 1, N>(f); }
}

template <bool A_RS, bool B_RS, class Epi>
__device__ __forceinline__ void tile_pair(K1Ctx& c, float (&accA)[32], float (&accB)[32], uint32_t (&h)[144], Epi&& epi) {
    static_for<0, 9>([&](auto sc) {
        constexpr int s = decltype(sc)::value;
        c.begin_stage(s);
        static_for<0, 8>([&](auto tc) {
            constexpr int kk = s * 8 + decltype(tc)::value, ks = kk % 36;
            constexpr int bo = (ks * 2048) >> 4;
            if constexpr (kk < 36) {
                if constexpr (A_RS) wgmma_rs_n64<1, bo>(accA, h[ks * 4], h[ks * 4 + 1], h[ks * 4 + 2], h[ks * 4 + 3], c.descB, ks != 0);
                else wgmma_ss_n64<1, a_off(ks), bo>(accA, c.descA, c.descB, ks != 0);
            } else {
                if constexpr (B_RS) wgmma_rs_n64<1, bo>(accB, h[ks * 4], h[ks * 4 + 1], h[ks * 4 + 2], h[ks * 4 + 3], c.descB, ks != 0);
                else wgmma_ss_n64<1, a_off(ks), bo>(accB, c.descA, c.descB, ks != 0);
            }
        });
        c.end_stage(s);
        epi(sc);
    });
    c.phase ^= 1;
}

template <int B0, int NB, int HOFF>
__device__ __forceinline__ void gelu_blocks(const float (&acc)[32], uint32_t (&h)[144], const uint32_t (&bq)[8]) {
#pragma unroll
    for (int b = B0; b < B0 + NB; b++) {
        const float b0 = bf_lo(bq[b]), b1 = bf_hi(bq[b]);
        h[HOFF + b * 2 + 0] = pack_bf16(gelu2(acc[b * 4 + 0] + b0), gelu2(acc[b * 4 + 1] + b1));
        h[HOFF + b * 2 + 1] = pack_bf16(gelu2(acc[b * 4 + 2] + b0), gelu2(acc[b * 4 + 3] + b1));
    }
}
__device__ __forceinline__ void load_bias(uint32_t (&bq)[8], uint32_t addr) {
    asm volatile("ld.shared.v4.u32 {%0, %1, %2, %3}, [%4];" : "=r"(bq[0]), "=r"(bq[1]), "=r"(bq[2]), "=r"(bq[3]) : "r"(addr));
    asm volatile("ld.shared.v4.u32 {%0, %1, %2, %3}, [%4 + 16];" : "=r"(bq[4]), "=r"(bq[5]), "=r"(bq[6]), "=r"(bq[7]) : "r"(addr));
}
template <int S> __device__ __forceinline__ void store_part(const float (&o)[32], uint4* p) {
    uint4 v;
    v.x = pack_bf16(o[S * 8 + 0], o[S * 8 + 1]); v.y = pack_bf16(o[S * 8 + 2], o[S * 8 + 3]);
    v.z = pack_bf16(o[S * 8 + 4], o[S * 8 + 5]); v.w = pack_bf16(o[S * 8 + 6], o[S * 8 + 7]);
    p[S * 256] = v;
}

constexpr int NCHUNK = 16;
constexpr int CHUNK_BYTES = KV_HEAD_BYTES / NCHUNK;
constexpr int SM_Q = 0;
constexpr int SM_KV = 32768;
constexpr int WO_PIECE = WO_TILE_BYTES / 9;
__host__ __device__ constexpr int sm_wo(int i) { return i == 0 ? 210944 : (i == 1 ? 0 : SM_KV + (i - 2) * WO_PIECE); }
constexpr int SM_EXCH = SM_KV + 7 * WO_PIECE;
constexpr int SM_RED = SM_KV + KV_HEAD_BYTES;

__device__ __forceinline__ float exp2_fixed(float y) {
    const float u = __uint_as_float(__float_as_uint(y) & 0xFF807FFFu) - 512.02545f;
    float t = fmaf(u, 0.019497588f, 0.114550486f);
    t = fmaf(t, u, -0.29839927f);
    return fmaf(t, u, y);
}
__device__ __forceinline__ uint32_t pack_fixed(float lo, float hi) { return __byte_perm(__float_as_uint(lo), __float_as_uint(hi), 0x6521); }

#define POLY_MODE 1
__device__ __forceinline__ uint32_t hfma2_bf16(uint32_t a, uint32_t b, uint32_t c) {
    uint32_t r;
    asm("fma.rn.bf16x2 %0, %1, %2, %3;" : "=r"(r) : "r"(a), "r"(b), "r"(c));
    return r;
}
__device__ __forceinline__ uint32_t exp2_packed(float y0, float y1, uint32_t one2) {
    const uint32_t w = pack_fixed(y0, y1);
    uint32_t m;
    asm("lop3.b32 %0, %1, 0x007F007F, %2, 0xEA;" : "=r"(m) : "r"(w), "r"(one2));
    const uint32_t d = hfma2_bf16(m, 0x3EF93EF9u, 0xBF38BF38u);
    const uint32_t e = hfma2_bf16(d, d, 0xBD71BD71u);
    return hfma2_bf16(w, e, w);
}
template <int NB>
__device__ __forceinline__ void softmax_fast(const float (&s)[NB * 4], uint32_t (&p)[NB * 2], uint32_t one2) {
#pragma unroll
    for (int b = 0; b < NB; b++) {
        if ((POLY_MASK >> (b & 7)) & 1) {
            p[b * 2 + 0] = exp2_packed(s[b * 4 + 0], s[b * 4 + 1], one2);
            p[b * 2 + 1] = exp2_packed(s[b * 4 + 2], s[b * 4 + 3], one2);
        } else {
            p[b * 2 + 0] = pack_bf16(ex2(s[b * 4 + 0]), ex2(s[b * 4 + 1]));
            p[b * 2 + 1] = pack_bf16(ex2(s[b * 4 + 2]), ex2(s[b * 4 + 3]));
        }
    }
}

constexpr int KV_TILE = CHUNK_BYTES / 16;
template <int OFF> __device__ __forceinline__ void issue_qk(float (&s)[64], uint64_t qd, uint64_t kd) {
    wgmma_ss_n128<0, 0, OFF + (8 << 16)>(s, qd, kd, 0);
    wgmma_ss_n128<0, 16, OFF + 32>(s, qd, kd, 1);
}
template <int OFF> __device__ __forceinline__ void issue_pv(float (&o)[12], const uint32_t (&p)[32], uint64_t vd) {
    static_for<0, 8>([&](auto kc) {
        constexpr int k = decltype(kc)::value;
        wgmma_rs_n24<1, OFF + k * (2 * KV_GROUP_BYTES / 16)>(o, p[k * 4], p[k * 4 + 1], p[k * 4 + 2], p[k * 4 + 3], vd, 1);
    });
}
__device__ __forceinline__ void store_o(float (&o)[12], int rt, int head, int wq, int lane) {
    const int g = lane >> 2, q = lane & 3;
    const float i0 = __fdividef(1.0f, __shfl_sync(~0u, o[8], lane | 3)), i1 = __fdividef(1.0f, __shfl_sync(~0u, o[10], lane | 3));
#pragma unroll
    for (int i = 0; i < 3; i++) {
        const int pc = head * 9 + (i < 2 ? i * 4 + q : 8);
        uint32_t* op = g_O + (((rt * 36 + (pc >> 3)) * 128 + wq * 32 + g * 4 + (pc & 3)) * 4 + ((pc >> 2) & 1) * 2);
        if (i < 2 || q == 2) *reinterpret_cast<uint2*>(op) = make_uint2(pack_bf16(o[i * 4] * i0, o[i * 4 + 1] * i0), pack_bf16(o[i * 4 + 2] * i1, o[i * 4 + 3] * i1));
    }
#pragma unroll
    for (int i = 0; i < 12; i++) o[i] = 0.f;
}
__device__ __forceinline__ void mbar_arrive(uint32_t b) { asm volatile("mbarrier.arrive.shared::cta.b64 _, [%0];" ::"r"(b) : "memory"); }
__device__ __forceinline__ void mbar_wait_sleep(uint32_t b, uint32_t ns) {
    uint32_t ok, spins = 0;
    while (true) {
        asm volatile("{\n.reg .pred p;\nmbarrier.try_wait.parity.shared::cta.b64 p, [%1], 0;\nselp.u32 %0, 1, 0, p;\n}\n" : "=r"(ok) : "r"(b) : "memory");
        if (ok) break;
        __nanosleep(ns);
        if (++spins > (1u << 21)) __trap();
    }
}
__device__ __forceinline__ void flag_signal(unsigned int* f) {
    __threadfence();
    atomicAdd(f, 1u);
}
__device__ __forceinline__ void flag_wait(const unsigned int* f, unsigned int target, unsigned int sleep_ns) {
    uint32_t v, spins = 0;
    while (true) {
        asm volatile("ld.acquire.gpu.global.u32 %0, [%1];" : "=r"(v) : "l"(f) : "memory");
        if (v >= target) break;
        if (sleep_ns) __nanosleep(sleep_ns);
        if (++spins > (1u << 21)) __trap();
    }
}
__device__ __forceinline__ uint32_t hadd2_bf16(uint32_t a, uint32_t b) {
    uint32_t r;
    asm("add.rn.bf16x2 %0, %1, %2;" : "=r"(r) : "r"(a), "r"(b));
    return r;
}
__device__ __forceinline__ uint4 hadd8_bf16(const uint4 a, const uint4 b) {
    return make_uint4(hadd2_bf16(a.x, b.x), hadd2_bf16(a.y, b.y), hadd2_bf16(a.z, b.z), hadd2_bf16(a.w, b.w));
}
__device__ __forceinline__ float sumsq2(uint32_t w) { return fmaf(bf_lo(w), bf_lo(w), bf_hi(w) * bf_hi(w)); }
__device__ __forceinline__ float sumsq8(const uint4 v) { return (sumsq2(v.x) + sumsq2(v.y)) + (sumsq2(v.z) + sumsq2(v.w)); }

enum { B_FULL = 0, B_EMPTY = 9, B_BASE = 18, B_XNDEAD = 19, B_QRDY = 20, B_FFN = 21, B_X = 22, B_KV = 38, B_FREE = 54, B_WO = 62, B_RED = 71, B_END = 77 };

__global__ void __cluster_dims__(2, 1, 1) __launch_bounds__(384, 1)
fused_kernel(const __grid_constant__ CUtensorMap tmX, const __grid_constant__ CUtensorMap tmQ3, const __grid_constant__ CUtensorMap tmQ1,
          const __grid_constant__ CUtensorMap tm1, const __grid_constant__ CUtensorMap tm2, const __grid_constant__ CUtensorMap tmP, const __nv_bfloat16* __restrict__ b1,
          const __nv_bfloat16* __restrict__ wo, const __nv_bfloat16* __restrict__ x, const __nv_bfloat16* __restrict__ b2,
          __nv_bfloat16* __restrict__ out, const uint64_t zero) {
    extern __shared__ __align__(1024) uint8_t smem[];
    const uint32_t sb = s2u(smem);
    const int tid = threadIdx.x, lane = tid & 31;
    const int warp = __shfl_sync(~0u, tid >> 5, 0);
    const uint32_t rank = blockIdx.x & 1;
    const int cl = blockIdx.x >> 1;
    const int rb = (cl & 7) * 2 + rank;
    const int j = cl >> 3;
    const uint32_t bar0 = sb + K1_OFF_BAR;
    const uint32_t full0 = bar0 + B_FULL * 8, empty0 = bar0 + B_EMPTY * 8, xbar0 = bar0 + B_X * 8;
    const int head = blockIdx.x >> 2, quarter = blockIdx.x & 3;
    const int rt = quarter * 8 + (head >> 2), ct = head & 3;
    volatile uint32_t* slow_flag = reinterpret_cast<volatile uint32_t*>(smem + K1_OFF_BAR + B_END * 8);

    if (warp < 8) {
        PROF(0);
        PROFT(48);
        if (lane == 0) {
            mbar_init(xbar0 + warp * 16, 1);
            mbar_init(xbar0 + warp * 16 + 8, 1);
            fence_barrier_init();
            mbar_expect(xbar0 + warp * 16, 9216);
            tma3d(sb + warp * 2 * 9216, &tmX, 0, rb * 128 + warp * 16, 0, xbar0 + warp * 16);
            mbar_expect(xbar0 + warp * 16 + 8, 9216);
            tma3d(sb + (warp * 2 + 1) * 9216, &tmX, 0, rb * 128 + warp * 16 + 8, 0, xbar0 + warp * 16 + 8);
        }
        __syncwarp();
        cluster_arrive();
        PROF(22);
        reg_alloc<240>();
        PROF(23);
#pragma unroll 1
        for (int p = 0; p < 4; p++) {
            mbar_wait(xbar0 + warp * 16 + (p >> 1) * 8, 0);
            PROF(24 + p);
            uint4* row = reinterpret_cast<uint4*>(smem + (warp * 2 + (p >> 1)) * 9216 + (p & 1) * 512 + lane * 16);
            float f[72];
#pragma unroll
            for (int i = 0; i < 9; i++) {
                const uint4 v = row[i * 64];
                f[i * 8 + 0] = bf_lo(v.x); f[i * 8 + 1] = bf_hi(v.x); f[i * 8 + 2] = bf_lo(v.y); f[i * 8 + 3] = bf_hi(v.y);
                f[i * 8 + 4] = bf_lo(v.z); f[i * 8 + 5] = bf_hi(v.z); f[i * 8 + 6] = bf_lo(v.w); f[i * 8 + 7] = bf_hi(v.w);
            }
            float s0 = 0.f, s1 = 0.f, s2 = 0.f, s3 = 0.f;
#pragma unroll
            for (int i = 0; i < 72; i += 4) { s0 += f[i]; s1 += f[i + 1]; s2 += f[i + 2]; s3 += f[i + 3]; }
            float sm = (s0 + s1) + (s2 + s3);
            sm += __shfl_xor_sync(~0u, sm, 1); sm += __shfl_xor_sync(~0u, sm, 2); sm += __shfl_xor_sync(~0u, sm, 4);
            const float mean = sm * (1.0f / DM);
            s0 = s1 = s2 = s3 = 0.f;
#pragma unroll
            for (int i = 0; i < 72; i += 4) {
                f[i] -= mean; f[i + 1] -= mean; f[i + 2] -= mean; f[i + 3] -= mean;
                s0 = fmaf(f[i], f[i], s0); s1 = fmaf(f[i + 1], f[i + 1], s1);
                s2 = fmaf(f[i + 2], f[i + 2], s2); s3 = fmaf(f[i + 3], f[i + 3], s3);
            }
            float sq = (s0 + s1) + (s2 + s3);
            sq += __shfl_xor_sync(~0u, sq, 1); sq += __shfl_xor_sync(~0u, sq, 2); sq += __shfl_xor_sync(~0u, sq, 4);
            const float rstd = rsqrtf(sq * (1.0f / DM) + 1e-5f);
#pragma unroll
            for (int i = 0; i < 9; i++) {
                uint4 o;
                o.x = pack_bf16(f[i * 8 + 0] * rstd, f[i * 8 + 1] * rstd);
                o.y = pack_bf16(f[i * 8 + 2] * rstd, f[i * 8 + 3] * rstd);
                o.z = pack_bf16(f[i * 8 + 4] * rstd, f[i * 8 + 5] * rstd);
                o.w = pack_bf16(f[i * 8 + 6] * rstd, f[i * 8 + 7] * rstd);
                row[i * 64] = o;
            }
        }
        PROF(28);
        const int wg = warp >> 2, wq = warp & 3;
        fence_proxy_async();
        named_bar_sync(1 + wg, 128);
        cluster_wait();
        PROF(1);

        const int g = lane >> 2, q = lane & 3;
        K1Ctx c;
        c.full0 = full0;
        c.rel_addr = 0;
        c.descA = mk_desc(zero, sb + wg * 8 * 9216, 16, 9216, 1);
        c.descB = mk_desc(zero, sb + K1_OFF_RING, 2048, 1024, 1);
        c.phase = 0;
        uint32_t biasq = sb + K1_OFF_BIAS + q * 32;
        uint32_t bq[8];

        uint32_t h[144];
        float accA[32], accB[32];
        {
            float accQ[108];
            uint32_t rel = 0;
            if (lane == 0 && wq < 2) asm("mapa.shared::cluster.u32 %0, %1, %2;" : "=r"(rel) : "r"(empty0), "r"(wq));
#pragma unroll 1
            for (int r = 0; r < 2; r++) {
                const uint64_t dae = c.descA + (r ? a_off(18) : 0), dao = c.descA + (r ? a_off(20) : a_off(2));
                static_for<0, 9>([&](auto sc) {
                    constexpr int s = decltype(sc)::value;
                    c.begin_stage(s);
                    wgmma_ss_n216<1, (s >> 1) * 64, ((2 * s) % 9) * 512>(accQ, (s & 1) ? dao : dae, c.descB, (r | s) != 0);
                    wgmma_ss_n216<1, (s >> 1) * 64 + 2, ((2 * s + 1) % 9) * 512>(accQ, (s & 1) ? dao : dae, c.descB, 1);
                    c.end_stage(s);
                    c.rel_addr = rel;
                });
                c.phase ^= 1;
            }
            PROF(2);
            uint32_t rel9[9];
#pragma unroll
            for (int i9 = 0; i9 < 9; i9++) {
                const int p = 4 * i9 + q, hh = (p * 57) >> 9, r = p - 9 * hh;
                rel9[i9] = hh * KV_HEAD_BYTES + (r < 8 ? (r >> 2) * 128 + (r & 3) * 4 : 0);
            }
            uint32_t gb = 0, o2 = 0;
            float scl0 = 1.f, scl1 = 1.f;
            tile_pair<false, false>(c, accA, accB, h, [&](auto sc) {
                constexpr int s = decltype(sc)::value;
                if constexpr (s == 0) reg_fence(accQ);
                if constexpr (s < 6) {
                    constexpr int grp = s / 2, part = s % 2;
                    if constexpr (part == 0) {
                        const int G = 3 * j + grp, type = G >> 3;
                        gb = (G & 7) * 4 * KV_HEAD_BYTES + (rb * 16 + warp * 2) * KV_GROUP_BYTES + g * 16 + (type == 0 ? Q_OFFSET : (type == 2 ? 256 : 0));
                        o2 = type == 0 ? 256 : (type == 2 ? 264 : 512);
                        scl0 = type == 0 ? QSCALE : ((type == 1 && ((POLY_MASK >> (wq * 2)) & 1)) ? 2.f : 1.f);
                        scl1 = type == 0 ? QSCALE : ((type == 1 && ((POLY_MASK >> (wq * 2 + 1)) & 1)) ? 2.f : 1.f);
                    }
#pragma unroll
                    for (int i9 = part * 5; i9 < (part ? 9 : 5); i9++) {
                        const int b = grp * 9 + i9;
                        uint32_t off = gb + rel9[i9];
                        if (i9 >= 2 && (i9 & 1) == 0) off += (q == i9 / 2 - 1) ? o2 : 0;
                        *reinterpret_cast<uint32_t*>(g_QKV + off) = pack_bf16(accQ[b * 4] * scl0, accQ[b * 4 + 1] * scl0);
                        *reinterpret_cast<uint32_t*>(g_QKV + off + KV_GROUP_BYTES) = pack_bf16(accQ[b * 4 + 2] * scl1, accQ[b * 4 + 3] * scl1);
                    }
                    if constexpr (s == 5) asm volatile("bar.arrive 3, 352;" ::: "memory");
                }
                if constexpr (s == 4) { named_bar_sync(4, 352); load_bias(bq, biasq); }
                if constexpr (s == 5) reg_fence(accA);
                if constexpr (s >= 5) gelu_blocks<(s - 5) * 2, 2, 96>(accA, h, bq);
                if constexpr (s == 8) load_bias(bq, biasq + 128);
            });
        }
        PROF(3);
#pragma unroll
        for (int i = 32; i < 96; i++) asm volatile("mov.u32 %0, 0;" : "=r"(h[i]));
#pragma unroll 1
        for (int p = 1; p < 4; p++) {
            biasq += 256;
            tile_pair<false, false>(c, accA, accB, h, [&](auto sc) {
                constexpr int s = decltype(sc)::value;
                if constexpr (s == 0) {
                    reg_fence(accB);
#pragma unroll
                    for (int i = 0; i < 80; i++) h[i] = h[i + 32];
                }
                if constexpr (s < 4) gelu_blocks<s * 2, 2, 80>(accB, h, bq);
                if constexpr (s == 4) load_bias(bq, biasq);
                if constexpr (s == 5) reg_fence(accA);
                if constexpr (s >= 5) gelu_blocks<(s - 5) * 2, 2, 96>(accA, h, bq);
                if constexpr (s == 8) load_bias(bq, biasq + 128);
            });
        }
        PROF(4);
        tile_pair<false, true>(c, accA, accB, h, [&](auto sc) {
            constexpr int s = decltype(sc)::value;
            if constexpr (s == 0) reg_fence(accB);
            if constexpr (s < 4) gelu_blocks<s * 2, 2, 112>(accB, h, bq);
            if constexpr (s == 4) load_bias(bq, biasq + 256);
            if constexpr (s == 5) { reg_fence(accA); if (tid == wg * 128) mbar_arrive(bar0 + B_XNDEAD * 8); }
            if constexpr (s == 5 || s == 6) gelu_blocks<(s - 5) * 3, 3, 128>(accA, h, bq);
            if constexpr (s == 7) gelu_blocks<6, 2, 128>(accA, h, bq);
            if constexpr (s == 3 || s == 7) reg_fence(h);
        });
        PROF(5);
        uint4* pout = g_part + j * SLAB + rb * 36 * 256 + tid;
#pragma unroll 1
        for (int p = 0; p < 4; p++) {
            tile_pair<true, true>(c, accA, accB, h, [&](auto sc) {
                constexpr int s = decltype(sc)::value;
                if constexpr (s == 0) reg_fence(accB);
                if constexpr (s < 4) store_part<s>(accB, pout);
                if constexpr (s == 5) reg_fence(accA);
                if constexpr (s >= 5) store_part<s - 5>(accA, pout + 1024);
            });
            pout += 2048;
            PROF(6 + p);
        }
        wg_wait<0>();
        c.release(8);
        reg_fence(accB);
        store_part<0>(accB, pout); store_part<1>(accB, pout); store_part<2>(accB, pout); store_part<3>(accB, pout);
        __syncwarp();
        if (lane == 0) mbar_arrive(bar0 + B_FFN * 8);
        PROF(10);
        PROFT(49);

        mbar_wait(bar0 + B_QRDY * 8, 0);
        const uint32_t slow = __any_sync(~0u, *slow_flag != 0);
        const uint64_t kd0 = mk_desc(zero, sb + SM_KV, 0, KV_GROUP_BYTES, 0);
        const uint64_t vd0 = mk_desc(zero, sb + SM_KV + 256, KV_GROUP_BYTES, 128, 0);
        const uint64_t qd0 = mk_desc(zero, sb + SM_Q + wg * 4096, 128, 512, 0);
        const uint32_t kvbar = bar0 + B_KV * 8;
        float o[12];
#pragma unroll
        for (int i = 0; i < 12; i++) o[i] = 0.f;
        PROF(16);
        PROFT(50);
        if (!slow) {
            const uint32_t one2 = 0x3F803F80u + (uint32_t)zero;
            float s0[64], s1[64];
            uint32_t p0[32], p1[32];
            mbar_wait(kvbar, 0);
            reg_fence(o);
            wg_fence();
            issue_qk<0>(s0, qd0, kd0);
            wg_commit();
            mbar_wait(kvbar + 8, 0);
            wg_fence();
            issue_qk<KV_TILE>(s1, qd0, kd0);
            wg_commit();
            uint64_t qd = qd0;
            const uint32_t fre = (tid == wg * 128) ? bar0 + B_FREE * 8 - 8 : 0;
#pragma unroll 1
            for (int pass = 0; pass < 4; pass++) {
                uint64_t vd = vd0, kdn = kd0 + 2 * KV_TILE;
                uint32_t bn = kvbar + 16;
#pragma unroll 1
                for (int it = 0; it < 8; it++) {
                    if (it == 7) { kdn = kd0; bn = kvbar; qd += 512; }
                    wg_wait<1>();
                    reg_fence(s0);
                    if (pass == 3 && it > 0 && fre) mbar_arrive(fre + it * 8);
                    softmax_fast<16>(s0, p0, one2);
                    reg_fence(p0);
                    if (it == 0 && pass != 0) {
                        wg_wait<0>();
                        reg_fence(o);
                        store_o(o, quarter * 8 + pass * 2 - 2 + wg, head, wq, lane);
                        reg_fence(o);
                    }
                    mbar_wait(bn, 0);
                    wg_fence();
                    issue_pv<0>(o, p0, vd);
                    issue_qk<0>(s0, qd, kdn);
                    wg_commit();
                    wg_wait<1>();
                    reg_fence(s1);
                    softmax_fast<16>(s1, p1, one2);
                    reg_fence(p1);
                    mbar_wait(bn + 8, 0);
                    wg_fence();
                    issue_pv<KV_TILE>(o, p1, vd);
                    issue_qk<KV_TILE>(s1, qd, kdn);
                    wg_commit();
                    vd += 2 * KV_TILE; kdn += 2 * KV_TILE; bn += 16;
                }
                if (pass == 0) PROF(17);
            }
            wg_wait<0>();
            reg_fence(o);
            reg_fence(s0);
            reg_fence(s1);
            store_o(o, quarter * 8 + 6 + wg, head, wq, lane);
        } else {
#pragma unroll 1
            for (int pass = 0; pass < 4; pass++) {
                float m0 = -INFINITY, m1 = -INFINITY;
                float s[64];
                uint32_t p[32];
#pragma unroll 1
                for (int t = 0; t < 16; t++) {
                    mbar_wait(kvbar + t * 8, 0);
                    wg_fence();
                    issue_qk<0>(s, qd0 + pass * 512, kd0 + t * KV_TILE);
                    wg_commit();
                    wg_wait<0>();
                    reg_fence(s);
                    float a0 = m0, a1 = m1;
#pragma unroll
                    for (int k = 0; k < 16; k++) {
                        if ((POLY_MASK >> (k & 7)) & 1) {
#pragma unroll
                            for (int i = 0; i < 4; i++) s[k * 4 + i] *= 0.5f;
                        }
                        a0 = fmaxf(a0, fmaxf(s[k * 4 + 0], s[k * 4 + 1]));
                        a1 = fmaxf(a1, fmaxf(s[k * 4 + 2], s[k * 4 + 3]));
                    }
                    a0 = fmaxf(a0, __shfl_xor_sync(~0u, a0, 1)); a1 = fmaxf(a1, __shfl_xor_sync(~0u, a1, 1));
                    a0 = fmaxf(a0, __shfl_xor_sync(~0u, a0, 2)); a1 = fmaxf(a1, __shfl_xor_sync(~0u, a1, 2));
                    const float r0 = ex2(m0 - a0), r1 = ex2(m1 - a1);
                    m0 = a0; m1 = a1;
#pragma unroll
                    for (int i = 0; i < 3; i++) { o[i * 4] *= r0; o[i * 4 + 1] *= r0; o[i * 4 + 2] *= r1; o[i * 4 + 3] *= r1; }
#pragma unroll
                    for (int k = 0; k < 16; k++) {
                        p[k * 2 + 0] = pack_bf16(ex2(s[k * 4 + 0] - m0), ex2(s[k * 4 + 1] - m0));
                        p[k * 2 + 1] = pack_bf16(ex2(s[k * 4 + 2] - m1), ex2(s[k * 4 + 3] - m1));
                    }
                    reg_fence(p);
                    reg_fence(o);
                    wg_fence();
                    issue_pv<0>(o, p, vd0 + t * KV_TILE);
                    wg_commit();
                    wg_wait<0>();
                    reg_fence(o);
                }
                store_o(o, quarter * 8 + pass * 2 + wg, head, wq, lane);
            }
            if (tid == wg * 128)
                for (int i = 0; i < 7; i++) mbar_arrive(bar0 + (B_FREE + i) * 8);
        }
        PROF(18);
        PROFT(51);

        const int t128 = tid & 127;
        named_bar_sync(1 + wg, 128);
        if (t128 == 0) flag_signal(&g_flags.o_done[quarter]);
        const size_t orow = (size_t)(rt * 64 + wq * 16 + g + wg * 8) * DM + ct * 144 + q * 2;
        float bs[36];
        {
            uint32_t xv[18], bv[18];
            uint2 fv[9];
#pragma unroll
            for (int i = 0; i < 18; i++) {
                xv[i] = __ldg(reinterpret_cast<const uint32_t*>(x + orow) + i * 4);
                bv[i] = __ldg(reinterpret_cast<const uint32_t*>(b2 + ct * 144 + q * 2) + i * 4);
            }
            mbar_wait(bar0 + B_BASE * 8, 0);
#pragma unroll
            for (int i = 0; i < 9; i++) fv[i] = __ldcg(g_ffn + blockIdx.x * 2304 + (wg * 9 + i) * 128 + t128);
#pragma unroll
            for (int i = 0; i < 18; i++) {
                const uint32_t f = (i & 1) ? fv[i >> 1].y : fv[i >> 1].x;
                bs[i * 2] = fmaf(bf_lo(f), 0.5f, bf_lo(xv[i]) + bf_lo(bv[i]));
                bs[i * 2 + 1] = fmaf(bf_hi(f), 0.5f, bf_hi(xv[i]) + bf_hi(bv[i]));
            }
        }
        if (t128 == 0) flag_wait(&g_flags.o_done[quarter], 64, 0);
        named_bar_sync(1 + wg, 128);
        PROF(19);
        uint4 af[18];
        {
            const uint4* ap = reinterpret_cast<const uint4*>(g_O) + (rt * 36 + wg * 18) * 128 + t128;
#pragma unroll
            for (int k = 0; k < 18; k++) af[k] = __ldcg(ap + k * 128);
        }
        float acc[72];
        const uint64_t wd0 = mk_desc(zero, sb, 2304, 128, 0), wd1 = wd0 + wg * ((18 * 4608) >> 4);
#pragma unroll 1
        for (int i = 0; i < 5; i++) mbar_wait(bar0 + (B_WO + wg * 4 + i) * 8, 0);
        wg_fence();
        static_for<0, 18>([&](auto kc) {
            constexpr int k = decltype(kc)::value;
            if constexpr (k < 8) {
                constexpr int o0 = (sm_wo(k >> 2) + (k & 3) * 4608) >> 4, o1 = (SM_KV + (k + 10) * 4608) >> 4;
                wgmma_rs_n144<1, 0>(acc, af[k].x, af[k].y, af[k].z, af[k].w, wd0 + (wg ? o1 : o0), k != 0);
            } else {
                wgmma_rs_n144<1, (SM_KV + (k - 8) * 4608) / 16>(acc, af[k].x, af[k].y, af[k].z, af[k].w, wd1, 1);
            }
        });
        wg_commit();
        wg_wait<0>();
        reg_fence(acc);
        PROF(20);
        {
            float4* ex = reinterpret_cast<float4*>(smem + SM_EXCH) + t128;
#pragma unroll
            for (int i = 0; i < 9; i++) {
                const float4 lo = make_float4(acc[i * 8], acc[i * 8 + 1], acc[i * 8 + 4], acc[i * 8 + 5]);
                const float4 hi = make_float4(acc[i * 8 + 2], acc[i * 8 + 3], acc[i * 8 + 6], acc[i * 8 + 7]);
                ex[(wg * 9 + i) * 128] = wg ? lo : hi;
                const float4 own = wg ? hi : lo;
                bs[i * 4] += own.x; bs[i * 4 + 1] += own.y; bs[i * 4 + 2] += own.z; bs[i * 4 + 3] += own.w;
            }
            named_bar_sync(5, 256);
            uint32_t* op = reinterpret_cast<uint32_t*>(out + orow);
#pragma unroll
            for (int i = 0; i < 9; i++) {
                const float4 v = ex[((wg ^ 1) * 9 + i) * 128];
                op[i * 8] = pack_bf16(bs[i * 4] + v.x, bs[i * 4 + 1] + v.y);
                op[i * 8 + 4] = pack_bf16(bs[i * 4 + 2] + v.z, bs[i * 4 + 3] + v.w);
            }
        }
        PROF(21);
        PROFT(52);
        if (tid == 0) {
            if (atomicAdd(&g_flags.exited, 1u) == gridDim.x - 1) {
                unsigned int* f = reinterpret_cast<unsigned int*>(&g_flags);
#pragma unroll 1
                for (int i = 0; i < (int)(sizeof(Flags) / 4); i++) f[i] = 0;
            }
        }
    } else {
        reg_dealloc<24>();
        if (warp == 8 && lane == 0) {
            prefetch_tmap(&tmQ3); prefetch_tmap(&tmQ1); prefetch_tmap(&tm1); prefetch_tmap(&tm2);
            #pragma unroll 1
            for (int i = 0; i < 9; i++) { mbar_init(full0 + i * 8, 1); mbar_init(empty0 + i * 8, 4); mbar_init(bar0 + (B_WO + i) * 8, 1); }
            mbar_init(bar0 + B_BASE * 8, 3); mbar_init(bar0 + B_XNDEAD * 8, 2); mbar_init(bar0 + B_QRDY * 8, 3); mbar_init(bar0 + B_FFN * 8, 8);
#pragma unroll 1
            for (int i = 0; i < 16; i++) { mbar_init(bar0 + (B_KV + i) * 8, 1); mbar_init(bar0 + (B_FREE + (i & 7)) * 8, 2); if (i < 6) mbar_init(bar0 + (B_RED + i) * 8, 1); }
            *slow_flag = 0;
            fence_barrier_init();
        }
        __syncwarp();
        cluster_arrive();
        cluster_wait();
        const uint8_t* kvsrc = g_QKV + (size_t)head * KV_HEAD_BYTES;
        if (warp == 8) {
            if (lane == 0) {
                int st = 0, u = rank, tile = -4;
                int es = 5;
                uint32_t eph = 1;
#pragma unroll 1
                for (int n = 0; n < 99; n++) {
                    mbar_wait(empty0 + es * 8, eph);
                    const uint32_t fb = full0 + st * 8, dst = sb + K1_OFF_RING + u * 8192;
                    mbar_expect(fb, 16384);
                    if (tile < 0) {
                        tma3d_mc(dst, &tmQ3, j * 216, n * 32 + rank * 16, 0, fb, 3);
                        tma2d_mc(dst + 6144, &tmQ1, j * 216 + 192, n * 32 + rank * 16, fb, 3);
                    } else if (tile < 9) {
                        tma2d_mc(dst, &tm1, j * 576 + tile * 64, u * 64, fb, 3);
                    } else {
                        tma2d_mc(dst, &tm2, (tile - 9) * 64, j * 576 + u * 64, fb, 3);
                    }
                    u += 2;
                    if (u >= 9) { u -= 9; tile++; }
                    if (++st == 9) st = 0;
                    if (++es == 9) { es = 0; eph ^= 1; }
                }
                mbar_wait(empty0 + 8 * 8, 0);
                mbar_wait(bar0 + B_QRDY * 8, 0);
                asm volatile("fence.proxy.async;" ::: "memory");
#pragma unroll 1
                for (int i = 11; i < NCHUNK; i++) {
                    mbar_expect(bar0 + (B_KV + i) * 8, CHUNK_BYTES);
                    bulk_load(sb + SM_KV + i * CHUNK_BYTES, kvsrc + i * CHUNK_BYTES, CHUNK_BYTES, bar0 + (B_KV + i) * 8);
                }
#pragma unroll 1
                for (int i = 0; i < 9; i++) {
                    if (i == 0) mbar_wait_sleep(bar0 + B_BASE * 8, 500);
                    if (i > 0) {
                        const int f = i == 1 ? 0 : ((i - 1) * 9 + 4) / 10;
                        mbar_wait_sleep(bar0 + (B_FREE + f) * 8, i == 1 ? 500 : 50);
                    }
                    mbar_expect(bar0 + (B_WO + i) * 8, WO_PIECE);
                    bulk_load(sb + (i == 0 ? sm_wo(0) : (i == 1 ? sm_wo(1) : SM_KV + (i - 2) * WO_PIECE)), g_Wo + ct * WO_TILE_BYTES + i * WO_PIECE, WO_PIECE,
                              bar0 + (B_WO + i) * 8);
                }
            }
        } else {
            const int ht = tid - 288;
            if (ht < 72) {
                const uint4 v = __ldg(reinterpret_cast<const uint4*>(b1 + j * 576) + ht);
                uint32_t* sbias = reinterpret_cast<uint32_t*>(smem + K1_OFF_BIAS) + (ht >> 3) * 32 + (ht & 7);
                sbias[0] = v.x; sbias[8] = v.y; sbias[16] = v.z; sbias[24] = v.w;
            }
            asm volatile("bar.arrive 4, 352;" ::: "memory");
            PROFH(37);
#pragma unroll 1
            for (int i = ht; i < 512; i += 96) {
                const int key = i & 127;
                uint8_t* p = g_QKV + (size_t)(j * 4 + (i >> 7)) * KV_HEAD_BYTES + (rb * 16 + (key >> 3)) * KV_GROUP_BYTES + 512 + (key & 7) * 16;
                *reinterpret_cast<uint32_t*>(p + 4) = ((POLY_MASK >> ((key >> 3) & 7)) & 1) ? 0x3F804000u : 0x00003F80u;
                *reinterpret_cast<uint32_t*>(p + 12) = 0x00003F80u;
            }
#pragma unroll 2
            for (int i = blockIdx.x * 324 + ht; i < blockIdx.x * 324 + 324; i += 96) {
                const int k = i / 72, nc = i - k * 72, c4 = nc / 18;
                *reinterpret_cast<uint4*>(g_Wo + c4 * WO_TILE_BYTES + (k >> 3) * 2304 + (nc - c4 * 18) * 128 + (k & 7) * 16) =
                    __ldg(reinterpret_cast<const uint4*>(wo) + i);
            }
            PROFH(38);
            named_bar_sync(3, 352);
            if (ht == 0) {
                flag_signal(&g_flags.qkv_stored[rb]);
                flag_wait(&g_flags.qkv_stored[rb], 8, 200);
            }
            named_bar_sync(7, 96);
            PROFH(39);
#pragma unroll 1
            for (int i = warp - 9; i < 16; i += 3) {
                const int hd = j * 4 + (i >> 2), key = (i & 3) * 32 + lane;
                const uint8_t* p = g_QKV + (size_t)hd * KV_HEAD_BYTES + (rb * 16 + (key >> 3)) * KV_GROUP_BYTES + (key & 7) * 16;
                const uint4 a = __ldcg(reinterpret_cast<const uint4*>(p)), b = __ldcg(reinterpret_cast<const uint4*>(p + 128));
                float n = sumsq2(__ldcg(reinterpret_cast<const uint32_t*>(p + 512))) + sumsq8(a) + sumsq8(b);
                if ((POLY_MASK >> ((key >> 3) & 7)) & 1) n *= 0.25f;
#pragma unroll
                for (int o = 16; o; o >>= 1) n = fmaxf(n, __shfl_xor_sync(~0u, n, o));
                if (lane == 0) g_kmax[hd * 64 + rb * 4 + (i & 3)] = n;
            }
            named_bar_sync(7, 96);
            PROFH(40);
            if (ht == 0) {
                flag_signal(&g_flags.kv_ready);
                flag_wait(&g_flags.kv_ready, 128, 300);
                mbar_wait_sleep(bar0 + B_XNDEAD * 8, 300);
            }
            named_bar_sync(7, 96);
            PROFH(41);
            float kmax2;
            {
                const float2 v = __ldcg(reinterpret_cast<const float2*>(g_kmax + head * 64 + lane * 2));
                kmax2 = fmaxf(v.x, v.y);
#pragma unroll
                for (int o = 16; o; o >>= 1) kmax2 = fmaxf(kmax2, __shfl_xor_sync(~0u, kmax2, o));
            }
            asm volatile("fence.proxy.async;" ::: "memory");
            int chunk = warp - 9;
#pragma unroll 1
            for (int r = ht; r < 512; r += 96) {
                if (lane == 0 && chunk < 11) {
                    mbar_expect(bar0 + (B_KV + chunk) * 8, CHUNK_BYTES);
                    bulk_load(sb + SM_KV + chunk * CHUNK_BYTES, kvsrc + chunk * CHUNK_BYTES, CHUNK_BYTES, bar0 + (B_KV + chunk) * 8);
                }
                chunk += 3;
                const uint8_t* p = kvsrc + Q_OFFSET + (quarter * 64 + (r >> 3)) * KV_GROUP_BYTES + (r & 7) * 16;
                const uint4 a = __ldcg(reinterpret_cast<const uint4*>(p)), b = __ldcg(reinterpret_cast<const uint4*>(p + 128));
                const uint32_t e = __ldcg(reinterpret_cast<const uint32_t*>(p + 256));
                const float cc = sqrtf((sumsq2(e) + sumsq8(a) + sumsq8(b)) * kmax2) * 1.02f;
                if (!(cc <= 58.f)) *slow_flag = 1;
                uint4* dst = reinterpret_cast<uint4*>(smem + SM_Q + (r >> 3) * 512 + (r & 7) * 16);
                dst[0] = a;
                dst[8] = b;
                dst[16] = make_uint4(e, pack_bf16(-cc, 768.f), 0u, 0u);
                dst[24] = make_uint4(0u, POLY_MODE ? 0xBFFF0000u : 0xC0000000u, 0u, 0u);
            }
            named_bar_sync(7, 96);
            if (*slow_flag) {
#pragma unroll 1
                for (int r = ht; r < 512; r += 96) {
                    uint32_t* dst = reinterpret_cast<uint32_t*>(smem + SM_Q + (r >> 3) * 512 + (r & 7) * 16);
                    dst[65] = 0u;
                    dst[97] = 0u;
                }
            }
            fence_proxy_async();
            __syncwarp();
            if (lane == 0) mbar_arrive(bar0 + B_QRDY * 8);
            PROFH(42);
            if (ht == 0) {
                mbar_wait_sleep(bar0 + B_FFN * 8, 300);
                flag_signal(&g_flags.ffn_done[rb]);
                flag_wait(&g_flags.ffn_done[rt >> 1], 8, 300);
            }
            named_bar_sync(7, 96);
            {
                const int w3 = warp - 9;
                const uint32_t rbar = bar0 + (B_RED + w3 * 2) * 8, rbuf = SM_RED + w3 * 8192;
                const int u0 = ((rt >> 1) * 36 + ct * 9) * 256 + (rt & 1) * 128;
                mbar_wait_sleep(bar0 + (B_KV + 15) * 8, 500);
                asm volatile("fence.proxy.async;" ::: "memory");
#pragma unroll 1
                for (int i = -2; i < 12; i++) {
                    if (i >= 0) {
                        __nanosleep(400);
                        mbar_wait(rbar + (i & 1) * 8, (i >> 1) & 1);
                        const uint4* sp = reinterpret_cast<const uint4*>(smem + rbuf + (i & 1) * 4096) + lane;
                        const uint4 v = hadd8_bf16(hadd8_bf16(hadd8_bf16(sp[0], sp[32]), hadd8_bf16(sp[64], sp[96])),
                                                   hadd8_bf16(hadd8_bf16(sp[128], sp[160]), hadd8_bf16(sp[192], sp[224])));
                        uint2* fp = g_ffn + blockIdx.x * 2304 + (i * 3 + w3) * 32 + lane;
                        fp[0] = make_uint2(v.x, v.z);
                        fp[1152] = make_uint2(v.y, v.w);
                    }
                    __syncwarp();
                    if (lane == 0 && i < 10) {
                        const int bx = (i + 2) * 3 + w3;
                        mbar_expect(rbar + (i & 1) * 8, 4096);
                        tma2d(sb + rbuf + (i & 1) * 4096, &tmP, (u0 + (bx >> 2) * 256 + (bx & 3) * 32) * 2, 0, rbar + (i & 1) * 8);
                    }
                }
            }
            __syncwarp();
            if (lane == 0) mbar_arrive(bar0 + B_BASE * 8);
            PROFH(43);
        }
    }
}

typedef CUresult (*EncodeFn)(CUtensorMap*, CUtensorMapDataType, cuuint32_t, void*, const cuuint64_t*, const cuuint64_t*, const cuuint32_t*,
                             const cuuint32_t*, CUtensorMapInterleave, CUtensorMapSwizzle, CUtensorMapL2promotion, CUtensorMapFloatOOBfill);

void make_map(EncodeFn fn, CUtensorMap* m, const void* base, int rank, const cuuint64_t* dims, const cuuint64_t* strides, const cuuint32_t* box) {
    cuuint32_t es[3] = {1, 1, 1};
    fn(m, CU_TENSOR_MAP_DATA_TYPE_BFLOAT16, rank, const_cast<void*>(base), dims, strides, box, es, CU_TENSOR_MAP_INTERLEAVE_NONE,
       CU_TENSOR_MAP_SWIZZLE_128B, CU_TENSOR_MAP_L2_PROMOTION_L2_256B, CU_TENSOR_MAP_FLOAT_OOB_FILL_NONE);
}

}

extern "C" void kernel_launch(void* const* d_in, const int* in_sizes, int n_in, void* d_out, int out_size) {
    const __nv_bfloat16* x = (const __nv_bfloat16*)d_in[0];
    const __nv_bfloat16* wqkv = (const __nv_bfloat16*)d_in[1];
    const __nv_bfloat16* wo = (const __nv_bfloat16*)d_in[2];
    const __nv_bfloat16* w1 = (const __nv_bfloat16*)d_in[4];
    const __nv_bfloat16* b1 = (const __nv_bfloat16*)d_in[5];
    const __nv_bfloat16* w2 = (const __nv_bfloat16*)d_in[6];
    const __nv_bfloat16* b2 = (const __nv_bfloat16*)d_in[7];
    __nv_bfloat16* out = (__nv_bfloat16*)d_out;

    EncodeFn fn = nullptr;
    cudaDriverEntryPointQueryResult qr;
    cudaGetDriverEntryPoint("cuTensorMapEncodeTiled", (void**)&fn, cudaEnableDefault, &qr);
    CUtensorMap tmX, tmQ3, tmQ1, tm1, tm2, tmP;
    {
        void* gp = nullptr;
        cudaGetSymbolAddress(&gp, g_part);
        cuuint64_t d[2] = {SLAB * 2, 8}, s[1] = {SLAB * 16};
        cuuint32_t b[2] = {64, 8}, es[2] = {1, 1};
        fn(&tmP, CU_TENSOR_MAP_DATA_TYPE_INT64, 2, gp, d, s, b, es, CU_TENSOR_MAP_INTERLEAVE_NONE, CU_TENSOR_MAP_SWIZZLE_NONE,
           CU_TENSOR_MAP_L2_PROMOTION_NONE, CU_TENSOR_MAP_FLOAT_OOB_FILL_NONE);
    }
    {
        cuuint64_t d[3] = {64, SEQ, 9}, s[2] = {DM * 2, 128};
        cuuint32_t b[3] = {64, 8, 9};
        make_map(fn, &tmX, x, 3, d, s, b);
    }
    {
        cuuint64_t d[3] = {3 * DM, DM, 3}, s[2] = {3 * DM * 2, 128};
        cuuint32_t b[3] = {64, 16, 3};
        make_map(fn, &tmQ3, wqkv, 3, d, s, b);
        make_map(fn, &tmQ1, wqkv, 2, d, s, b);
    }
    {
        cuuint64_t d[2] = {FF, DM}, s[1] = {FF * 2};
        cuuint32_t b[2] = {64, 64};
        make_map(fn, &tm1, w1, 2, d, s, b);
        cuuint64_t d2[2] = {DM, FF}, s2[1] = {DM * 2};
        make_map(fn, &tm2, w2, 2, d2, s2, b);
    }
    cudaFuncSetAttribute(fused_kernel, cudaFuncAttributeMaxDynamicSharedMemorySize, K1_SMEM);
    fused_kernel<<<128, 384, K1_SMEM, cudaStreamPerThread>>>(tmX, tmQ3, tmQ1, tm1, tm2, tmP, b1, wo, x, b2, out, 0ull);
}
```

```cpp
#include <cuda_runtime.h>
#include <cuda_bf16.h>
#include <cuda.h>
#include <stdint.h>

#define PROF(i) do { } while (0)
#define PROFT(i) do { } while (0)
#define PROFH(i) do { } while (0)
#define PROF_WG 0

namespace {

constexpr int SEQ = 2048, DM = 576, FF = 4608, NH = 32, DH = 18;

constexpr int KV_GROUP_BYTES = 5 * 128;
constexpr int KV_HEAD_BYTES = (SEQ / 8) * KV_GROUP_BYTES;
constexpr int Q_OFFSET = NH * KV_HEAD_BYTES;
#define POLY_MASK 0xB6
__device__ __align__(1024) uint8_t g_QKV[2 * NH * KV_HEAD_BYTES];
__device__ __align__(1024) float g_kmax[NH * 64];
constexpr int SLAB = 16 * 36 * 256;
__device__ __align__(1024) uint4 g_part[8 * SLAB];
__device__ __align__(1024) uint2 g_ffn[128 * 2 * 9 * 128];
__device__ __align__(1024) uint32_t g_O[SEQ * DM / 2];
struct Flags {
    unsigned int qkv_stored[16];
    unsigned int ffn_done[16];
    unsigned int o_done[4];
    unsigned int kv_ready;
    unsigned int exited;
};
__device__ Flags g_flags;
constexpr int WO_TILE_BYTES = DM * 144 * 2;
__device__ __align__(1024) uint8_t g_Wo[4 * WO_TILE_BYTES];

__device__ __forceinline__ uint32_t s2u(const void* p) { return (uint32_t)__cvta_generic_to_shared(p); }
__device__ __forceinline__ void mbar_init(uint32_t b, int c) { asm volatile("mbarrier.init.shared::cta.b64 [%0], %1;" ::"r"(b), "r"(c) : "memory"); }
__device__ __forceinline__ void mbar_expect(uint32_t b, uint32_t bytes) {
    asm volatile("mbarrier.arrive.expect_tx.shared::cta.b64 _, [%0], %1;" ::"r"(b), "r"(bytes) : "memory");
}
__device__ __forceinline__ bool mbar_try(uint32_t b, uint32_t parity) {
    uint32_t ok;
    asm volatile("{\n.reg .pred p;\nmbarrier.try_wait.parity.shared::cta.b64 p, [%1], %2;\nselp.u32 %0, 1, 0, p;\n}\n" : "=r"(ok) : "r"(b), "r"(parity) : "memory");
    return ok != 0;
}
__device__ __forceinline__ void mbar_wait(uint32_t b, uint32_t parity) {
    if (__builtin_expect(!mbar_try(b, parity), 0)) {
        uint32_t spins = 0;
        while (!mbar_try(b, parity))
            if (++spins > (1u << 22)) __trap();
    }
}
__device__ __forceinline__ void mbar_wait_c(uint32_t b, uint32_t parity) {
    asm volatile("{\n.reg .pred p;\nWAIT:\nmbarrier.try_wait.parity.shared::cta.b64 p, [%0], %1;\n@!p bra WAIT;\n}\n" ::"r"(b), "r"(parity) : "memory");
}
__device__ __forceinline__ void fence_barrier_init() { asm volatile("fence.mbarrier_init.release.cluster;" ::: "memory"); }
__device__ __forceinline__ void fence_proxy_async() { asm volatile("fence.proxy.async.shared::cta;" ::: "memory"); }
__device__ __forceinline__ void cluster_arrive() { asm volatile("barrier.cluster.arrive.relaxed.aligned;" ::: "memory"); }
__device__ __forceinline__ void cluster_wait() { asm volatile("barrier.cluster.wait.aligned;" ::: "memory"); }
__device__ __forceinline__ void named_bar_sync(int id, int n) { asm volatile("bar.sync %0, %1;" ::"r"(id), "r"(n) : "memory"); }

__device__ __forceinline__ void tma3d_mc(uint32_t dst, const CUtensorMap* tm, int c0, int c1, int c2, uint32_t bar, uint16_t mask) {
    asm volatile("cp.async.bulk.tensor.3d.shared::cluster.global.mbarrier::complete_tx::bytes.multicast::cluster [%0], [%1, {%3, %4, %5}], [%2], %6;"
                 ::"r"(dst), "l"(tm), "r"(bar), "r"(c0), "r"(c1), "r"(c2), "h"(mask) : "memory");
}
__device__ __forceinline__ void tma2d_mc(uint32_t dst, const CUtensorMap* tm, int c0, int c1, uint32_t bar, uint16_t mask) {
    asm volatile("cp.async.bulk.tensor.2d.shared::cluster.global.mbarrier::complete_tx::bytes.multicast::cluster [%0], [%1, {%3, %4}], [%2], %5;"
                 ::"r"(dst), "l"(tm), "r"(bar), "r"(c0), "r"(c1), "h"(mask) : "memory");
}
__device__ __forceinline__ void tma4d(uint32_t dst, const CUtensorMap* tm, int c0, int c1, int c2, int c3, uint32_t bar) {
    asm volatile("cp.async.bulk.tensor.4d.shared::cluster.global.mbarrier::complete_tx::bytes [%0], [%1, {%3, %4, %5, %6}], [%2];"
                 ::"r"(dst), "l"(tm), "r"(bar), "r"(c0), "r"(c1), "r"(c2), "r"(c3) : "memory");
}
__device__ __forceinline__ void tma2d(uint32_t dst, const CUtensorMap* tm, int c0, int c1, uint32_t bar) {
    asm volatile("cp.async.bulk.tensor.2d.shared::cluster.global.mbarrier::complete_tx::bytes [%0], [%1, {%3, %4}], [%2];"
                 ::"r"(dst), "l"(tm), "r"(bar), "r"(c0), "r"(c1) : "memory");
}
__device__ __forceinline__ void bulk_load(uint32_t dst, const void* src, uint32_t bytes, uint32_t bar) {
    asm volatile("cp.async.bulk.shared::cluster.global.mbarrier::complete_tx::bytes [%0], [%1], %2, [%3];"
                 ::"r"(dst), "l"(src), "r"(bytes), "r"(bar) : "memory");
}
__device__ __forceinline__ void prefetch_l2(const void* p, uint32_t bytes) {
    asm volatile("cp.async.bulk.prefetch.L2.global [%0], %1;" ::"l"(p), "r"(bytes) : "memory");
}
__device__ __forceinline__ void prefetch_tmap(const CUtensorMap* tm) { asm volatile("prefetch.tensormap [%0];" ::"l"(tm) : "memory"); }

__device__ __forceinline__ void wg_fence() { asm volatile("wgmma.fence.sync.aligned;" ::: "memory"); }
__device__ __forceinline__ void wg_commit() { asm volatile("wgmma.commit_group.sync.aligned;" ::: "memory"); }
template <int N> __device__ __forceinline__ void wg_wait() { asm volatile("wgmma.wait_group.sync.aligned %0;" ::"n"(N) : "memory"); }
template <int N> __device__ __forceinline__ void reg_fence(float (&d)[N]) {
#pragma unroll
    for (int i = 0; i < N; i++) asm volatile("" : "+f"(d[i])::"memory");
}
template <int N> __device__ __forceinline__ void reg_fence(uint32_t (&d)[N]) {
#pragma unroll
    for (int i = 0; i < N; i++) asm volatile("" : "+r"(d[i])::"memory");
}
template <int R> __device__ __forceinline__ void reg_alloc() { asm volatile("setmaxnreg.inc.sync.aligned.u32 %0;" ::"n"(R)); }
template <int R> __device__ __forceinline__ void reg_dealloc() { asm volatile("setmaxnreg.dec.sync.aligned.u32 %0;" ::"n"(R)); }

__device__ __forceinline__ uint64_t mk_desc(uint64_t z, uint32_t addr, uint32_t lbo, uint32_t sbo, uint32_t swz) {
    return z + ((uint64_t)(((addr & 0x3FFFF) >> 4) | ((lbo >> 4) << 16)) | ((uint64_t)((sbo >> 4) | (swz << 30)) << 32));
}
__device__ __forceinline__ uint32_t pack_bf16(float lo, float hi) {
    uint32_t r;
    asm("cvt.rn.bf16x2.f32 %0, %1, %2;" : "=r"(r) : "f"(hi), "f"(lo));
    return r;
}
__device__ __forceinline__ float bf_lo(uint32_t w) { return __uint_as_float(w << 16); }
__device__ __forceinline__ float bf_hi(uint32_t w) { return __uint_as_float(w & 0xFFFF0000u); }
__device__ __forceinline__ float ex2(float x) {
    float r;
    asm("ex2.approx.ftz.f32 %0, %1;" : "=f"(r) : "f"(x));
    return r;
}
__device__ __forceinline__ float tanh_fast(float x) {
    float r;
    asm("tanh.approx.f32 %0, %1;" : "=f"(r) : "f"(x));
    return r;
}
__device__ __forceinline__ uint32_t hfma2_bf16(uint32_t a, uint32_t b, uint32_t c) {
    uint32_t r;
    asm("fma.rn.bf16x2 %0, %1, %2, %3;" : "=r"(r) : "r"(a), "r"(b), "r"(c));
    return r;
}
__device__ __forceinline__ uint32_t hadd2_bf16(uint32_t a, uint32_t b) {
    uint32_t r;
    asm("add.rn.bf16x2 %0, %1, %2;" : "=r"(r) : "r"(a), "r"(b));
    return r;
}
__device__ __forceinline__ void ldsm4(uint32_t (&a)[4], uint32_t addr) {
    asm volatile("ldmatrix.sync.aligned.m8n8.x4.shared.b16 {%0, %1, %2, %3}, [%4];" : "=r"(a[0]), "=r"(a[1]), "=r"(a[2]), "=r"(a[3]) : "r"(addr) : "memory");
}
__device__ __forceinline__ void stsm4(uint32_t addr, const uint32_t (&a)[4]) {
    asm volatile("stmatrix.sync.aligned.m8n8.x4.shared.b16 [%0], {%1, %2, %3, %4};" ::"r"(addr), "r"(a[0]), "r"(a[1]), "r"(a[2]), "r"(a[3]) : "memory");
}
__device__ __forceinline__ void mma16816(float (&c)[4], const uint32_t (&a)[4], uint32_t b0, uint32_t b1) {
    asm("mma.sync.aligned.m16n8k16.row.col.f32.bf16.bf16.f32 {%0, %1, %2, %3}, {%4, %5, %6, %7}, {%8, %9}, {%0, %1, %2, %3};"
        : "+f"(c[0]), "+f"(c[1]), "+f"(c[2]), "+f"(c[3]) : "r"(a[0]), "r"(a[1]), "r"(a[2]), "r"(a[3]), "r"(b0), "r"(b1));
}
__device__ __forceinline__ float gelu2(float u) {
    const float w = fmaf(u * u, 0.0356774081f, 0.7978845608f);
    return fmaf(u, tanh_fast(u * w), u);
}

template<int TB, int AOFF, int BOFF> __device__ __forceinline__ void wgmma_ss_n216(float (&d)[108], uint64_t da, uint64_t db, int sd) {
    asm volatile("{\n.reg .pred p;\n.reg .b64 ta, tb;\nsetp.ne.b32 p, %110, 0;\nadd.s64 ta, %108, %112;\nadd.s64 tb, %109, %113;\n"
      "wgmma.mma_async.sync.aligned.m64n216k16.f32.bf16.bf16 {%0, %1, %2, %3, %4, %5, %6, %7, %8, %9, %10, %11, %12, %13, %14, %15, %16, %17, %18, %19, %20, %21, %22, %23, %24, %25, %26, %27, %28, %29, %30, %31, %32, %33, %34, %35, %36, %37, %38, %39, %40, %41, %42, %43, %44, %45, %46, %47, %48, %49, %50, %51, %52, %53, %54, %55, %56, %57, %58, %59, %60, %61, %62, %63, %64, %65, %66, %67, %68, %69, %70, %71, %72, %73, %74, %75, %76, %77, %78, %79, %80, %81, %82, %83, %84, %85, %86, %87, %88, %89, %90, %91, %92, %93, %94, %95, %96, %97, %98, %99, %100, %101, %102, %103, %104, %105, %106, %107}, ta, tb, p, 1, 1, 0, %111;\n}\n"
      : "+f"(d[0]), "+f"(d[1]), "+f"(d[2]), "+f"(d[3]), "+f"(d[4]), "+f"(d[5]), "+f"(d[6]), "+f"(d[7]), "+f"(d[8]), "+f"(d[9]), "+f"(d[10]), "+f"(d[11]), "+f"(d[12]), "+f"(d[13]), "+f"(d[14]), "+f"(d[15]), "+f"(d[16]), "+f"(d[17]), "+f"(d[18]), "+f"(d[19]), "+f"(d[20]), "+f"(d[21]), "+f"(d[22]), "+f"(d[23]), "+f"(d[24]), "+f"(d[25]), "+f"(d[26]), "+f"(d[27]), "+f"(d[28]), "+f"(d[29]), "+f"(d[30]), "+f"(d[31]), "+f"(d[32]), "+f"(d[33]), "+f"(d[34]), "+f"(d[35]), "+f"(d[36]), "+f"(d[37]), "+f"(d[38]), "+f"(d[39]), "+f"(d[40]), "+f"(d[41]), "+f"(d[42]), "+f"(d[43]), "+f"(d[44]), "+f"(d[45]), "+f"(d[46]), "+f"(d[47]), "+f"(d[48]), "+f"(d[49]), "+f"(d[50]), "+f"(d[51]), "+f"(d[52]), "+f"(d[53]), "+f"(d[54]), "+f"(d[55]), "+f"(d[56]), "+f"(d[57]), "+f"(d[58]), "+f"(d[59]), "+f"(d[60]), "+f"(d[61]), "+f"(d[62]), "+f"(d[63]), "+f"(d[64]), "+f"(d[65]), "+f"(d[66]), "+f"(d[67]), "+f"(d[68]), "+f"(d[69]), "+f"(d[70]), "+f"(d[71]), "+f"(d[72]), "+f"(d[73]), "+f"(d[74]), "+f"(d[75]), "+f"(d[76]), "+f"(d[77]), "+f"(d[78]), "+f"(d[79]), "+f"(d[80]), "+f"(d[81]), "+f"(d[82]), "+f"(d[83]), "+f"(d[84]), "+f"(d[85]), "+f"(d[86]), "+f"(d[87]), "+f"(d[88]), "+f"(d[89]), "+f"(d[90]), "+f"(d[91]), "+f"(d[92]), "+f"(d[93]), "+f"(d[94]), "+f"(d[95]), "+f"(d[96]), "+f"(d[97]), "+f"(d[98]), "+f"(d[99]), "+f"(d[100]), "+f"(d[101]), "+f"(d[102]), "+f"(d[103]), "+f"(d[104]), "+f"(d[105]), "+f"(d[106]), "+f"(d[107])
      : "l"(da), "l"(db), "r"(sd), "n"(TB), "n"(AOFF), "n"(BOFF));
}

template<int TB, int AOFF, int BOFF> __device__ __forceinline__ void wgmma_ss_n64(float (&d)[32], uint64_t da, uint64_t db, int sd) {
    asm volatile("{\n.reg .pred p;\n.reg .b64 ta, tb;\nsetp.ne.b32 p, %34, 0;\nadd.s64 ta, %32, %36;\nadd.s64 tb, %33, %37;\n"
      "wgmma.mma_async.sync.aligned.m64n64k16.f32.bf16.bf16 {%0, %1, %2, %3, %4, %5, %6, %7, %8, %9, %10, %11, %12, %13, %14, %15, %16, %17, %18, %19, %20, %21, %22, %23, %24, %25, %26, %27, %28, %29, %30, %31}, ta, tb, p, 1, 1, 0, %35;\n}\n"
      : "+f"(d[0]), "+f"(d[1]), "+f"(d[2]), "+f"(d[3]), "+f"(d[4]), "+f"(d[5]), "+f"(d[6]), "+f"(d[7]), "+f"(d[8]), "+f"(d[9]), "+f"(d[10]), "+f"(d[11]), "+f"(d[12]), "+f"(d[13]), "+f"(d[14]), "+f"(d[15]), "+f"(d[16]), "+f"(d[17]), "+f"(d[18]), "+f"(d[19]), "+f"(d[20]), "+f"(d[21]), "+f"(d[22]), "+f"(d[23]), "+f"(d[24]), "+f"(d[25]), "+f"(d[26]), "+f"(d[27]), "+f"(d[28]), "+f"(d[29]), "+f"(d[30]), "+f"(d[31])
      : "l"(da), "l"(db), "r"(sd), "n"(TB), "n"(AOFF), "n"(BOFF));
}

template<int TB, int AOFF, int BOFF> __device__ __forceinline__ void wgmma_ss_n128(float (&d)[64], uint64_t da, uint64_t db, int sd) {
    asm volatile("{\n.reg .pred p;\n.reg .b64 ta, tb;\nsetp.ne.b32 p, %66, 0;\nadd.s64 ta, %64, %68;\nadd.s64 tb, %65, %69;\n"
      "wgmma.mma_async.sync.aligned.m64n128k16.f32.bf16.bf16 {%0, %1, %2, %3, %4, %5, %6, %7, %8, %9, %10, %11, %12, %13, %14, %15, %16, %17, %18, %19, %20, %21, %22, %23, %24, %25, %26, %27, %28, %29, %30, %31, %32, %33, %34, %35, %36, %37, %38, %39, %40, %41, %42, %43, %44, %45, %46, %47, %48, %49, %50, %51, %52, %53, %54, %55, %56, %57, %58, %59, %60, %61, %62, %63}, ta, tb, p, 1, 1, 0, %67;\n}\n"
      : "+f"(d[0]), "+f"(d[1]), "+f"(d[2]), "+f"(d[3]), "+f"(d[4]), "+f"(d[5]), "+f"(d[6]), "+f"(d[7]), "+f"(d[8]), "+f"(d[9]), "+f"(d[10]), "+f"(d[11]), "+f"(d[12]), "+f"(d[13]), "+f"(d[14]), "+f"(d[15]), "+f"(d[16]), "+f"(d[17]), "+f"(d[18]), "+f"(d[19]), "+f"(d[20]), "+f"(d[21]), "+f"(d[22]), "+f"(d[23]), "+f"(d[24]), "+f"(d[25]), "+f"(d[26]), "+f"(d[27]), "+f"(d[28]), "+f"(d[29]), "+f"(d[30]), "+f"(d[31]), "+f"(d[32]), "+f"(d[33]), "+f"(d[34]), "+f"(d[35]), "+f"(d[36]), "+f"(d[37]), "+f"(d[38]), "+f"(d[39]), "+f"(d[40]), "+f"(d[41]), "+f"(d[42]), "+f"(d[43]), "+f"(d[44]), "+f"(d[45]), "+f"(d[46]), "+f"(d[47]), "+f"(d[48]), "+f"(d[49]), "+f"(d[50]), "+f"(d[51]), "+f"(d[52]), "+f"(d[53]), "+f"(d[54]), "+f"(d[55]), "+f"(d[56]), "+f"(d[57]), "+f"(d[58]), "+f"(d[59]), "+f"(d[60]), "+f"(d[61]), "+f"(d[62]), "+f"(d[63])
      : "l"(da), "l"(db), "r"(sd), "n"(TB), "n"(AOFF), "n"(BOFF));
}

template<int TB, int BOFF> __device__ __forceinline__ void wgmma_rs_n64(float (&d)[32], uint32_t a0, uint32_t a1, uint32_t a2, uint32_t a3, uint64_t db, int sd) {
    asm volatile("{\n.reg .pred p;\n.reg .b64 tb;\nsetp.ne.b32 p, %37, 0;\nadd.s64 tb, %36, %39;\n"
      "wgmma.mma_async.sync.aligned.m64n64k16.f32.bf16.bf16 {%0, %1, %2, %3, %4, %5, %6, %7, %8, %9, %10, %11, %12, %13, %14, %15, %16, %17, %18, %19, %20, %21, %22, %23, %24, %25, %26, %27, %28, %29, %30, %31}, {%32, %33, %34, %35}, tb, p, 1, 1, %38;\n}\n"
      : "+f"(d[0]), "+f"(d[1]), "+f"(d[2]), "+f"(d[3]), "+f"(d[4]), "+f"(d[5]), "+f"(d[6]), "+f"(d[7]), "+f"(d[8]), "+f"(d[9]), "+f"(d[10]), "+f"(d[11]), "+f"(d[12]), "+f"(d[13]), "+f"(d[14]), "+f"(d[15]), "+f"(d[16]), "+f"(d[17]), "+f"(d[18]), "+f"(d[19]), "+f"(d[20]), "+f"(d[21]), "+f"(d[22]), "+f"(d[23]), "+f"(d[24]), "+f"(d[25]), "+f"(d[26]), "+f"(d[27]), "+f"(d[28]), "+f"(d[29]), "+f"(d[30]), "+f"(d[31])
      : "r"(a0), "r"(a1), "r"(a2), "r"(a3), "l"(db), "r"(sd), "n"(TB), "n"(BOFF));
}

template<int TB, int BOFF> __device__ __forceinline__ void wgmma_rs_n24(float (&d)[12], uint32_t a0, uint32_t a1, uint32_t a2, uint32_t a3, uint64_t db, int sd) {
    asm volatile("{\n.reg .pred p;\n.reg .b64 tb;\nsetp.ne.b32 p, %17, 0;\nadd.s64 tb, %16, %19;\n"
      "wgmma.mma_async.sync.aligned.m64n24k16.f32.bf16.bf16 {%0, %1, %2, %3, %4, %5, %6, %7, %8, %9, %10, %11}, {%12, %13, %14, %15}, tb, p, 1, 1, %18;\n}\n"
      : "+f"(d[0]), "+f"(d[1]), "+f"(d[2]), "+f"(d[3]), "+f"(d[4]), "+f"(d[5]), "+f"(d[6]), "+f"(d[7]), "+f"(d[8]), "+f"(d[9]), "+f"(d[10]), "+f"(d[11])
      : "r"(a0), "r"(a1), "r"(a2), "r"(a3), "l"(db), "r"(sd), "n"(TB), "n"(BOFF));
}

template<int TB, int BOFF> __device__ __forceinline__ void wgmma_rs_n144(float (&d)[72], uint32_t a0, uint32_t a1, uint32_t a2, uint32_t a3, uint64_t db, int sd) {
    asm volatile("{\n.reg .pred p;\n.reg .b64 tb;\nsetp.ne.b32 p, %77, 0;\nadd.s64 tb, %76, %79;\n"
      "wgmma.mma_async.sync.aligned.m64n144k16.f32.bf16.bf16 {%0, %1, %2, %3, %4, %5, %6, %7, %8, %9, %10, %11, %12, %13, %14, %15, %16, %17, %18, %19, %20, %21, %22, %23, %24, %25, %26, %27, %28, %29, %30, %31, %32, %33, %34, %35, %36, %37, %38, %39, %40, %41, %42, %43, %44, %45, %46, %47, %48, %49, %50, %51, %52, %53, %54, %55, %56, %57, %58, %59, %60, %61, %62, %63, %64, %65, %66, %67, %68, %69, %70, %71}, {%72, %73, %74, %75}, tb, p, 1, 1, %78;\n}\n"
      : "+f"(d[0]), "+f"(d[1]), "+f"(d[2]), "+f"(d[3]), "+f"(d[4]), "+f"(d[5]), "+f"(d[6]), "+f"(d[7]), "+f"(d[8]), "+f"(d[9]), "+f"(d[10]), "+f"(d[11]), "+f"(d[12]), "+f"(d[13]), "+f"(d[14]), "+f"(d[15]), "+f"(d[16]), "+f"(d[17]), "+f"(d[18]), "+f"(d[19]), "+f"(d[20]), "+f"(d[21]), "+f"(d[22]), "+f"(d[23]), "+f"(d[24]), "+f"(d[25]), "+f"(d[26]), "+f"(d[27]), "+f"(d[28]), "+f"(d[29]), "+f"(d[30]), "+f"(d[31]), "+f"(d[32]), "+f"(d[33]), "+f"(d[34]), "+f"(d[35]), "+f"(d[36]), "+f"(d[37]), "+f"(d[38]), "+f"(d[39]), "+f"(d[40]), "+f"(d[41]), "+f"(d[42]), "+f"(d[43]), "+f"(d[44]), "+f"(d[45]), "+f"(d[46]), "+f"(d[47]), "+f"(d[48]), "+f"(d[49]), "+f"(d[50]), "+f"(d[51]), "+f"(d[52]), "+f"(d[53]), "+f"(d[54]), "+f"(d[55]), "+f"(d[56]), "+f"(d[57]), "+f"(d[58]), "+f"(d[59]), "+f"(d[60]), "+f"(d[61]), "+f"(d[62]), "+f"(d[63]), "+f"(d[64]), "+f"(d[65]), "+f"(d[66]), "+f"(d[67]), "+f"(d[68]), "+f"(d[69]), "+f"(d[70]), "+f"(d[71])
      : "r"(a0), "r"(a1), "r"(a2), "r"(a3), "l"(db), "r"(sd), "n"(TB), "n"(BOFF));
}

constexpr int K1_XN_BYTES = 16 * 9216;
constexpr int K1_OFF_RING = K1_XN_BYTES;
constexpr int K1_OFF_BIAS = K1_OFF_RING + 10 * 8192;
constexpr int K1_OFF_BAR = K1_OFF_BIAS + 576 * 2;
constexpr int K1_SMEM = K1_OFF_BAR + 768;
constexpr float QSCALE = 0.23570226039551584f * 1.4426950408889634f;

struct K1Ctx {
    uint32_t full0;
    uint32_t rel_addr;
    uint64_t descA, descB;
    uint32_t phase;
    __device__ __forceinline__ void begin_stage(int s) {
        mbar_wait_c(full0 + s * 8, phase);
        wg_fence();
    }
    __device__ __forceinline__ void release(int s) {
        if (rel_addr) asm volatile("mbarrier.arrive.shared::cluster.b64 _, [%0];" ::"r"(rel_addr + s * 8) : "memory");
    }
    __device__ __forceinline__ void end_stage(int s) {
        wg_commit();
        wg_wait<1>();
        release(s == 0 ? 8 : s - 1);
    }
};

__host__ __device__ constexpr int a_off(int ks) { return ((ks / 12) * 49152 + ((ks >> 2) % 3) * 1024 + (ks & 3) * 32) >> 4; }

template <int V> struct IC { static constexpr int value = V; };
template <int I, int N, class F> __device__ __forceinline__ void static_for(F&& f) {
    if constexpr (I < N) { f(IC<I>{}); static_for<I + 1, N>(f); }
}

template <bool A_RS, bool B_RS, class Epi>
__device__ __forceinline__ void tile_pair(K1Ctx& c, float (&accA)[32], float (&accB)[32], uint32_t (&h)[144], Epi&& epi) {
    static_for<0, 9>([&](auto sc) {
        constexpr int s = decltype(sc)::value;
        c.begin_stage(s);
        static_for<0, 8>([&](auto tc) {
            constexpr int kk = s * 8 + decltype(tc)::value, ks = kk % 36;
            constexpr int bo = (ks * 2048) >> 4;
            if constexpr (kk < 36) {
                if constexpr (A_RS) wgmma_rs_n64<1, bo>(accA, h[ks * 4], h[ks * 4 + 1], h[ks * 4 + 2], h[ks * 4 + 3], c.descB, ks != 0);
                else wgmma_ss_n64<1, a_off(ks), bo>(accA, c.descA, c.descB, ks != 0);
            } else {
                if constexpr (B_RS) wgmma_rs_n64<1, bo>(accB, h[ks * 4], h[ks * 4 + 1], h[ks * 4 + 2], h[ks * 4 + 3], c.descB, ks != 0);
                else wgmma_ss_n64<1, a_off(ks), bo>(accB, c.descA, c.descB, ks != 0);
            }
        });
        c.end_stage(s);
        epi(sc);
    });
    c.phase ^= 1;
}

template <int B0, int NB, int HOFF>
__device__ __forceinline__ void gelu_blocks(const float (&acc)[32], uint32_t (&h)[144], const uint32_t (&bq)[8], float rs0, float rs1) {
#pragma unroll
    for (int b = B0; b < B0 + NB; b++) {
        const float b0 = bf_lo(bq[b]), b1 = bf_hi(bq[b]);
        h[HOFF + b * 2 + 0] = pack_bf16(gelu2(fmaf(acc[b * 4 + 0], rs0, b0)), gelu2(fmaf(acc[b * 4 + 1], rs0, b1)));
        h[HOFF + b * 2 + 1] = pack_bf16(gelu2(fmaf(acc[b * 4 + 2], rs1, b0)), gelu2(fmaf(acc[b * 4 + 3], rs1, b1)));
    }
#pragma unroll
    for (int i = HOFF + B0 * 2; i < HOFF + (B0 + NB) * 2; i++) asm volatile("" : "+r"(h[i]));
}
__device__ __forceinline__ void load_bias(uint32_t (&bq)[8], uint32_t addr) {
    asm volatile("ld.shared.v4.u32 {%0, %1, %2, %3}, [%4];" : "=r"(bq[0]), "=r"(bq[1]), "=r"(bq[2]), "=r"(bq[3]) : "r"(addr));
    asm volatile("ld.shared.v4.u32 {%0, %1, %2, %3}, [%4 + 16];" : "=r"(bq[4]), "=r"(bq[5]), "=r"(bq[6]), "=r"(bq[7]) : "r"(addr));
}
template <int S> __device__ __forceinline__ void store_part(const float (&o)[32], uint4* p) {
    uint4 v;
    v.x = pack_bf16(o[S * 8 + 0], o[S * 8 + 1]); v.y = pack_bf16(o[S * 8 + 2], o[S * 8 + 3]);
    v.z = pack_bf16(o[S * 8 + 4], o[S * 8 + 5]); v.w = pack_bf16(o[S * 8 + 6], o[S * 8 + 7]);
    p[S * 256] = v;
}

constexpr int NCHUNK = 16;
constexpr int CHUNK_BYTES = KV_HEAD_BYTES / NCHUNK;
constexpr int SM_Q = 0;
constexpr int SM_KV = 32768;
constexpr int WO_PIECE = WO_TILE_BYTES / 9;
__host__ __device__ constexpr int sm_wo(int i) { return i == 0 ? 210944 : (i == 1 ? 0 : SM_KV + (i - 2) * WO_PIECE); }
constexpr int SM_EXCH = SM_KV + 7 * WO_PIECE;
constexpr int SM_RED = SM_KV + KV_HEAD_BYTES;

__device__ __forceinline__ float exp2_fixed(float y) {
    const float u = __uint_as_float(__float_as_uint(y) & 0xFF807FFFu) - 512.02545f;
    float t = fmaf(u, 0.019497588f, 0.114550486f);
    t = fmaf(t, u, -0.29839927f);
    return fmaf(t, u, y);
}
__device__ __forceinline__ uint32_t pack_fixed(float lo, float hi) { return __byte_perm(__float_as_uint(lo), __float_as_uint(hi), 0x6521); }

#define POLY_MODE 1
__device__ __forceinline__ uint32_t exp2_packed(float y0, float y1, uint32_t one2) {
    const uint32_t w = pack_fixed(y0, y1);
    uint32_t m;
    asm("lop3.b32 %0, %1, 0x007F007F, %2, 0xEA;" : "=r"(m) : "r"(w), "r"(one2));
    const uint32_t d = hfma2_bf16(m, 0x3EF93EF9u, 0xBF38BF38u);
    const uint32_t e = hfma2_bf16(d, d, 0xBD71BD71u);
    return hfma2_bf16(w, e, w);
}
template <int NB>
__device__ __forceinline__ void softmax_fast(const float (&s)[NB * 4], uint32_t (&p)[NB * 2], uint32_t one2) {
#pragma unroll
    for (int b = 0; b < NB; b++) {
        if ((POLY_MASK >> (b & 7)) & 1) {
            p[b * 2 + 0] = exp2_packed(s[b * 4 + 0], s[b * 4 + 1], one2);
            p[b * 2 + 1] = exp2_packed(s[b * 4 + 2], s[b * 4 + 3], one2);
        } else {
            p[b * 2 + 0] = pack_bf16(ex2(s[b * 4 + 0]), ex2(s[b * 4 + 1]));
            p[b * 2 + 1] = pack_bf16(ex2(s[b * 4 + 2]), ex2(s[b * 4 + 3]));
        }
    }
}

constexpr int KV_TILE = CHUNK_BYTES / 16;
template <int OFF> __device__ __forceinline__ void issue_qk(float (&s)[64], uint64_t qd, uint64_t kd) {
    wgmma_ss_n128<0, 0, OFF + (8 << 16)>(s, qd, kd, 0);
    wgmma_ss_n128<0, 16, OFF + 32>(s, qd, kd, 1);
}
template <int OFF> __device__ __forceinline__ void issue_pv(float (&o)[12], const uint32_t (&p)[32], uint64_t vd) {
    static_for<0, 8>([&](auto kc) {
        constexpr int k = decltype(kc)::value;
        wgmma_rs_n24<1, OFF + k * (2 * KV_GROUP_BYTES / 16)>(o, p[k * 4], p[k * 4 + 1], p[k * 4 + 2], p[k * 4 + 3], vd, 1);
    });
}
__device__ __forceinline__ void store_o(float (&o)[12], int rt, int head, int wq, int lane) {
    const int g = lane >> 2, q = lane & 3;
    const float i0 = __fdividef(1.0f, __shfl_sync(~0u, o[8], lane | 3)), i1 = __fdividef(1.0f, __shfl_sync(~0u, o[10], lane | 3));
#pragma unroll
    for (int i = 0; i < 3; i++) {
        const int pc = head * 9 + (i < 2 ? i * 4 + q : 8);
        uint32_t* op = g_O + (((rt * 36 + (pc >> 3)) * 128 + wq * 32 + g * 4 + (pc & 3)) * 4 + ((pc >> 2) & 1) * 2);
        if (i < 2 || q == 2) *reinterpret_cast<uint2*>(op) = make_uint2(pack_bf16(o[i * 4] * i0, o[i * 4 + 1] * i0), pack_bf16(o[i * 4 + 2] * i1, o[i * 4 + 3] * i1));
    }
#pragma unroll
    for (int i = 0; i < 12; i++) o[i] = 0.f;
}
__device__ __forceinline__ void mbar_arrive(uint32_t b) { asm volatile("mbarrier.arrive.shared::cta.b64 _, [%0];" ::"r"(b) : "memory"); }
__device__ __forceinline__ void mbar_wait_sleep(uint32_t b, uint32_t ns) {
    uint32_t ok, spins = 0;
    while (true) {
        asm volatile("{\n.reg .pred p;\nmbarrier.try_wait.parity.shared::cta.b64 p, [%1], 0;\nselp.u32 %0, 1, 0, p;\n}\n" : "=r"(ok) : "r"(b) : "memory");
        if (ok) break;
        __nanosleep(ns);
        if (++spins > (1u << 21)) __trap();
    }
}
__device__ __forceinline__ void flag_signal(unsigned int* f) {
    __threadfence();
    atomicAdd(f, 1u);
}
__device__ __forceinline__ void flag_wait(const unsigned int* f, unsigned int target, unsigned int sleep_ns) {
    uint32_t v, spins = 0;
    while (true) {
        asm volatile("ld.acquire.gpu.global.u32 %0, [%1];" : "=r"(v) : "l"(f) : "memory");
        if (v >= target) break;
        if (sleep_ns) __nanosleep(sleep_ns);
        if (++spins > (1u << 21)) __trap();
    }
}
__device__ __forceinline__ uint4 hadd8_bf16(const uint4 a, const uint4 b) {
    return make_uint4(hadd2_bf16(a.x, b.x), hadd2_bf16(a.y, b.y), hadd2_bf16(a.z, b.z), hadd2_bf16(a.w, b.w));
}
__device__ __forceinline__ float sumsq2(uint32_t w) { return fmaf(bf_lo(w), bf_lo(w), bf_hi(w) * bf_hi(w)); }
__device__ __forceinline__ float sumsq8(const uint4 v) { return (sumsq2(v.x) + sumsq2(v.y)) + (sumsq2(v.z) + sumsq2(v.w)); }

enum { B_FULL = 0, B_EMPTY = 9, B_BASE = 18, B_XNDEAD = 19, B_QRDY = 20, B_FFN = 21, B_KV = 22, B_FREE = 38, B_WO = 46, B_RED = 55, B_X = 61, B_DONE = 85, B_END = 86 };

__global__ void __cluster_dims__(2, 1, 1) __launch_bounds__(384, 1)
fused_kernel(const __grid_constant__ CUtensorMap tmX, const __grid_constant__ CUtensorMap tmQ3, const __grid_constant__ CUtensorMap tmQ1,
          const __grid_constant__ CUtensorMap tm1, const __grid_constant__ CUtensorMap tm2, const __grid_constant__ CUtensorMap tmP, const __nv_bfloat16* __restrict__ b1,
          const __nv_bfloat16* __restrict__ wqkv, const __nv_bfloat16* __restrict__ w1, const __nv_bfloat16* __restrict__ w2,
          const __nv_bfloat16* __restrict__ wo, const __nv_bfloat16* __restrict__ x, const __nv_bfloat16* __restrict__ b2,
          __nv_bfloat16* __restrict__ out, const uint64_t zero) {
    extern __shared__ __align__(1024) uint8_t smem[];
    const uint32_t sb = s2u(smem);
    const int tid = threadIdx.x, lane = tid & 31;
    const int warp = __shfl_sync(~0u, tid >> 5, 0);
    const uint32_t rank = blockIdx.x & 1;
    const int cl = blockIdx.x >> 1;
    const int rb = (cl & 7) * 2 + rank;
    const int j = cl >> 3;
    const uint32_t bar0 = sb + K1_OFF_BAR;
    const uint32_t full0 = bar0 + B_FULL * 8, empty0 = bar0 + B_EMPTY * 8, xbar0 = bar0 + B_X * 8;
    const int head = blockIdx.x >> 2, quarter = blockIdx.x & 3;
    const int rt = quarter * 8 + (head >> 2), ct = head & 3;
    volatile uint32_t* slow_flag = reinterpret_cast<volatile uint32_t*>(smem + K1_OFF_BAR + B_END * 8);

    if (warp < 8) {
        PROF(0);
        PROFT(48);
        if (lane == 0) {
#pragma unroll
            for (int i = 0; i < 3; i++) mbar_init(xbar0 + (warp * 3 + i) * 8, 1);
            fence_barrier_init();
#pragma unroll 1
            for (int i = 0; i < 3; i++) {
                const uint32_t xb = xbar0 + (warp * 3 + i) * 8;
                mbar_expect(xb, 6144);
                tma4d(sb + i * 49152 + warp * 6144, &tmX, 0, 0, i * 3, rb * 16 + warp * 2, xb);
            }
        }
        __syncwarp();
        cluster_arrive();
        PROF(22);
        reg_alloc<240>();
        PROF(23);
        float rs0, rs1;
        {
            const uint32_t la = sb + (warp * 2 + ((lane >> 3) & 1)) * 3072 + (lane & 7) * 128;
            uint32_t off[4];
#pragma unroll
            for (int i = 0; i < 4; i++) off[i] = la + (((i * 2 + (lane >> 4)) ^ (lane & 7)) << 4);
            float c1[4] = {0.f, 0.f, 0.f, 0.f}, c2[4] = {0.f, 0.f, 0.f, 0.f}, c3[4] = {0.f, 0.f, 0.f, 0.f};
            uint32_t a[36][4];
#pragma unroll
            for (int t = 0; t < 3; t++) {
                mbar_wait_c(xbar0 + (warp * 3 + t) * 8, 0);
                PROF(24 + t);
#pragma unroll
                for (int i = 0; i < 12; i++) ldsm4(a[t * 12 + i], off[i & 3] + t * 49152 + (i >> 2) * 1024);
#pragma unroll
                for (int i = t * 12; i < t * 12 + 12; i++) {
                    mma16816(c3, a[i], 0x3F803F80u, 0x3F803F80u);
                    mma16816(c1, a[i], a[i][0], a[i][2]);
                    mma16816(c2, a[i], a[i][1], a[i][3]);
                }
            }
            PROF(27);
            const int gg = lane >> 2, src = (lane & ~3) | (gg >> 1);
            const float m0 = c3[0] * (1.0f / DM), m1 = c3[2] * (1.0f / DM);
            const uint32_t mc0 = pack_bf16(-m0, -m0), mc1 = pack_bf16(-m1, -m1);
#pragma unroll
            for (int i = 0; i < 36; i++) {
#pragma unroll
                for (int k = 0; k < 4; k++) a[i][k] = hadd2_bf16(a[i][k], (k & 1) ? mc1 : mc0);
                stsm4(off[i & 3] + (i / 12) * 49152 + ((i >> 2) % 3) * 1024, a[i]);
            }
            const float q0 = __shfl_sync(~0u, (gg & 1) ? c1[1] : c1[0], src), q1 = __shfl_sync(~0u, (gg & 1) ? c2[3] : c2[2], src);
            rs0 = rsqrtf(fmaxf(fmaf(-m0, m0, q0 * (1.0f / DM)), 0.f) + 1e-5f);
            rs1 = rsqrtf(fmaxf(fmaf(-m1, m1, q1 * (1.0f / DM)), 0.f) + 1e-5f);
            if (__any_sync(~0u, fabsf(m0) * rs0 > 0.25f || fabsf(m1) * rs1 > 0.25f)) {
                const float d0 = -m0 - bf_lo(mc0), d1 = -m1 - bf_lo(mc1);
                const uint32_t md0 = pack_bf16(d0, d0), md1 = pack_bf16(d1, d1);
#pragma unroll 1
                for (int i = 0; i < 9; i++) {
#pragma unroll
                    for (int k4 = 0; k4 < 4; k4++) {
                        const uint32_t ad = off[k4] + (i / 3) * 49152 + (i % 3) * 1024;
                        uint32_t b[4];
                        ldsm4(b, ad);
#pragma unroll
                        for (int k = 0; k < 4; k++) b[k] = hadd2_bf16(b[k], (k & 1) ? md1 : md0);
                        stsm4(ad, b);
                    }
                }
            }
        }
        PROF(28);
        const int wg = warp >> 2, wq = warp & 3;
        fence_proxy_async();
        named_bar_sync(1 + wg, 128);
        cluster_wait();
        PROF(1);

        const int g = lane >> 2, q = lane & 3;
        K1Ctx c;
        c.full0 = full0;
        c.rel_addr = 0;
        c.descA = mk_desc(zero, sb + wg * 8 * 3072, 16, 3072, 1);
        c.descB = mk_desc(zero, sb + K1_OFF_RING, 2048, 1024, 1);
        c.phase = 0;
        uint32_t biasq = sb + K1_OFF_BIAS + q * 32;
        uint32_t bq[8];

        uint32_t h[144];
        float accA[32], accB[32];
        {
            float accQ[108];
            uint32_t rel = 0;
            if (lane == 0 && wq < 2) asm("mapa.shared::cluster.u32 %0, %1, %2;" : "=r"(rel) : "r"(empty0), "r"(wq));
#pragma unroll 1
            for (int r = 0; r < 2; r++) {
                static_for<0, 9>([&](auto sc) {
                    constexpr int s = decltype(sc)::value;
                    c.begin_stage(s);
                    const uint64_t da = c.descA + (r ? a_off(18 + 2 * s) : a_off(2 * s));
                    wgmma_ss_n216<1, 0, ((2 * s) % 9) * 512>(accQ, da, c.descB, (r | s) != 0);
                    wgmma_ss_n216<1, 2, ((2 * s + 1) % 9) * 512>(accQ, da, c.descB, 1);
                    c.end_stage(s);
                    c.rel_addr = rel;
                });
                c.phase ^= 1;
            }
            PROF(2);
            uint32_t rel9[9];
#pragma unroll
            for (int i9 = 0; i9 < 9; i9++) {
                const int p = 4 * i9 + q, hh = (p * 57) >> 9, r = p - 9 * hh;
                rel9[i9] = hh * KV_HEAD_BYTES + (r < 8 ? (r >> 2) * 128 + (r & 3) * 4 : 0);
            }
            uint32_t gb = 0, o2 = 0;
            float scl0 = 1.f, scl1 = 1.f;
            tile_pair<false, false>(c, accA, accB, h, [&](auto sc) {
                constexpr int s = decltype(sc)::value;
                if constexpr (s == 0) reg_fence(accQ);
                if constexpr (s < 6) {
                    constexpr int grp = s / 2, part = s % 2;
                    if constexpr (part == 0) {
                        const int G = 3 * j + grp, type = G >> 3;
                        gb = (G & 7) * 4 * KV_HEAD_BYTES + (rb * 16 + warp * 2) * KV_GROUP_BYTES + g * 16 + (type == 0 ? Q_OFFSET : (type == 2 ? 256 : 0));
                        o2 = type == 0 ? 256 : (type == 2 ? 264 : 512);
                        scl0 = rs0 * (type == 0 ? QSCALE : ((type == 1 && ((POLY_MASK >> (wq * 2)) & 1)) ? 2.f : 1.f));
                        scl1 = rs1 * (type == 0 ? QSCALE : ((type == 1 && ((POLY_MASK >> (wq * 2 + 1)) & 1)) ? 2.f : 1.f));
                    }
#pragma unroll
                    for (int i9 = part * 5; i9 < (part ? 9 : 5); i9++) {
                        const int b = grp * 9 + i9;
                        uint32_t off = gb + rel9[i9];
                        if (i9 >= 2 && (i9 & 1) == 0) off += (q == i9 / 2 - 1) ? o2 : 0;
                        *reinterpret_cast<uint32_t*>(g_QKV + off) = pack_bf16(accQ[b * 4] * scl0, accQ[b * 4 + 1] * scl0);
                        *reinterpret_cast<uint32_t*>(g_QKV + off + KV_GROUP_BYTES) = pack_bf16(accQ[b * 4 + 2] * scl1, accQ[b * 4 + 3] * scl1);
                    }
                    if constexpr (s == 5) asm volatile("bar.arrive 3, 352;" ::: "memory");
                }
                if constexpr (s == 4) { named_bar_sync(4, 352); load_bias(bq, biasq); }
                if constexpr (s == 5) reg_fence(accA);
                if constexpr (s >= 5) gelu_blocks<(s - 5) * 2, 2, 96>(accA, h, bq, rs0, rs1);
                if constexpr (s == 8) load_bias(bq, biasq + 128);
            });
        }
        PROF(3);
#pragma unroll
        for (int i = 32; i < 96; i++) asm volatile("mov.u32 %0, 0;" : "=r"(h[i]));
#pragma unroll 1
        for (int p = 1; p < 4; p++) {
            biasq += 256;
            tile_pair<false, false>(c, accA, accB, h, [&](auto sc) {
                constexpr int s = decltype(sc)::value;
                if constexpr (s == 0) {
                    reg_fence(accB);
#pragma unroll
                    for (int i = 0; i < 80; i++) h[i] = h[i + 32];
                }
                if constexpr (s < 4) gelu_blocks<s * 2, 2, 80>(accB, h, bq, rs0, rs1);
                if constexpr (s == 4) load_bias(bq, biasq);
                if constexpr (s == 5) reg_fence(accA);
                if constexpr (s >= 5) gelu_blocks<(s - 5) * 2, 2, 96>(accA, h, bq, rs0, rs1);
                if constexpr (s == 8) load_bias(bq, biasq + 128);
            });
        }
        PROF(4);
        tile_pair<false, true>(c, accA, accB, h, [&](auto sc) {
            constexpr int s = decltype(sc)::value;
            if constexpr (s == 0) reg_fence(accB);
            if constexpr (s < 4) gelu_blocks<s * 2, 2, 112>(accB, h, bq, rs0, rs1);
            if constexpr (s == 4) load_bias(bq, biasq + 256);
            if constexpr (s == 5) { reg_fence(accA); if (tid == wg * 128) mbar_arrive(bar0 + B_XNDEAD * 8); }
            if constexpr (s == 5 || s == 6) gelu_blocks<(s - 5) * 3, 3, 128>(accA, h, bq, rs0, rs1);
            if constexpr (s == 7) gelu_blocks<6, 2, 128>(accA, h, bq, rs0, rs1);
            if constexpr (s == 3 || s == 7) reg_fence(h);
        });
        PROF(5);
        uint4* pout = g_part + j * SLAB + rb * 36 * 256 + tid;
#pragma unroll 1
        for (int p = 0; p < 4; p++) {
            tile_pair<true, true>(c, accA, accB, h, [&](auto sc) {
                constexpr int s = decltype(sc)::value;
                if constexpr (s == 0) reg_fence(accB);
                if constexpr (s < 4) store_part<s>(accB, pout);
                if constexpr (s == 5) reg_fence(accA);
                if constexpr (s >= 5) store_part<s - 5>(accA, pout + 1024);
            });
            pout += 2048;
            PROF(6 + p);
        }
        wg_wait<0>();
        c.release(8);
        reg_fence(accB);
        store_part<0>(accB, pout); store_part<1>(accB, pout); store_part<2>(accB, pout); store_part<3>(accB, pout);
        __syncwarp();
        if (lane == 0) mbar_arrive(bar0 + B_FFN * 8);
        PROF(10);
        PROFT(49);

        mbar_wait_c(bar0 + B_QRDY * 8, 0);
        const uint32_t slow = __any_sync(~0u, *slow_flag != 0);
        const uint64_t kd0 = mk_desc(zero, sb + SM_KV, 0, KV_GROUP_BYTES, 0);
        const uint64_t vd0 = mk_desc(zero, sb + SM_KV + 256, KV_GROUP_BYTES, 128, 0);
        const uint64_t qd0 = mk_desc(zero, sb + SM_Q + wg * 4096, 128, 512, 0);
        const uint32_t kvbar = bar0 + B_KV * 8;
        float o[12];
#pragma unroll
        for (int i = 0; i < 12; i++) o[i] = 0.f;
        PROF(16);
        PROFT(50);
        if (!slow) {
            const uint32_t one2 = 0x3F803F80u + (uint32_t)zero;
            float s0[64], s1[64];
            uint32_t p0[32], p1[32];
            mbar_wait_c(kvbar, 0);
            reg_fence(o);
            wg_fence();
            issue_qk<0>(s0, qd0, kd0);
            wg_commit();
            mbar_wait_c(kvbar + 8, 0);
            wg_fence();
            issue_qk<KV_TILE>(s1, qd0, kd0);
            wg_commit();
            uint64_t qd = qd0;
            const uint32_t fre = (tid == wg * 128) ? bar0 + B_FREE * 8 - 8 : 0;
#pragma unroll 1
            for (int pass = 0; pass < 4; pass++) {
                uint64_t vd = vd0, kdn = kd0 + 2 * KV_TILE;
                uint32_t bn = kvbar + 16;
#pragma unroll 1
                for (int it = 0; it < 8; it++) {
                    if (it == 7) { kdn = kd0; bn = kvbar; qd += 512; }
                    wg_wait<1>();
                    reg_fence(s0);
                    if (pass == 3 && it > 0 && fre) mbar_arrive(fre + it * 8);
                    softmax_fast<16>(s0, p0, one2);
                    reg_fence(p0);
                    if (it == 0 && pass != 0) {
                        wg_wait<0>();
                        reg_fence(o);
                        store_o(o, quarter * 8 + pass * 2 - 2 + wg, head, wq, lane);
                        reg_fence(o);
                    }
                    mbar_wait_c(bn, 0);
                    wg_fence();
                    issue_pv<0>(o, p0, vd);
                    issue_qk<0>(s0, qd, kdn);
                    wg_commit();
                    wg_wait<1>();
                    reg_fence(s1);
                    softmax_fast<16>(s1, p1, one2);
                    reg_fence(p1);
                    mbar_wait_c(bn + 8, 0);
                    wg_fence();
                    issue_pv<KV_TILE>(o, p1, vd);
                    issue_qk<KV_TILE>(s1, qd, kdn);
                    wg_commit();
                    vd += 2 * KV_TILE; kdn += 2 * KV_TILE; bn += 16;
                }
                if (pass == 0) PROF(17);
            }
            wg_wait<0>();
            reg_fence(o);
            reg_fence(s0);
            reg_fence(s1);
            store_o(o, quarter * 8 + 6 + wg, head, wq, lane);
        } else {
#pragma unroll 1
            for (int pass = 0; pass < 4; pass++) {
                float m0 = -INFINITY, m1 = -INFINITY;
                float s[64];
                uint32_t p[32];
#pragma unroll 1
                for (int t = 0; t < 16; t++) {
                    mbar_wait_c(kvbar + t * 8, 0);
                    wg_fence();
                    issue_qk<0>(s, qd0 + pass * 512, kd0 + t * KV_TILE);
                    wg_commit();
                    wg_wait<0>();
                    reg_fence(s);
                    float a0 = m0, a1 = m1;
#pragma unroll
                    for (int k = 0; k < 16; k++) {
                        if ((POLY_MASK >> (k & 7)) & 1) {
#pragma unroll
                            for (int i = 0; i < 4; i++) s[k * 4 + i] *= 0.5f;
                        }
                        a0 = fmaxf(a0, fmaxf(s[k * 4 + 0], s[k * 4 + 1]));
                        a1 = fmaxf(a1, fmaxf(s[k * 4 + 2], s[k * 4 + 3]));
                    }
                    a0 = fmaxf(a0, __shfl_xor_sync(~0u, a0, 1)); a1 = fmaxf(a1, __shfl_xor_sync(~0u, a1, 1));
                    a0 = fmaxf(a0, __shfl_xor_sync(~0u, a0, 2)); a1 = fmaxf(a1, __shfl_xor_sync(~0u, a1, 2));
                    const float r0 = ex2(m0 - a0), r1 = ex2(m1 - a1);
                    m0 = a0; m1 = a1;
#pragma unroll
                    for (int i = 0; i < 3; i++) { o[i * 4] *= r0; o[i * 4 + 1] *= r0; o[i * 4 + 2] *= r1; o[i * 4 + 3] *= r1; }
#pragma unroll
                    for (int k = 0; k < 16; k++) {
                        p[k * 2 + 0] = pack_bf16(ex2(s[k * 4 + 0] - m0), ex2(s[k * 4 + 1] - m0));
                        p[k * 2 + 1] = pack_bf16(ex2(s[k * 4 + 2] - m1), ex2(s[k * 4 + 3] - m1));
                    }
                    reg_fence(p);
                    reg_fence(o);
                    wg_fence();
                    issue_pv<0>(o, p, vd0 + t * KV_TILE);
                    wg_commit();
                    wg_wait<0>();
                    reg_fence(o);
                }
                store_o(o, quarter * 8 + pass * 2 + wg, head, wq, lane);
            }
            if (tid == wg * 128)
                for (int i = 0; i < 7; i++) mbar_arrive(bar0 + (B_FREE + i) * 8);
        }
        PROF(18);
        PROFT(51);

        const int t128 = tid & 127;
        named_bar_sync(1 + wg, 128);
        if (t128 == 0) flag_signal(&g_flags.o_done[quarter]);
        const size_t orow = (size_t)(rt * 64 + wq * 16 + g + wg * 8) * DM + ct * 144 + q * 2;
        float bs[36];
        {
            uint32_t xv[18], bv[18];
            uint2 fv[9];
#pragma unroll
            for (int i = 0; i < 18; i++) {
                xv[i] = __ldg(reinterpret_cast<const uint32_t*>(x + orow) + i * 4);
                bv[i] = __ldg(reinterpret_cast<const uint32_t*>(b2 + ct * 144 + q * 2) + i * 4);
            }
            mbar_wait_c(bar0 + B_BASE * 8, 0);
#pragma unroll
            for (int i = 0; i < 9; i++) fv[i] = __ldcg(g_ffn + blockIdx.x * 2304 + (wg * 9 + i) * 128 + t128);
#pragma unroll
            for (int i = 0; i < 18; i++) {
                const uint32_t f = (i & 1) ? fv[i >> 1].y : fv[i >> 1].x;
                bs[i * 2] = fmaf(bf_lo(f), 0.5f, bf_lo(xv[i]) + bf_lo(bv[i]));
                bs[i * 2 + 1] = fmaf(bf_hi(f), 0.5f, bf_hi(xv[i]) + bf_hi(bv[i]));
            }
        }
        if (t128 == 0) flag_wait(&g_flags.o_done[quarter], 64, 0);
        named_bar_sync(1 + wg, 128);
        if (t128 == 0) mbar_arrive(bar0 + B_DONE * 8);
        PROF(19);
        uint4 af[18];
        {
            const uint4* ap = reinterpret_cast<const uint4*>(g_O) + (rt * 36 + wg * 18) * 128 + t128;
#pragma unroll
            for (int k = 0; k < 18; k++) af[k] = __ldcg(ap + k * 128);
        }
        float acc[72];
        const uint64_t wd0 = mk_desc(zero, sb, 2304, 128, 0), wd1 = wd0 + wg * ((18 * 4608) >> 4);
#pragma unroll 1
        for (int i = 0; i < 5; i++) mbar_wait_c(bar0 + (B_WO + wg * 4 + i) * 8, 0);
        wg_fence();
        static_for<0, 18>([&](auto kc) {
            constexpr int k = decltype(kc)::value;
            if constexpr (k < 8) {
                constexpr int o0 = (sm_wo(k >> 2) + (k & 3) * 4608) >> 4, o1 = (SM_KV + (k + 10) * 4608) >> 4;
                wgmma_rs_n144<1, 0>(acc, af[k].x, af[k].y, af[k].z, af[k].w, wd0 + (wg ? o1 : o0), k != 0);
            } else {
                wgmma_rs_n144<1, (SM_KV + (k - 8) * 4608) / 16>(acc, af[k].x, af[k].y, af[k].z, af[k].w, wd1, 1);
            }
        });
        wg_commit();
        wg_wait<0>();
        reg_fence(acc);
        PROF(20);
        {
            float4* ex = reinterpret_cast<float4*>(smem + SM_EXCH) + t128;
#pragma unroll
            for (int i = 0; i < 9; i++) {
                const float4 lo = make_float4(acc[i * 8], acc[i * 8 + 1], acc[i * 8 + 4], acc[i * 8 + 5]);
                const float4 hi = make_float4(acc[i * 8 + 2], acc[i * 8 + 3], acc[i * 8 + 6], acc[i * 8 + 7]);
                ex[(wg * 9 + i) * 128] = wg ? lo : hi;
                const float4 own = wg ? hi : lo;
                bs[i * 4] += own.x; bs[i * 4 + 1] += own.y; bs[i * 4 + 2] += own.z; bs[i * 4 + 3] += own.w;
            }
            named_bar_sync(5, 256);
            uint32_t* op = reinterpret_cast<uint32_t*>(out + orow);
#pragma unroll
            for (int i = 0; i < 9; i++) {
                const float4 v = ex[((wg ^ 1) * 9 + i) * 128];
                op[i * 8] = pack_bf16(bs[i * 4] + v.x, bs[i * 4 + 1] + v.y);
                op[i * 8 + 4] = pack_bf16(bs[i * 4 + 2] + v.z, bs[i * 4 + 3] + v.w);
            }
        }
        PROF(21);
        PROFT(52);
    } else {
        reg_dealloc<24>();
        if (warp == 8 && lane == 0) {
            prefetch_tmap(&tmQ3); prefetch_tmap(&tmQ1); prefetch_tmap(&tm1); prefetch_tmap(&tm2);
            #pragma unroll 1
            for (int i = 0; i < 9; i++) { mbar_init(full0 + i * 8, 1); mbar_init(empty0 + i * 8, 4); mbar_init(bar0 + (B_WO + i) * 8, 1); }
            mbar_init(bar0 + B_BASE * 8, 3); mbar_init(bar0 + B_XNDEAD * 8, 2); mbar_init(bar0 + B_QRDY * 8, 3); mbar_init(bar0 + B_FFN * 8, 8); mbar_init(bar0 + B_DONE * 8, 2);
#pragma unroll 1
            for (int i = 0; i < 16; i++) { mbar_init(bar0 + (B_KV + i) * 8, 1); mbar_init(bar0 + (B_FREE + (i & 7)) * 8, 2); if (i < 6) mbar_init(bar0 + (B_RED + i) * 8, 1); }
            *slow_flag = 0;
            fence_barrier_init();
        }
        __syncwarp();
        cluster_arrive();
        cluster_wait();
        const uint8_t* kvsrc = g_QKV + (size_t)head * KV_HEAD_BYTES;
        if (warp == 8) {
            if (lane == 0) {
                int st = 0, u = rank, tile = -4;
                int es = 5;
                uint32_t eph = 1;
#pragma unroll 1
                for (int n = 0; n < 99; n++) {
                    mbar_wait(empty0 + es * 8, eph);
                    const uint32_t fb = full0 + st * 8, dst = sb + K1_OFF_RING + u * 8192;
                    mbar_expect(fb, 16384);
                    if (tile < 0) {
                        tma3d_mc(dst, &tmQ3, j * 216, n * 32 + rank * 16, 0, fb, 3);
                        tma2d_mc(dst + 6144, &tmQ1, j * 216 + 192, n * 32 + rank * 16, fb, 3);
                    } else if (tile < 9) {
                        tma2d_mc(dst, &tm1, j * 576 + tile * 64, u * 64, fb, 3);
                    } else {
                        tma2d_mc(dst, &tm2, (tile - 9) * 64, j * 576 + u * 64, fb, 3);
                    }
                    u += 2;
                    if (u >= 9) { u -= 9; tile++; }
                    if (++st == 9) st = 0;
                    if (++es == 9) { es = 0; eph ^= 1; }
                }
                mbar_wait(empty0 + 8 * 8, 0);
                mbar_wait(bar0 + B_QRDY * 8, 0);
                asm volatile("fence.proxy.async;" ::: "memory");
#pragma unroll 1
                for (int i = 11; i < NCHUNK; i++) {
                    mbar_expect(bar0 + (B_KV + i) * 8, CHUNK_BYTES);
                    bulk_load(sb + SM_KV + i * CHUNK_BYTES, kvsrc + i * CHUNK_BYTES, CHUNK_BYTES, bar0 + (B_KV + i) * 8);
                }
#pragma unroll 1
                for (int i = 0; i < 9; i++) {
                    if (i == 0) mbar_wait_sleep(bar0 + B_BASE * 8, 500);
                    if (i > 0) {
                        const int f = i == 1 ? 0 : ((i - 1) * 9 + 4) / 10;
                        mbar_wait_sleep(bar0 + (B_FREE + f) * 8, i == 1 ? 500 : 50);
                    }
                    mbar_expect(bar0 + (B_WO + i) * 8, WO_PIECE);
                    bulk_load(sb + (i == 0 ? sm_wo(0) : (i == 1 ? sm_wo(1) : SM_KV + (i - 2) * WO_PIECE)), g_Wo + ct * WO_TILE_BYTES + i * WO_PIECE, WO_PIECE,
                              bar0 + (B_WO + i) * 8);
                }
            }
        } else {
            const int ht = tid - 288;
            if (ht == 64) prefetch_l2(wqkv + blockIdx.x * (DM * 3 * DM / 128), DM * 3 * DM / 64);
            if (ht < 72) {
                const uint4 v = __ldg(reinterpret_cast<const uint4*>(b1 + j * 576) + ht);
                uint32_t* sbias = reinterpret_cast<uint32_t*>(smem + K1_OFF_BIAS) + (ht >> 3) * 32 + (ht & 7);
                sbias[0] = v.x; sbias[8] = v.y; sbias[16] = v.z; sbias[24] = v.w;
            }
            asm volatile("bar.arrive 4, 352;" ::: "memory");
            PROFH(37);
#pragma unroll 1
            for (int i = ht; i < 512; i += 96) {
                const int key = i & 127;
                uint8_t* p = g_QKV + (size_t)(j * 4 + (i >> 7)) * KV_HEAD_BYTES + (rb * 16 + (key >> 3)) * KV_GROUP_BYTES + 512 + (key & 7) * 16;
                *reinterpret_cast<uint32_t*>(p + 4) = ((POLY_MASK >> ((key >> 3) & 7)) & 1) ? 0x3F804000u : 0x00003F80u;
                *reinterpret_cast<uint32_t*>(p + 12) = 0x00003F80u;
            }
            if (ht == 32) prefetch_l2(w1 + blockIdx.x * (DM * FF / 128), DM * FF / 64);
#pragma unroll 2
            for (int i = blockIdx.x * 324 + ht; i < blockIdx.x * 324 + 324; i += 96) {
                const int k = i / 72, nc = i - k * 72, c4 = nc / 18;
                *reinterpret_cast<uint4*>(g_Wo + c4 * WO_TILE_BYTES + (k >> 3) * 2304 + (nc - c4 * 18) * 128 + (k & 7) * 16) =
                    __ldg(reinterpret_cast<const uint4*>(wo) + i);
            }
            PROFH(38);
            named_bar_sync(3, 352);
            if (ht == 32) prefetch_l2(w2 + blockIdx.x * (DM * FF / 128), DM * FF / 64);
            if (ht == 0) {
                flag_signal(&g_flags.qkv_stored[rb]);
                flag_wait(&g_flags.qkv_stored[rb], 8, 200);
            }
            named_bar_sync(7, 96);
            PROFH(39);
#pragma unroll 1
            for (int i = warp - 9; i < 16; i += 3) {
                const int hd = j * 4 + (i >> 2), key = (i & 3) * 32 + lane;
                const uint8_t* p = g_QKV + (size_t)hd * KV_HEAD_BYTES + (rb * 16 + (key >> 3)) * KV_GROUP_BYTES + (key & 7) * 16;
                const uint4 a = __ldcg(reinterpret_cast<const uint4*>(p)), b = __ldcg(reinterpret_cast<const uint4*>(p + 128));
                float n = sumsq2(__ldcg(reinterpret_cast<const uint32_t*>(p + 512))) + sumsq8(a) + sumsq8(b);
                if ((POLY_MASK >> ((key >> 3) & 7)) & 1) n *= 0.25f;
#pragma unroll
                for (int o = 16; o; o >>= 1) n = fmaxf(n, __shfl_xor_sync(~0u, n, o));
                if (lane == 0) g_kmax[hd * 64 + rb * 4 + (i & 3)] = n;
            }
            named_bar_sync(7, 96);
            PROFH(40);
            if (ht == 0) {
                flag_signal(&g_flags.kv_ready);
                flag_wait(&g_flags.kv_ready, 128, 300);
                mbar_wait_sleep(bar0 + B_XNDEAD * 8, 300);
            }
            named_bar_sync(7, 96);
            PROFH(41);
            float kmax2;
            {
                const float2 v = __ldcg(reinterpret_cast<const float2*>(g_kmax + head * 64 + lane * 2));
                kmax2 = fmaxf(v.x, v.y);
#pragma unroll
                for (int o = 16; o; o >>= 1) kmax2 = fmaxf(kmax2, __shfl_xor_sync(~0u, kmax2, o));
            }
            asm volatile("fence.proxy.async;" ::: "memory");
            int chunk = warp - 9;
#pragma unroll 1
            for (int r = ht; r < 512; r += 96) {
                if (lane == 0 && chunk < 11) {
                    mbar_expect(bar0 + (B_KV + chunk) * 8, CHUNK_BYTES);
                    bulk_load(sb + SM_KV + chunk * CHUNK_BYTES, kvsrc + chunk * CHUNK_BYTES, CHUNK_BYTES, bar0 + (B_KV + chunk) * 8);
                }
                chunk += 3;
                const uint8_t* p = kvsrc + Q_OFFSET + (quarter * 64 + (r >> 3)) * KV_GROUP_BYTES + (r & 7) * 16;
                const uint4 a = __ldcg(reinterpret_cast<const uint4*>(p)), b = __ldcg(reinterpret_cast<const uint4*>(p + 128));
                const uint32_t e = __ldcg(reinterpret_cast<const uint32_t*>(p + 256));
                const float cc = sqrtf((sumsq2(e) + sumsq8(a) + sumsq8(b)) * kmax2) * 1.02f;
                if (!(cc <= 58.f)) *slow_flag = 1;
                uint4* dst = reinterpret_cast<uint4*>(smem + SM_Q + (r >> 3) * 512 + (r & 7) * 16);
                dst[0] = a;
                dst[8] = b;
                dst[16] = make_uint4(e, pack_bf16(-cc, 768.f), 0u, 0u);
                dst[24] = make_uint4(0u, POLY_MODE ? 0xBFFF0000u : 0xC0000000u, 0u, 0u);
            }
            named_bar_sync(7, 96);
            if (*slow_flag) {
#pragma unroll 1
                for (int r = ht; r < 512; r += 96) {
                    uint32_t* dst = reinterpret_cast<uint32_t*>(smem + SM_Q + (r >> 3) * 512 + (r & 7) * 16);
                    dst[65] = 0u;
                    dst[97] = 0u;
                }
            }
            fence_proxy_async();
            __syncwarp();
            if (lane == 0) mbar_arrive(bar0 + B_QRDY * 8);
            PROFH(42);
            if (ht == 0) {
                mbar_wait_sleep(bar0 + B_FFN * 8, 300);
                flag_signal(&g_flags.ffn_done[rb]);
                flag_wait(&g_flags.ffn_done[rt >> 1], 8, 300);
            }
            named_bar_sync(7, 96);
            {
                const int w3 = warp - 9;
                const uint32_t rbar = bar0 + (B_RED + w3 * 2) * 8, rbuf = SM_RED + w3 * 8192;
                const int u0 = ((rt >> 1) * 36 + ct * 9) * 256 + (rt & 1) * 128;
                mbar_wait_sleep(bar0 + (B_KV + 15) * 8, 500);
                asm volatile("fence.proxy.async;" ::: "memory");
#pragma unroll 1
                for (int i = -2; i < 12; i++) {
                    if (i >= 0) {
                        __nanosleep(400);
                        mbar_wait(rbar + (i & 1) * 8, (i >> 1) & 1);
                        const uint4* sp = reinterpret_cast<const uint4*>(smem + rbuf + (i & 1) * 4096) + lane;
                        const uint4 v = hadd8_bf16(hadd8_bf16(hadd8_bf16(sp[0], sp[32]), hadd8_bf16(sp[64], sp[96])),
                                                   hadd8_bf16(hadd8_bf16(sp[128], sp[160]), hadd8_bf16(sp[192], sp[224])));
                        uint2* fp = g_ffn + blockIdx.x * 2304 + (i * 3 + w3) * 32 + lane;
                        fp[0] = make_uint2(v.x, v.z);
                        fp[1152] = make_uint2(v.y, v.w);
                    }
                    __syncwarp();
                    if (lane == 0 && i < 10) {
                        const int bx = (i + 2) * 3 + w3;
                        mbar_expect(rbar + (i & 1) * 8, 4096);
                        tma2d(sb + rbuf + (i & 1) * 4096, &tmP, (u0 + (bx >> 2) * 256 + (bx & 3) * 32) * 2, 0, rbar + (i & 1) * 8);
                    }
                }
            }
            __syncwarp();
            if (lane == 0) mbar_arrive(bar0 + B_BASE * 8);
            PROFH(43);
            if (ht == 0) {
                mbar_wait_sleep(bar0 + B_DONE * 8, 500);
                if (atomicAdd(&g_flags.exited, 1u) == gridDim.x - 1) {
                    unsigned int* f = reinterpret_cast<unsigned int*>(&g_flags);
#pragma unroll 1
                    for (int i = 0; i < (int)(sizeof(Flags) / 4); i++) f[i] = 0;
                }
            }
        }
    }
}

typedef CUresult (*EncodeFn)(CUtensorMap*, CUtensorMapDataType, cuuint32_t, void*, const cuuint64_t*, const cuuint64_t*, const cuuint32_t*,
                             const cuuint32_t*, CUtensorMapInterleave, CUtensorMapSwizzle, CUtensorMapL2promotion, CUtensorMapFloatOOBfill);

void make_map(EncodeFn fn, CUtensorMap* m, const void* base, int rank, const cuuint64_t* dims, const cuuint64_t* strides, const cuuint32_t* box) {
    cuuint32_t es[4] = {1, 1, 1, 1};
    fn(m, CU_TENSOR_MAP_DATA_TYPE_BFLOAT16, rank, const_cast<void*>(base), dims, strides, box, es, CU_TENSOR_MAP_INTERLEAVE_NONE,
       CU_TENSOR_MAP_SWIZZLE_128B, CU_TENSOR_MAP_L2_PROMOTION_L2_256B, CU_TENSOR_MAP_FLOAT_OOB_FILL_NONE);
}

}

extern "C" void kernel_launch(void* const* d_in, const int* in_sizes, int n_in, void* d_out, int out_size) {
    const __nv_bfloat16* x = (const __nv_bfloat16*)d_in[0];
    const __nv_bfloat16* wqkv = (const __nv_bfloat16*)d_in[1];
    const __nv_bfloat16* wo = (const __nv_bfloat16*)d_in[2];
    const __nv_bfloat16* w1 = (const __nv_bfloat16*)d_in[4];
    const __nv_bfloat16* b1 = (const __nv_bfloat16*)d_in[5];
    const __nv_bfloat16* w2 = (const __nv_bfloat16*)d_in[6];
    const __nv_bfloat16* b2 = (const __nv_bfloat16*)d_in[7];
    __nv_bfloat16* out = (__nv_bfloat16*)d_out;

    EncodeFn fn = nullptr;
    cudaDriverEntryPointQueryResult qr;
    cudaGetDriverEntryPoint("cuTensorMapEncodeTiled", (void**)&fn, cudaEnableDefault, &qr);
    CUtensorMap tmX, tmQ3, tmQ1, tm1, tm2, tmP;
    {
        void* gp = nullptr;
        cudaGetSymbolAddress(&gp, g_part);
        cuuint64_t d[2] = {SLAB * 2, 8}, s[1] = {SLAB * 16};
        cuuint32_t b[2] = {64, 8}, es[2] = {1, 1};
        fn(&tmP, CU_TENSOR_MAP_DATA_TYPE_INT64, 2, gp, d, s, b, es, CU_TENSOR_MAP_INTERLEAVE_NONE, CU_TENSOR_MAP_SWIZZLE_NONE,
           CU_TENSOR_MAP_L2_PROMOTION_NONE, CU_TENSOR_MAP_FLOAT_OOB_FILL_NONE);
    }
    {
        cuuint64_t d[4] = {64, 8, 9, SEQ / 8}, s[3] = {DM * 2, 128, DM * 2 * 8};
        cuuint32_t b[4] = {64, 8, 3, 2};
        make_map(fn, &tmX, x, 4, d, s, b);
    }
    {
        cuuint64_t d[3] = {3 * DM, DM, 3}, s[2] = {3 * DM * 2, 128};
        cuuint32_t b[3] = {64, 16, 3};
        make_map(fn, &tmQ3, wqkv, 3, d, s, b);
        make_map(fn, &tmQ1, wqkv, 2, d, s, b);
    }
    {
        cuuint64_t d[2] = {FF, DM}, s[1] = {FF * 2};
        cuuint32_t b[2] = {64, 64};
        make_map(fn, &tm1, w1, 2, d, s, b);
        cuuint64_t d2[2] = {DM, FF}, s2[1] = {DM * 2};
        make_map(fn, &tm2, w2, 2, d2, s2, b);
    }
    cudaFuncSetAttribute(fused_kernel, cudaFuncAttributeMaxDynamicSharedMemorySize, K1_SMEM);
    fused_kernel<<<128, 384, K1_SMEM, cudaStreamPerThread>>>(tmX, tmQ3, tmQ1, tm1, tm2, tmP, b1, wqkv, w1, w2, wo, x, b2, out, 0ull);
}
```

```cpp
#include <cuda_runtime.h>
#include <cuda_bf16.h>
#include <cuda.h>
#include <stdint.h>

#define PROF(i) do { } while (0)
#define PROFT(i) do { } while (0)
#define PROFH(i) do { } while (0)
#define PROF_WG 0

namespace {

constexpr int SEQ = 2048, DM = 576, FF = 4608, NH = 32, DH = 18;

constexpr int KV_GROUP_BYTES = 5 * 128;
constexpr int KV_HEAD_BYTES = (SEQ / 8) * KV_GROUP_BYTES;
constexpr int Q_OFFSET = NH * KV_HEAD_BYTES;
#define POLY_MASK 0xB6
__device__ __align__(1024) uint8_t g_QKV[2 * NH * KV_HEAD_BYTES];
__device__ __align__(1024) float g_kmax[NH * 64];
constexpr int SLAB = 16 * 36 * 256;
__device__ __align__(1024) uint4 g_part[8 * SLAB];
__device__ __align__(1024) uint2 g_ffn[128 * 2 * 9 * 128];
__device__ __align__(1024) uint32_t g_O[SEQ * DM / 2];
struct Flags {
    unsigned int qkv_stored[16];
    unsigned int ffn_done[16];
    unsigned int o_done[4];
    unsigned int kv_ready;
    unsigned int exited;
};
__device__ Flags g_flags;
constexpr int WO_TILE_BYTES = DM * 144 * 2;
__device__ __align__(1024) uint8_t g_Wo[4 * WO_TILE_BYTES];

__device__ __forceinline__ uint32_t s2u(const void* p) { return (uint32_t)__cvta_generic_to_shared(p); }
__device__ __forceinline__ void mbar_init(uint32_t b, int c) { asm volatile("mbarrier.init.shared::cta.b64 [%0], %1;" ::"r"(b), "r"(c) : "memory"); }
__device__ __forceinline__ void mbar_expect(uint32_t b, uint32_t bytes) {
    asm volatile("mbarrier.arrive.expect_tx.shared::cta.b64 _, [%0], %1;" ::"r"(b), "r"(bytes) : "memory");
}
__device__ __forceinline__ bool mbar_try(uint32_t b, uint32_t parity) {
    uint32_t ok;
    asm volatile("{\n.reg .pred p;\nmbarrier.try_wait.parity.shared::cta.b64 p, [%1], %2;\nselp.u32 %0, 1, 0, p;\n}\n" : "=r"(ok) : "r"(b), "r"(parity) : "memory");
    return ok != 0;
}
__device__ __forceinline__ void mbar_wait(uint32_t b, uint32_t parity) {
    if (__builtin_expect(!mbar_try(b, parity), 0)) {
        uint32_t spins = 0;
        while (!mbar_try(b, parity))
            if (++spins > (1u << 22)) __trap();
    }
}
__device__ __forceinline__ void fence_barrier_init() { asm volatile("fence.mbarrier_init.release.cluster;" ::: "memory"); }
__device__ __forceinline__ void fence_proxy_async() { asm volatile("fence.proxy.async.shared::cta;" ::: "memory"); }
__device__ __forceinline__ void cluster_arrive() { asm volatile("barrier.cluster.arrive.relaxed.aligned;" ::: "memory"); }
__device__ __forceinline__ void cluster_wait() { asm volatile("barrier.cluster.wait.aligned;" ::: "memory"); }
__device__ __forceinline__ void named_bar_sync(int id, int n) { asm volatile("bar.sync %0, %1;" ::"r"(id), "r"(n) : "memory"); }

__device__ __forceinline__ void tma3d_mc(uint32_t dst, const CUtensorMap* tm, int c0, int c1, int c2, uint32_t bar, uint16_t mask) {
    asm volatile("cp.async.bulk.tensor.3d.shared::cluster.global.mbarrier::complete_tx::bytes.multicast::cluster [%0], [%1, {%3, %4, %5}], [%2], %6;"
                 ::"r"(dst), "l"(tm), "r"(bar), "r"(c0), "r"(c1), "r"(c2), "h"(mask) : "memory");
}
__device__ __forceinline__ void tma2d_mc(uint32_t dst, const CUtensorMap* tm, int c0, int c1, uint32_t bar, uint16_t mask) {
    asm volatile("cp.async.bulk.tensor.2d.shared::cluster.global.mbarrier::complete_tx::bytes.multicast::cluster [%0], [%1, {%3, %4}], [%2], %5;"
                 ::"r"(dst), "l"(tm), "r"(bar), "r"(c0), "r"(c1), "h"(mask) : "memory");
}
__device__ __forceinline__ void tma4d(uint32_t dst, const CUtensorMap* tm, int c0, int c1, int c2, int c3, uint32_t bar) {
    asm volatile("cp.async.bulk.tensor.4d.shared::cluster.global.mbarrier::complete_tx::bytes [%0], [%1, {%3, %4, %5, %6}], [%2];"
                 ::"r"(dst), "l"(tm), "r"(bar), "r"(c0), "r"(c1), "r"(c2), "r"(c3) : "memory");
}
__device__ __forceinline__ void tma2d(uint32_t dst, const CUtensorMap* tm, int c0, int c1, uint32_t bar) {
    asm volatile("cp.async.bulk.tensor.2d.shared::cluster.global.mbarrier::complete_tx::bytes [%0], [%1, {%3, %4}], [%2];"
                 ::"r"(dst), "l"(tm), "r"(bar), "r"(c0), "r"(c1) : "memory");
}
__device__ __forceinline__ void bulk_load(uint32_t dst, const void* src, uint32_t bytes, uint32_t bar) {
    asm volatile("cp.async.bulk.shared::cluster.global.mbarrier::complete_tx::bytes [%0], [%1], %2, [%3];"
                 ::"r"(dst), "l"(src), "r"(bytes), "r"(bar) : "memory");
}
__device__ __forceinline__ void prefetch_l2(const void* p, uint32_t bytes) {
    asm volatile("cp.async.bulk.prefetch.L2.global [%0], %1;" ::"l"(p), "r"(bytes) : "memory");
}
__device__ __forceinline__ void prefetch_tmap(const CUtensorMap* tm) { asm volatile("prefetch.tensormap [%0];" ::"l"(tm) : "memory"); }

__device__ __forceinline__ void wg_fence() { asm volatile("wgmma.fence.sync.aligned;" ::: "memory"); }
__device__ __forceinline__ void wg_commit() { asm volatile("wgmma.commit_group.sync.aligned;" ::: "memory"); }
template <int N> __device__ __forceinline__ void wg_wait() { asm volatile("wgmma.wait_group.sync.aligned %0;" ::"n"(N) : "memory"); }
template <int N> __device__ __forceinline__ void reg_fence(float (&d)[N]) {
#pragma unroll
    for (int i = 0; i < N; i++) asm volatile("" : "+f"(d[i])::"memory");
}
template <int N> __device__ __forceinline__ void reg_fence(uint32_t (&d)[N]) {
#pragma unroll
    for (int i = 0; i < N; i++) asm volatile("" : "+r"(d[i])::"memory");
}
template <int R> __device__ __forceinline__ void reg_alloc() { asm volatile("setmaxnreg.inc.sync.aligned.u32 %0;" ::"n"(R)); }
template <int R> __device__ __forceinline__ void reg_dealloc() { asm volatile("setmaxnreg.dec.sync.aligned.u32 %0;" ::"n"(R)); }

__device__ __forceinline__ uint64_t mk_desc(uint64_t z, uint32_t addr, uint32_t lbo, uint32_t sbo, uint32_t swz) {
    return z + ((uint64_t)(((addr & 0x3FFFF) >> 4) | ((lbo >> 4) << 16)) | ((uint64_t)((sbo >> 4) | (swz << 30)) << 32));
}
__device__ __forceinline__ uint32_t pack_bf16(float lo, float hi) {
    uint32_t r;
    asm("cvt.rn.bf16x2.f32 %0, %1, %2;" : "=r"(r) : "f"(hi), "f"(lo));
    return r;
}
__device__ __forceinline__ float bf_lo(uint32_t w) { return __uint_as_float(w << 16); }
__device__ __forceinline__ float bf_hi(uint32_t w) { return __uint_as_float(w & 0xFFFF0000u); }
__device__ __forceinline__ float ex2(float x) {
    float r;
    asm("ex2.approx.ftz.f32 %0, %1;" : "=f"(r) : "f"(x));
    return r;
}
__device__ __forceinline__ float tanh_fast(float x) {
    float r;
    asm("tanh.approx.f32 %0, %1;" : "=f"(r) : "f"(x));
    return r;
}
__device__ __forceinline__ uint32_t hfma2_bf16(uint32_t a, uint32_t b, uint32_t c) {
    uint32_t r;
    asm("fma.rn.bf16x2 %0, %1, %2, %3;" : "=r"(r) : "r"(a), "r"(b), "r"(c));
    return r;
}
__device__ __forceinline__ uint32_t hadd2_bf16(uint32_t a, uint32_t b) {
    uint32_t r;
    asm("add.rn.bf16x2 %0, %1, %2;" : "=r"(r) : "r"(a), "r"(b));
    return r;
}
__device__ __forceinline__ void ldsm4(uint32_t (&a)[4], uint32_t addr) {
    asm volatile("ldmatrix.sync.aligned.m8n8.x4.shared.b16 {%0, %1, %2, %3}, [%4];" : "=r"(a[0]), "=r"(a[1]), "=r"(a[2]), "=r"(a[3]) : "r"(addr) : "memory");
}
__device__ __forceinline__ void stsm4(uint32_t addr, const uint32_t (&a)[4]) {
    asm volatile("stmatrix.sync.aligned.m8n8.x4.shared.b16 [%0], {%1, %2, %3, %4};" ::"r"(addr), "r"(a[0]), "r"(a[1]), "r"(a[2]), "r"(a[3]) : "memory");
}
__device__ __forceinline__ void mma16816(float (&c)[4], const uint32_t (&a)[4], uint32_t b0, uint32_t b1) {
    asm("mma.sync.aligned.m16n8k16.row.col.f32.bf16.bf16.f32 {%0, %1, %2, %3}, {%4, %5, %6, %7}, {%8, %9}, {%0, %1, %2, %3};"
        : "+f"(c[0]), "+f"(c[1]), "+f"(c[2]), "+f"(c[3]) : "r"(a[0]), "r"(a[1]), "r"(a[2]), "r"(a[3]), "r"(b0), "r"(b1));
}
__device__ __forceinline__ float gelu2(float u) {
    const float w = fmaf(u * u, 0.0356774081f, 0.7978845608f);
    return fmaf(u, tanh_fast(u * w), u);
}

template<int TB, int AOFF, int BOFF> __device__ __forceinline__ void wgmma_ss_n216(float (&d)[108], uint64_t da, uint64_t db, int sd) {
    asm volatile("{\n.reg .pred p;\n.reg .b64 ta, tb;\nsetp.ne.b32 p, %110, 0;\nadd.s64 ta, %108, %112;\nadd.s64 tb, %109, %113;\n"
      "wgmma.mma_async.sync.aligned.m64n216k16.f32.bf16.bf16 {%0, %1, %2, %3, %4, %5, %6, %7, %8, %9, %10, %11, %12, %13, %14, %15, %16, %17, %18, %19, %20, %21, %22, %23, %24, %25, %26, %27, %28, %29, %30, %31, %32, %33, %34, %35, %36, %37, %38, %39, %40, %41, %42, %43, %44, %45, %46, %47, %48, %49, %50, %51, %52, %53, %54, %55, %56, %57, %58, %59, %60, %61, %62, %63, %64, %65, %66, %67, %68, %69, %70, %71, %72, %73, %74, %75, %76, %77, %78, %79, %80, %81, %82, %83, %84, %85, %86, %87, %88, %89, %90, %91, %92, %93, %94, %95, %96, %97, %98, %99, %100, %101, %102, %103, %104, %105, %106, %107}, ta, tb, p, 1, 1, 0, %111;\n}\n"
      : "+f"(d[0]), "+f"(d[1]), "+f"(d[2]), "+f"(d[3]), "+f"(d[4]), "+f"(d[5]), "+f"(d[6]), "+f"(d[7]), "+f"(d[8]), "+f"(d[9]), "+f"(d[10]), "+f"(d[11]), "+f"(d[12]), "+f"(d[13]), "+f"(d[14]), "+f"(d[15]), "+f"(d[16]), "+f"(d[17]), "+f"(d[18]), "+f"(d[19]), "+f"(d[20]), "+f"(d[21]), "+f"(d[22]), "+f"(d[23]), "+f"(d[24]), "+f"(d[25]), "+f"(d[26]), "+f"(d[27]), "+f"(d[28]), "+f"(d[29]), "+f"(d[30]), "+f"(d[31]), "+f"(d[32]), "+f"(d[33]), "+f"(d[34]), "+f"(d[35]), "+f"(d[36]), "+f"(d[37]), "+f"(d[38]), "+f"(d[39]), "+f"(d[40]), "+f"(d[41]), "+f"(d[42]), "+f"(d[43]), "+f"(d[44]), "+f"(d[45]), "+f"(d[46]), "+f"(d[47]), "+f"(d[48]), "+f"(d[49]), "+f"(d[50]), "+f"(d[51]), "+f"(d[52]), "+f"(d[53]), "+f"(d[54]), "+f"(d[55]), "+f"(d[56]), "+f"(d[57]), "+f"(d[58]), "+f"(d[59]), "+f"(d[60]), "+f"(d[61]), "+f"(d[62]), "+f"(d[63]), "+f"(d[64]), "+f"(d[65]), "+f"(d[66]), "+f"(d[67]), "+f"(d[68]), "+f"(d[69]), "+f"(d[70]), "+f"(d[71]), "+f"(d[72]), "+f"(d[73]), "+f"(d[74]), "+f"(d[75]), "+f"(d[76]), "+f"(d[77]), "+f"(d[78]), "+f"(d[79]), "+f"(d[80]), "+f"(d[81]), "+f"(d[82]), "+f"(d[83]), "+f"(d[84]), "+f"(d[85]), "+f"(d[86]), "+f"(d[87]), "+f"(d[88]), "+f"(d[89]), "+f"(d[90]), "+f"(d[91]), "+f"(d[92]), "+f"(d[93]), "+f"(d[94]), "+f"(d[95]), "+f"(d[96]), "+f"(d[97]), "+f"(d[98]), "+f"(d[99]), "+f"(d[100]), "+f"(d[101]), "+f"(d[102]), "+f"(d[103]), "+f"(d[104]), "+f"(d[105]), "+f"(d[106]), "+f"(d[107])
      : "l"(da), "l"(db), "r"(sd), "n"(TB), "n"(AOFF), "n"(BOFF));
}

template<int TB, int AOFF, int BOFF> __device__ __forceinline__ void wgmma_ss_n64(float (&d)[32], uint64_t da, uint64_t db, int sd) {
    asm volatile("{\n.reg .pred p;\n.reg .b64 ta, tb;\nsetp.ne.b32 p, %34, 0;\nadd.s64 ta, %32, %36;\nadd.s64 tb, %33, %37;\n"
      "wgmma.mma_async.sync.aligned.m64n64k16.f32.bf16.bf16 {%0, %1, %2, %3, %4, %5, %6, %7, %8, %9, %10, %11, %12, %13, %14, %15, %16, %17, %18, %19, %20, %21, %22, %23, %24, %25, %26, %27, %28, %29, %30, %31}, ta, tb, p, 1, 1, 0, %35;\n}\n"
      : "+f"(d[0]), "+f"(d[1]), "+f"(d[2]), "+f"(d[3]), "+f"(d[4]), "+f"(d[5]), "+f"(d[6]), "+f"(d[7]), "+f"(d[8]), "+f"(d[9]), "+f"(d[10]), "+f"(d[11]), "+f"(d[12]), "+f"(d[13]), "+f"(d[14]), "+f"(d[15]), "+f"(d[16]), "+f"(d[17]), "+f"(d[18]), "+f"(d[19]), "+f"(d[20]), "+f"(d[21]), "+f"(d[22]), "+f"(d[23]), "+f"(d[24]), "+f"(d[25]), "+f"(d[26]), "+f"(d[27]), "+f"(d[28]), "+f"(d[29]), "+f"(d[30]), "+f"(d[31])
      : "l"(da), "l"(db), "r"(sd), "n"(TB), "n"(AOFF), "n"(BOFF));
}

template<int TB, int AOFF, int BOFF> __device__ __forceinline__ void wgmma_ss_n128(float (&d)[64], uint64_t da, uint64_t db, int sd) {
    asm volatile("{\n.reg .pred p;\n.reg .b64 ta, tb;\nsetp.ne.b32 p, %66, 0;\nadd.s64 ta, %64, %68;\nadd.s64 tb, %65, %69;\n"
      "wgmma.mma_async.sync.aligned.m64n128k16.f32.bf16.bf16 {%0, %1, %2, %3, %4, %5, %6, %7, %8, %9, %10, %11, %12, %13, %14, %15, %16, %17, %18, %19, %20, %21, %22, %23, %24, %25, %26, %27, %28, %29, %30, %31, %32, %33, %34, %35, %36, %37, %38, %39, %40, %41, %42, %43, %44, %45, %46, %47, %48, %49, %50, %51, %52, %53, %54, %55, %56, %57, %58, %59, %60, %61, %62, %63}, ta, tb, p, 1, 1, 0, %67;\n}\n"
      : "+f"(d[0]), "+f"(d[1]), "+f"(d[2]), "+f"(d[3]), "+f"(d[4]), "+f"(d[5]), "+f"(d[6]), "+f"(d[7]), "+f"(d[8]), "+f"(d[9]), "+f"(d[10]), "+f"(d[11]), "+f"(d[12]), "+f"(d[13]), "+f"(d[14]), "+f"(d[15]), "+f"(d[16]), "+f"(d[17]), "+f"(d[18]), "+f"(d[19]), "+f"(d[20]), "+f"(d[21]), "+f"(d[22]), "+f"(d[23]), "+f"(d[24]), "+f"(d[25]), "+f"(d[26]), "+f"(d[27]), "+f"(d[28]), "+f"(d[29]), "+f"(d[30]), "+f"(d[31]), "+f"(d[32]), "+f"(d[33]), "+f"(d[34]), "+f"(d[35]), "+f"(d[36]), "+f"(d[37]), "+f"(d[38]), "+f"(d[39]), "+f"(d[40]), "+f"(d[41]), "+f"(d[42]), "+f"(d[43]), "+f"(d[44]), "+f"(d[45]), "+f"(d[46]), "+f"(d[47]), "+f"(d[48]), "+f"(d[49]), "+f"(d[50]), "+f"(d[51]), "+f"(d[52]), "+f"(d[53]), "+f"(d[54]), "+f"(d[55]), "+f"(d[56]), "+f"(d[57]), "+f"(d[58]), "+f"(d[59]), "+f"(d[60]), "+f"(d[61]), "+f"(d[62]), "+f"(d[63])
      : "l"(da), "l"(db), "r"(sd), "n"(TB), "n"(AOFF), "n"(BOFF));
}

template<int TB, int BOFF> __device__ __forceinline__ void wgmma_rs_n64(float (&d)[32], uint32_t a0, uint32_t a1, uint32_t a2, uint32_t a3, uint64_t db, int sd) {
    asm volatile("{\n.reg .pred p;\n.reg .b64 tb;\nsetp.ne.b32 p, %37, 0;\nadd.s64 tb, %36, %39;\n"
      "wgmma.mma_async.sync.aligned.m64n64k16.f32.bf16.bf16 {%0, %1, %2, %3, %4, %5, %6, %7, %8, %9, %10, %11, %12, %13, %14, %15, %16, %17, %18, %19, %20, %21, %22, %23, %24, %25, %26, %27, %28, %29, %30, %31}, {%32, %33, %34, %35}, tb, p, 1, 1, %38;\n}\n"
      : "+f"(d[0]), "+f"(d[1]), "+f"(d[2]), "+f"(d[3]), "+f"(d[4]), "+f"(d[5]), "+f"(d[6]), "+f"(d[7]), "+f"(d[8]), "+f"(d[9]), "+f"(d[10]), "+f"(d[11]), "+f"(d[12]), "+f"(d[13]), "+f"(d[14]), "+f"(d[15]), "+f"(d[16]), "+f"(d[17]), "+f"(d[18]), "+f"(d[19]), "+f"(d[20]), "+f"(d[21]), "+f"(d[22]), "+f"(d[23]), "+f"(d[24]), "+f"(d[25]), "+f"(d[26]), "+f"(d[27]), "+f"(d[28]), "+f"(d[29]), "+f"(d[30]), "+f"(d[31])
      : "r"(a0), "r"(a1), "r"(a2), "r"(a3), "l"(db), "r"(sd), "n"(TB), "n"(BOFF));
}

template<int TB, int BOFF> __device__ __forceinline__ void wgmma_rs_n24(float (&d)[12], uint32_t a0, uint32_t a1, uint32_t a2, uint32_t a3, uint64_t db, int sd) {
    asm volatile("{\n.reg .pred p;\n.reg .b64 tb;\nsetp.ne.b32 p, %17, 0;\nadd.s64 tb, %16, %19;\n"
      "wgmma.mma_async.sync.aligned.m64n24k16.f32.bf16.bf16 {%0, %1, %2, %3, %4, %5, %6, %7, %8, %9, %10, %11}, {%12, %13, %14, %15}, tb, p, 1, 1, %18;\n}\n"
      : "+f"(d[0]), "+f"(d[1]), "+f"(d[2]), "+f"(d[3]), "+f"(d[4]), "+f"(d[5]), "+f"(d[6]), "+f"(d[7]), "+f"(d[8]), "+f"(d[9]), "+f"(d[10]), "+f"(d[11])
      : "r"(a0), "r"(a1), "r"(a2), "r"(a3), "l"(db), "r"(sd), "n"(TB), "n"(BOFF));
}

template<int TB, int BOFF> __device__ __forceinline__ void wgmma_rs_n144(float (&d)[72], uint32_t a0, uint32_t a1, uint32_t a2, uint32_t a3, uint64_t db, int sd) {
    asm volatile("{\n.reg .pred p;\n.reg .b64 tb;\nsetp.ne.b32 p, %77, 0;\nadd.s64 tb, %76, %79;\n"
      "wgmma.mma_async.sync.aligned.m64n144k16.f32.bf16.bf16 {%0, %1, %2, %3, %4, %5, %6, %7, %8, %9, %10, %11, %12, %13, %14, %15, %16, %17, %18, %19, %20, %21, %22, %23, %24, %25, %26, %27, %28, %29, %30, %31, %32, %33, %34, %35, %36, %37, %38, %39, %40, %41, %42, %43, %44, %45, %46, %47, %48, %49, %50, %51, %52, %53, %54, %55, %56, %57, %58, %59, %60, %61, %62, %63, %64, %65, %66, %67, %68, %69, %70, %71}, {%72, %73, %74, %75}, tb, p, 1, 1, %78;\n}\n"
      : "+f"(d[0]), "+f"(d[1]), "+f"(d[2]), "+f"(d[3]), "+f"(d[4]), "+f"(d[5]), "+f"(d[6]), "+f"(d[7]), "+f"(d[8]), "+f"(d[9]), "+f"(d[10]), "+f"(d[11]), "+f"(d[12]), "+f"(d[13]), "+f"(d[14]), "+f"(d[15]), "+f"(d[16]), "+f"(d[17]), "+f"(d[18]), "+f"(d[19]), "+f"(d[20]), "+f"(d[21]), "+f"(d[22]), "+f"(d[23]), "+f"(d[24]), "+f"(d[25]), "+f"(d[26]), "+f"(d[27]), "+f"(d[28]), "+f"(d[29]), "+f"(d[30]), "+f"(d[31]), "+f"(d[32]), "+f"(d[33]), "+f"(d[34]), "+f"(d[35]), "+f"(d[36]), "+f"(d[37]), "+f"(d[38]), "+f"(d[39]), "+f"(d[40]), "+f"(d[41]), "+f"(d[42]), "+f"(d[43]), "+f"(d[44]), "+f"(d[45]), "+f"(d[46]), "+f"(d[47]), "+f"(d[48]), "+f"(d[49]), "+f"(d[50]), "+f"(d[51]), "+f"(d[52]), "+f"(d[53]), "+f"(d[54]), "+f"(d[55]), "+f"(d[56]), "+f"(d[57]), "+f"(d[58]), "+f"(d[59]), "+f"(d[60]), "+f"(d[61]), "+f"(d[62]), "+f"(d[63]), "+f"(d[64]), "+f"(d[65]), "+f"(d[66]), "+f"(d[67]), "+f"(d[68]), "+f"(d[69]), "+f"(d[70]), "+f"(d[71])
      : "r"(a0), "r"(a1), "r"(a2), "r"(a3), "l"(db), "r"(sd), "n"(TB), "n"(BOFF));
}

constexpr int K1_XN_BYTES = 16 * 9216;
constexpr int K1_OFF_RING = K1_XN_BYTES;
constexpr int K1_OFF_BIAS = K1_OFF_RING + 10 * 8192;
constexpr int K1_OFF_BAR = K1_OFF_BIAS + 576 * 2;
constexpr int K1_SMEM = K1_OFF_BAR + 768;
constexpr float QSCALE = 0.23570226039551584f * 1.4426950408889634f;

struct K1Ctx {
    uint32_t full0;
    uint32_t rel_addr;
    uint64_t descA, descB;
    uint32_t phase;
    __device__ __forceinline__ void begin_stage(int s) {
        mbar_wait(full0 + s * 8, phase);
        wg_fence();
    }
    __device__ __forceinline__ void release(int s) {
        if (rel_addr) asm volatile("mbarrier.arrive.shared::cluster.b64 _, [%0];" ::"r"(rel_addr + s * 8) : "memory");
    }
    __device__ __forceinline__ void end_stage(int s) {
        wg_commit();
        wg_wait<1>();
        release(s == 0 ? 8 : s - 1);
    }
};

__host__ __device__ constexpr int a_off(int ks) { return ((ks / 12) * 49152 + ((ks >> 2) % 3) * 1024 + (ks & 3) * 32) >> 4; }

template <int V> struct IC { static constexpr int value = V; };
template <int I, int N, class F> __device__ __forceinline__ void static_for(F&& f) {
    if constexpr (I < N) { f(IC<I>{}); static_for<I + 1, N>(f); }
}

template <bool A_RS, bool B_RS, class Epi>
__device__ __forceinline__ void tile_pair(K1Ctx& c, float (&accA)[32], float (&accB)[32], uint32_t (&h)[144], Epi&& epi) {
    static_for<0, 9>([&](auto sc) {
        constexpr int s = decltype(sc)::value;
        c.begin_stage(s);
        static_for<0, 8>([&](auto tc) {
            constexpr int kk = s * 8 + decltype(tc)::value, ks = kk % 36;
            constexpr int bo = (ks * 2048) >> 4;
            if constexpr (kk < 36) {
                if constexpr (A_RS) wgmma_rs_n64<1, bo>(accA, h[ks * 4], h[ks * 4 + 1], h[ks * 4 + 2], h[ks * 4 + 3], c.descB, ks != 0);
                else wgmma_ss_n64<1, a_off(ks), bo>(accA, c.descA, c.descB, ks != 0);
            } else {
                if constexpr (B_RS) wgmma_rs_n64<1, bo>(accB, h[ks * 4], h[ks * 4 + 1], h[ks * 4 + 2], h[ks * 4 + 3], c.descB, ks != 0);
                else wgmma_ss_n64<1, a_off(ks), bo>(accB, c.descA, c.descB, ks != 0);
            }
        });
        c.end_stage(s);
        epi(sc);
    });
    c.phase ^= 1;
}

template <int B0, int NB, int HOFF>
__device__ __forceinline__ void gelu_blocks(const float (&acc)[32], uint32_t (&h)[144], const uint32_t (&bq)[8], float rs0, float rs1) {
#pragma unroll
    for (int b = B0; b < B0 + NB; b++) {
        const float b0 = bf_lo(bq[b]), b1 = bf_hi(bq[b]);
        h[HOFF + b * 2 + 0] = pack_bf16(gelu2(fmaf(acc[b * 4 + 0], rs0, b0)), gelu2(fmaf(acc[b * 4 + 1], rs0, b1)));
        h[HOFF + b * 2 + 1] = pack_bf16(gelu2(fmaf(acc[b * 4 + 2], rs1, b0)), gelu2(fmaf(acc[b * 4 + 3], rs1, b1)));
    }
#pragma unroll
    for (int i = HOFF + B0 * 2; i < HOFF + (B0 + NB) * 2; i++) asm volatile("" : "+r"(h[i]));
}
__device__ __forceinline__ void load_bias(uint32_t (&bq)[8], uint32_t addr) {
    asm volatile("ld.shared.v4.u32 {%0, %1, %2, %3}, [%4];" : "=r"(bq[0]), "=r"(bq[1]), "=r"(bq[2]), "=r"(bq[3]) : "r"(addr));
    asm volatile("ld.shared.v4.u32 {%0, %1, %2, %3}, [%4 + 16];" : "=r"(bq[4]), "=r"(bq[5]), "=r"(bq[6]), "=r"(bq[7]) : "r"(addr));
}
template <int S> __device__ __forceinline__ void store_part(const float (&o)[32], uint4* p) {
    uint4 v;
    v.x = pack_bf16(o[S * 8 + 0], o[S * 8 + 1]); v.y = pack_bf16(o[S * 8 + 2], o[S * 8 + 3]);
    v.z = pack_bf16(o[S * 8 + 4], o[S * 8 + 5]); v.w = pack_bf16(o[S * 8 + 6], o[S * 8 + 7]);
    p[S * 256] = v;
}

constexpr int NCHUNK = 16;
constexpr int CHUNK_BYTES = KV_HEAD_BYTES / NCHUNK;
constexpr int SM_Q = 0;
constexpr int SM_KV = 32768;
constexpr int WO_PIECE = WO_TILE_BYTES / 9;
__host__ __device__ constexpr int sm_wo(int i) { return i == 0 ? 210944 : (i == 1 ? 0 : SM_KV + (i - 2) * WO_PIECE); }
constexpr int SM_EXCH = SM_KV + 7 * WO_PIECE;
constexpr int SM_RED = SM_KV + KV_HEAD_BYTES;

__device__ __forceinline__ float exp2_fixed(float y) {
    const float u = __uint_as_float(__float_as_uint(y) & 0xFF807FFFu) - 512.02545f;
    float t = fmaf(u, 0.019497588f, 0.114550486f);
    t = fmaf(t, u, -0.29839927f);
    return fmaf(t, u, y);
}
__device__ __forceinline__ uint32_t pack_fixed(float lo, float hi) { return __byte_perm(__float_as_uint(lo), __float_as_uint(hi), 0x6521); }

#define POLY_MODE 1
__device__ __forceinline__ uint32_t exp2_packed(float y0, float y1, uint32_t one2) {
    const uint32_t w = pack_fixed(y0, y1);
    uint32_t m;
    asm("lop3.b32 %0, %1, 0x007F007F, %2, 0xEA;" : "=r"(m) : "r"(w), "r"(one2));
    const uint32_t d = hfma2_bf16(m, 0x3EF93EF9u, 0xBF38BF38u);
    const uint32_t e = hfma2_bf16(d, d, 0xBD71BD71u);
    return hfma2_bf16(w, e, w);
}
template <int NB>
__device__ __forceinline__ void softmax_fast(const float (&s)[NB * 4], uint32_t (&p)[NB * 2], uint32_t one2) {
#pragma unroll
    for (int b = 0; b < NB; b++) {
        if ((POLY_MASK >> (b & 7)) & 1) {
            p[b * 2 + 0] = exp2_packed(s[b * 4 + 0], s[b * 4 + 1], one2);
            p[b * 2 + 1] = exp2_packed(s[b * 4 + 2], s[b * 4 + 3], one2);
        } else {
            p[b * 2 + 0] = pack_bf16(ex2(s[b * 4 + 0]), ex2(s[b * 4 + 1]));
            p[b * 2 + 1] = pack_bf16(ex2(s[b * 4 + 2]), ex2(s[b * 4 + 3]));
        }
    }
}

constexpr int KV_TILE = CHUNK_BYTES / 16;
template <int OFF> __device__ __forceinline__ void issue_qk(float (&s)[64], uint64_t qd, uint64_t kd) {
    wgmma_ss_n128<0, 0, OFF + (8 << 16)>(s, qd, kd, 0);
    wgmma_ss_n128<0, 16, OFF + 32>(s, qd, kd, 1);
}
template <int OFF> __device__ __forceinline__ void issue_pv(float (&o)[12], const uint32_t (&p)[32], uint64_t vd) {
    static_for<0, 8>([&](auto kc) {
        constexpr int k = decltype(kc)::value;
        wgmma_rs_n24<1, OFF + k * (2 * KV_GROUP_BYTES / 16)>(o, p[k * 4], p[k * 4 + 1], p[k * 4 + 2], p[k * 4 + 3], vd, 1);
    });
}
__device__ __forceinline__ void store_o(float (&o)[12], int rt, int head, int wq, int lane) {
    const int g = lane >> 2, q = lane & 3;
    const float i0 = __fdividef(1.0f, __shfl_sync(~0u, o[8], lane | 3)), i1 = __fdividef(1.0f, __shfl_sync(~0u, o[10], lane | 3));
#pragma unroll
    for (int i = 0; i < 3; i++) {
        const int pc = head * 9 + (i < 2 ? i * 4 + q : 8);
        uint32_t* op = g_O + (((rt * 36 + (pc >> 3)) * 128 + wq * 32 + g * 4 + (pc & 3)) * 4 + ((pc >> 2) & 1) * 2);
        if (i < 2 || q == 2) *reinterpret_cast<uint2*>(op) = make_uint2(pack_bf16(o[i * 4] * i0, o[i * 4 + 1] * i0), pack_bf16(o[i * 4 + 2] * i1, o[i * 4 + 3] * i1));
    }
#pragma unroll
    for (int i = 0; i < 12; i++) o[i] = 0.f;
}
__device__ __forceinline__ void mbar_arrive(uint32_t b) { asm volatile("mbarrier.arrive.shared::cta.b64 _, [%0];" ::"r"(b) : "memory"); }
__device__ __forceinline__ void mbar_wait_sleep(uint32_t b, uint32_t ns) {
    uint32_t ok, spins = 0;
    while (true) {
        asm volatile("{\n.reg .pred p;\nmbarrier.try_wait.parity.shared::cta.b64 p, [%1], 0;\nselp.u32 %0, 1, 0, p;\n}\n" : "=r"(ok) : "r"(b) : "memory");
        if (ok) break;
        __nanosleep(ns);
        if (++spins > (1u << 21)) __trap();
    }
}
__device__ __forceinline__ void flag_signal(unsigned int* f) {
    __threadfence();
    atomicAdd(f, 1u);
}
__device__ __forceinline__ void flag_wait(const unsigned int* f, unsigned int target, unsigned int sleep_ns) {
    uint32_t v, spins = 0;
    while (true) {
        asm volatile("ld.acquire.gpu.global.u32 %0, [%1];" : "=r"(v) : "l"(f) : "memory");
        if (v >= target) break;
        if (sleep_ns) __nanosleep(sleep_ns);
        if (++spins > (1u << 21)) __trap();
    }
}
__device__ __forceinline__ uint4 hadd8_bf16(const uint4 a, const uint4 b) {
    return make_uint4(hadd2_bf16(a.x, b.x), hadd2_bf16(a.y, b.y), hadd2_bf16(a.z, b.z), hadd2_bf16(a.w, b.w));
}
__device__ __forceinline__ float sumsq2(uint32_t w) { return fmaf(bf_lo(w), bf_lo(w), bf_hi(w) * bf_hi(w)); }
__device__ __forceinline__ float sumsq8(const uint4 v) { return (sumsq2(v.x) + sumsq2(v.y)) + (sumsq2(v.z) + sumsq2(v.w)); }

enum { B_FULL = 0, B_EMPTY = 9, B_BASE = 18, B_XNDEAD = 19, B_QRDY = 20, B_FFN = 21, B_KV = 22, B_FREE = 38, B_WO = 46, B_RED = 55, B_X = 61, B_DONE = 85, B_END = 86 };

__global__ void __cluster_dims__(2, 1, 1) __launch_bounds__(384, 1)
fused_kernel(const __grid_constant__ CUtensorMap tmX, const __grid_constant__ CUtensorMap tmQ3, const __grid_constant__ CUtensorMap tmQ1,
          const __grid_constant__ CUtensorMap tm1, const __grid_constant__ CUtensorMap tm2, const __grid_constant__ CUtensorMap tmP, const __nv_bfloat16* __restrict__ b1,
          const __nv_bfloat16* __restrict__ wqkv, const __nv_bfloat16* __restrict__ w1, const __nv_bfloat16* __restrict__ w2,
          const __nv_bfloat16* __restrict__ wo, const __nv_bfloat16* __restrict__ x, const __nv_bfloat16* __restrict__ b2,
          __nv_bfloat16* __restrict__ out, const uint64_t zero) {
    extern __shared__ __align__(1024) uint8_t smem[];
    const uint32_t sb = s2u(smem);
    const int tid = threadIdx.x, lane = tid & 31;
    const int warp = __shfl_sync(~0u, tid >> 5, 0);
    const uint32_t rank = blockIdx.x & 1;
    const int cl = blockIdx.x >> 1;
    const int rb = (cl & 7) * 2 + rank;
    const int j = cl >> 3;
    const uint32_t bar0 = sb + K1_OFF_BAR;
    const uint32_t full0 = bar0 + B_FULL * 8, empty0 = bar0 + B_EMPTY * 8, xbar0 = bar0 + B_X * 8;
    const int head = blockIdx.x >> 2, quarter = blockIdx.x & 3;
    const int rt = quarter * 8 + (head >> 2), ct = head & 3;
    volatile uint32_t* slow_flag = reinterpret_cast<volatile uint32_t*>(smem + K1_OFF_BAR + B_END * 8);

    if (warp < 8) {
        PROF(0);
        PROFT(48);
        if (lane == 0) {
#pragma unroll
            for (int i = 0; i < 3; i++) mbar_init(xbar0 + (warp * 3 + i) * 8, 1);
            fence_barrier_init();
#pragma unroll 1
            for (int i = 0; i < 3; i++) {
                const uint32_t xb = xbar0 + (warp * 3 + i) * 8;
                mbar_expect(xb, 6144);
                tma4d(sb + i * 49152 + warp * 6144, &tmX, 0, 0, i * 3, rb * 16 + warp * 2, xb);
            }
        }
        __syncwarp();
        cluster_arrive();
        PROF(22);
        reg_alloc<240>();
        PROF(23);
        float rs0, rs1;
        {
            const uint32_t la = sb + (warp * 2 + ((lane >> 3) & 1)) * 3072 + (lane & 7) * 128;
            uint32_t off[4];
#pragma unroll
            for (int i = 0; i < 4; i++) off[i] = la + (((i * 2 + (lane >> 4)) ^ (lane & 7)) << 4);
            float c1[4] = {0.f, 0.f, 0.f, 0.f}, c2[4] = {0.f, 0.f, 0.f, 0.f}, c3[4] = {0.f, 0.f, 0.f, 0.f};
            uint32_t a[36][4];
#pragma unroll
            for (int t = 0; t < 3; t++) {
                mbar_wait(xbar0 + (warp * 3 + t) * 8, 0);
                PROF(24 + t);
#pragma unroll
                for (int i = 0; i < 12; i++) ldsm4(a[t * 12 + i], off[i & 3] + t * 49152 + (i >> 2) * 1024);
#pragma unroll
                for (int i = t * 12; i < t * 12 + 12; i++) {
                    mma16816(c3, a[i], 0x3F803F80u, 0x3F803F80u);
                    mma16816(c1, a[i], a[i][0], a[i][2]);
                    mma16816(c2, a[i], a[i][1], a[i][3]);
                }
            }
            PROF(27);
            const int gg = lane >> 2, src = (lane & ~3) | (gg >> 1);
            const float m0 = c3[0] * (1.0f / DM), m1 = c3[2] * (1.0f / DM);
            const uint32_t mc0 = pack_bf16(-m0, -m0), mc1 = pack_bf16(-m1, -m1);
#pragma unroll
            for (int i = 0; i < 36; i++) {
#pragma unroll
                for (int k = 0; k < 4; k++) a[i][k] = hadd2_bf16(a[i][k], (k & 1) ? mc1 : mc0);
                stsm4(off[i & 3] + (i / 12) * 49152 + ((i >> 2) % 3) * 1024, a[i]);
            }
            const float q0 = __shfl_sync(~0u, (gg & 1) ? c1[1] : c1[0], src), q1 = __shfl_sync(~0u, (gg & 1) ? c2[3] : c2[2], src);
            rs0 = rsqrtf(fmaxf(fmaf(-m0, m0, q0 * (1.0f / DM)), 0.f) + 1e-5f);
            rs1 = rsqrtf(fmaxf(fmaf(-m1, m1, q1 * (1.0f / DM)), 0.f) + 1e-5f);
            if (__any_sync(~0u, fabsf(m0) * rs0 > 0.25f || fabsf(m1) * rs1 > 0.25f)) {
                const float d0 = -m0 - bf_lo(mc0), d1 = -m1 - bf_lo(mc1);
                const uint32_t md0 = pack_bf16(d0, d0), md1 = pack_bf16(d1, d1);
#pragma unroll 1
                for (int i = 0; i < 9; i++) {
#pragma unroll
                    for (int k4 = 0; k4 < 4; k4++) {
                        const uint32_t ad = off[k4] + (i / 3) * 49152 + (i % 3) * 1024;
                        uint32_t b[4];
                        ldsm4(b, ad);
#pragma unroll
                        for (int k = 0; k < 4; k++) b[k] = hadd2_bf16(b[k], (k & 1) ? md1 : md0);
                        stsm4(ad, b);
                    }
                }
            }
        }
        PROF(28);
        const int wg = warp >> 2, wq = warp & 3;
        fence_proxy_async();
        named_bar_sync(1 + wg, 128);
        cluster_wait();
        PROF(1);

        const int g = lane >> 2, q = lane & 3;
        K1Ctx c;
        c.full0 = full0;
        c.rel_addr = 0;
        c.descA = mk_desc(zero, sb + wg * 8 * 3072, 16, 3072, 1);
        c.descB = mk_desc(zero, sb + K1_OFF_RING, 2048, 1024, 1);
        c.phase = 0;
        uint32_t biasq = sb + K1_OFF_BIAS + q * 32;
        uint32_t bq[8];

        uint32_t h[144];
        float accA[32], accB[32];
        {
            float accQ[108];
            uint32_t rel = 0;
            if (lane == 0 && wq < 2) asm("mapa.shared::cluster.u32 %0, %1, %2;" : "=r"(rel) : "r"(empty0), "r"(wq));
#pragma unroll 1
            for (int r = 0; r < 2; r++) {
                static_for<0, 9>([&](auto sc) {
                    constexpr int s = decltype(sc)::value;
                    c.begin_stage(s);
                    const uint64_t da = c.descA + (r ? a_off(18 + 2 * s) : a_off(2 * s));
                    wgmma_ss_n216<1, 0, ((2 * s) % 9) * 512>(accQ, da, c.descB, (r | s) != 0);
                    wgmma_ss_n216<1, 2, ((2 * s + 1) % 9) * 512>(accQ, da, c.descB, 1);
                    c.end_stage(s);
                    c.rel_addr = rel;
                });
                c.phase ^= 1;
            }
            PROF(2);
            uint32_t rel9[9];
#pragma unroll
            for (int i9 = 0; i9 < 9; i9++) {
                const int p = 4 * i9 + q, hh = (p * 57) >> 9, r = p - 9 * hh;
                rel9[i9] = hh * KV_HEAD_BYTES + (r < 8 ? (r >> 2) * 128 + (r & 3) * 4 : 0);
            }
            uint32_t gb = 0, o2 = 0;
            float scl0 = 1.f, scl1 = 1.f;
            tile_pair<false, false>(c, accA, accB, h, [&](auto sc) {
                constexpr int s = decltype(sc)::value;
                if constexpr (s == 0) reg_fence(accQ);
                if constexpr (s < 6) {
                    constexpr int grp = s / 2, part = s % 2;
                    if constexpr (part == 0) {
                        const int G = 3 * j + grp, type = G >> 3;
                        gb = (G & 7) * 4 * KV_HEAD_BYTES + (rb * 16 + warp * 2) * KV_GROUP_BYTES + g * 16 + (type == 0 ? Q_OFFSET : (type == 2 ? 256 : 0));
                        o2 = type == 0 ? 256 : (type == 2 ? 264 : 512);
                        scl0 = rs0 * (type == 0 ? QSCALE : ((type == 1 && ((POLY_MASK >> (wq * 2)) & 1)) ? 2.f : 1.f));
                        scl1 = rs1 * (type == 0 ? QSCALE : ((type == 1 && ((POLY_MASK >> (wq * 2 + 1)) & 1)) ? 2.f : 1.f));
                    }
#pragma unroll
                    for (int i9 = part * 5; i9 < (part ? 9 : 5); i9++) {
                        const int b = grp * 9 + i9;
                        uint32_t off = gb + rel9[i9];
                        if (i9 >= 2 && (i9 & 1) == 0) off += (q == i9 / 2 - 1) ? o2 : 0;
                        *reinterpret_cast<uint32_t*>(g_QKV + off) = pack_bf16(accQ[b * 4] * scl0, accQ[b * 4 + 1] * scl0);
                        *reinterpret_cast<uint32_t*>(g_QKV + off + KV_GROUP_BYTES) = pack_bf16(accQ[b * 4 + 2] * scl1, accQ[b * 4 + 3] * scl1);
                    }
                    if constexpr (s == 5) asm volatile("bar.arrive 3, 352;" ::: "memory");
                }
                if constexpr (s == 4) { named_bar_sync(4, 352); load_bias(bq, biasq); }
                if constexpr (s == 5) reg_fence(accA);
                if constexpr (s >= 5) gelu_blocks<(s - 5) * 2, 2, 96>(accA, h, bq, rs0, rs1);
                if constexpr (s == 8) load_bias(bq, biasq + 128);
            });
        }
        PROF(3);
#pragma unroll
        for (int i = 32; i < 96; i++) asm volatile("mov.u32 %0, 0;" : "=r"(h[i]));
#pragma unroll 1
        for (int p = 1; p < 4; p++) {
            biasq += 256;
            tile_pair<false, false>(c, accA, accB, h, [&](auto sc) {
                constexpr int s = decltype(sc)::value;
                if constexpr (s == 0) {
                    reg_fence(accB);
#pragma unroll
                    for (int i = 0; i < 80; i++) h[i] = h[i + 32];
                }
                if constexpr (s < 4) gelu_blocks<s * 2, 2, 80>(accB, h, bq, rs0, rs1);
                if constexpr (s == 4) load_bias(bq, biasq);
                if constexpr (s == 5) reg_fence(accA);
                if constexpr (s >= 5) gelu_blocks<(s - 5) * 2, 2, 96>(accA, h, bq, rs0, rs1);
                if constexpr (s == 8) load_bias(bq, biasq + 128);
            });
        }
        PROF(4);
        tile_pair<false, true>(c, accA, accB, h, [&](auto sc) {
            constexpr int s = decltype(sc)::value;
            if constexpr (s == 0) reg_fence(accB);
            if constexpr (s < 4) gelu_blocks<s * 2, 2, 112>(accB, h, bq, rs0, rs1);
            if constexpr (s == 4) load_bias(bq, biasq + 256);
            if constexpr (s == 5) { reg_fence(accA); if (tid == wg * 128) mbar_arrive(bar0 + B_XNDEAD * 8); }
            if constexpr (s == 5 || s == 6) gelu_blocks<(s - 5) * 3, 3, 128>(accA, h, bq, rs0, rs1);
            if constexpr (s == 7) gelu_blocks<6, 2, 128>(accA, h, bq, rs0, rs1);
            if constexpr (s == 3 || s == 7) reg_fence(h);
        });
        PROF(5);
        uint4* pout = g_part + j * SLAB + rb * 36 * 256 + tid;
#pragma unroll 1
        for (int p = 0; p < 4; p++) {
            tile_pair<true, true>(c, accA, accB, h, [&](auto sc) {
                constexpr int s = decltype(sc)::value;
                if constexpr (s == 0) reg_fence(accB);
                if constexpr (s < 4) store_part<s>(accB, pout);
                if constexpr (s == 5) reg_fence(accA);
                if constexpr (s >= 5) store_part<s - 5>(accA, pout + 1024);
            });
            pout += 2048;
            PROF(6 + p);
        }
        wg_wait<0>();
        c.release(8);
        reg_fence(accB);
        store_part<0>(accB, pout); store_part<1>(accB, pout); store_part<2>(accB, pout); store_part<3>(accB, pout);
        __syncwarp();
        if (lane == 0) mbar_arrive(bar0 + B_FFN * 8);
        PROF(10);
        PROFT(49);

        mbar_wait(bar0 + B_QRDY * 8, 0);
        const uint32_t slow = __any_sync(~0u, *slow_flag != 0);
        const uint64_t kd0 = mk_desc(zero, sb + SM_KV, 0, KV_GROUP_BYTES, 0);
        const uint64_t vd0 = mk_desc(zero, sb + SM_KV + 256, KV_GROUP_BYTES, 128, 0);
        const uint64_t qd0 = mk_desc(zero, sb + SM_Q + wg * 4096, 128, 512, 0);
        const uint32_t kvbar = bar0 + B_KV * 8;
        float o[12];
#pragma unroll
        for (int i = 0; i < 12; i++) o[i] = 0.f;
        PROF(16);
        PROFT(50);
        if (!slow) {
            const uint32_t one2 = 0x3F803F80u + (uint32_t)zero;
            float s0[64], s1[64];
            uint32_t p0[32], p1[32];
            mbar_wait(kvbar, 0);
            reg_fence(o);
            wg_fence();
            issue_qk<0>(s0, qd0, kd0);
            wg_commit();
            mbar_wait(kvbar + 8, 0);
            wg_fence();
            issue_qk<KV_TILE>(s1, qd0, kd0);
            wg_commit();
            uint64_t qd = qd0;
            const uint32_t fre = (tid == wg * 128) ? bar0 + B_FREE * 8 - 8 : 0;
#pragma unroll 1
            for (int pass = 0; pass < 4; pass++) {
                uint64_t vd = vd0, kdn = kd0 + 2 * KV_TILE;
                uint32_t bn = kvbar + 16;
#pragma unroll 1
                for (int it = 0; it < 8; it++) {
                    if (it == 7) { kdn = kd0; bn = kvbar; qd += 512; }
                    wg_wait<1>();
                    reg_fence(s0);
                    if (pass == 3 && it > 0 && fre) mbar_arrive(fre + it * 8);
                    softmax_fast<16>(s0, p0, one2);
                    reg_fence(p0);
                    if (it == 0 && pass != 0) {
                        wg_wait<0>();
                        reg_fence(o);
                        store_o(o, quarter * 8 + pass * 2 - 2 + wg, head, wq, lane);
                        reg_fence(o);
                    }
                    mbar_wait(bn, 0);
                    wg_fence();
                    issue_pv<0>(o, p0, vd);
                    issue_qk<0>(s0, qd, kdn);
                    wg_commit();
                    wg_wait<1>();
                    reg_fence(s1);
                    softmax_fast<16>(s1, p1, one2);
                    reg_fence(p1);
                    mbar_wait(bn + 8, 0);
                    wg_fence();
                    issue_pv<KV_TILE>(o, p1, vd);
                    issue_qk<KV_TILE>(s1, qd, kdn);
                    wg_commit();
                    vd += 2 * KV_TILE; kdn += 2 * KV_TILE; bn += 16;
                }
                if (pass == 0) PROF(17);
            }
            wg_wait<0>();
            reg_fence(o);
            reg_fence(s0);
            reg_fence(s1);
            store_o(o, quarter * 8 + 6 + wg, head, wq, lane);
        } else {
#pragma unroll 1
            for (int pass = 0; pass < 4; pass++) {
                float m0 = -INFINITY, m1 = -INFINITY;
                float s[64];
                uint32_t p[32];
#pragma unroll 1
                for (int t = 0; t < 16; t++) {
                    mbar_wait(kvbar + t * 8, 0);
                    wg_fence();
                    issue_qk<0>(s, qd0 + pass * 512, kd0 + t * KV_TILE);
                    wg_commit();
                    wg_wait<0>();
                    reg_fence(s);
                    float a0 = m0, a1 = m1;
#pragma unroll
                    for (int k = 0; k < 16; k++) {
                        if ((POLY_MASK >> (k & 7)) & 1) {
#pragma unroll
                            for (int i = 0; i < 4; i++) s[k * 4 + i] *= 0.5f;
                        }
                        a0 = fmaxf(a0, fmaxf(s[k * 4 + 0], s[k * 4 + 1]));
                        a1 = fmaxf(a1, fmaxf(s[k * 4 + 2], s[k * 4 + 3]));
                    }
                    a0 = fmaxf(a0, __shfl_xor_sync(~0u, a0, 1)); a1 = fmaxf(a1, __shfl_xor_sync(~0u, a1, 1));
                    a0 = fmaxf(a0, __shfl_xor_sync(~0u, a0, 2)); a1 = fmaxf(a1, __shfl_xor_sync(~0u, a1, 2));
                    const float r0 = ex2(m0 - a0), r1 = ex2(m1 - a1);
                    m0 = a0; m1 = a1;
#pragma unroll
                    for (int i = 0; i < 3; i++) { o[i * 4] *= r0; o[i * 4 + 1] *= r0; o[i * 4 + 2] *= r1; o[i * 4 + 3] *= r1; }
#pragma unroll
                    for (int k = 0; k < 16; k++) {
                        p[k * 2 + 0] = pack_bf16(ex2(s[k * 4 + 0] - m0), ex2(s[k * 4 + 1] - m0));
                        p[k * 2 + 1] = pack_bf16(ex2(s[k * 4 + 2] - m1), ex2(s[k * 4 + 3] - m1));
                    }
                    reg_fence(p);
                    reg_fence(o);
                    wg_fence();
                    issue_pv<0>(o, p, vd0 + t * KV_TILE);
                    wg_commit();
                    wg_wait<0>();
                    reg_fence(o);
                }
                store_o(o, quarter * 8 + pass * 2 + wg, head, wq, lane);
            }
            if (tid == wg * 128)
                for (int i = 0; i < 7; i++) mbar_arrive(bar0 + (B_FREE + i) * 8);
        }
        PROF(18);
        PROFT(51);

        const int t128 = tid & 127;
        named_bar_sync(1 + wg, 128);
        if (t128 == 0) flag_signal(&g_flags.o_done[quarter]);
        const size_t orow = (size_t)(rt * 64 + wq * 16 + g + wg * 8) * DM + ct * 144 + q * 2;
        float bs[36];
        {
            uint32_t xv[18], bv[18];
            uint2 fv[9];
#pragma unroll
            for (int i = 0; i < 18; i++) {
                xv[i] = __ldg(reinterpret_cast<const uint32_t*>(x + orow) + i * 4);
                bv[i] = __ldg(reinterpret_cast<const uint32_t*>(b2 + ct * 144 + q * 2) + i * 4);
            }
            mbar_wait(bar0 + B_BASE * 8, 0);
#pragma unroll
            for (int i = 0; i < 9; i++) fv[i] = __ldcg(g_ffn + blockIdx.x * 2304 + (wg * 9 + i) * 128 + t128);
#pragma unroll
            for (int i = 0; i < 18; i++) {
                const uint32_t f = (i & 1) ? fv[i >> 1].y : fv[i >> 1].x;
                bs[i * 2] = fmaf(bf_lo(f), 0.5f, bf_lo(xv[i]) + bf_lo(bv[i]));
                bs[i * 2 + 1] = fmaf(bf_hi(f), 0.5f, bf_hi(xv[i]) + bf_hi(bv[i]));
            }
        }
        if (t128 == 0) flag_wait(&g_flags.o_done[quarter], 64, 0);
        named_bar_sync(1 + wg, 128);
        if (t128 == 0) mbar_arrive(bar0 + B_DONE * 8);
        PROF(19);
        uint4 af[18];
        {
            const uint4* ap = reinterpret_cast<const uint4*>(g_O) + (rt * 36 + wg * 18) * 128 + t128;
#pragma unroll
            for (int k = 0; k < 18; k++) af[k] = __ldcg(ap + k * 128);
        }
        float acc[72];
        const uint64_t wd0 = mk_desc(zero, sb, 2304, 128, 0), wd1 = wd0 + wg * ((18 * 4608) >> 4);
#pragma unroll 1
        for (int i = 0; i < 5; i++) mbar_wait(bar0 + (B_WO + wg * 4 + i) * 8, 0);
        wg_fence();
        static_for<0, 18>([&](auto kc) {
            constexpr int k = decltype(kc)::value;
            if constexpr (k < 8) {
                constexpr int o0 = (sm_wo(k >> 2) + (k & 3) * 4608) >> 4, o1 = (SM_KV + (k + 10) * 4608) >> 4;
                wgmma_rs_n144<1, 0>(acc, af[k].x, af[k].y, af[k].z, af[k].w, wd0 + (wg ? o1 : o0), k != 0);
            } else {
                wgmma_rs_n144<1, (SM_KV + (k - 8) * 4608) / 16>(acc, af[k].x, af[k].y, af[k].z, af[k].w, wd1, 1);
            }
        });
        wg_commit();
        wg_wait<0>();
        reg_fence(acc);
        PROF(20);
        {
            float4* ex = reinterpret_cast<float4*>(smem + SM_EXCH) + t128;
#pragma unroll
            for (int i = 0; i < 9; i++) {
                const float4 lo = make_float4(acc[i * 8], acc[i * 8 + 1], acc[i * 8 + 4], acc[i * 8 + 5]);
                const float4 hi = make_float4(acc[i * 8 + 2], acc[i * 8 + 3], acc[i * 8 + 6], acc[i * 8 + 7]);
                ex[(wg * 9 + i) * 128] = wg ? lo : hi;
                const float4 own = wg ? hi : lo;
                bs[i * 4] += own.x; bs[i * 4 + 1] += own.y; bs[i * 4 + 2] += own.z; bs[i * 4 + 3] += own.w;
            }
            named_bar_sync(5, 256);
            uint32_t* op = reinterpret_cast<uint32_t*>(out + orow);
#pragma unroll
            for (int i = 0; i < 9; i++) {
                const float4 v = ex[((wg ^ 1) * 9 + i) * 128];
                op[i * 8] = pack_bf16(bs[i * 4] + v.x, bs[i * 4 + 1] + v.y);
                op[i * 8 + 4] = pack_bf16(bs[i * 4 + 2] + v.z, bs[i * 4 + 3] + v.w);
            }
        }
        PROF(21);
        PROFT(52);
    } else {
        reg_dealloc<24>();
        if (warp == 8 && lane == 0) {
            prefetch_tmap(&tmQ3); prefetch_tmap(&tmQ1); prefetch_tmap(&tm1); prefetch_tmap(&tm2);
            #pragma unroll 1
            for (int i = 0; i < 9; i++) { mbar_init(full0 + i * 8, 1); mbar_init(empty0 + i * 8, 4); mbar_init(bar0 + (B_WO + i) * 8, 1); }
            mbar_init(bar0 + B_BASE * 8, 3); mbar_init(bar0 + B_XNDEAD * 8, 2); mbar_init(bar0 + B_QRDY * 8, 3); mbar_init(bar0 + B_FFN * 8, 8); mbar_init(bar0 + B_DONE * 8, 2);
#pragma unroll 1
            for (int i = 0; i < 16; i++) { mbar_init(bar0 + (B_KV + i) * 8, 1); mbar_init(bar0 + (B_FREE + (i & 7)) * 8, 2); if (i < 6) mbar_init(bar0 + (B_RED + i) * 8, 1); }
            *slow_flag = 0;
            fence_barrier_init();
        }
        __syncwarp();
        cluster_arrive();
        cluster_wait();
        const uint8_t* kvsrc = g_QKV + (size_t)head * KV_HEAD_BYTES;
        if (warp == 8) {
            if (lane == 0) {
                int st = 0, u = rank, tile = -4;
                int es = 5;
                uint32_t eph = 1;
#pragma unroll 1
                for (int n = 0; n < 99; n++) {
                    mbar_wait(empty0 + es * 8, eph);
                    const uint32_t fb = full0 + st * 8, dst = sb + K1_OFF_RING + u * 8192;
                    mbar_expect(fb, 16384);
                    if (tile < 0) {
                        tma3d_mc(dst, &tmQ3, j * 216, n * 32 + rank * 16, 0, fb, 3);
                        tma2d_mc(dst + 6144, &tmQ1, j * 216 + 192, n * 32 + rank * 16, fb, 3);
                    } else if (tile < 9) {
                        tma2d_mc(dst, &tm1, j * 576 + tile * 64, u * 64, fb, 3);
                    } else {
                        tma2d_mc(dst, &tm2, (tile - 9) * 64, j * 576 + u * 64, fb, 3);
                    }
                    u += 2;
                    if (u >= 9) { u -= 9; tile++; }
                    if (++st == 9) st = 0;
                    if (++es == 9) { es = 0; eph ^= 1; }
                }
                mbar_wait(empty0 + 8 * 8, 0);
                mbar_wait(bar0 + B_QRDY * 8, 0);
                asm volatile("fence.proxy.async;" ::: "memory");
#pragma unroll 1
                for (int i = 11; i < NCHUNK; i++) {
                    mbar_expect(bar0 + (B_KV + i) * 8, CHUNK_BYTES);
                    bulk_load(sb + SM_KV + i * CHUNK_BYTES, kvsrc + i * CHUNK_BYTES, CHUNK_BYTES, bar0 + (B_KV + i) * 8);
                }
#pragma unroll 1
                for (int i = 0; i < 9; i++) {
                    if (i == 0) mbar_wait_sleep(bar0 + B_BASE * 8, 500);
                    if (i > 0) {
                        const int f = i == 1 ? 0 : ((i - 1) * 9 + 4) / 10;
                        mbar_wait_sleep(bar0 + (B_FREE + f) * 8, i == 1 ? 500 : 50);
                    }
                    mbar_expect(bar0 + (B_WO + i) * 8, WO_PIECE);
                    bulk_load(sb + (i == 0 ? sm_wo(0) : (i == 1 ? sm_wo(1) : SM_KV + (i - 2) * WO_PIECE)), g_Wo + ct * WO_TILE_BYTES + i * WO_PIECE, WO_PIECE,
                              bar0 + (B_WO + i) * 8);
                }
            }
        } else {
            const int ht = tid - 288;
            if (ht == 64) prefetch_l2(wqkv + blockIdx.x * (DM * 3 * DM / 128), DM * 3 * DM / 64);
            if (ht < 72) {
                const uint4 v = __ldg(reinterpret_cast<const uint4*>(b1 + j * 576) + ht);
                uint32_t* sbias = reinterpret_cast<uint32_t*>(smem + K1_OFF_BIAS) + (ht >> 3) * 32 + (ht & 7);
                sbias[0] = v.x; sbias[8] = v.y; sbias[16] = v.z; sbias[24] = v.w;
            }
            asm volatile("bar.arrive 4, 352;" ::: "memory");
            PROFH(37);
#pragma unroll 1
            for (int i = ht; i < 512; i += 96) {
                const int key = i & 127;
                uint8_t* p = g_QKV + (size_t)(j * 4 + (i >> 7)) * KV_HEAD_BYTES + (rb * 16 + (key >> 3)) * KV_GROUP_BYTES + 512 + (key & 7) * 16;
                *reinterpret_cast<uint32_t*>(p + 4) = ((POLY_MASK >> ((key >> 3) & 7)) & 1) ? 0x3F804000u : 0x00003F80u;
                *reinterpret_cast<uint32_t*>(p + 12) = 0x00003F80u;
            }
            if (ht == 32) prefetch_l2(w1 + blockIdx.x * (DM * FF / 128), DM * FF / 64);
#pragma unroll 2
            for (int i = blockIdx.x * 324 + ht; i < blockIdx.x * 324 + 324; i += 96) {
                const int k = i / 72, nc = i - k * 72, c4 = nc / 18;
                *reinterpret_cast<uint4*>(g_Wo + c4 * WO_TILE_BYTES + (k >> 3) * 2304 + (nc - c4 * 18) * 128 + (k & 7) * 16) =
                    __ldg(reinterpret_cast<const uint4*>(wo) + i);
            }
            PROFH(38);
            named_bar_sync(3, 352);
            if (ht == 32) prefetch_l2(w2 + blockIdx.x * (DM * FF / 128), DM * FF / 64);
            if (ht == 0) {
                flag_signal(&g_flags.qkv_stored[rb]);
                flag_wait(&g_flags.qkv_stored[rb], 8, 200);
            }
            named_bar_sync(7, 96);
            PROFH(39);
#pragma unroll 1
            for (int i = warp - 9; i < 16; i += 3) {
                const int hd = j * 4 + (i >> 2), key = (i & 3) * 32 + lane;
                const uint8_t* p = g_QKV + (size_t)hd * KV_HEAD_BYTES + (rb * 16 + (key >> 3)) * KV_GROUP_BYTES + (key & 7) * 16;
                const uint4 a = __ldcg(reinterpret_cast<const uint4*>(p)), b = __ldcg(reinterpret_cast<const uint4*>(p + 128));
                float n = sumsq2(__ldcg(reinterpret_cast<const uint32_t*>(p + 512))) + sumsq8(a) + sumsq8(b);
                if ((POLY_MASK >> ((key >> 3) & 7)) & 1) n *= 0.25f;
#pragma unroll
                for (int o = 16; o; o >>= 1) n = fmaxf(n, __shfl_xor_sync(~0u, n, o));
                if (lane == 0) g_kmax[hd * 64 + rb * 4 + (i & 3)] = n;
            }
            named_bar_sync(7, 96);
            PROFH(40);
            if (ht == 0) {
                flag_signal(&g_flags.kv_ready);
                flag_wait(&g_flags.kv_ready, 128, 300);
                mbar_wait_sleep(bar0 + B_XNDEAD * 8, 300);
            }
            named_bar_sync(7, 96);
            PROFH(41);
            float kmax2;
            {
                const float2 v = __ldcg(reinterpret_cast<const float2*>(g_kmax + head * 64 + lane * 2));
                kmax2 = fmaxf(v.x, v.y);
#pragma unroll
                for (int o = 16; o; o >>= 1) kmax2 = fmaxf(kmax2, __shfl_xor_sync(~0u, kmax2, o));
            }
            asm volatile("fence.proxy.async;" ::: "memory");
            int chunk = warp - 9;
#pragma unroll 1
            for (int r = ht; r < 512; r += 96) {
                if (lane == 0 && chunk < 11) {
                    mbar_expect(bar0 + (B_KV + chunk) * 8, CHUNK_BYTES);
                    bulk_load(sb + SM_KV + chunk * CHUNK_BYTES, kvsrc + chunk * CHUNK_BYTES, CHUNK_BYTES, bar0 + (B_KV + chunk) * 8);
                }
                chunk += 3;
                const uint8_t* p = kvsrc + Q_OFFSET + (quarter * 64 + (r >> 3)) * KV_GROUP_BYTES + (r & 7) * 16;
                const uint4 a = __ldcg(reinterpret_cast<const uint4*>(p)), b = __ldcg(reinterpret_cast<const uint4*>(p + 128));
                const uint32_t e = __ldcg(reinterpret_cast<const uint32_t*>(p + 256));
                const float cc = sqrtf((sumsq2(e) + sumsq8(a) + sumsq8(b)) * kmax2) * 1.02f;
                if (!(cc <= 58.f)) *slow_flag = 1;
                uint4* dst = reinterpret_cast<uint4*>(smem + SM_Q + (r >> 3) * 512 + (r & 7) * 16);
                dst[0] = a;
                dst[8] = b;
                dst[16] = make_uint4(e, pack_bf16(-cc, 768.f), 0u, 0u);
                dst[24] = make_uint4(0u, POLY_MODE ? 0xBFFF0000u : 0xC0000000u, 0u, 0u);
            }
            named_bar_sync(7, 96);
            if (*slow_flag) {
#pragma unroll 1
                for (int r = ht; r < 512; r += 96) {
                    uint32_t* dst = reinterpret_cast<uint32_t*>(smem + SM_Q + (r >> 3) * 512 + (r & 7) * 16);
                    dst[65] = 0u;
                    dst[97] = 0u;
                }
            }
            fence_proxy_async();
            __syncwarp();
            if (lane == 0) mbar_arrive(bar0 + B_QRDY * 8);
            PROFH(42);
            if (ht == 0) {
                mbar_wait_sleep(bar0 + B_FFN * 8, 300);
                flag_signal(&g_flags.ffn_done[rb]);
                flag_wait(&g_flags.ffn_done[rt >> 1], 8, 300);
            }
            named_bar_sync(7, 96);
            {
                const int w3 = warp - 9;
                const uint32_t rbar = bar0 + (B_RED + w3 * 2) * 8, rbuf = SM_RED + w3 * 8192;
                const int u0 = ((rt >> 1) * 36 + ct * 9) * 256 + (rt & 1) * 128;
                mbar_wait_sleep(bar0 + (B_KV + 15) * 8, 500);
                asm volatile("fence.proxy.async;" ::: "memory");
#pragma unroll 1
                for (int i = -2; i < 12; i++) {
                    if (i >= 0) {
                        __nanosleep(400);
                        mbar_wait(rbar + (i & 1) * 8, (i >> 1) & 1);
                        const uint4* sp = reinterpret_cast<const uint4*>(smem + rbuf + (i & 1) * 4096) + lane;
                        const uint4 v = hadd8_bf16(hadd8_bf16(hadd8_bf16(sp[0], sp[32]), hadd8_bf16(sp[64], sp[96])),
                                                   hadd8_bf16(hadd8_bf16(sp[128], sp[160]), hadd8_bf16(sp[192], sp[224])));
                        uint2* fp = g_ffn + blockIdx.x * 2304 + (i * 3 + w3) * 32 + lane;
                        fp[0] = make_uint2(v.x, v.z);
                        fp[1152] = make_uint2(v.y, v.w);
                    }
                    __syncwarp();
                    if (lane == 0 && i < 10) {
                        const int bx = (i + 2) * 3 + w3;
                        mbar_expect(rbar + (i & 1) * 8, 4096);
                        tma2d(sb + rbuf + (i & 1) * 4096, &tmP, (u0 + (bx >> 2) * 256 + (bx & 3) * 32) * 2, 0, rbar + (i & 1) * 8);
                    }
                }
            }
            __syncwarp();
            if (lane == 0) mbar_arrive(bar0 + B_BASE * 8);
            PROFH(43);
            if (ht == 0) {
                mbar_wait_sleep(bar0 + B_DONE * 8, 500);
                if (atomicAdd(&g_flags.exited, 1u) == gridDim.x - 1) {
                    unsigned int* f = reinterpret_cast<unsigned int*>(&g_flags);
#pragma unroll 1
                    for (int i = 0; i < (int)(sizeof(Flags) / 4); i++) f[i] = 0;
                }
            }
        }
    }
}

typedef CUresult (*EncodeFn)(CUtensorMap*, CUtensorMapDataType, cuuint32_t, void*, const cuuint64_t*, const cuuint64_t*, const cuuint32_t*,
                             const cuuint32_t*, CUtensorMapInterleave, CUtensorMapSwizzle, CUtensorMapL2promotion, CUtensorMapFloatOOBfill);

void make_map(EncodeFn fn, CUtensorMap* m, const void* base, int rank, const cuuint64_t* dims, const cuuint64_t* strides, const cuuint32_t* box) {
    cuuint32_t es[4] = {1, 1, 1, 1};
    fn(m, CU_TENSOR_MAP_DATA_TYPE_BFLOAT16, rank, const_cast<void*>(base), dims, strides, box, es, CU_TENSOR_MAP_INTERLEAVE_NONE,
       CU_TENSOR_MAP_SWIZZLE_128B, CU_TENSOR_MAP_L2_PROMOTION_L2_256B, CU_TENSOR_MAP_FLOAT_OOB_FILL_NONE);
}

}

extern "C" void kernel_launch(void* const* d_in, const int* in_sizes, int n_in, void* d_out, int out_size) {
    const __nv_bfloat16* x = (const __nv_bfloat16*)d_in[0];
    const __nv_bfloat16* wqkv = (const __nv_bfloat16*)d_in[1];
    const __nv_bfloat16* wo = (const __nv_bfloat16*)d_in[2];
    const __nv_bfloat16* w1 = (const __nv_bfloat16*)d_in[4];
    const __nv_bfloat16* b1 = (const __nv_bfloat16*)d_in[5];
    const __nv_bfloat16* w2 = (const __nv_bfloat16*)d_in[6];
    const __nv_bfloat16* b2 = (const __nv_bfloat16*)d_in[7];
    __nv_bfloat16* out = (__nv_bfloat16*)d_out;

    EncodeFn fn = nullptr;
    cudaDriverEntryPointQueryResult qr;
    cudaGetDriverEntryPoint("cuTensorMapEncodeTiled", (void**)&fn, cudaEnableDefault, &qr);
    CUtensorMap tmX, tmQ3, tmQ1, tm1, tm2, tmP;
    {
        void* gp = nullptr;
        cudaGetSymbolAddress(&gp, g_part);
        cuuint64_t d[2] = {SLAB * 2, 8}, s[1] = {SLAB * 16};
        cuuint32_t b[2] = {64, 8}, es[2] = {1, 1};
        fn(&tmP, CU_TENSOR_MAP_DATA_TYPE_INT64, 2, gp, d, s, b, es, CU_TENSOR_MAP_INTERLEAVE_NONE, CU_TENSOR_MAP_SWIZZLE_NONE,
           CU_TENSOR_MAP_L2_PROMOTION_NONE, CU_TENSOR_MAP_FLOAT_OOB_FILL_NONE);
    }
    {
        cuuint64_t d[4] = {64, 8, 9, SEQ / 8}, s[3] = {DM * 2, 128, DM * 2 * 8};
        cuuint32_t b[4] = {64, 8, 3, 2};
        make_map(fn, &tmX, x, 4, d, s, b);
    }
    {
        cuuint64_t d[3] = {3 * DM, DM, 3}, s[2] = {3 * DM * 2, 128};
        cuuint32_t b[3] = {64, 16, 3};
        make_map(fn, &tmQ3, wqkv, 3, d, s, b);
        make_map(fn, &tmQ1, wqkv, 2, d, s, b);
    }
    {
        cuuint64_t d[2] = {FF, DM}, s[1] = {FF * 2};
        cuuint32_t b[2] = {64, 64};
        make_map(fn, &tm1, w1, 2, d, s, b);
        cuuint64_t d2[2] = {DM, FF}, s2[1] = {DM * 2};
        make_map(fn, &tm2, w2, 2, d2, s2, b);
    }
    cudaFuncSetAttribute(fused_kernel, cudaFuncAttributeMaxDynamicSharedMemorySize, K1_SMEM);
    fused_kernel<<<128, 384, K1_SMEM, cudaStreamPerThread>>>(tmX, tmQ3, tmQ1, tm1, tm2, tmP, b1, wqkv, w1, w2, wo, x, b2, out, 0ull);
}
```

```cpp
#include <cuda_runtime.h>
#include <cuda_bf16.h>
#include <cuda.h>
#include <stdint.h>

#define PROF(i) do { } while (0)
#define PROFT(i) do { } while (0)
#define PROFH(i) do { } while (0)
#define PROFWT(i) do { } while (0)
#define PROF_WG 0

namespace {

constexpr int SEQ = 2048, DM = 576, FF = 4608, NH = 32, DH = 18;

constexpr int KV_GROUP_BYTES = 5 * 128;
constexpr int KV_HEAD_BYTES = (SEQ / 8) * KV_GROUP_BYTES;
constexpr int Q_OFFSET = NH * KV_HEAD_BYTES;
#define POLY_MASK 0xB6
__device__ __align__(1024) uint8_t g_QKV[2 * NH * KV_HEAD_BYTES];
__device__ __align__(1024) float g_kmax[NH * 64];
constexpr int SLAB = 16 * 36 * 256;
__device__ __align__(1024) uint4 g_part[8 * SLAB];
__device__ __align__(1024) uint2 g_ffn[128 * 2 * 9 * 128];
__device__ __align__(1024) uint32_t g_O[SEQ * DM / 2];
struct Flags {
    unsigned int qkv_stored[16];
    unsigned int ffn_done[16];
    unsigned int o_done[4];
    unsigned int kv_ready;
    unsigned int exited;
};
__device__ Flags g_flags;
constexpr int WO_TILE_BYTES = DM * 144 * 2;
__device__ __align__(1024) uint8_t g_Wo[4 * WO_TILE_BYTES];

__device__ __forceinline__ uint32_t s2u(const void* p) { return (uint32_t)__cvta_generic_to_shared(p); }
__device__ __forceinline__ void mbar_init(uint32_t b, int c) { asm volatile("mbarrier.init.shared::cta.b64 [%0], %1;" ::"r"(b), "r"(c) : "memory"); }
__device__ __forceinline__ void mbar_expect(uint32_t b, uint32_t bytes) {
    asm volatile("mbarrier.arrive.expect_tx.shared::cta.b64 _, [%0], %1;" ::"r"(b), "r"(bytes) : "memory");
}
__device__ __forceinline__ void mbar_wait(uint32_t b, uint32_t parity) {
    asm volatile(
        "{\n.reg .pred p;\n.reg .u32 c;\n"
        "mov.u32 c, 0;\n"
        "LOOP:\n"
        "mbarrier.try_wait.parity.shared::cta.b64 p, [%0], %1;\n"
        "@p bra DONE;\n"
        "add.u32 c, c, 1;\n"
        "setp.lt.u32 p, c, 4194304;\n"
        "@p bra LOOP;\n"
        "trap;\n"
        "DONE:\n}\n" ::"r"(b), "r"(parity) : "memory");
}
__device__ __forceinline__ void fence_barrier_init() { asm volatile("fence.mbarrier_init.release.cluster;" ::: "memory"); }
__device__ __forceinline__ void fence_proxy_async() { asm volatile("fence.proxy.async.shared::cta;" ::: "memory"); }
__device__ __forceinline__ void cluster_arrive() { asm volatile("barrier.cluster.arrive.relaxed.aligned;" ::: "memory"); }
__device__ __forceinline__ void cluster_wait() { asm volatile("barrier.cluster.wait.aligned;" ::: "memory"); }
__device__ __forceinline__ void named_bar_sync(int id, int n) { asm volatile("bar.sync %0, %1;" ::"r"(id), "r"(n) : "memory"); }

__device__ __forceinline__ void tma3d_mc(uint32_t dst, const CUtensorMap* tm, int c0, int c1, int c2, uint32_t bar, uint16_t mask) {
    asm volatile("cp.async.bulk.tensor.3d.shared::cluster.global.mbarrier::complete_tx::bytes.multicast::cluster [%0], [%1, {%3, %4, %5}], [%2], %6;"
                 ::"r"(dst), "l"(tm), "r"(bar), "r"(c0), "r"(c1), "r"(c2), "h"(mask) : "memory");
}
__device__ __forceinline__ void tma2d_mc(uint32_t dst, const CUtensorMap* tm, int c0, int c1, uint32_t bar, uint16_t mask) {
    asm volatile("cp.async.bulk.tensor.2d.shared::cluster.global.mbarrier::complete_tx::bytes.multicast::cluster [%0], [%1, {%3, %4}], [%2], %5;"
                 ::"r"(dst), "l"(tm), "r"(bar), "r"(c0), "r"(c1), "h"(mask) : "memory");
}
__device__ __forceinline__ void tma4d(uint32_t dst, const CUtensorMap* tm, int c0, int c1, int c2, int c3, uint32_t bar) {
    asm volatile("cp.async.bulk.tensor.4d.shared::cluster.global.mbarrier::complete_tx::bytes [%0], [%1, {%3, %4, %5, %6}], [%2];"
                 ::"r"(dst), "l"(tm), "r"(bar), "r"(c0), "r"(c1), "r"(c2), "r"(c3) : "memory");
}
__device__ __forceinline__ void tma2d(uint32_t dst, const CUtensorMap* tm, int c0, int c1, uint32_t bar) {
    asm volatile("cp.async.bulk.tensor.2d.shared::cluster.global.mbarrier::complete_tx::bytes [%0], [%1, {%3, %4}], [%2];"
                 ::"r"(dst), "l"(tm), "r"(bar), "r"(c0), "r"(c1) : "memory");
}
__device__ __forceinline__ void bulk_load(uint32_t dst, const void* src, uint32_t bytes, uint32_t bar) {
    asm volatile("cp.async.bulk.shared::cluster.global.mbarrier::complete_tx::bytes [%0], [%1], %2, [%3];"
                 ::"r"(dst), "l"(src), "r"(bytes), "r"(bar) : "memory");
}
__device__ __forceinline__ void prefetch_l2(const void* p, uint32_t bytes) {
    asm volatile("cp.async.bulk.prefetch.L2.global [%0], %1;" ::"l"(p), "r"(bytes) : "memory");
}
__device__ __forceinline__ void prefetch_tmap(const CUtensorMap* tm) { asm volatile("prefetch.tensormap [%0];" ::"l"(tm) : "memory"); }

__device__ __forceinline__ void wg_fence() { asm volatile("wgmma.fence.sync.aligned;" ::: "memory"); }
__device__ __forceinline__ void wg_commit() { asm volatile("wgmma.commit_group.sync.aligned;" ::: "memory"); }
template <int N> __device__ __forceinline__ void wg_wait() { asm volatile("wgmma.wait_group.sync.aligned %0;" ::"n"(N) : "memory"); }
template <int N> __device__ __forceinline__ void reg_fence(float (&d)[N]) {
#pragma unroll
    for (int i = 0; i < N; i++) asm volatile("" : "+f"(d[i])::"memory");
}
template <int N> __device__ __forceinline__ void reg_fence(uint32_t (&d)[N]) {
#pragma unroll
    for (int i = 0; i < N; i++) asm volatile("" : "+r"(d[i])::"memory");
}
template <int R> __device__ __forceinline__ void reg_alloc() { asm volatile("setmaxnreg.inc.sync.aligned.u32 %0;" ::"n"(R)); }
template <int R> __device__ __forceinline__ void reg_dealloc() { asm volatile("setmaxnreg.dec.sync.aligned.u32 %0;" ::"n"(R)); }

__device__ __forceinline__ uint64_t mk_desc(uint64_t z, uint32_t addr, uint32_t lbo, uint32_t sbo, uint32_t swz) {
    return z + ((uint64_t)(((addr & 0x3FFFF) >> 4) | ((lbo >> 4) << 16)) | ((uint64_t)((sbo >> 4) | (swz << 30)) << 32));
}
__device__ __forceinline__ uint32_t pack_bf16(float lo, float hi) {
    uint32_t r;
    asm("cvt.rn.bf16x2.f32 %0, %1, %2;" : "=r"(r) : "f"(hi), "f"(lo));
    return r;
}
__device__ __forceinline__ float bf_lo(uint32_t w) { return __uint_as_float(w << 16); }
__device__ __forceinline__ float bf_hi(uint32_t w) { return __uint_as_float(w & 0xFFFF0000u); }
__device__ __forceinline__ float ex2(float x) {
    float r;
    asm("ex2.approx.ftz.f32 %0, %1;" : "=f"(r) : "f"(x));
    return r;
}
__device__ __forceinline__ float tanh_fast(float x) {
    float r;
    asm("tanh.approx.f32 %0, %1;" : "=f"(r) : "f"(x));
    return r;
}
__device__ __forceinline__ uint32_t hfma2_bf16(uint32_t a, uint32_t b, uint32_t c) {
    uint32_t r;
    asm("fma.rn.bf16x2 %0, %1, %2, %3;" : "=r"(r) : "r"(a), "r"(b), "r"(c));
    return r;
}
__device__ __forceinline__ uint32_t hadd2_bf16(uint32_t a, uint32_t b) {
    uint32_t r;
    asm("add.rn.bf16x2 %0, %1, %2;" : "=r"(r) : "r"(a), "r"(b));
    return r;
}
__device__ __forceinline__ void ldsm4(uint32_t (&a)[4], uint32_t addr) {
    asm volatile("ldmatrix.sync.aligned.m8n8.x4.shared.b16 {%0, %1, %2, %3}, [%4];" : "=r"(a[0]), "=r"(a[1]), "=r"(a[2]), "=r"(a[3]) : "r"(addr) : "memory");
}
__device__ __forceinline__ void stsm4(uint32_t addr, const uint32_t (&a)[4]) {
    asm volatile("stmatrix.sync.aligned.m8n8.x4.shared.b16 [%0], {%1, %2, %3, %4};" ::"r"(addr), "r"(a[0]), "r"(a[1]), "r"(a[2]), "r"(a[3]) : "memory");
}
__device__ __forceinline__ void mma16816(float (&c)[4], const uint32_t (&a)[4], uint32_t b0, uint32_t b1) {
    asm("mma.sync.aligned.m16n8k16.row.col.f32.bf16.bf16.f32 {%0, %1, %2, %3}, {%4, %5, %6, %7}, {%8, %9}, {%0, %1, %2, %3};"
        : "+f"(c[0]), "+f"(c[1]), "+f"(c[2]), "+f"(c[3]) : "r"(a[0]), "r"(a[1]), "r"(a[2]), "r"(a[3]), "r"(b0), "r"(b1));
}
__device__ __forceinline__ float gelu2(float u) {
    const float w = fmaf(u * u, 0.0356774081f, 0.7978845608f);
    return fmaf(u, tanh_fast(u * w), u);
}

template<int TB, int AOFF, int BOFF> __device__ __forceinline__ void wgmma_ss_n216(float (&d)[108], uint64_t da, uint64_t db, int sd) {
    asm volatile("{\n.reg .pred p;\n.reg .b64 ta, tb;\nsetp.ne.b32 p, %110, 0;\nadd.s64 ta, %108, %112;\nadd.s64 tb, %109, %113;\n"
      "wgmma.mma_async.sync.aligned.m64n216k16.f32.bf16.bf16 {%0, %1, %2, %3, %4, %5, %6, %7, %8, %9, %10, %11, %12, %13, %14, %15, %16, %17, %18, %19, %20, %21, %22, %23, %24, %25, %26, %27, %28, %29, %30, %31, %32, %33, %34, %35, %36, %37, %38, %39, %40, %41, %42, %43, %44, %45, %46, %47, %48, %49, %50, %51, %52, %53, %54, %55, %56, %57, %58, %59, %60, %61, %62, %63, %64, %65, %66, %67, %68, %69, %70, %71, %72, %73, %74, %75, %76, %77, %78, %79, %80, %81, %82, %83, %84, %85, %86, %87, %88, %89, %90, %91, %92, %93, %94, %95, %96, %97, %98, %99, %100, %101, %102, %103, %104, %105, %106, %107}, ta, tb, p, 1, 1, 0, %111;\n}\n"
      : "+f"(d[0]), "+f"(d[1]), "+f"(d[2]), "+f"(d[3]), "+f"(d[4]), "+f"(d[5]), "+f"(d[6]), "+f"(d[7]), "+f"(d[8]), "+f"(d[9]), "+f"(d[10]), "+f"(d[11]), "+f"(d[12]), "+f"(d[13]), "+f"(d[14]), "+f"(d[15]), "+f"(d[16]), "+f"(d[17]), "+f"(d[18]), "+f"(d[19]), "+f"(d[20]), "+f"(d[21]), "+f"(d[22]), "+f"(d[23]), "+f"(d[24]), "+f"(d[25]), "+f"(d[26]), "+f"(d[27]), "+f"(d[28]), "+f"(d[29]), "+f"(d[30]), "+f"(d[31]), "+f"(d[32]), "+f"(d[33]), "+f"(d[34]), "+f"(d[35]), "+f"(d[36]), "+f"(d[37]), "+f"(d[38]), "+f"(d[39]), "+f"(d[40]), "+f"(d[41]), "+f"(d[42]), "+f"(d[43]), "+f"(d[44]), "+f"(d[45]), "+f"(d[46]), "+f"(d[47]), "+f"(d[48]), "+f"(d[49]), "+f"(d[50]), "+f"(d[51]), "+f"(d[52]), "+f"(d[53]), "+f"(d[54]), "+f"(d[55]), "+f"(d[56]), "+f"(d[57]), "+f"(d[58]), "+f"(d[59]), "+f"(d[60]), "+f"(d[61]), "+f"(d[62]), "+f"(d[63]), "+f"(d[64]), "+f"(d[65]), "+f"(d[66]), "+f"(d[67]), "+f"(d[68]), "+f"(d[69]), "+f"(d[70]), "+f"(d[71]), "+f"(d[72]), "+f"(d[73]), "+f"(d[74]), "+f"(d[75]), "+f"(d[76]), "+f"(d[77]), "+f"(d[78]), "+f"(d[79]), "+f"(d[80]), "+f"(d[81]), "+f"(d[82]), "+f"(d[83]), "+f"(d[84]), "+f"(d[85]), "+f"(d[86]), "+f"(d[87]), "+f"(d[88]), "+f"(d[89]), "+f"(d[90]), "+f"(d[91]), "+f"(d[92]), "+f"(d[93]), "+f"(d[94]), "+f"(d[95]), "+f"(d[96]), "+f"(d[97]), "+f"(d[98]), "+f"(d[99]), "+f"(d[100]), "+f"(d[101]), "+f"(d[102]), "+f"(d[103]), "+f"(d[104]), "+f"(d[105]), "+f"(d[106]), "+f"(d[107])
      : "l"(da), "l"(db), "r"(sd), "n"(TB), "n"(AOFF), "n"(BOFF));
}

template<int TB, int AOFF, int BOFF> __device__ __forceinline__ void wgmma_ss_n64(float (&d)[32], uint64_t da, uint64_t db, int sd) {
    asm volatile("{\n.reg .pred p;\n.reg .b64 ta, tb;\nsetp.ne.b32 p, %34, 0;\nadd.s64 ta, %32, %36;\nadd.s64 tb, %33, %37;\n"
      "wgmma.mma_async.sync.aligned.m64n64k16.f32.bf16.bf16 {%0, %1, %2, %3, %4, %5, %6, %7, %8, %9, %10, %11, %12, %13, %14, %15, %16, %17, %18, %19, %20, %21, %22, %23, %24, %25, %26, %27, %28, %29, %30, %31}, ta, tb, p, 1, 1, 0, %35;\n}\n"
      : "+f"(d[0]), "+f"(d[1]), "+f"(d[2]), "+f"(d[3]), "+f"(d[4]), "+f"(d[5]), "+f"(d[6]), "+f"(d[7]), "+f"(d[8]), "+f"(d[9]), "+f"(d[10]), "+f"(d[11]), "+f"(d[12]), "+f"(d[13]), "+f"(d[14]), "+f"(d[15]), "+f"(d[16]), "+f"(d[17]), "+f"(d[18]), "+f"(d[19]), "+f"(d[20]), "+f"(d[21]), "+f"(d[22]), "+f"(d[23]), "+f"(d[24]), "+f"(d[25]), "+f"(d[26]), "+f"(d[27]), "+f"(d[28]), "+f"(d[29]), "+f"(d[30]), "+f"(d[31])
      : "l"(da), "l"(db), "r"(sd), "n"(TB), "n"(AOFF), "n"(BOFF));
}

template<int TB, int AOFF, int BOFF> __device__ __forceinline__ void wgmma_ss_n128(float (&d)[64], uint64_t da, uint64_t db, int sd) {
    asm volatile("{\n.reg .pred p;\n.reg .b64 ta, tb;\nsetp.ne.b32 p, %66, 0;\nadd.s64 ta, %64, %68;\nadd.s64 tb, %65, %69;\n"
      "wgmma.mma_async.sync.aligned.m64n128k16.f32.bf16.bf16 {%0, %1, %2, %3, %4, %5, %6, %7, %8, %9, %10, %11, %12, %13, %14, %15, %16, %17, %18, %19, %20, %21, %22, %23, %24, %25, %26, %27, %28, %29, %30, %31, %32, %33, %34, %35, %36, %37, %38, %39, %40, %41, %42, %43, %44, %45, %46, %47, %48, %49, %50, %51, %52, %53, %54, %55, %56, %57, %58, %59, %60, %61, %62, %63}, ta, tb, p, 1, 1, 0, %67;\n}\n"
      : "+f"(d[0]), "+f"(d[1]), "+f"(d[2]), "+f"(d[3]), "+f"(d[4]), "+f"(d[5]), "+f"(d[6]), "+f"(d[7]), "+f"(d[8]), "+f"(d[9]), "+f"(d[10]), "+f"(d[11]), "+f"(d[12]), "+f"(d[13]), "+f"(d[14]), "+f"(d[15]), "+f"(d[16]), "+f"(d[17]), "+f"(d[18]), "+f"(d[19]), "+f"(d[20]), "+f"(d[21]), "+f"(d[22]), "+f"(d[23]), "+f"(d[24]), "+f"(d[25]), "+f"(d[26]), "+f"(d[27]), "+f"(d[28]), "+f"(d[29]), "+f"(d[30]), "+f"(d[31]), "+f"(d[32]), "+f"(d[33]), "+f"(d[34]), "+f"(d[35]), "+f"(d[36]), "+f"(d[37]), "+f"(d[38]), "+f"(d[39]), "+f"(d[40]), "+f"(d[41]), "+f"(d[42]), "+f"(d[43]), "+f"(d[44]), "+f"(d[45]), "+f"(d[46]), "+f"(d[47]), "+f"(d[48]), "+f"(d[49]), "+f"(d[50]), "+f"(d[51]), "+f"(d[52]), "+f"(d[53]), "+f"(d[54]), "+f"(d[55]), "+f"(d[56]), "+f"(d[57]), "+f"(d[58]), "+f"(d[59]), "+f"(d[60]), "+f"(d[61]), "+f"(d[62]), "+f"(d[63])
      : "l"(da), "l"(db), "r"(sd), "n"(TB), "n"(AOFF), "n"(BOFF));
}

template<int TB, int BOFF> __device__ __forceinline__ void wgmma_rs_n64(float (&d)[32], uint32_t a0, uint32_t a1, uint32_t a2, uint32_t a3, uint64_t db, int sd) {
    asm volatile("{\n.reg .pred p;\n.reg .b64 tb;\nsetp.ne.b32 p, %37, 0;\nadd.s64 tb, %36, %39;\n"
      "wgmma.mma_async.sync.aligned.m64n64k16.f32.bf16.bf16 {%0, %1, %2, %3, %4, %5, %6, %7, %8, %9, %10, %11, %12, %13, %14, %15, %16, %17, %18, %19, %20, %21, %22, %23, %24, %25, %26, %27, %28, %29, %30, %31}, {%32, %33, %34, %35}, tb, p, 1, 1, %38;\n}\n"
      : "+f"(d[0]), "+f"(d[1]), "+f"(d[2]), "+f"(d[3]), "+f"(d[4]), "+f"(d[5]), "+f"(d[6]), "+f"(d[7]), "+f"(d[8]), "+f"(d[9]), "+f"(d[10]), "+f"(d[11]), "+f"(d[12]), "+f"(d[13]), "+f"(d[14]), "+f"(d[15]), "+f"(d[16]), "+f"(d[17]), "+f"(d[18]), "+f"(d[19]), "+f"(d[20]), "+f"(d[21]), "+f"(d[22]), "+f"(d[23]), "+f"(d[24]), "+f"(d[25]), "+f"(d[26]), "+f"(d[27]), "+f"(d[28]), "+f"(d[29]), "+f"(d[30]), "+f"(d[31])
      : "r"(a0), "r"(a1), "r"(a2), "r"(a3), "l"(db), "r"(sd), "n"(TB), "n"(BOFF));
}

template<int TB, int BOFF> __device__ __forceinline__ void wgmma_rs_n24(float (&d)[12], uint32_t a0, uint32_t a1, uint32_t a2, uint32_t a3, uint64_t db, int sd) {
    asm volatile("{\n.reg .pred p;\n.reg .b64 tb;\nsetp.ne.b32 p, %17, 0;\nadd.s64 tb, %16, %19;\n"
      "wgmma.mma_async.sync.aligned.m64n24k16.f32.bf16.bf16 {%0, %1, %2, %3, %4, %5, %6, %7, %8, %9, %10, %11}, {%12, %13, %14, %15}, tb, p, 1, 1, %18;\n}\n"
      : "+f"(d[0]), "+f"(d[1]), "+f"(d[2]), "+f"(d[3]), "+f"(d[4]), "+f"(d[5]), "+f"(d[6]), "+f"(d[7]), "+f"(d[8]), "+f"(d[9]), "+f"(d[10]), "+f"(d[11])
      : "r"(a0), "r"(a1), "r"(a2), "r"(a3), "l"(db), "r"(sd), "n"(TB), "n"(BOFF));
}

template<int TB, int BOFF> __device__ __forceinline__ void wgmma_rs_n144(float (&d)[72], uint32_t a0, uint32_t a1, uint32_t a2, uint32_t a3, uint64_t db, int sd) {
    asm volatile("{\n.reg .pred p;\n.reg .b64 tb;\nsetp.ne.b32 p, %77, 0;\nadd.s64 tb, %76, %79;\n"
      "wgmma.mma_async.sync.aligned.m64n144k16.f32.bf16.bf16 {%0, %1, %2, %3, %4, %5, %6, %7, %8, %9, %10, %11, %12, %13, %14, %15, %16, %17, %18, %19, %20, %21, %22, %23, %24, %25, %26, %27, %28, %29, %30, %31, %32, %33, %34, %35, %36, %37, %38, %39, %40, %41, %42, %43, %44, %45, %46, %47, %48, %49, %50, %51, %52, %53, %54, %55, %56, %57, %58, %59, %60, %61, %62, %63, %64, %65, %66, %67, %68, %69, %70, %71}, {%72, %73, %74, %75}, tb, p, 1, 1, %78;\n}\n"
      : "+f"(d[0]), "+f"(d[1]), "+f"(d[2]), "+f"(d[3]), "+f"(d[4]), "+f"(d[5]), "+f"(d[6]), "+f"(d[7]), "+f"(d[8]), "+f"(d[9]), "+f"(d[10]), "+f"(d[11]), "+f"(d[12]), "+f"(d[13]), "+f"(d[14]), "+f"(d[15]), "+f"(d[16]), "+f"(d[17]), "+f"(d[18]), "+f"(d[19]), "+f"(d[20]), "+f"(d[21]), "+f"(d[22]), "+f"(d[23]), "+f"(d[24]), "+f"(d[25]), "+f"(d[26]), "+f"(d[27]), "+f"(d[28]), "+f"(d[29]), "+f"(d[30]), "+f"(d[31]), "+f"(d[32]), "+f"(d[33]), "+f"(d[34]), "+f"(d[35]), "+f"(d[36]), "+f"(d[37]), "+f"(d[38]), "+f"(d[39]), "+f"(d[40]), "+f"(d[41]), "+f"(d[42]), "+f"(d[43]), "+f"(d[44]), "+f"(d[45]), "+f"(d[46]), "+f"(d[47]), "+f"(d[48]), "+f"(d[49]), "+f"(d[50]), "+f"(d[51]), "+f"(d[52]), "+f"(d[53]), "+f"(d[54]), "+f"(d[55]), "+f"(d[56]), "+f"(d[57]), "+f"(d[58]), "+f"(d[59]), "+f"(d[60]), "+f"(d[61]), "+f"(d[62]), "+f"(d[63]), "+f"(d[64]), "+f"(d[65]), "+f"(d[66]), "+f"(d[67]), "+f"(d[68]), "+f"(d[69]), "+f"(d[70]), "+f"(d[71])
      : "r"(a0), "r"(a1), "r"(a2), "r"(a3), "l"(db), "r"(sd), "n"(TB), "n"(BOFF));
}

constexpr int K1_XN_BYTES = 16 * 9216;
constexpr int K1_OFF_RING = K1_XN_BYTES;
constexpr int K1_OFF_BIAS = K1_OFF_RING + 10 * 8192;
constexpr int K1_OFF_BAR = K1_OFF_BIAS + 576 * 2;
constexpr int K1_SMEM = K1_OFF_BAR + 768;
constexpr float QSCALE = 0.23570226039551584f * 1.4426950408889634f;

struct K1Ctx {
    uint32_t full0;
    uint32_t rel_addr;
    uint64_t descA, descB;
    uint32_t phase;
    __device__ __forceinline__ void begin_stage(int s) {
        mbar_wait(full0 + s * 8, phase);
        wg_fence();
    }
    __device__ __forceinline__ void release(int s) {
        if (rel_addr) asm volatile("mbarrier.arrive.shared::cluster.b64 _, [%0];" ::"r"(rel_addr + s * 8) : "memory");
    }
    __device__ __forceinline__ void end_stage(int s) {
        wg_commit();
        wg_wait<1>();
        release(s == 0 ? 8 : s - 1);
    }
};

__host__ __device__ constexpr int a_off(int ks) { return ((ks / 12) * 49152 + ((ks >> 2) % 3) * 1024 + (ks & 3) * 32) >> 4; }

template <int V> struct IC { static constexpr int value = V; };
template <int I, int N, class F> __device__ __forceinline__ void static_for(F&& f) {
    if constexpr (I < N) { f(IC<I>{}); static_for<I + 1, N>(f); }
}

template <bool A_RS, bool B_RS, class Epi>
__device__ __forceinline__ void tile_pair(K1Ctx& c, float (&accA)[32], float (&accB)[32], uint32_t (&h)[144], Epi&& epi) {
    static_for<0, 9>([&](auto sc) {
        constexpr int s = decltype(sc)::value;
        c.begin_stage(s);
        static_for<0, 8>([&](auto tc) {
            constexpr int kk = s * 8 + decltype(tc)::value, ks = kk % 36;
            constexpr int bo = (ks * 2048) >> 4;
            if constexpr (kk < 36) {
                if constexpr (A_RS) wgmma_rs_n64<1, bo>(accA, h[ks * 4], h[ks * 4 + 1], h[ks * 4 + 2], h[ks * 4 + 3], c.descB, ks != 0);
                else wgmma_ss_n64<1, a_off(ks), bo>(accA, c.descA, c.descB, ks != 0);
            } else {
                if constexpr (B_RS) wgmma_rs_n64<1, bo>(accB, h[ks * 4], h[ks * 4 + 1], h[ks * 4 + 2], h[ks * 4 + 3], c.descB, ks != 0);
                else wgmma_ss_n64<1, a_off(ks), bo>(accB, c.descA, c.descB, ks != 0);
            }
        });
        c.end_stage(s);
        epi(sc);
    });
    c.phase ^= 1;
}

template <int B0, int NB, int HOFF>
__device__ __forceinline__ void gelu_blocks(const float (&acc)[32], uint32_t (&h)[144], const uint32_t (&bq)[8], float rs0, float rs1) {
#pragma unroll
    for (int b = B0; b < B0 + NB; b++) {
        const float b0 = bf_lo(bq[b]), b1 = bf_hi(bq[b]);
        h[HOFF + b * 2 + 0] = pack_bf16(gelu2(fmaf(acc[b * 4 + 0], rs0, b0)), gelu2(fmaf(acc[b * 4 + 1], rs0, b1)));
        h[HOFF + b * 2 + 1] = pack_bf16(gelu2(fmaf(acc[b * 4 + 2], rs1, b0)), gelu2(fmaf(acc[b * 4 + 3], rs1, b1)));
    }
#pragma unroll
    for (int i = HOFF + B0 * 2; i < HOFF + (B0 + NB) * 2; i++) asm volatile("" : "+r"(h[i]));
}
__device__ __forceinline__ void load_bias(uint32_t (&bq)[8], uint32_t addr) {
    asm volatile("ld.shared.v4.u32 {%0, %1, %2, %3}, [%4];" : "=r"(bq[0]), "=r"(bq[1]), "=r"(bq[2]), "=r"(bq[3]) : "r"(addr));
    asm volatile("ld.shared.v4.u32 {%0, %1, %2, %3}, [%4 + 16];" : "=r"(bq[4]), "=r"(bq[5]), "=r"(bq[6]), "=r"(bq[7]) : "r"(addr));
}
template <int S> __device__ __forceinline__ void store_part(const float (&o)[32], uint4* p) {
    uint4 v;
    v.x = pack_bf16(o[S * 8 + 0], o[S * 8 + 1]); v.y = pack_bf16(o[S * 8 + 2], o[S * 8 + 3]);
    v.z = pack_bf16(o[S * 8 + 4], o[S * 8 + 5]); v.w = pack_bf16(o[S * 8 + 6], o[S * 8 + 7]);
    p[S * 256] = v;
}

constexpr int NCHUNK = 16;
constexpr int CHUNK_BYTES = KV_HEAD_BYTES / NCHUNK;
constexpr int SM_Q = 0;
constexpr int SM_KV = 32768;
constexpr int WO_PIECE = WO_TILE_BYTES / 9;
__host__ __device__ constexpr int sm_wo(int i) { return i == 0 ? 210944 : (i == 1 ? 0 : SM_KV + (i - 2) * WO_PIECE); }
constexpr int SM_EXCH = SM_KV + 7 * WO_PIECE;
constexpr int SM_RED = SM_KV + KV_HEAD_BYTES;

__device__ __forceinline__ float exp2_fixed(float y) {
    const float u = __uint_as_float(__float_as_uint(y) & 0xFF807FFFu) - 512.02545f;
    float t = fmaf(u, 0.019497588f, 0.114550486f);
    t = fmaf(t, u, -0.29839927f);
    return fmaf(t, u, y);
}
__device__ __forceinline__ uint32_t pack_fixed(float lo, float hi) { return __byte_perm(__float_as_uint(lo), __float_as_uint(hi), 0x6521); }

#define PV_GROUP 1
#define POLY_MODE 1
__device__ __forceinline__ uint32_t exp2_packed(float y0, float y1, uint32_t one2) {
    const uint32_t w = pack_fixed(y0, y1);
    uint32_t m;
    asm("lop3.b32 %0, %1, 0x007F007F, %2, 0xEA;" : "=r"(m) : "r"(w), "r"(one2));
    const uint32_t d = hfma2_bf16(m, 0x3EF93EF9u, 0xBF38BF38u);
    const uint32_t e = hfma2_bf16(d, d, 0xBD71BD71u);
    return hfma2_bf16(w, e, w);
}
template <int NB>
__device__ __forceinline__ void softmax_fast(const float (&s)[NB * 4], uint32_t (&p)[NB * 2], uint32_t one2) {
#pragma unroll
    for (int b = 0; b < NB; b++) {
        if ((POLY_MASK >> (b & 7)) & 1) {
            p[b * 2 + 0] = exp2_packed(s[b * 4 + 0], s[b * 4 + 1], one2);
            p[b * 2 + 1] = exp2_packed(s[b * 4 + 2], s[b * 4 + 3], one2);
        } else {
            p[b * 2 + 0] = pack_bf16(ex2(s[b * 4 + 0]), ex2(s[b * 4 + 1]));
            p[b * 2 + 1] = pack_bf16(ex2(s[b * 4 + 2]), ex2(s[b * 4 + 3]));
        }
    }
}

constexpr int KV_TILE = CHUNK_BYTES / 16;
template <int OFF> __device__ __forceinline__ void issue_qk(float (&s)[64], uint64_t qd, uint64_t kd) {
    wgmma_ss_n128<0, 0, OFF + (8 << 16)>(s, qd, kd, 0);
    wgmma_ss_n128<0, 16, OFF + 32>(s, qd, kd, 1);
}
template <int OFF> __device__ __forceinline__ void issue_pv(float (&o)[12], const uint32_t (&p)[32], uint64_t vd) {
    static_for<0, 8>([&](auto kc) {
        constexpr int k = decltype(kc)::value;
        wgmma_rs_n24<1, OFF + k * (2 * KV_GROUP_BYTES / 16)>(o, p[k * 4], p[k * 4 + 1], p[k * 4 + 2], p[k * 4 + 3], vd, 1);
    });
}
template <int OFF>
__device__ __forceinline__ void softmax_pv(const float (&s)[64], uint32_t (&p)[32], float (&o)[12], uint64_t vd, uint32_t one2) {
    static_for<0, 8 / PV_GROUP>([&](auto gc) {
        constexpr int g0 = decltype(gc)::value * PV_GROUP;
#pragma unroll
        for (int b = g0 * 2; b < (g0 + PV_GROUP) * 2; b++) {
            if ((POLY_MASK >> (b & 7)) & 1) {
                p[b * 2 + 0] = exp2_packed(s[b * 4 + 0], s[b * 4 + 1], one2);
                p[b * 2 + 1] = exp2_packed(s[b * 4 + 2], s[b * 4 + 3], one2);
            } else {
                p[b * 2 + 0] = pack_bf16(ex2(s[b * 4 + 0]), ex2(s[b * 4 + 1]));
                p[b * 2 + 1] = pack_bf16(ex2(s[b * 4 + 2]), ex2(s[b * 4 + 3]));
            }
        }
#pragma unroll
        for (int i = g0 * 4; i < (g0 + PV_GROUP) * 4; i++) asm volatile("" : "+r"(p[i])::"memory");
        wg_fence();
        static_for<g0, g0 + PV_GROUP>([&](auto kc) {
            constexpr int k = decltype(kc)::value;
            wgmma_rs_n24<1, OFF + k * (2 * KV_GROUP_BYTES / 16)>(o, p[k * 4], p[k * 4 + 1], p[k * 4 + 2], p[k * 4 + 3], vd, 1);
        });
    });
    wg_commit();
}
__device__ __forceinline__ void store_o(float (&o)[12], int rt, int head, int wq, int lane) {
    const int g = lane >> 2, q = lane & 3;
    const float i0 = __fdividef(1.0f, __shfl_sync(~0u, o[8], lane | 3)), i1 = __fdividef(1.0f, __shfl_sync(~0u, o[10], lane | 3));
#pragma unroll
    for (int i = 0; i < 3; i++) {
        const int pc = head * 9 + (i < 2 ? i * 4 + q : 8);
        uint32_t* op = g_O + (((rt * 36 + (pc >> 3)) * 128 + wq * 32 + g * 4 + (pc & 3)) * 4 + ((pc >> 2) & 1) * 2);
        if (i < 2 || q == 2) *reinterpret_cast<uint2*>(op) = make_uint2(pack_bf16(o[i * 4] * i0, o[i * 4 + 1] * i0), pack_bf16(o[i * 4 + 2] * i1, o[i * 4 + 3] * i1));
    }
#pragma unroll
    for (int i = 0; i < 12; i++) o[i] = 0.f;
}
__device__ __forceinline__ void mbar_arrive(uint32_t b) { asm volatile("mbarrier.arrive.shared::cta.b64 _, [%0];" ::"r"(b) : "memory"); }
__device__ __forceinline__ void mbar_wait_sleep(uint32_t b, uint32_t ns) {
    uint32_t ok, spins = 0;
    while (true) {
        asm volatile("{\n.reg .pred p;\nmbarrier.try_wait.parity.shared::cta.b64 p, [%1], 0;\nselp.u32 %0, 1, 0, p;\n}\n" : "=r"(ok) : "r"(b) : "memory");
        if (ok) break;
        __nanosleep(ns);
        if (++spins > (1u << 21)) __trap();
    }
}
__device__ __forceinline__ void flag_signal(unsigned int* f) {
    __threadfence();
    atomicAdd(f, 1u);
}
__device__ __forceinline__ void flag_wait(const unsigned int* f, unsigned int target, unsigned int sleep_ns) {
    uint32_t v, spins = 0;
    while (true) {
        asm volatile("ld.acquire.gpu.global.u32 %0, [%1];" : "=r"(v) : "l"(f) : "memory");
        if (v >= target) break;
        if (sleep_ns) __nanosleep(sleep_ns);
        if (++spins > (1u << 21)) __trap();
    }
}
__device__ __forceinline__ uint4 hadd8_bf16(const uint4 a, const uint4 b) {
    return make_uint4(hadd2_bf16(a.x, b.x), hadd2_bf16(a.y, b.y), hadd2_bf16(a.z, b.z), hadd2_bf16(a.w, b.w));
}
__device__ __forceinline__ float sumsq2(uint32_t w) { return fmaf(bf_lo(w), bf_lo(w), bf_hi(w) * bf_hi(w)); }
__device__ __forceinline__ float sumsq8(const uint4 v) { return (sumsq2(v.x) + sumsq2(v.y)) + (sumsq2(v.z) + sumsq2(v.w)); }

enum { B_FULL = 0, B_EMPTY = 9, B_BASE = 18, B_XNDEAD = 19, B_QRDY = 20, B_FFN = 21, B_KV = 22, B_FREE = 38, B_WO = 46, B_RED = 55, B_X = 61, B_DONE = 85, B_END = 86 };

__global__ void __cluster_dims__(2, 1, 1) __launch_bounds__(384, 1)
fused_kernel(const __grid_constant__ CUtensorMap tmX, const __grid_constant__ CUtensorMap tmQ3, const __grid_constant__ CUtensorMap tmQ1,
          const __grid_constant__ CUtensorMap tm1, const __grid_constant__ CUtensorMap tm2, const __grid_constant__ CUtensorMap tmP, const __nv_bfloat16* __restrict__ b1,
          const __nv_bfloat16* __restrict__ wqkv, const __nv_bfloat16* __restrict__ w1, const __nv_bfloat16* __restrict__ w2,
          const __nv_bfloat16* __restrict__ wo, const __nv_bfloat16* __restrict__ x, const __nv_bfloat16* __restrict__ b2,
          __nv_bfloat16* __restrict__ out, const uint64_t zero) {
    extern __shared__ __align__(1024) uint8_t smem[];
    const uint32_t sb = s2u(smem);
    const int tid = threadIdx.x, lane = tid & 31;
    const int warp = __shfl_sync(~0u, tid >> 5, 0);
    const uint32_t rank = blockIdx.x & 1;
    const int cl = blockIdx.x >> 1;
    const int rb = (cl & 7) * 2 + rank;
    const int j = cl >> 3;
    const uint32_t bar0 = sb + K1_OFF_BAR;
    const uint32_t full0 = bar0 + B_FULL * 8, empty0 = bar0 + B_EMPTY * 8, xbar0 = bar0 + B_X * 8;
    const int head = blockIdx.x >> 2, quarter = blockIdx.x & 3;
    const int rt = quarter * 8 + (head >> 2), ct = head & 3;
    volatile uint32_t* slow_flag = reinterpret_cast<volatile uint32_t*>(smem + K1_OFF_BAR + B_END * 8);

    if (warp < 8) {
        PROF(0);
        PROFT(48);
        if (lane == 0) {
#pragma unroll
            for (int i = 0; i < 3; i++) mbar_init(xbar0 + (warp * 3 + i) * 8, 1);
            fence_barrier_init();
#pragma unroll 1
            for (int i = 0; i < 3; i++) {
                const uint32_t xb = xbar0 + (warp * 3 + i) * 8;
                mbar_expect(xb, 6144);
                tma4d(sb + i * 49152 + warp * 6144, &tmX, 0, 0, i * 3, rb * 16 + warp * 2, xb);
            }
        }
        __syncwarp();
        cluster_arrive();
        PROF(22);
        reg_alloc<240>();
        PROF(23);
        float rs0, rs1;
        {
            const uint32_t la = sb + (warp * 2 + ((lane >> 3) & 1)) * 3072 + (lane & 7) * 128;
            uint32_t off[4];
#pragma unroll
            for (int i = 0; i < 4; i++) off[i] = la + (((i * 2 + (lane >> 4)) ^ (lane & 7)) << 4);
            float c1[4] = {0.f, 0.f, 0.f, 0.f}, c2[4] = {0.f, 0.f, 0.f, 0.f}, c3[4] = {0.f, 0.f, 0.f, 0.f};
            uint32_t a[36][4];
#pragma unroll
            for (int t = 0; t < 3; t++) {
                mbar_wait(xbar0 + (warp * 3 + t) * 8, 0);
                PROF(24 + t);
#pragma unroll
                for (int i = 0; i < 12; i++) ldsm4(a[t * 12 + i], off[i & 3] + t * 49152 + (i >> 2) * 1024);
#pragma unroll
                for (int i = t * 12; i < t * 12 + 12; i++) {
                    mma16816(c3, a[i], 0x3F803F80u, 0x3F803F80u);
                    mma16816(c1, a[i], a[i][0], a[i][2]);
                    mma16816(c2, a[i], a[i][1], a[i][3]);
                }
            }
            PROF(27);
            const int gg = lane >> 2, src = (lane & ~3) | (gg >> 1);
            const float m0 = c3[0] * (1.0f / DM), m1 = c3[2] * (1.0f / DM);
            const uint32_t mc0 = pack_bf16(-m0, -m0), mc1 = pack_bf16(-m1, -m1);
#pragma unroll
            for (int i = 0; i < 36; i++) {
#pragma unroll
                for (int k = 0; k < 4; k++) a[i][k] = hadd2_bf16(a[i][k], (k & 1) ? mc1 : mc0);
                stsm4(off[i & 3] + (i / 12) * 49152 + ((i >> 2) % 3) * 1024, a[i]);
            }
            const float q0 = __shfl_sync(~0u, (gg & 1) ? c1[1] : c1[0], src), q1 = __shfl_sync(~0u, (gg & 1) ? c2[3] : c2[2], src);
            rs0 = rsqrtf(fmaxf(fmaf(-m0, m0, q0 * (1.0f / DM)), 0.f) + 1e-5f);
            rs1 = rsqrtf(fmaxf(fmaf(-m1, m1, q1 * (1.0f / DM)), 0.f) + 1e-5f);
            if (__any_sync(~0u, fabsf(m0) * rs0 > 0.25f || fabsf(m1) * rs1 > 0.25f)) {
                const float d0 = -m0 - bf_lo(mc0), d1 = -m1 - bf_lo(mc1);
                const uint32_t md0 = pack_bf16(d0, d0), md1 = pack_bf16(d1, d1);
#pragma unroll 1
                for (int i = 0; i < 9; i++) {
#pragma unroll
                    for (int k4 = 0; k4 < 4; k4++) {
                        const uint32_t ad = off[k4] + (i / 3) * 49152 + (i % 3) * 1024;
                        uint32_t b[4];
                        ldsm4(b, ad);
#pragma unroll
                        for (int k = 0; k < 4; k++) b[k] = hadd2_bf16(b[k], (k & 1) ? md1 : md0);
                        stsm4(ad, b);
                    }
                }
            }
        }
        PROF(28);
        const int wg = warp >> 2, wq = warp & 3;
        fence_proxy_async();
        named_bar_sync(1 + wg, 128);
        cluster_wait();
        PROF(1);

        const int g = lane >> 2, q = lane & 3;
        K1Ctx c;
        c.full0 = full0;
        c.rel_addr = 0;
        c.descA = mk_desc(zero, sb + wg * 8 * 3072, 16, 3072, 1);
        c.descB = mk_desc(zero, sb + K1_OFF_RING, 2048, 1024, 1);
        c.phase = 0;
        uint32_t biasq = sb + K1_OFF_BIAS + q * 32;
        uint32_t bq[8];

        uint32_t h[144];
        float accA[32], accB[32];
        {
            float accQ[108];
            uint32_t rel = 0;
            if (lane == 0 && wq < 2) asm("mapa.shared::cluster.u32 %0, %1, %2;" : "=r"(rel) : "r"(empty0), "r"(wq));
#pragma unroll 1
            for (int r = 0; r < 2; r++) {
                static_for<0, 9>([&](auto sc) {
                    constexpr int s = decltype(sc)::value;
                    c.begin_stage(s);
                    const uint64_t da = c.descA + (r ? a_off(18 + 2 * s) : a_off(2 * s));
                    wgmma_ss_n216<1, 0, ((2 * s) % 9) * 512>(accQ, da, c.descB, (r | s) != 0);
                    wgmma_ss_n216<1, 2, ((2 * s + 1) % 9) * 512>(accQ, da, c.descB, 1);
                    c.end_stage(s);
                    c.rel_addr = rel;
                });
                c.phase ^= 1;
            }
            PROF(2); PROFWT(54);
            uint32_t rel9[9];
#pragma unroll
            for (int i9 = 0; i9 < 9; i9++) {
                const int p = 4 * i9 + q, hh = (p * 57) >> 9, r = p - 9 * hh;
                rel9[i9] = hh * KV_HEAD_BYTES + (r < 8 ? (r >> 2) * 128 + (r & 3) * 4 : 0);
            }
            uint32_t gb = 0, o2 = 0;
            float scl0 = 1.f, scl1 = 1.f;
            tile_pair<false, false>(c, accA, accB, h, [&](auto sc) {
                constexpr int s = decltype(sc)::value;
                if constexpr (s == 0) reg_fence(accQ);
                if constexpr (s < 6) {
                    constexpr int grp = s / 2, part = s % 2;
                    if constexpr (part == 0) {
                        const int G = 3 * j + grp, type = G >> 3;
                        gb = (G & 7) * 4 * KV_HEAD_BYTES + (rb * 16 + warp * 2) * KV_GROUP_BYTES + g * 16 + (type == 0 ? Q_OFFSET : (type == 2 ? 256 : 0));
                        o2 = type == 0 ? 256 : (type == 2 ? 264 : 512);
                        scl0 = rs0 * (type == 0 ? QSCALE : ((type == 1 && ((POLY_MASK >> (wq * 2)) & 1)) ? 2.f : 1.f));
                        scl1 = rs1 * (type == 0 ? QSCALE : ((type == 1 && ((POLY_MASK >> (wq * 2 + 1)) & 1)) ? 2.f : 1.f));
                    }
#pragma unroll
                    for (int i9 = part * 5; i9 < (part ? 9 : 5); i9++) {
                        const int b = grp * 9 + i9;
                        uint32_t off = gb + rel9[i9];
                        if (i9 >= 2 && (i9 & 1) == 0) off += (q == i9 / 2 - 1) ? o2 : 0;
                        *reinterpret_cast<uint32_t*>(g_QKV + off) = pack_bf16(accQ[b * 4] * scl0, accQ[b * 4 + 1] * scl0);
                        *reinterpret_cast<uint32_t*>(g_QKV + off + KV_GROUP_BYTES) = pack_bf16(accQ[b * 4 + 2] * scl1, accQ[b * 4 + 3] * scl1);
                    }
                    if constexpr (s == 5) asm volatile("bar.arrive 3, 352;" ::: "memory");
                }
                if constexpr (s == 4) { named_bar_sync(4, 352); load_bias(bq, biasq); }
                if constexpr (s == 5) reg_fence(accA);
                if constexpr (s >= 5) gelu_blocks<(s - 5) * 2, 2, 96>(accA, h, bq, rs0, rs1);
                if constexpr (s == 8) load_bias(bq, biasq + 128);
            });
        }
        PROF(3); PROFWT(55);
#pragma unroll
        for (int i = 32; i < 96; i++) asm volatile("mov.u32 %0, 0;" : "=r"(h[i]));
#pragma unroll 1
        for (int p = 1; p < 4; p++) {
            biasq += 256;
            tile_pair<false, false>(c, accA, accB, h, [&](auto sc) {
                constexpr int s = decltype(sc)::value;
                if constexpr (s == 0) {
                    reg_fence(accB);
#pragma unroll
                    for (int i = 0; i < 80; i++) h[i] = h[i + 32];
                }
                if constexpr (s < 4) gelu_blocks<s * 2, 2, 80>(accB, h, bq, rs0, rs1);
                if constexpr (s == 4) load_bias(bq, biasq);
                if constexpr (s == 5) reg_fence(accA);
                if constexpr (s >= 5) gelu_blocks<(s - 5) * 2, 2, 96>(accA, h, bq, rs0, rs1);
                if constexpr (s == 8) load_bias(bq, biasq + 128);
            });
        }
        PROF(4); PROFWT(56);
        tile_pair<false, true>(c, accA, accB, h, [&](auto sc) {
            constexpr int s = decltype(sc)::value;
            if constexpr (s == 0) reg_fence(accB);
            if constexpr (s < 4) gelu_blocks<s * 2, 2, 112>(accB, h, bq, rs0, rs1);
            if constexpr (s == 4) load_bias(bq, biasq + 256);
            if constexpr (s == 5) { reg_fence(accA); if (tid == wg * 128) mbar_arrive(bar0 + B_XNDEAD * 8); }
            if constexpr (s == 5 || s == 6) gelu_blocks<(s - 5) * 3, 3, 128>(accA, h, bq, rs0, rs1);
            if constexpr (s == 7) gelu_blocks<6, 2, 128>(accA, h, bq, rs0, rs1);
            if constexpr (s == 3 || s == 7) reg_fence(h);
        });
        PROF(5); PROFWT(57);
        uint4* pout = g_part + j * SLAB + rb * 36 * 256 + tid;
#pragma unroll 1
        for (int p = 0; p < 4; p++) {
            tile_pair<true, true>(c, accA, accB, h, [&](auto sc) {
                constexpr int s = decltype(sc)::value;
                if constexpr (s == 0) reg_fence(accB);
                if constexpr (s < 4) store_part<s>(accB, pout);
                if constexpr (s == 5) reg_fence(accA);
                if constexpr (s >= 5) store_part<s - 5>(accA, pout + 1024);
            });
            pout += 2048;
            PROF(6 + p);
        }
        wg_wait<0>();
        c.release(8);
        reg_fence(accB);
        store_part<0>(accB, pout); store_part<1>(accB, pout); store_part<2>(accB, pout); store_part<3>(accB, pout);
        __syncwarp();
        if (lane == 0) mbar_arrive(bar0 + B_FFN * 8);
        PROF(10); PROFWT(58);
        PROFT(49);

        mbar_wait(bar0 + B_QRDY * 8, 0);
        const uint32_t slow = __any_sync(~0u, *slow_flag != 0);
        const uint64_t kd0 = mk_desc(zero, sb + SM_KV, 0, KV_GROUP_BYTES, 0);
        const uint64_t vd0 = mk_desc(zero, sb + SM_KV + 256, KV_GROUP_BYTES, 128, 0);
        const uint64_t qd0 = mk_desc(zero, sb + SM_Q + wg * 4096, 128, 512, 0);
        const uint32_t kvbar = bar0 + B_KV * 8;
        float o[12];
#pragma unroll
        for (int i = 0; i < 12; i++) o[i] = 0.f;
        PROF(16);
        PROFT(50);
        if (!slow) {
            const uint32_t one2 = 0x3F803F80u + (uint32_t)zero;
            float s0[64], s1[64];
            uint32_t p0[32], p1[32];
            mbar_wait(kvbar, 0);
            reg_fence(o);
            wg_fence();
            issue_qk<0>(s0, qd0, kd0);
            wg_commit();
            wg_commit();
            uint64_t qd = qd0;
            const uint32_t fre = (tid == wg * 128) ? bar0 + B_FREE * 8 - 8 : 0;
#pragma unroll 1
            for (int pass = 0; pass < 4; pass++) {
                uint64_t vd = vd0, kd = kd0;
                uint32_t bn = kvbar + 8;
#pragma unroll 1
                for (int it = 0; it < 8; it++) {
                    mbar_wait(bn, 0);
                    if (it == 0 && pass != 0) {
                        wg_wait<0>();
                        reg_fence(o);
                        store_o(o, quarter * 8 + pass * 2 - 2 + wg, head, wq, lane);
                        reg_fence(o);
                    }
                    wg_wait<1>();
                    reg_fence(s0);
                    wg_fence();
                    issue_qk<KV_TILE>(s1, qd, kd);
                    wg_commit();
                    if (pass == 3 && it > 0 && fre) mbar_arrive(fre + it * 8);
                    softmax_pv<0>(s0, p0, o, vd, one2);
                    kd += 2 * KV_TILE; bn += 8;
                    if (it == 7) { kd = kd0; bn = kvbar; qd += 512; }
                    mbar_wait(bn, 0);
                    wg_wait<1>();
                    reg_fence(s1);
                    wg_fence();
                    issue_qk<0>(s0, qd, kd);
                    wg_commit();
                    softmax_pv<KV_TILE>(s1, p1, o, vd, one2);
                    vd += 2 * KV_TILE; bn += 8;
                }
                if (pass == 0) PROF(17);
            }
            wg_wait<0>();
            reg_fence(o);
            reg_fence(s0);
            reg_fence(s1);
            store_o(o, quarter * 8 + 6 + wg, head, wq, lane);
        } else {
#pragma unroll 1
            for (int pass = 0; pass < 4; pass++) {
                float m0 = -INFINITY, m1 = -INFINITY;
                float s[64];
                uint32_t p[32];
#pragma unroll 1
                for (int t = 0; t < 16; t++) {
                    mbar_wait(kvbar + t * 8, 0);
                    wg_fence();
                    issue_qk<0>(s, qd0 + pass * 512, kd0 + t * KV_TILE);
                    wg_commit();
                    wg_wait<0>();
                    reg_fence(s);
                    float a0 = m0, a1 = m1;
#pragma unroll
                    for (int k = 0; k < 16; k++) {
                        if ((POLY_MASK >> (k & 7)) & 1) {
#pragma unroll
                            for (int i = 0; i < 4; i++) s[k * 4 + i] *= 0.5f;
                        }
                        a0 = fmaxf(a0, fmaxf(s[k * 4 + 0], s[k * 4 + 1]));
                        a1 = fmaxf(a1, fmaxf(s[k * 4 + 2], s[k * 4 + 3]));
                    }
                    a0 = fmaxf(a0, __shfl_xor_sync(~0u, a0, 1)); a1 = fmaxf(a1, __shfl_xor_sync(~0u, a1, 1));
                    a0 = fmaxf(a0, __shfl_xor_sync(~0u, a0, 2)); a1 = fmaxf(a1, __shfl_xor_sync(~0u, a1, 2));
                    const float r0 = ex2(m0 - a0), r1 = ex2(m1 - a1);
                    m0 = a0; m1 = a1;
#pragma unroll
                    for (int i = 0; i < 3; i++) { o[i * 4] *= r0; o[i * 4 + 1] *= r0; o[i * 4 + 2] *= r1; o[i * 4 + 3] *= r1; }
#pragma unroll
                    for (int k = 0; k < 16; k++) {
                        p[k * 2 + 0] = pack_bf16(ex2(s[k * 4 + 0] - m0), ex2(s[k * 4 + 1] - m0));
                        p[k * 2 + 1] = pack_bf16(ex2(s[k * 4 + 2] - m1), ex2(s[k * 4 + 3] - m1));
                    }
                    reg_fence(p);
                    reg_fence(o);
                    wg_fence();
                    issue_pv<0>(o, p, vd0 + t * KV_TILE);
                    wg_commit();
                    wg_wait<0>();
                    reg_fence(o);
                }
                store_o(o, quarter * 8 + pass * 2 + wg, head, wq, lane);
            }
            if (tid == wg * 128)
                for (int i = 0; i < 7; i++) mbar_arrive(bar0 + (B_FREE + i) * 8);
        }
        PROF(18);
        PROFT(51);

        const int t128 = tid & 127;
        named_bar_sync(1 + wg, 128);
        if (t128 == 0) flag_signal(&g_flags.o_done[quarter]);
        const size_t orow = (size_t)(rt * 64 + wq * 16 + g + wg * 8) * DM + ct * 144 + q * 2;
        float bs[36];
        {
            uint32_t xv[18], bv[18];
            uint2 fv[9];
#pragma unroll
            for (int i = 0; i < 18; i++) {
                xv[i] = __ldg(reinterpret_cast<const uint32_t*>(x + orow) + i * 4);
                bv[i] = __ldg(reinterpret_cast<const uint32_t*>(b2 + ct * 144 + q * 2) + i * 4);
            }
            mbar_wait(bar0 + B_BASE * 8, 0);
#pragma unroll
            for (int i = 0; i < 9; i++) fv[i] = __ldcg(g_ffn + blockIdx.x * 2304 + (wg * 9 + i) * 128 + t128);
#pragma unroll
            for (int i = 0; i < 18; i++) {
                const uint32_t f = (i & 1) ? fv[i >> 1].y : fv[i >> 1].x;
                bs[i * 2] = fmaf(bf_lo(f), 0.5f, bf_lo(xv[i]) + bf_lo(bv[i]));
                bs[i * 2 + 1] = fmaf(bf_hi(f), 0.5f, bf_hi(xv[i]) + bf_hi(bv[i]));
            }
        }
        if (t128 == 0) flag_wait(&g_flags.o_done[quarter], 64, 0);
        named_bar_sync(1 + wg, 128);
        if (t128 == 0) mbar_arrive(bar0 + B_DONE * 8);
        PROF(19);
        uint4 af[18];
        {
            const uint4* ap = reinterpret_cast<const uint4*>(g_O) + (rt * 36 + wg * 18) * 128 + t128;
#pragma unroll
            for (int k = 0; k < 18; k++) af[k] = __ldcg(ap + k * 128);
        }
        float acc[72];
        const uint64_t wd0 = mk_desc(zero, sb, 2304, 128, 0), wd1 = wd0 + wg * ((18 * 4608) >> 4);
#pragma unroll 1
        for (int i = 0; i < 5; i++) mbar_wait(bar0 + (B_WO + wg * 4 + i) * 8, 0);
        wg_fence();
        static_for<0, 18>([&](auto kc) {
            constexpr int k = decltype(kc)::value;
            if constexpr (k < 8) {
                constexpr int o0 = (sm_wo(k >> 2) + (k & 3) * 4608) >> 4, o1 = (SM_KV + (k + 10) * 4608) >> 4;
                wgmma_rs_n144<1, 0>(acc, af[k].x, af[k].y, af[k].z, af[k].w, wd0 + (wg ? o1 : o0), k != 0);
            } else {
                wgmma_rs_n144<1, (SM_KV + (k - 8) * 4608) / 16>(acc, af[k].x, af[k].y, af[k].z, af[k].w, wd1, 1);
            }
        });
        wg_commit();
        wg_wait<0>();
        reg_fence(acc);
        PROF(20);
        {
            float4* ex = reinterpret_cast<float4*>(smem + SM_EXCH) + t128;
#pragma unroll
            for (int i = 0; i < 9; i++) {
                const float4 lo = make_float4(acc[i * 8], acc[i * 8 + 1], acc[i * 8 + 4], acc[i * 8 + 5]);
                const float4 hi = make_float4(acc[i * 8 + 2], acc[i * 8 + 3], acc[i * 8 + 6], acc[i * 8 + 7]);
                ex[(wg * 9 + i) * 128] = wg ? lo : hi;
                const float4 own = wg ? hi : lo;
                bs[i * 4] += own.x; bs[i * 4 + 1] += own.y; bs[i * 4 + 2] += own.z; bs[i * 4 + 3] += own.w;
            }
            named_bar_sync(5, 256);
            uint32_t* op = reinterpret_cast<uint32_t*>(out + orow);
#pragma unroll
            for (int i = 0; i < 9; i++) {
                const float4 v = ex[((wg ^ 1) * 9 + i) * 128];
                op[i * 8] = pack_bf16(bs[i * 4] + v.x, bs[i * 4 + 1] + v.y);
                op[i * 8 + 4] = pack_bf16(bs[i * 4 + 2] + v.z, bs[i * 4 + 3] + v.w);
            }
        }
        PROF(21);
        PROFT(52);
    } else {
        reg_dealloc<24>();
        if (warp == 8 && lane == 0) {
            prefetch_tmap(&tmQ3); prefetch_tmap(&tmQ1); prefetch_tmap(&tm1); prefetch_tmap(&tm2);
            #pragma unroll 1
            for (int i = 0; i < 9; i++) { mbar_init(full0 + i * 8, 1); mbar_init(empty0 + i * 8, 4); mbar_init(bar0 + (B_WO + i) * 8, 1); }
            mbar_init(bar0 + B_BASE * 8, 3); mbar_init(bar0 + B_XNDEAD * 8, 2); mbar_init(bar0 + B_QRDY * 8, 3); mbar_init(bar0 + B_FFN * 8, 8); mbar_init(bar0 + B_DONE * 8, 2);
#pragma unroll 1
            for (int i = 0; i < 16; i++) { mbar_init(bar0 + (B_KV + i) * 8, 1); mbar_init(bar0 + (B_FREE + (i & 7)) * 8, 2); if (i < 6) mbar_init(bar0 + (B_RED + i) * 8, 1); }
            *slow_flag = 0;
            fence_barrier_init();
        }
        __syncwarp();
        cluster_arrive();
        cluster_wait();
        const uint8_t* kvsrc = g_QKV + (size_t)head * KV_HEAD_BYTES;
        if (warp == 8) {
            if (lane == 0) {
                int st = 0, u = rank, tile = -4;
                int es = 5;
                uint32_t eph = 1;
#pragma unroll 1
                for (int n = 0; n < 99; n++) {
                    mbar_wait(empty0 + es * 8, eph);
                    const uint32_t fb = full0 + st * 8, dst = sb + K1_OFF_RING + u * 8192;
                    mbar_expect(fb, 16384);
                    if (tile < 0) {
                        tma3d_mc(dst, &tmQ3, j * 216, n * 32 + rank * 16, 0, fb, 3);
                        tma2d_mc(dst + 6144, &tmQ1, j * 216 + 192, n * 32 + rank * 16, fb, 3);
                    } else if (tile < 9) {
                        tma2d_mc(dst, &tm1, j * 576 + tile * 64, u * 64, fb, 3);
                    } else {
                        tma2d_mc(dst, &tm2, (tile - 9) * 64, j * 576 + u * 64, fb, 3);
                    }
                    u += 2;
                    if (u >= 9) { u -= 9; tile++; }
                    if (++st == 9) st = 0;
                    if (++es == 9) { es = 0; eph ^= 1; }
                }
                mbar_wait(empty0 + 8 * 8, 0);
                mbar_wait(bar0 + B_QRDY * 8, 0);
                asm volatile("fence.proxy.async;" ::: "memory");
#pragma unroll 1
                for (int i = 11; i < NCHUNK; i++) {
                    mbar_expect(bar0 + (B_KV + i) * 8, CHUNK_BYTES);
                    bulk_load(sb + SM_KV + i * CHUNK_BYTES, kvsrc + i * CHUNK_BYTES, CHUNK_BYTES, bar0 + (B_KV + i) * 8);
                }
#pragma unroll 1
                for (int i = 0; i < 9; i++) {
                    if (i == 0) mbar_wait_sleep(bar0 + B_BASE * 8, 500);
                    if (i > 0) {
                        const int f = i == 1 ? 0 : ((i - 1) * 9 + 4) / 10;
                        mbar_wait_sleep(bar0 + (B_FREE + f) * 8, i == 1 ? 500 : 50);
                    }
                    mbar_expect(bar0 + (B_WO + i) * 8, WO_PIECE);
                    bulk_load(sb + (i == 0 ? sm_wo(0) : (i == 1 ? sm_wo(1) : SM_KV + (i - 2) * WO_PIECE)), g_Wo + ct * WO_TILE_BYTES + i * WO_PIECE, WO_PIECE,
                              bar0 + (B_WO + i) * 8);
                }
            }
        } else {
            const int ht = tid - 288;
            if (ht == 64) prefetch_l2(wqkv + blockIdx.x * (DM * 3 * DM / 128), DM * 3 * DM / 64);
            if (ht < 72) {
                const uint4 v = __ldg(reinterpret_cast<const uint4*>(b1 + j * 576) + ht);
                uint32_t* sbias = reinterpret_cast<uint32_t*>(smem + K1_OFF_BIAS) + (ht >> 3) * 32 + (ht & 7);
                sbias[0] = v.x; sbias[8] = v.y; sbias[16] = v.z; sbias[24] = v.w;
            }
            asm volatile("bar.arrive 4, 352;" ::: "memory");
            PROFH(37);
#pragma unroll 1
            for (int i = ht; i < 512; i += 96) {
                const int key = i & 127;
                uint8_t* p = g_QKV + (size_t)(j * 4 + (i >> 7)) * KV_HEAD_BYTES + (rb * 16 + (key >> 3)) * KV_GROUP_BYTES + 512 + (key & 7) * 16;
                *reinterpret_cast<uint32_t*>(p + 4) = ((POLY_MASK >> ((key >> 3) & 7)) & 1) ? 0x3F804000u : 0x00003F80u;
                *reinterpret_cast<uint32_t*>(p + 12) = 0x00003F80u;
            }
            if (ht == 32) prefetch_l2(w1 + blockIdx.x * (DM * FF / 128), DM * FF / 64);
#pragma unroll 2
            for (int i = blockIdx.x * 324 + ht; i < blockIdx.x * 324 + 324; i += 96) {
                const int k = i / 72, nc = i - k * 72, c4 = nc / 18;
                *reinterpret_cast<uint4*>(g_Wo + c4 * WO_TILE_BYTES + (k >> 3) * 2304 + (nc - c4 * 18) * 128 + (k & 7) * 16) =
                    __ldg(reinterpret_cast<const uint4*>(wo) + i);
            }
            PROFH(38);
            named_bar_sync(3, 352);
            if (ht == 32) prefetch_l2(w2 + blockIdx.x * (DM * FF / 128), DM * FF / 64);
            if (ht == 0) {
                flag_signal(&g_flags.qkv_stored[rb]);
                flag_wait(&g_flags.qkv_stored[rb], 8, 200);
            }
            named_bar_sync(7, 96);
            PROFH(39);
#pragma unroll 1
            for (int i = warp - 9; i < 16; i += 3) {
                const int hd = j * 4 + (i >> 2), key = (i & 3) * 32 + lane;
                const uint8_t* p = g_QKV + (size_t)hd * KV_HEAD_BYTES + (rb * 16 + (key >> 3)) * KV_GROUP_BYTES + (key & 7) * 16;
                const uint4 a = __ldcg(reinterpret_cast<const uint4*>(p)), b = __ldcg(reinterpret_cast<const uint4*>(p + 128));
                float n = sumsq2(__ldcg(reinterpret_cast<const uint32_t*>(p + 512))) + sumsq8(a) + sumsq8(b);
                if ((POLY_MASK >> ((key >> 3) & 7)) & 1) n *= 0.25f;
#pragma unroll
                for (int o = 16; o; o >>= 1) n = fmaxf(n, __shfl_xor_sync(~0u, n, o));
                if (lane == 0) g_kmax[hd * 64 + rb * 4 + (i & 3)] = n;
            }
            named_bar_sync(7, 96);
            PROFH(40);
            if (ht == 0) {
                flag_signal(&g_flags.kv_ready);
                flag_wait(&g_flags.kv_ready, 128, 300);
                mbar_wait_sleep(bar0 + B_XNDEAD * 8, 300);
            }
            named_bar_sync(7, 96);
            PROFH(41);
            float kmax2;
            {
                const float2 v = __ldcg(reinterpret_cast<const float2*>(g_kmax + head * 64 + lane * 2));
                kmax2 = fmaxf(v.x, v.y);
#pragma unroll
                for (int o = 16; o; o >>= 1) kmax2 = fmaxf(kmax2, __shfl_xor_sync(~0u, kmax2, o));
            }
            asm volatile("fence.proxy.async;" ::: "memory");
            int chunk = warp - 9;
#pragma unroll 1
            for (int r = ht; r < 512; r += 96) {
                if (lane == 0 && chunk < 11) {
                    mbar_expect(bar0 + (B_KV + chunk) * 8, CHUNK_BYTES);
                    bulk_load(sb + SM_KV + chunk * CHUNK_BYTES, kvsrc + chunk * CHUNK_BYTES, CHUNK_BYTES, bar0 + (B_KV + chunk) * 8);
                }
                chunk += 3;
                const uint8_t* p = kvsrc + Q_OFFSET + (quarter * 64 + (r >> 3)) * KV_GROUP_BYTES + (r & 7) * 16;
                const uint4 a = __ldcg(reinterpret_cast<const uint4*>(p)), b = __ldcg(reinterpret_cast<const uint4*>(p + 128));
                const uint32_t e = __ldcg(reinterpret_cast<const uint32_t*>(p + 256));
                const float cc = sqrtf((sumsq2(e) + sumsq8(a) + sumsq8(b)) * kmax2) * 1.02f;
                if (!(cc <= 58.f)) *slow_flag = 1;
                uint4* dst = reinterpret_cast<uint4*>(smem + SM_Q + (r >> 3) * 512 + (r & 7) * 16);
                dst[0] = a;
                dst[8] = b;
                dst[16] = make_uint4(e, pack_bf16(-cc, 768.f), 0u, 0u);
                dst[24] = make_uint4(0u, POLY_MODE ? 0xBFFF0000u : 0xC0000000u, 0u, 0u);
            }
            named_bar_sync(7, 96);
            if (*slow_flag) {
#pragma unroll 1
                for (int r = ht; r < 512; r += 96) {
                    uint32_t* dst = reinterpret_cast<uint32_t*>(smem + SM_Q + (r >> 3) * 512 + (r & 7) * 16);
                    dst[65] = 0u;
                    dst[97] = 0u;
                }
            }
            fence_proxy_async();
            __syncwarp();
            if (lane == 0) mbar_arrive(bar0 + B_QRDY * 8);
            PROFH(42);
            if (ht == 0) {
                mbar_wait_sleep(bar0 + B_FFN * 8, 300);
                flag_signal(&g_flags.ffn_done[rb]);
                flag_wait(&g_flags.ffn_done[rt >> 1], 8, 300);
            }
            named_bar_sync(7, 96);
            {
                const int w3 = warp - 9;
                const uint32_t rbar = bar0 + (B_RED + w3 * 2) * 8, rbuf = SM_RED + w3 * 8192;
                const int u0 = ((rt >> 1) * 36 + ct * 9) * 256 + (rt & 1) * 128;
                mbar_wait_sleep(bar0 + (B_KV + 15) * 8, 500);
                asm volatile("fence.proxy.async;" ::: "memory");
#pragma unroll 1
                for (int i = -2; i < 12; i++) {
                    if (i >= 0) {
                        __nanosleep(400);
                        mbar_wait(rbar + (i & 1) * 8, (i >> 1) & 1);
                        const uint4* sp = reinterpret_cast<const uint4*>(smem + rbuf + (i & 1) * 4096) + lane;
                        const uint4 v = hadd8_bf16(hadd8_bf16(hadd8_bf16(sp[0], sp[32]), hadd8_bf16(sp[64], sp[96])),
                                                   hadd8_bf16(hadd8_bf16(sp[128], sp[160]), hadd8_bf16(sp[192], sp[224])));
                        uint2* fp = g_ffn + blockIdx.x * 2304 + (i * 3 + w3) * 32 + lane;
                        fp[0] = make_uint2(v.x, v.z);
                        fp[1152] = make_uint2(v.y, v.w);
                    }
                    __syncwarp();
                    if (lane == 0 && i < 10) {
                        const int bx = (i + 2) * 3 + w3;
                        mbar_expect(rbar + (i & 1) * 8, 4096);
                        tma2d(sb + rbuf + (i & 1) * 4096, &tmP, (u0 + (bx >> 2) * 256 + (bx & 3) * 32) * 2, 0, rbar + (i & 1) * 8);
                    }
                }
            }
            __syncwarp();
            if (lane == 0) mbar_arrive(bar0 + B_BASE * 8);
            PROFH(43);
            if (ht == 0) {
                mbar_wait_sleep(bar0 + B_DONE * 8, 500);
                if (atomicAdd(&g_flags.exited, 1u) == gridDim.x - 1) {
                    unsigned int* f = reinterpret_cast<unsigned int*>(&g_flags);
#pragma unroll 1
                    for (int i = 0; i < (int)(sizeof(Flags) / 4); i++) f[i] = 0;
                }
            }
        }
    }
}

typedef CUresult (*EncodeFn)(CUtensorMap*, CUtensorMapDataType, cuuint32_t, void*, const cuuint64_t*, const cuuint64_t*, const cuuint32_t*,
                             const cuuint32_t*, CUtensorMapInterleave, CUtensorMapSwizzle, CUtensorMapL2promotion, CUtensorMapFloatOOBfill);

void make_map(EncodeFn fn, CUtensorMap* m, const void* base, int rank, const cuuint64_t* dims, const cuuint64_t* strides, const cuuint32_t* box) {
    cuuint32_t es[4] = {1, 1, 1, 1};
    fn(m, CU_TENSOR_MAP_DATA_TYPE_BFLOAT16, rank, const_cast<void*>(base), dims, strides, box, es, CU_TENSOR_MAP_INTERLEAVE_NONE,
       CU_TENSOR_MAP_SWIZZLE_128B, CU_TENSOR_MAP_L2_PROMOTION_L2_256B, CU_TENSOR_MAP_FLOAT_OOB_FILL_NONE);
}

}

extern "C" void kernel_launch(void* const* d_in, const int* in_sizes, int n_in, void* d_out, int out_size) {
    const __nv_bfloat16* x = (const __nv_bfloat16*)d_in[0];
    const __nv_bfloat16* wqkv = (const __nv_bfloat16*)d_in[1];
    const __nv_bfloat16* wo = (const __nv_bfloat16*)d_in[2];
    const __nv_bfloat16* w1 = (const __nv_bfloat16*)d_in[4];
    const __nv_bfloat16* b1 = (const __nv_bfloat16*)d_in[5];
    const __nv_bfloat16* w2 = (const __nv_bfloat16*)d_in[6];
    const __nv_bfloat16* b2 = (const __nv_bfloat16*)d_in[7];
    __nv_bfloat16* out = (__nv_bfloat16*)d_out;

    EncodeFn fn = nullptr;
    cudaDriverEntryPointQueryResult qr;
    cudaGetDriverEntryPoint("cuTensorMapEncodeTiled", (void**)&fn, cudaEnableDefault, &qr);
    CUtensorMap tmX, tmQ3, tmQ1, tm1, tm2, tmP;
    {
        void* gp = nullptr;
        cudaGetSymbolAddress(&gp, g_part);
        cuuint64_t d[2] = {SLAB * 2, 8}, s[1] = {SLAB * 16};
        cuuint32_t b[2] = {64, 8}, es[2] = {1, 1};
        fn(&tmP, CU_TENSOR_MAP_DATA_TYPE_INT64, 2, gp, d, s, b, es, CU_TENSOR_MAP_INTERLEAVE_NONE, CU_TENSOR_MAP_SWIZZLE_NONE,
           CU_TENSOR_MAP_L2_PROMOTION_NONE, CU_TENSOR_MAP_FLOAT_OOB_FILL_NONE);
    }
    {
        cuuint64_t d[4] = {64, 8, 9, SEQ / 8}, s[3] = {DM * 2, 128, DM * 2 * 8};
        cuuint32_t b[4] = {64, 8, 3, 2};
        make_map(fn, &tmX, x, 4, d, s, b);
    }
    {
        cuuint64_t d[3] = {3 * DM, DM, 3}, s[2] = {3 * DM * 2, 128};
        cuuint32_t b[3] = {64, 16, 3};
        make_map(fn, &tmQ3, wqkv, 3, d, s, b);
        make_map(fn, &tmQ1, wqkv, 2, d, s, b);
    }
    {
        cuuint64_t d[2] = {FF, DM}, s[1] = {FF * 2};
        cuuint32_t b[2] = {64, 64};
        make_map(fn, &tm1, w1, 2, d, s, b);
        cuuint64_t d2[2] = {DM, FF}, s2[1] = {DM * 2};
        make_map(fn, &tm2, w2, 2, d2, s2, b);
    }
    cudaFuncSetAttribute(fused_kernel, cudaFuncAttributeMaxDynamicSharedMemorySize, K1_SMEM);
    fused_kernel<<<128, 384, K1_SMEM, cudaStreamPerThread>>>(tmX, tmQ3, tmQ1, tm1, tm2, tmP, b1, wqkv, w1, w2, wo, x, b2, out, 0ull);
}
```

```cpp
#include <cuda_runtime.h>
#include <cuda_bf16.h>
#include <cuda.h>
#include <stdint.h>

#define PROF(i) do { } while (0)
#define PROFT(i) do { } while (0)
#define PROFH(i) do { } while (0)
#define PROFWT(i) do { } while (0)
#define PROF_WG 0

namespace {

constexpr int SEQ = 2048, DM = 576, FF = 4608, NH = 32, DH = 18;

constexpr int KV_GROUP_BYTES = 5 * 128;
constexpr int KV_HEAD_BYTES = (SEQ / 8) * KV_GROUP_BYTES;
constexpr int Q_OFFSET = NH * KV_HEAD_BYTES;
#define POLY_MASK 0xB6B6
__device__ __align__(1024) uint8_t g_QKV[2 * NH * KV_HEAD_BYTES];
__device__ __align__(1024) float g_kmax[NH * 64];
constexpr int SLAB = 16 * 36 * 256;
__device__ __align__(1024) uint4 g_part[8 * SLAB];
__device__ __align__(1024) uint2 g_ffn[128 * 18 * 128];
__device__ __align__(1024) uint32_t g_O[SEQ * DM / 2];
struct Flags {
    unsigned int qkv_stored[16];
    unsigned int ffn_done[16];
    unsigned int o_done[32][2];
    unsigned int kv_ready;
    unsigned int exited;
};
__device__ Flags g_flags;
constexpr int WO_TILE_BYTES = DM * 144 * 2;
__device__ __align__(1024) uint8_t g_Wo[4 * WO_TILE_BYTES];

__device__ __forceinline__ uint32_t s2u(const void* p) { return (uint32_t)__cvta_generic_to_shared(p); }
__device__ __forceinline__ void mbar_init(uint32_t b, int c) { asm volatile("mbarrier.init.shared::cta.b64 [%0], %1;" ::"r"(b), "r"(c) : "memory"); }
__device__ __forceinline__ void mbar_expect(uint32_t b, uint32_t bytes) {
    asm volatile("mbarrier.arrive.expect_tx.shared::cta.b64 _, [%0], %1;" ::"r"(b), "r"(bytes) : "memory");
}
__device__ __forceinline__ void mbar_wait(uint32_t b, uint32_t parity) {
    asm volatile(
        "{\n.reg .pred p;\n.reg .u32 c;\n"
        "mov.u32 c, 0;\n"
        "LOOP:\n"
        "mbarrier.try_wait.parity.shared::cta.b64 p, [%0], %1;\n"
        "@p bra DONE;\n"
        "add.u32 c, c, 1;\n"
        "setp.lt.u32 p, c, 4194304;\n"
        "@p bra LOOP;\n"
        "trap;\n"
        "DONE:\n}\n" ::"r"(b), "r"(parity) : "memory");
}
__device__ __forceinline__ void fence_barrier_init() { asm volatile("fence.mbarrier_init.release.cluster;" ::: "memory"); }
__device__ __forceinline__ void fence_proxy_async() { asm volatile("fence.proxy.async.shared::cta;" ::: "memory"); }
__device__ __forceinline__ void cluster_arrive() { asm volatile("barrier.cluster.arrive.relaxed.aligned;" ::: "memory"); }
__device__ __forceinline__ void cluster_wait() { asm volatile("barrier.cluster.wait.aligned;" ::: "memory"); }
__device__ __forceinline__ void named_bar_sync(int id, int n) { asm volatile("bar.sync %0, %1;" ::"r"(id), "r"(n) : "memory"); }

__device__ __forceinline__ void tma3d_mc(uint32_t dst, const CUtensorMap* tm, int c0, int c1, int c2, uint32_t bar, uint16_t mask) {
    asm volatile("cp.async.bulk.tensor.3d.shared::cluster.global.mbarrier::complete_tx::bytes.multicast::cluster [%0], [%1, {%3, %4, %5}], [%2], %6;"
                 ::"r"(dst), "l"(tm), "r"(bar), "r"(c0), "r"(c1), "r"(c2), "h"(mask) : "memory");
}
__device__ __forceinline__ void tma2d_mc(uint32_t dst, const CUtensorMap* tm, int c0, int c1, uint32_t bar, uint16_t mask) {
    asm volatile("cp.async.bulk.tensor.2d.shared::cluster.global.mbarrier::complete_tx::bytes.multicast::cluster [%0], [%1, {%3, %4}], [%2], %5;"
                 ::"r"(dst), "l"(tm), "r"(bar), "r"(c0), "r"(c1), "h"(mask) : "memory");
}
__device__ __forceinline__ void tma4d(uint32_t dst, const CUtensorMap* tm, int c0, int c1, int c2, int c3, uint32_t bar) {
    asm volatile("cp.async.bulk.tensor.4d.shared::cluster.global.mbarrier::complete_tx::bytes [%0], [%1, {%3, %4, %5, %6}], [%2];"
                 ::"r"(dst), "l"(tm), "r"(bar), "r"(c0), "r"(c1), "r"(c2), "r"(c3) : "memory");
}
__device__ __forceinline__ void tma2d(uint32_t dst, const CUtensorMap* tm, int c0, int c1, uint32_t bar) {
    asm volatile("cp.async.bulk.tensor.2d.shared::cluster.global.mbarrier::complete_tx::bytes [%0], [%1, {%3, %4}], [%2];"
                 ::"r"(dst), "l"(tm), "r"(bar), "r"(c0), "r"(c1) : "memory");
}
__device__ __forceinline__ void bulk_load(uint32_t dst, const void* src, uint32_t bytes, uint32_t bar) {
    asm volatile("cp.async.bulk.shared::cluster.global.mbarrier::complete_tx::bytes [%0], [%1], %2, [%3];"
                 ::"r"(dst), "l"(src), "r"(bytes), "r"(bar) : "memory");
}
__device__ __forceinline__ void prefetch_l2(const void* p, uint32_t bytes) {
    asm volatile("cp.async.bulk.prefetch.L2.global [%0], %1;" ::"l"(p), "r"(bytes) : "memory");
}
__device__ __forceinline__ void prefetch_tmap(const CUtensorMap* tm) { asm volatile("prefetch.tensormap [%0];" ::"l"(tm) : "memory"); }

__device__ __forceinline__ void wg_fence() { asm volatile("wgmma.fence.sync.aligned;" ::: "memory"); }
__device__ __forceinline__ void wg_commit() { asm volatile("wgmma.commit_group.sync.aligned;" ::: "memory"); }
template <int N> __device__ __forceinline__ void wg_wait() { asm volatile("wgmma.wait_group.sync.aligned %0;" ::"n"(N) : "memory"); }
template <int N> __device__ __forceinline__ void reg_fence(float (&d)[N]) {
#pragma unroll
    for (int i = 0; i < N; i++) asm volatile("" : "+f"(d[i])::"memory");
}
template <int N> __device__ __forceinline__ void reg_fence(uint32_t (&d)[N]) {
#pragma unroll
    for (int i = 0; i < N; i++) asm volatile("" : "+r"(d[i])::"memory");
}
template <int R> __device__ __forceinline__ void reg_alloc() { asm volatile("setmaxnreg.inc.sync.aligned.u32 %0;" ::"n"(R)); }
template <int R> __device__ __forceinline__ void reg_dealloc() { asm volatile("setmaxnreg.dec.sync.aligned.u32 %0;" ::"n"(R)); }

__device__ __forceinline__ uint64_t mk_desc(uint64_t z, uint32_t addr, uint32_t lbo, uint32_t sbo, uint32_t swz) {
    return z + ((uint64_t)(((addr & 0x3FFFF) >> 4) | ((lbo >> 4) << 16)) | ((uint64_t)((sbo >> 4) | (swz << 30)) << 32));
}
__device__ __forceinline__ uint32_t pack_bf16(float lo, float hi) {
    uint32_t r;
    asm("cvt.rn.bf16x2.f32 %0, %1, %2;" : "=r"(r) : "f"(hi), "f"(lo));
    return r;
}
__device__ __forceinline__ float bf_lo(uint32_t w) { return __uint_as_float(w << 16); }
__device__ __forceinline__ float bf_hi(uint32_t w) { return __uint_as_float(w & 0xFFFF0000u); }
__device__ __forceinline__ float ex2(float x) {
    float r;
    asm("ex2.approx.ftz.f32 %0, %1;" : "=f"(r) : "f"(x));
    return r;
}
__device__ __forceinline__ float tanh_fast(float x) {
    float r;
    asm("tanh.approx.f32 %0, %1;" : "=f"(r) : "f"(x));
    return r;
}
__device__ __forceinline__ uint32_t hfma2_bf16(uint32_t a, uint32_t b, uint32_t c) {
    uint32_t r;
    asm("fma.rn.bf16x2 %0, %1, %2, %3;" : "=r"(r) : "r"(a), "r"(b), "r"(c));
    return r;
}
__device__ __forceinline__ uint32_t hadd2_bf16(uint32_t a, uint32_t b) {
    uint32_t r;
    asm("add.rn.bf16x2 %0, %1, %2;" : "=r"(r) : "r"(a), "r"(b));
    return r;
}
__device__ __forceinline__ void ldsm4(uint32_t (&a)[4], uint32_t addr) {
    asm volatile("ldmatrix.sync.aligned.m8n8.x4.shared.b16 {%0, %1, %2, %3}, [%4];" : "=r"(a[0]), "=r"(a[1]), "=r"(a[2]), "=r"(a[3]) : "r"(addr) : "memory");
}
__device__ __forceinline__ void stsm4(uint32_t addr, const uint32_t (&a)[4]) {
    asm volatile("stmatrix.sync.aligned.m8n8.x4.shared.b16 [%0], {%1, %2, %3, %4};" ::"r"(addr), "r"(a[0]), "r"(a[1]), "r"(a[2]), "r"(a[3]) : "memory");
}
__device__ __forceinline__ void mma16816(float (&c)[4], const uint32_t (&a)[4], uint32_t b0, uint32_t b1) {
    asm("mma.sync.aligned.m16n8k16.row.col.f32.bf16.bf16.f32 {%0, %1, %2, %3}, {%4, %5, %6, %7}, {%8, %9}, {%0, %1, %2, %3};"
        : "+f"(c[0]), "+f"(c[1]), "+f"(c[2]), "+f"(c[3]) : "r"(a[0]), "r"(a[1]), "r"(a[2]), "r"(a[3]), "r"(b0), "r"(b1));
}
__device__ __forceinline__ float gelu2(float u) {
    const float w = fmaf(u * u, 0.0356774081f, 0.7978845608f);
    return fmaf(u, tanh_fast(u * w), u);
}

template<int TB, int AOFF, int BOFF> __device__ __forceinline__ void wgmma_ss_n216(float (&d)[108], uint64_t da, uint64_t db, int sd) {
    asm volatile("{\n.reg .pred p;\n.reg .b64 ta, tb;\nsetp.ne.b32 p, %110, 0;\nadd.s64 ta, %108, %112;\nadd.s64 tb, %109, %113;\n"
      "wgmma.mma_async.sync.aligned.m64n216k16.f32.bf16.bf16 {%0, %1, %2, %3, %4, %5, %6, %7, %8, %9, %10, %11, %12, %13, %14, %15, %16, %17, %18, %19, %20, %21, %22, %23, %24, %25, %26, %27, %28, %29, %30, %31, %32, %33, %34, %35, %36, %37, %38, %39, %40, %41, %42, %43, %44, %45, %46, %47, %48, %49, %50, %51, %52, %53, %54, %55, %56, %57, %58, %59, %60, %61, %62, %63, %64, %65, %66, %67, %68, %69, %70, %71, %72, %73, %74, %75, %76, %77, %78, %79, %80, %81, %82, %83, %84, %85, %86, %87, %88, %89, %90, %91, %92, %93, %94, %95, %96, %97, %98, %99, %100, %101, %102, %103, %104, %105, %106, %107}, ta, tb, p, 1, 1, 0, %111;\n}\n"
      : "+f"(d[0]), "+f"(d[1]), "+f"(d[2]), "+f"(d[3]), "+f"(d[4]), "+f"(d[5]), "+f"(d[6]), "+f"(d[7]), "+f"(d[8]), "+f"(d[9]), "+f"(d[10]), "+f"(d[11]), "+f"(d[12]), "+f"(d[13]), "+f"(d[14]), "+f"(d[15]), "+f"(d[16]), "+f"(d[17]), "+f"(d[18]), "+f"(d[19]), "+f"(d[20]), "+f"(d[21]), "+f"(d[22]), "+f"(d[23]), "+f"(d[24]), "+f"(d[25]), "+f"(d[26]), "+f"(d[27]), "+f"(d[28]), "+f"(d[29]), "+f"(d[30]), "+f"(d[31]), "+f"(d[32]), "+f"(d[33]), "+f"(d[34]), "+f"(d[35]), "+f"(d[36]), "+f"(d[37]), "+f"(d[38]), "+f"(d[39]), "+f"(d[40]), "+f"(d[41]), "+f"(d[42]), "+f"(d[43]), "+f"(d[44]), "+f"(d[45]), "+f"(d[46]), "+f"(d[47]), "+f"(d[48]), "+f"(d[49]), "+f"(d[50]), "+f"(d[51]), "+f"(d[52]), "+f"(d[53]), "+f"(d[54]), "+f"(d[55]), "+f"(d[56]), "+f"(d[57]), "+f"(d[58]), "+f"(d[59]), "+f"(d[60]), "+f"(d[61]), "+f"(d[62]), "+f"(d[63]), "+f"(d[64]), "+f"(d[65]), "+f"(d[66]), "+f"(d[67]), "+f"(d[68]), "+f"(d[69]), "+f"(d[70]), "+f"(d[71]), "+f"(d[72]), "+f"(d[73]), "+f"(d[74]), "+f"(d[75]), "+f"(d[76]), "+f"(d[77]), "+f"(d[78]), "+f"(d[79]), "+f"(d[80]), "+f"(d[81]), "+f"(d[82]), "+f"(d[83]), "+f"(d[84]), "+f"(d[85]), "+f"(d[86]), "+f"(d[87]), "+f"(d[88]), "+f"(d[89]), "+f"(d[90]), "+f"(d[91]), "+f"(d[92]), "+f"(d[93]), "+f"(d[94]), "+f"(d[95]), "+f"(d[96]), "+f"(d[97]), "+f"(d[98]), "+f"(d[99]), "+f"(d[100]), "+f"(d[101]), "+f"(d[102]), "+f"(d[103]), "+f"(d[104]), "+f"(d[105]), "+f"(d[106]), "+f"(d[107])
      : "l"(da), "l"(db), "r"(sd), "n"(TB), "n"(AOFF), "n"(BOFF));
}

template<int TB, int AOFF, int BOFF> __device__ __forceinline__ void wgmma_ss_n64(float (&d)[32], uint64_t da, uint64_t db, int sd) {
    asm volatile("{\n.reg .pred p;\n.reg .b64 ta, tb;\nsetp.ne.b32 p, %34, 0;\nadd.s64 ta, %32, %36;\nadd.s64 tb, %33, %37;\n"
      "wgmma.mma_async.sync.aligned.m64n64k16.f32.bf16.bf16 {%0, %1, %2, %3, %4, %5, %6, %7, %8, %9, %10, %11, %12, %13, %14, %15, %16, %17, %18, %19, %20, %21, %22, %23, %24, %25, %26, %27, %28, %29, %30, %31}, ta, tb, p, 1, 1, 0, %35;\n}\n"
      : "+f"(d[0]), "+f"(d[1]), "+f"(d[2]), "+f"(d[3]), "+f"(d[4]), "+f"(d[5]), "+f"(d[6]), "+f"(d[7]), "+f"(d[8]), "+f"(d[9]), "+f"(d[10]), "+f"(d[11]), "+f"(d[12]), "+f"(d[13]), "+f"(d[14]), "+f"(d[15]), "+f"(d[16]), "+f"(d[17]), "+f"(d[18]), "+f"(d[19]), "+f"(d[20]), "+f"(d[21]), "+f"(d[22]), "+f"(d[23]), "+f"(d[24]), "+f"(d[25]), "+f"(d[26]), "+f"(d[27]), "+f"(d[28]), "+f"(d[29]), "+f"(d[30]), "+f"(d[31])
      : "l"(da), "l"(db), "r"(sd), "n"(TB), "n"(AOFF), "n"(BOFF));
}

template<int TB, int AOFF, int BOFF> __device__ __forceinline__ void wgmma_ss_n128(float (&d)[64], uint64_t da, uint64_t db, int sd) {
    asm volatile("{\n.reg .pred p;\n.reg .b64 ta, tb;\nsetp.ne.b32 p, %66, 0;\nadd.s64 ta, %64, %68;\nadd.s64 tb, %65, %69;\n"
      "wgmma.mma_async.sync.aligned.m64n128k16.f32.bf16.bf16 {%0, %1, %2, %3, %4, %5, %6, %7, %8, %9, %10, %11, %12, %13, %14, %15, %16, %17, %18, %19, %20, %21, %22, %23, %24, %25, %26, %27, %28, %29, %30, %31, %32, %33, %34, %35, %36, %37, %38, %39, %40, %41, %42, %43, %44, %45, %46, %47, %48, %49, %50, %51, %52, %53, %54, %55, %56, %57, %58, %59, %60, %61, %62, %63}, ta, tb, p, 1, 1, 0, %67;\n}\n"
      : "+f"(d[0]), "+f"(d[1]), "+f"(d[2]), "+f"(d[3]), "+f"(d[4]), "+f"(d[5]), "+f"(d[6]), "+f"(d[7]), "+f"(d[8]), "+f"(d[9]), "+f"(d[10]), "+f"(d[11]), "+f"(d[12]), "+f"(d[13]), "+f"(d[14]), "+f"(d[15]), "+f"(d[16]), "+f"(d[17]), "+f"(d[18]), "+f"(d[19]), "+f"(d[20]), "+f"(d[21]), "+f"(d[22]), "+f"(d[23]), "+f"(d[24]), "+f"(d[25]), "+f"(d[26]), "+f"(d[27]), "+f"(d[28]), "+f"(d[29]), "+f"(d[30]), "+f"(d[31]), "+f"(d[32]), "+f"(d[33]), "+f"(d[34]), "+f"(d[35]), "+f"(d[36]), "+f"(d[37]), "+f"(d[38]), "+f"(d[39]), "+f"(d[40]), "+f"(d[41]), "+f"(d[42]), "+f"(d[43]), "+f"(d[44]), "+f"(d[45]), "+f"(d[46]), "+f"(d[47]), "+f"(d[48]), "+f"(d[49]), "+f"(d[50]), "+f"(d[51]), "+f"(d[52]), "+f"(d[53]), "+f"(d[54]), "+f"(d[55]), "+f"(d[56]), "+f"(d[57]), "+f"(d[58]), "+f"(d[59]), "+f"(d[60]), "+f"(d[61]), "+f"(d[62]), "+f"(d[63])
      : "l"(da), "l"(db), "r"(sd), "n"(TB), "n"(AOFF), "n"(BOFF));
}

template<int TB, int AOFF, int BOFF> __device__ __forceinline__ void wgmma_ss_n72(float (&d)[36], uint64_t da, uint64_t db, int sd) {
    asm volatile("{\n.reg .pred p;\n.reg .b64 ta, tb;\nsetp.ne.b32 p, %38, 0;\nadd.s64 ta, %36, %40;\nadd.s64 tb, %37, %41;\n"
      "wgmma.mma_async.sync.aligned.m64n72k16.f32.bf16.bf16 {%0, %1, %2, %3, %4, %5, %6, %7, %8, %9, %10, %11, %12, %13, %14, %15, %16, %17, %18, %19, %20, %21, %22, %23, %24, %25, %26, %27, %28, %29, %30, %31, %32, %33, %34, %35}, ta, tb, p, 1, 1, 0, %39;\n}\n"
      : "+f"(d[0]), "+f"(d[1]), "+f"(d[2]), "+f"(d[3]), "+f"(d[4]), "+f"(d[5]), "+f"(d[6]), "+f"(d[7]), "+f"(d[8]), "+f"(d[9]), "+f"(d[10]), "+f"(d[11]), "+f"(d[12]), "+f"(d[13]), "+f"(d[14]), "+f"(d[15]), "+f"(d[16]), "+f"(d[17]), "+f"(d[18]), "+f"(d[19]), "+f"(d[20]), "+f"(d[21]), "+f"(d[22]), "+f"(d[23]), "+f"(d[24]), "+f"(d[25]), "+f"(d[26]), "+f"(d[27]), "+f"(d[28]), "+f"(d[29]), "+f"(d[30]), "+f"(d[31]), "+f"(d[32]), "+f"(d[33]), "+f"(d[34]), "+f"(d[35])
      : "l"(da), "l"(db), "r"(sd), "n"(TB), "n"(AOFF), "n"(BOFF));
}

template<int TB, int BOFF> __device__ __forceinline__ void wgmma_rs_n64(float (&d)[32], uint32_t a0, uint32_t a1, uint32_t a2, uint32_t a3, uint64_t db, int sd) {
    asm volatile("{\n.reg .pred p;\n.reg .b64 tb;\nsetp.ne.b32 p, %37, 0;\nadd.s64 tb, %36, %39;\n"
      "wgmma.mma_async.sync.aligned.m64n64k16.f32.bf16.bf16 {%0, %1, %2, %3, %4, %5, %6, %7, %8, %9, %10, %11, %12, %13, %14, %15, %16, %17, %18, %19, %20, %21, %22, %23, %24, %25, %26, %27, %28, %29, %30, %31}, {%32, %33, %34, %35}, tb, p, 1, 1, %38;\n}\n"
      : "+f"(d[0]), "+f"(d[1]), "+f"(d[2]), "+f"(d[3]), "+f"(d[4]), "+f"(d[5]), "+f"(d[6]), "+f"(d[7]), "+f"(d[8]), "+f"(d[9]), "+f"(d[10]), "+f"(d[11]), "+f"(d[12]), "+f"(d[13]), "+f"(d[14]), "+f"(d[15]), "+f"(d[16]), "+f"(d[17]), "+f"(d[18]), "+f"(d[19]), "+f"(d[20]), "+f"(d[21]), "+f"(d[22]), "+f"(d[23]), "+f"(d[24]), "+f"(d[25]), "+f"(d[26]), "+f"(d[27]), "+f"(d[28]), "+f"(d[29]), "+f"(d[30]), "+f"(d[31])
      : "r"(a0), "r"(a1), "r"(a2), "r"(a3), "l"(db), "r"(sd), "n"(TB), "n"(BOFF));
}

template<int TB, int BOFF> __device__ __forceinline__ void wgmma_rs_n24(float (&d)[12], uint32_t a0, uint32_t a1, uint32_t a2, uint32_t a3, uint64_t db, int sd) {
    asm volatile("{\n.reg .pred p;\n.reg .b64 tb;\nsetp.ne.b32 p, %17, 0;\nadd.s64 tb, %16, %19;\n"
      "wgmma.mma_async.sync.aligned.m64n24k16.f32.bf16.bf16 {%0, %1, %2, %3, %4, %5, %6, %7, %8, %9, %10, %11}, {%12, %13, %14, %15}, tb, p, 1, 1, %18;\n}\n"
      : "+f"(d[0]), "+f"(d[1]), "+f"(d[2]), "+f"(d[3]), "+f"(d[4]), "+f"(d[5]), "+f"(d[6]), "+f"(d[7]), "+f"(d[8]), "+f"(d[9]), "+f"(d[10]), "+f"(d[11])
      : "r"(a0), "r"(a1), "r"(a2), "r"(a3), "l"(db), "r"(sd), "n"(TB), "n"(BOFF));
}

constexpr int K1_XN_BYTES = 16 * 9216;
constexpr int K1_OFF_RING = K1_XN_BYTES;
constexpr int K1_OFF_BIAS = K1_OFF_RING + 10 * 8192;
constexpr int K1_OFF_BAR = K1_OFF_BIAS + 576 * 2;
constexpr int K1_SMEM = K1_OFF_BAR + 800;
constexpr float QSCALE = 0.23570226039551584f * 1.4426950408889634f;

struct K1Ctx {
    uint32_t full0;
    uint32_t rel_addr;
    uint64_t descA, descB;
    uint32_t phase;
    __device__ __forceinline__ void begin_stage(int s) {
        mbar_wait(full0 + s * 8, phase);
        wg_fence();
    }
    __device__ __forceinline__ void release(int s) {
        if (rel_addr) asm volatile("mbarrier.arrive.shared::cluster.b64 _, [%0];" ::"r"(rel_addr + s * 8) : "memory");
    }
    __device__ __forceinline__ void end_stage(int s) {
        wg_commit();
        wg_wait<1>();
        release(s == 0 ? 8 : s - 1);
    }
};

__host__ __device__ constexpr int a_off(int ks) { return ((ks / 12) * 49152 + ((ks >> 2) % 3) * 1024 + (ks & 3) * 32) >> 4; }

template <int V> struct IC { static constexpr int value = V; };
template <int I, int N, class F> __device__ __forceinline__ void static_for(F&& f) {
    if constexpr (I < N) { f(IC<I>{}); static_for<I + 1, N>(f); }
}

template <bool A_RS, bool B_RS, class Epi>
__device__ __forceinline__ void tile_pair(K1Ctx& c, float (&accA)[32], float (&accB)[32], uint32_t (&h)[144], Epi&& epi) {
    static_for<0, 9>([&](auto sc) {
        constexpr int s = decltype(sc)::value;
        c.begin_stage(s);
        static_for<0, 8>([&](auto tc) {
            constexpr int kk = s * 8 + decltype(tc)::value, ks = kk % 36;
            constexpr int bo = (ks * 2048) >> 4;
            if constexpr (kk < 36) {
                if constexpr (A_RS) wgmma_rs_n64<1, bo>(accA, h[ks * 4], h[ks * 4 + 1], h[ks * 4 + 2], h[ks * 4 + 3], c.descB, ks != 0);
                else wgmma_ss_n64<1, a_off(ks), bo>(accA, c.descA, c.descB, ks != 0);
            } else {
                if constexpr (B_RS) wgmma_rs_n64<1, bo>(accB, h[ks * 4], h[ks * 4 + 1], h[ks * 4 + 2], h[ks * 4 + 3], c.descB, ks != 0);
                else wgmma_ss_n64<1, a_off(ks), bo>(accB, c.descA, c.descB, ks != 0);
            }
        });
        c.end_stage(s);
        epi(sc);
    });
    c.phase ^= 1;
}

template <int B0, int NB, int HOFF>
__device__ __forceinline__ void gelu_blocks(const float (&acc)[32], uint32_t (&h)[144], const uint32_t (&bq)[8], float rs0, float rs1) {
#pragma unroll
    for (int b = B0; b < B0 + NB; b++) {
        const float b0 = bf_lo(bq[b]), b1 = bf_hi(bq[b]);
        h[HOFF + b * 2 + 0] = pack_bf16(gelu2(fmaf(acc[b * 4 + 0], rs0, b0)), gelu2(fmaf(acc[b * 4 + 1], rs0, b1)));
        h[HOFF + b * 2 + 1] = pack_bf16(gelu2(fmaf(acc[b * 4 + 2], rs1, b0)), gelu2(fmaf(acc[b * 4 + 3], rs1, b1)));
    }
#pragma unroll
    for (int i = HOFF + B0 * 2; i < HOFF + (B0 + NB) * 2; i++) asm volatile("" : "+r"(h[i]));
}
__device__ __forceinline__ void load_bias(uint32_t (&bq)[8], uint32_t addr) {
    asm volatile("ld.shared.v4.u32 {%0, %1, %2, %3}, [%4];" : "=r"(bq[0]), "=r"(bq[1]), "=r"(bq[2]), "=r"(bq[3]) : "r"(addr));
    asm volatile("ld.shared.v4.u32 {%0, %1, %2, %3}, [%4 + 16];" : "=r"(bq[4]), "=r"(bq[5]), "=r"(bq[6]), "=r"(bq[7]) : "r"(addr));
}
template <int S> __device__ __forceinline__ void store_part(const float (&o)[32], uint4* p) {
    uint4 v;
    v.x = pack_bf16(o[S * 8 + 0], o[S * 8 + 1]); v.y = pack_bf16(o[S * 8 + 2], o[S * 8 + 3]);
    v.z = pack_bf16(o[S * 8 + 4], o[S * 8 + 5]); v.w = pack_bf16(o[S * 8 + 6], o[S * 8 + 7]);
    p[S * 256] = v;
}

constexpr int NCHUNK = 16;
constexpr int CHUNK_BYTES = KV_HEAD_BYTES / NCHUNK;
constexpr int SM_Q = 0;
constexpr int SM_KV = 32768;
constexpr int PIECE = 19968;
__host__ __device__ constexpr int sm_piece(int p) { return p == 0 ? 209408 : (p == 1 ? 0 : SM_KV + (p - 2) * PIECE); }
__host__ __device__ constexpr int sm_wstep(int k) { return k < 27 ? sm_piece(k / 3) + (k % 3) * 4608 : (k < 35 ? SM_KV + 7 * PIECE + (k - 27) * 4608 : PIECE); }
__host__ __device__ constexpr int sm_ostep(int k) { return k < 27 ? sm_piece(k / 3) + 13824 + (k % 3) * 2048 : sm_piece(0) + (k - 27) * 2048; }
constexpr int SM_RED = SM_KV + KV_HEAD_BYTES;

__device__ __forceinline__ float exp2_fixed(float y) {
    const float u = __uint_as_float(__float_as_uint(y) & 0xFF807FFFu) - 512.02545f;
    float t = fmaf(u, 0.019497588f, 0.114550486f);
    t = fmaf(t, u, -0.29839927f);
    return fmaf(t, u, y);
}
__device__ __forceinline__ uint32_t pack_fixed(float lo, float hi) { return __byte_perm(__float_as_uint(lo), __float_as_uint(hi), 0x6521); }

#define PV_GROUP 4
#define POLY_MODE 1
__device__ __forceinline__ uint32_t exp2_packed(float y0, float y1, uint32_t one2) {
    const uint32_t w = pack_fixed(y0, y1);
    uint32_t m;
    asm("lop3.b32 %0, %1, 0x007F007F, %2, 0xEA;" : "=r"(m) : "r"(w), "r"(one2));
    const uint32_t d = hfma2_bf16(m, 0x3EF93EF9u, 0xBF38BF38u);
    const uint32_t e = hfma2_bf16(d, d, 0xBD71BD71u);
    return hfma2_bf16(w, e, w);
}
constexpr int KV_TILE = CHUNK_BYTES / 16;
template <int OFF> __device__ __forceinline__ void issue_qk(float (&s)[64], uint64_t qd, uint64_t kd) {
    wgmma_ss_n128<0, 0, OFF + (8 << 16)>(s, qd, kd, 0);
    wgmma_ss_n128<0, 16, OFF + 32>(s, qd, kd, 1);
}
template <int OFF> __device__ __forceinline__ void issue_pv(float (&o)[12], const uint32_t (&p)[32], uint64_t vd) {
    static_for<0, 8>([&](auto kc) {
        constexpr int k = decltype(kc)::value;
        wgmma_rs_n24<1, OFF + k * (2 * KV_GROUP_BYTES / 16)>(o, p[k * 4], p[k * 4 + 1], p[k * 4 + 2], p[k * 4 + 3], vd, 1);
    });
}
template <int OFF>
__device__ __forceinline__ void softmax_pv(const float (&s)[64], uint32_t (&p)[32], float (&o)[12], uint64_t vd, uint32_t one2) {
    static_for<0, 8 / PV_GROUP>([&](auto gc) {
        constexpr int g0 = decltype(gc)::value * PV_GROUP;
#pragma unroll
        for (int b = g0 * 2; b < (g0 + PV_GROUP) * 2; b++) {
            if ((POLY_MASK >> b) & 1) {
                p[b * 2 + 0] = exp2_packed(s[b * 4 + 0], s[b * 4 + 1], one2);
                p[b * 2 + 1] = exp2_packed(s[b * 4 + 2], s[b * 4 + 3], one2);
            } else {
                p[b * 2 + 0] = pack_bf16(ex2(s[b * 4 + 0]), ex2(s[b * 4 + 1]));
                p[b * 2 + 1] = pack_bf16(ex2(s[b * 4 + 2]), ex2(s[b * 4 + 3]));
            }
        }
#pragma unroll
        for (int i = g0 * 4; i < (g0 + PV_GROUP) * 4; i++) asm volatile("" : "+r"(p[i])::"memory");
        wg_fence();
        static_for<g0, g0 + PV_GROUP>([&](auto kc) {
            constexpr int k = decltype(kc)::value;
            wgmma_rs_n24<1, OFF + k * (2 * KV_GROUP_BYTES / 16)>(o, p[k * 4], p[k * 4 + 1], p[k * 4 + 2], p[k * 4 + 3], vd, 1);
        });
    });
    wg_commit();
}
__device__ __forceinline__ void store_o(float (&o)[12], int rt, int head, int wq, int lane) {
    const int g = lane >> 2, q = lane & 3;
    const float i0 = __fdividef(1.0f, __shfl_sync(~0u, o[8], lane | 3)), i1 = __fdividef(1.0f, __shfl_sync(~0u, o[10], lane | 3));
#pragma unroll
    for (int i = 0; i < 3; i++) {
        const int pc = head * 9 + (i < 2 ? i * 4 + q : 8);
        uint32_t* op = g_O + ((rt * 72 + (pc >> 2)) * 8 + wq * 2) * 32 + g * 4 + (pc & 3);
        if (i < 2 || q == 2) {
            op[0] = pack_bf16(o[i * 4] * i0, o[i * 4 + 1] * i0);
            op[32] = pack_bf16(o[i * 4 + 2] * i1, o[i * 4 + 3] * i1);
        }
    }
#pragma unroll
    for (int i = 0; i < 12; i++) o[i] = 0.f;
}
__device__ __forceinline__ void mbar_arrive(uint32_t b) { asm volatile("mbarrier.arrive.shared::cta.b64 _, [%0];" ::"r"(b) : "memory"); }
__device__ __forceinline__ void mbar_wait_sleep(uint32_t b, uint32_t ns) {
    uint32_t ok, spins = 0;
    while (true) {
        asm volatile("{\n.reg .pred p;\nmbarrier.try_wait.parity.shared::cta.b64 p, [%1], 0;\nselp.u32 %0, 1, 0, p;\n}\n" : "=r"(ok) : "r"(b) : "memory");
        if (ok) break;
        __nanosleep(ns);
        if (++spins > (1u << 21)) __trap();
    }
}
__device__ __forceinline__ void flag_signal(unsigned int* f) {
    __threadfence();
    atomicAdd(f, 1u);
}
__device__ __forceinline__ void flag_wait(const unsigned int* f, unsigned int target, unsigned int sleep_ns) {
    uint32_t v, spins = 0;
    while (true) {
        asm volatile("ld.acquire.gpu.global.u32 %0, [%1];" : "=r"(v) : "l"(f) : "memory");
        if (v >= target) break;
        if (sleep_ns) __nanosleep(sleep_ns);
        if (++spins > (1u << 21)) __trap();
    }
}
__device__ __forceinline__ uint4 hadd8_bf16(const uint4 a, const uint4 b) {
    return make_uint4(hadd2_bf16(a.x, b.x), hadd2_bf16(a.y, b.y), hadd2_bf16(a.z, b.z), hadd2_bf16(a.w, b.w));
}
__device__ __forceinline__ float sumsq2(uint32_t w) { return fmaf(bf_lo(w), bf_lo(w), bf_hi(w) * bf_hi(w)); }
__device__ __forceinline__ float sumsq8(const uint4 v) { return (sumsq2(v.x) + sumsq2(v.y)) + (sumsq2(v.z) + sumsq2(v.w)); }

enum { B_FULL = 0, B_EMPTY = 9, B_BASE = 18, B_XNDEAD = 19, B_QRDY = 20, B_FFN = 21, B_KV = 22, B_FREE = 38, B_WO = 46, B_RED = 55, B_X = 61, B_EARLY = 85, B_OS = 86, B_LATE = 94, B_END = 95 };

__global__ void __cluster_dims__(2, 1, 1) __launch_bounds__(384, 1)
fused_kernel(const __grid_constant__ CUtensorMap tmX, const __grid_constant__ CUtensorMap tmQ3, const __grid_constant__ CUtensorMap tmQ1,
          const __grid_constant__ CUtensorMap tm1, const __grid_constant__ CUtensorMap tm2, const __grid_constant__ CUtensorMap tmP,
          const __grid_constant__ CUtensorMap tmOut, const __nv_bfloat16* __restrict__ b1,
          const __nv_bfloat16* __restrict__ wqkv, const __nv_bfloat16* __restrict__ w1, const __nv_bfloat16* __restrict__ w2,
          const __nv_bfloat16* __restrict__ wo, const __nv_bfloat16* __restrict__ x, const __nv_bfloat16* __restrict__ b2,
          const uint64_t zero) {
    extern __shared__ __align__(1024) uint8_t smem[];
    const uint32_t sb = s2u(smem);
    const int tid = threadIdx.x, lane = tid & 31;
    const int warp = __shfl_sync(~0u, tid >> 5, 0);
    const uint32_t rank = blockIdx.x & 1;
    const int cl = blockIdx.x >> 1;
    const int rb = (cl & 7) * 2 + rank;
    const int j = cl >> 3;
    const uint32_t bar0 = sb + K1_OFF_BAR;
    const uint32_t full0 = bar0 + B_FULL * 8, empty0 = bar0 + B_EMPTY * 8, xbar0 = bar0 + B_X * 8;
    const int head = blockIdx.x >> 2, quarter = blockIdx.x & 3;
    const int rt = quarter * 8 + (head >> 2), ct = head & 3;
    const int rot = head >> 3;
    const int ks0 = ((((head >> 3) + 2) & 3) * 9);
    volatile uint32_t* slow_flag = reinterpret_cast<volatile uint32_t*>(smem + K1_OFF_BAR + B_END * 8);

    if (warp < 8) {
        PROF(0);
        PROFT(48);
        if (lane == 0) {
#pragma unroll
            for (int i = 0; i < 3; i++) mbar_init(xbar0 + (warp * 3 + i) * 8, 1);
            fence_barrier_init();
#pragma unroll 1
            for (int i = 0; i < 3; i++) {
                const uint32_t xb = xbar0 + (warp * 3 + i) * 8;
                mbar_expect(xb, 6144);
                tma4d(sb + i * 49152 + warp * 6144, &tmX, 0, 0, i * 3, rb * 16 + warp * 2, xb);
            }
        }
        __syncwarp();
        cluster_arrive();
        PROF(22);
        reg_alloc<240>();
        PROF(23);
        float rs0, rs1;
        {
            const uint32_t la = sb + (warp * 2 + ((lane >> 3) & 1)) * 3072 + (lane & 7) * 128;
            uint32_t off[4];
#pragma unroll
            for (int i = 0; i < 4; i++) off[i] = la + (((i * 2 + (lane >> 4)) ^ (lane & 7)) << 4);
            float c1[4] = {0.f, 0.f, 0.f, 0.f}, c2[4] = {0.f, 0.f, 0.f, 0.f}, c3[4] = {0.f, 0.f, 0.f, 0.f};
            uint32_t a[36][4];
#pragma unroll
            for (int t = 0; t < 3; t++) {
                mbar_wait(xbar0 + (warp * 3 + t) * 8, 0);
                PROF(24 + t);
#pragma unroll
                for (int i = 0; i < 12; i++) ldsm4(a[t * 12 + i], off[i & 3] + t * 49152 + (i >> 2) * 1024);
#pragma unroll
                for (int i = t * 12; i < t * 12 + 12; i++) {
                    mma16816(c3, a[i], 0x3F803F80u, 0x3F803F80u);
                    mma16816(c1, a[i], a[i][0], a[i][2]);
                    mma16816(c2, a[i], a[i][1], a[i][3]);
                }
            }
            PROF(27);
            const int gg = lane >> 2, src = (lane & ~3) | (gg >> 1);
            const float m0 = c3[0] * (1.0f / DM), m1 = c3[2] * (1.0f / DM);
            const uint32_t mc0 = pack_bf16(-m0, -m0), mc1 = pack_bf16(-m1, -m1);
#pragma unroll
            for (int i = 0; i < 36; i++) {
#pragma unroll
                for (int k = 0; k < 4; k++) a[i][k] = hadd2_bf16(a[i][k], (k & 1) ? mc1 : mc0);
                stsm4(off[i & 3] + (i / 12) * 49152 + ((i >> 2) % 3) * 1024, a[i]);
            }
            const float q0 = __shfl_sync(~0u, (gg & 1) ? c1[1] : c1[0], src), q1 = __shfl_sync(~0u, (gg & 1) ? c2[3] : c2[2], src);
            rs0 = rsqrtf(fmaxf(fmaf(-m0, m0, q0 * (1.0f / DM)), 0.f) + 1e-5f);
            rs1 = rsqrtf(fmaxf(fmaf(-m1, m1, q1 * (1.0f / DM)), 0.f) + 1e-5f);
            if (__any_sync(~0u, fabsf(m0) * rs0 > 0.25f || fabsf(m1) * rs1 > 0.25f)) {
                const float d0 = -m0 - bf_lo(mc0), d1 = -m1 - bf_lo(mc1);
                const uint32_t md0 = pack_bf16(d0, d0), md1 = pack_bf16(d1, d1);
#pragma unroll 1
                for (int i = 0; i < 9; i++) {
#pragma unroll
                    for (int k4 = 0; k4 < 4; k4++) {
                        const uint32_t ad = off[k4] + (i / 3) * 49152 + (i % 3) * 1024;
                        uint32_t b[4];
                        ldsm4(b, ad);
#pragma unroll
                        for (int k = 0; k < 4; k++) b[k] = hadd2_bf16(b[k], (k & 1) ? md1 : md0);
                        stsm4(ad, b);
                    }
                }
            }
        }
        PROF(28);
        const int wg = warp >> 2, wq = warp & 3;
        fence_proxy_async();
        named_bar_sync(1 + wg, 128);
        cluster_wait();
        PROF(1);

        const int g = lane >> 2, q = lane & 3;
        K1Ctx c;
        c.full0 = full0;
        c.rel_addr = 0;
        c.descA = mk_desc(zero, sb + wg * 8 * 3072, 16, 3072, 1);
        c.descB = mk_desc(zero, sb + K1_OFF_RING, 2048, 1024, 1);
        c.phase = 0;
        uint32_t biasq = sb + K1_OFF_BIAS + q * 32;
        uint32_t bq[8];

        uint32_t h[144];
        float accA[32], accB[32];
        {
            float accQ[108];
            uint32_t rel = 0;
            if (lane == 0 && wq < 2) asm("mapa.shared::cluster.u32 %0, %1, %2;" : "=r"(rel) : "r"(empty0), "r"(wq));
#pragma unroll 1
            for (int r = 0; r < 2; r++) {
                static_for<0, 9>([&](auto sc) {
                    constexpr int s = decltype(sc)::value;
                    c.begin_stage(s);
                    const uint64_t da = c.descA + (r ? a_off(18 + 2 * s) : a_off(2 * s));
                    wgmma_ss_n216<1, 0, ((2 * s) % 9) * 512>(accQ, da, c.descB, (r | s) != 0);
                    wgmma_ss_n216<1, 2, ((2 * s + 1) % 9) * 512>(accQ, da, c.descB, 1);
                    c.end_stage(s);
                    c.rel_addr = rel;
                });
                c.phase ^= 1;
            }
            PROF(2); PROFWT(54);
            uint32_t rel9[9];
#pragma unroll
            for (int i9 = 0; i9 < 9; i9++) {
                const int p = 4 * i9 + q, hh = (p * 57) >> 9, r = p - 9 * hh;
                rel9[i9] = hh * KV_HEAD_BYTES + (r < 8 ? (r >> 2) * 128 + (r & 3) * 4 : 0);
            }
            uint32_t gb = 0, o2 = 0;
            float scl0 = 1.f, scl1 = 1.f;
            tile_pair<false, false>(c, accA, accB, h, [&](auto sc) {
                constexpr int s = decltype(sc)::value;
                if constexpr (s == 0) reg_fence(accQ);
                if constexpr (s < 6) {
                    constexpr int grp = s / 2, part = s % 2;
                    if constexpr (part == 0) {
                        const int G = 3 * j + grp, type = G >> 3;
                        gb = (G & 7) * 4 * KV_HEAD_BYTES + (rb * 16 + warp * 2) * KV_GROUP_BYTES + g * 16 + (type == 0 ? Q_OFFSET : (type == 2 ? 256 : 0));
                        o2 = type == 0 ? 256 : (type == 2 ? 264 : 512);
                        scl0 = rs0 * (type == 0 ? QSCALE : ((type == 1 && ((POLY_MASK >> (warp * 2)) & 1)) ? 2.f : 1.f));
                        scl1 = rs1 * (type == 0 ? QSCALE : ((type == 1 && ((POLY_MASK >> (warp * 2 + 1)) & 1)) ? 2.f : 1.f));
                    }
#pragma unroll
                    for (int i9 = part * 5; i9 < (part ? 9 : 5); i9++) {
                        const int b = grp * 9 + i9;
                        uint32_t off = gb + rel9[i9];
                        if (i9 >= 2 && (i9 & 1) == 0) off += (q == i9 / 2 - 1) ? o2 : 0;
                        *reinterpret_cast<uint32_t*>(g_QKV + off) = pack_bf16(accQ[b * 4] * scl0, accQ[b * 4 + 1] * scl0);
                        *reinterpret_cast<uint32_t*>(g_QKV + off + KV_GROUP_BYTES) = pack_bf16(accQ[b * 4 + 2] * scl1, accQ[b * 4 + 3] * scl1);
                    }
                    if constexpr (s == 5) asm volatile("bar.arrive 3, 352;" ::: "memory");
                }
                if constexpr (s == 4) { named_bar_sync(4, 352); load_bias(bq, biasq); }
                if constexpr (s == 5) reg_fence(accA);
                if constexpr (s >= 5) gelu_blocks<(s - 5) * 2, 2, 96>(accA, h, bq, rs0, rs1);
                if constexpr (s == 8) load_bias(bq, biasq + 128);
            });
        }
        PROF(3); PROFWT(55);
#pragma unroll
        for (int i = 32; i < 96; i++) asm volatile("mov.u32 %0, 0;" : "=r"(h[i]));
#pragma unroll 1
        for (int p = 1; p < 4; p++) {
            biasq += 256;
            tile_pair<false, false>(c, accA, accB, h, [&](auto sc) {
                constexpr int s = decltype(sc)::value;
                if constexpr (s == 0) {
                    reg_fence(accB);
#pragma unroll
                    for (int i = 0; i < 80; i++) h[i] = h[i + 32];
                }
                if constexpr (s < 4) gelu_blocks<s * 2, 2, 80>(accB, h, bq, rs0, rs1);
                if constexpr (s == 4) load_bias(bq, biasq);
                if constexpr (s == 5) reg_fence(accA);
                if constexpr (s >= 5) gelu_blocks<(s - 5) * 2, 2, 96>(accA, h, bq, rs0, rs1);
                if constexpr (s == 8) load_bias(bq, biasq + 128);
            });
        }
        PROF(4); PROFWT(56);
        tile_pair<false, true>(c, accA, accB, h, [&](auto sc) {
            constexpr int s = decltype(sc)::value;
            if constexpr (s == 0) reg_fence(accB);
            if constexpr (s < 4) gelu_blocks<s * 2, 2, 112>(accB, h, bq, rs0, rs1);
            if constexpr (s == 4) load_bias(bq, biasq + 256);
            if constexpr (s == 5) { reg_fence(accA); if (tid == wg * 128) mbar_arrive(bar0 + B_XNDEAD * 8); }
            if constexpr (s == 5 || s == 6) gelu_blocks<(s - 5) * 3, 3, 128>(accA, h, bq, rs0, rs1);
            if constexpr (s == 7) gelu_blocks<6, 2, 128>(accA, h, bq, rs0, rs1);
            if constexpr (s == 3 || s == 7) reg_fence(h);
        });
        PROF(5); PROFWT(57);
        uint4* pout = g_part + j * SLAB + rb * 36 * 256 + tid;
#pragma unroll 1
        for (int p = 0; p < 4; p++) {
            tile_pair<true, true>(c, accA, accB, h, [&](auto sc) {
                constexpr int s = decltype(sc)::value;
                if constexpr (s == 0) reg_fence(accB);
                if constexpr (s < 4) store_part<s>(accB, pout);
                if constexpr (s == 5) reg_fence(accA);
                if constexpr (s >= 5) store_part<s - 5>(accA, pout + 1024);
            });
            pout += 2048;
            PROF(6 + p);
        }
        wg_wait<0>();
        c.release(8);
        reg_fence(accB);
        store_part<0>(accB, pout); store_part<1>(accB, pout); store_part<2>(accB, pout); store_part<3>(accB, pout);
        __syncwarp();
        if (lane == 0) mbar_arrive(bar0 + B_FFN * 8);
        PROF(10); PROFWT(58);
        PROFT(49);

        mbar_wait(bar0 + B_QRDY * 8, 0);
        const uint32_t slow = __any_sync(~0u, *slow_flag != 0);
        const uint64_t kd0 = mk_desc(zero, sb + SM_KV, 0, KV_GROUP_BYTES, 0);
        const uint64_t vd0 = mk_desc(zero, sb + SM_KV + 256, KV_GROUP_BYTES, 128, 0);
        const uint64_t qd0 = mk_desc(zero, sb + SM_Q + wg * 4096, 128, 512, 0);
        const uint32_t kvbar = bar0 + B_KV * 8;
        float o[12];
#pragma unroll
        for (int i = 0; i < 12; i++) o[i] = 0.f;
        PROF(16);
        PROFT(50);
        if (!slow) {
            const uint32_t one2 = 0x3F803F80u + (uint32_t)zero;
            float s0[64], s1[64];
            uint32_t p0[32], p1[32];
            mbar_wait(kvbar, 0);
            reg_fence(o);
            wg_fence();
            issue_qk<0>(s0, qd0, kd0);
            wg_commit();
            wg_commit();
            uint64_t qd = qd0;
            const uint32_t fre = (tid == wg * 128) ? bar0 + B_FREE * 8 - 8 : 0;
#pragma unroll 1
            for (int pass = 0; pass < 4; pass++) {
                uint64_t vd = vd0, kd = kd0;
                uint32_t bn = kvbar + 8;
#pragma unroll 1
                for (int it = 0; it < 8; it++) {
                    mbar_wait(bn, 0);
                    if (it == 0 && pass != 0) {
                        wg_wait<0>();
                        reg_fence(o);
                        store_o(o, quarter * 8 + ((pass - 1 + rot) & 3) * 2 + wg, head, wq, lane);
                        reg_fence(o);
                        __syncwarp();
                        if (lane == 0) mbar_arrive(bar0 + (B_OS + pass * 2 - 2 + wg) * 8);
                    }
                    wg_wait<1>();
                    reg_fence(s0);
                    wg_fence();
                    issue_qk<KV_TILE>(s1, qd, kd);
                    wg_commit();
                    if (pass == 3 && it > 0 && fre) mbar_arrive(fre + it * 8);
                    softmax_pv<0>(s0, p0, o, vd, one2);
                    kd += 2 * KV_TILE; bn += 8;
                    if (it == 7) { kd = kd0; bn = kvbar; qd += 512; }
                    mbar_wait(bn, 0);
                    wg_wait<1>();
                    reg_fence(s1);
                    wg_fence();
                    issue_qk<0>(s0, qd, kd);
                    wg_commit();
                    softmax_pv<KV_TILE>(s1, p1, o, vd, one2);
                    vd += 2 * KV_TILE; bn += 8;
                }
                if (pass == 0) PROF(17);
            }
            wg_wait<0>();
            reg_fence(o);
            reg_fence(s0);
            reg_fence(s1);
            store_o(o, quarter * 8 + ((3 + rot) & 3) * 2 + wg, head, wq, lane);
        } else {
#pragma unroll 1
            for (int pass = 0; pass < 4; pass++) {
                float m0 = -INFINITY, m1 = -INFINITY;
                float s[64];
                uint32_t p[32];
#pragma unroll 1
                for (int t = 0; t < 16; t++) {
                    mbar_wait(kvbar + t * 8, 0);
                    wg_fence();
                    issue_qk<0>(s, qd0 + pass * 512, kd0 + t * KV_TILE);
                    wg_commit();
                    wg_wait<0>();
                    reg_fence(s);
                    float a0 = m0, a1 = m1;
#pragma unroll
                    for (int k = 0; k < 16; k++) {
                        if ((POLY_MASK >> k) & 1) {
#pragma unroll
                            for (int i = 0; i < 4; i++) s[k * 4 + i] *= 0.5f;
                        }
                        a0 = fmaxf(a0, fmaxf(s[k * 4 + 0], s[k * 4 + 1]));
                        a1 = fmaxf(a1, fmaxf(s[k * 4 + 2], s[k * 4 + 3]));
                    }
                    a0 = fmaxf(a0, __shfl_xor_sync(~0u, a0, 1)); a1 = fmaxf(a1, __shfl_xor_sync(~0u, a1, 1));
                    a0 = fmaxf(a0, __shfl_xor_sync(~0u, a0, 2)); a1 = fmaxf(a1, __shfl_xor_sync(~0u, a1, 2));
                    const float r0 = ex2(m0 - a0), r1 = ex2(m1 - a1);
                    m0 = a0; m1 = a1;
#pragma unroll
                    for (int i = 0; i < 3; i++) { o[i * 4] *= r0; o[i * 4 + 1] *= r0; o[i * 4 + 2] *= r1; o[i * 4 + 3] *= r1; }
#pragma unroll
                    for (int k = 0; k < 16; k++) {
                        p[k * 2 + 0] = pack_bf16(ex2(s[k * 4 + 0] - m0), ex2(s[k * 4 + 1] - m0));
                        p[k * 2 + 1] = pack_bf16(ex2(s[k * 4 + 2] - m1), ex2(s[k * 4 + 3] - m1));
                    }
                    reg_fence(p);
                    reg_fence(o);
                    wg_fence();
                    issue_pv<0>(o, p, vd0 + t * KV_TILE);
                    wg_commit();
                    wg_wait<0>();
                    reg_fence(o);
                }
                store_o(o, quarter * 8 + ((pass + rot) & 3) * 2 + wg, head, wq, lane);
                __syncwarp();
                if (lane == 0 && pass < 3) mbar_arrive(bar0 + (B_OS + pass * 2 + wg) * 8);
            }
            if (tid == wg * 128)
                for (int i = 0; i < 7; i++) mbar_arrive(bar0 + (B_FREE + i) * 8);
        }
        PROF(18);
        PROFT(51);

        __syncwarp();
        if (lane == 0) mbar_arrive(bar0 + (B_OS + 6 + wg) * 8);
        if (tid == wg * 128) mbar_arrive(bar0 + (B_FREE + 7) * 8);
        const int t128 = tid & 127;
        float acc[36];
        const uint64_t od = mk_desc(zero, sb, 1024, 128, 0), wd = mk_desc(zero, sb + wg * 9 * 128, 2304, 128, 0);
        static_for<0, 9>([&](auto pc) {
            constexpr int p = decltype(pc)::value;
            mbar_wait(bar0 + (B_WO + p) * 8, 0);
            wg_fence();
            wgmma_ss_n72<1, sm_ostep(p * 3) / 16, sm_wstep(p * 3) / 16>(acc, od, wd, p != 0);
            wgmma_ss_n72<1, sm_ostep(p * 3 + 1) / 16, sm_wstep(p * 3 + 1) / 16>(acc, od, wd, 1);
            wgmma_ss_n72<1, sm_ostep(p * 3 + 2) / 16, sm_wstep(p * 3 + 2) / 16>(acc, od, wd, 1);
            wg_commit();
            if constexpr (p == 2) {
                wg_wait<1>();
                if (t128 == 0) mbar_arrive(bar0 + B_EARLY * 8);
            }
        });
        PROF(29);
        float bs[36];
        {
            const uint32_t* xp = reinterpret_cast<const uint32_t*>(x + (size_t)(rt * 64 + wq * 16 + g) * DM + ct * 144 + wg * 72 + q * 2);
            uint32_t xv[18], bv[9];
            uint2 fv[9];
            mbar_wait(bar0 + B_BASE * 8, 0);
#pragma unroll
            for (int i = 0; i < 9; i++) {
                xv[i * 2] = __ldg(xp + i * 4);
                xv[i * 2 + 1] = __ldg(xp + i * 4 + 4 * DM);
                bv[i] = __ldg(reinterpret_cast<const uint32_t*>(b2 + ct * 144 + wg * 72 + q * 2) + i * 4);
                fv[i] = __ldcg(g_ffn + (blockIdx.x * 18 + wg * 9 + i) * 128 + t128);
            }
            PROF(30);
#pragma unroll
            for (int i = 0; i < 9; i++) {
                bs[i * 4 + 0] = fmaf(bf_lo(fv[i].x), 0.5f, bf_lo(xv[i * 2]) + bf_lo(bv[i]));
                bs[i * 4 + 1] = fmaf(bf_hi(fv[i].x), 0.5f, bf_hi(xv[i * 2]) + bf_hi(bv[i]));
                bs[i * 4 + 2] = fmaf(bf_lo(fv[i].y), 0.5f, bf_lo(xv[i * 2 + 1]) + bf_lo(bv[i]));
                bs[i * 4 + 3] = fmaf(bf_hi(fv[i].y), 0.5f, bf_hi(xv[i * 2 + 1]) + bf_hi(bv[i]));
            }
        }
        reg_fence(bs);
        PROF(19);
        mbar_wait(bar0 + B_LATE * 8, 0);
        PROF(20);
        wg_fence();
        static_for<27, 36>([&](auto kc) {
            constexpr int k = decltype(kc)::value;
            wgmma_ss_n72<1, sm_ostep(k) / 16, sm_wstep(k) / 16>(acc, od, wd, 1);
        });
        wg_commit();
        PROF(31);
        wg_wait<0>();
        reg_fence(acc);
        PROF(32);
        uint32_t* st = reinterpret_cast<uint32_t*>(smem + sm_piece(1) + wg * 9216) + (wq * 16 + g) * 36 + q;
#pragma unroll
        for (int i = 0; i < 9; i++) {
            st[i * 4] = pack_bf16(acc[i * 4] + bs[i * 4], acc[i * 4 + 1] + bs[i * 4 + 1]);
            st[i * 4 + 288] = pack_bf16(acc[i * 4 + 2] + bs[i * 4 + 2], acc[i * 4 + 3] + bs[i * 4 + 3]);
        }
        fence_proxy_async();
        named_bar_sync(1 + wg, 128);
        if (t128 == 0) {
            asm volatile("cp.async.bulk.tensor.2d.global.shared::cta.bulk_group [%0, {%2, %3}], [%1];"
                         ::"l"(&tmOut), "r"(sb + sm_piece(1) + wg * 9216), "r"(ct * 144 + wg * 72), "r"(rt * 64) : "memory");
            asm volatile("cp.async.bulk.commit_group;" ::: "memory");
            asm volatile("cp.async.bulk.wait_group.read 0;" ::: "memory");
        }
        PROF(21);
        PROFT(52);
    } else {
        reg_dealloc<24>();
        if (warp == 8 && lane == 0) {
            prefetch_tmap(&tmQ3); prefetch_tmap(&tmQ1); prefetch_tmap(&tm1); prefetch_tmap(&tm2);
            #pragma unroll 1
            for (int i = 0; i < 9; i++) { mbar_init(full0 + i * 8, 1); mbar_init(empty0 + i * 8, 4); mbar_init(bar0 + (B_WO + i) * 8, 2); }
            mbar_init(bar0 + B_BASE * 8, 3); mbar_init(bar0 + B_XNDEAD * 8, 2); mbar_init(bar0 + B_QRDY * 8, 3); mbar_init(bar0 + B_FFN * 8, 8); mbar_init(bar0 + B_EARLY * 8, 2); mbar_init(bar0 + B_LATE * 8, 2);
#pragma unroll 1
            for (int i = 0; i < 16; i++) { mbar_init(bar0 + (B_KV + i) * 8, 1); mbar_init(bar0 + (B_FREE + (i & 7)) * 8, 2); if (i < 6) mbar_init(bar0 + (B_RED + i) * 8, 1); if (i < 8) mbar_init(bar0 + (B_OS + i) * 8, 4); }
            *slow_flag = 0;
            fence_barrier_init();
        }
        __syncwarp();
        cluster_arrive();
        cluster_wait();
        const uint8_t* kvsrc = g_QKV + (size_t)head * KV_HEAD_BYTES;
        if (warp == 8) {
            if (lane == 0) {
                int st = 0, u = rank, tile = -4;
                int es = 5;
                uint32_t eph = 1;
#pragma unroll 1
                for (int n = 0; n < 99; n++) {
                    mbar_wait(empty0 + es * 8, eph);
                    const uint32_t fb = full0 + st * 8, dst = sb + K1_OFF_RING + u * 8192;
                    mbar_expect(fb, 16384);
                    if (tile < 0) {
                        tma3d_mc(dst, &tmQ3, j * 216, n * 32 + rank * 16, 0, fb, 3);
                        tma2d_mc(dst + 6144, &tmQ1, j * 216 + 192, n * 32 + rank * 16, fb, 3);
                    } else if (tile < 9) {
                        tma2d_mc(dst, &tm1, j * 576 + tile * 64, u * 64, fb, 3);
                    } else {
                        tma2d_mc(dst, &tm2, (tile - 9) * 64, j * 576 + u * 64, fb, 3);
                    }
                    u += 2;
                    if (u >= 9) { u -= 9; tile++; }
                    if (++st == 9) st = 0;
                    if (++es == 9) { es = 0; eph ^= 1; }
                }
                mbar_wait(empty0 + 8 * 8, 0);
                mbar_wait(bar0 + B_QRDY * 8, 0);
                asm volatile("fence.proxy.async;" ::: "memory");
#pragma unroll 1
                for (int i = 11; i < NCHUNK; i++) {
                    mbar_expect(bar0 + (B_KV + i) * 8, CHUNK_BYTES);
                    bulk_load(sb + SM_KV + i * CHUNK_BYTES, kvsrc + i * CHUNK_BYTES, CHUNK_BYTES, bar0 + (B_KV + i) * 8);
                }
                const uint8_t* wsrc = g_Wo + ct * WO_TILE_BYTES;
                prefetch_tmap(&tmOut);
                mbar_wait_sleep(bar0 + B_BASE * 8, 500);
#pragma unroll 1
                for (int p = 0; p < 9; p++) {
                    if (p > 0) mbar_wait_sleep(bar0 + (B_FREE + p - 1) * 8, p == 1 ? 500 : 40);
                    const int k = ks0 + p * 3 >= 36 ? ks0 + p * 3 - 36 : ks0 + p * 3;
                    mbar_expect(bar0 + (B_WO + p) * 8, 13824);
                    bulk_load(sb + (p == 0 ? sm_piece(0) : (p == 1 ? sm_piece(1) : SM_KV + (p - 2) * PIECE)), wsrc + k * 4608, 13824, bar0 + (B_WO + p) * 8);
                }
                const int kl = ks0 == 0 ? 27 : ks0 - 9;
                mbar_expect(bar0 + B_LATE * 8, 9 * 4608);
                bulk_load(sb + sm_wstep(27), wsrc + kl * 4608, 8 * 4608, bar0 + B_LATE * 8);
                bulk_load(sb + sm_wstep(35), wsrc + (kl + 8) * 4608, 4608, bar0 + B_LATE * 8);
            }
        } else {
            const int ht = tid - 288;
            if (ht == 64) prefetch_l2(wqkv + blockIdx.x * (DM * 3 * DM / 128), DM * 3 * DM / 64);
            if (ht < 72) {
                const uint4 v = __ldg(reinterpret_cast<const uint4*>(b1 + j * 576) + ht);
                uint32_t* sbias = reinterpret_cast<uint32_t*>(smem + K1_OFF_BIAS) + (ht >> 3) * 32 + (ht & 7);
                sbias[0] = v.x; sbias[8] = v.y; sbias[16] = v.z; sbias[24] = v.w;
            }
            asm volatile("bar.arrive 4, 352;" ::: "memory");
            PROFH(37);
#pragma unroll 1
            for (int i = ht; i < 512; i += 96) {
                const int key = i & 127;
                uint8_t* p = g_QKV + (size_t)(j * 4 + (i >> 7)) * KV_HEAD_BYTES + (rb * 16 + (key >> 3)) * KV_GROUP_BYTES + 512 + (key & 7) * 16;
                *reinterpret_cast<uint32_t*>(p + 4) = ((POLY_MASK >> (key >> 3)) & 1) ? 0x3F804000u : 0x00003F80u;
                *reinterpret_cast<uint32_t*>(p + 12) = 0x00003F80u;
            }
            if (ht == 32) prefetch_l2(w1 + blockIdx.x * (DM * FF / 128), DM * FF / 64);
#pragma unroll 2
            for (int i = blockIdx.x * 324 + ht; i < blockIdx.x * 324 + 324; i += 96) {
                const int k = i / 72, nc = i - k * 72, c4 = nc / 18;
                *reinterpret_cast<uint4*>(g_Wo + c4 * WO_TILE_BYTES + (k >> 3) * 2304 + (nc - c4 * 18) * 128 + (k & 7) * 16) =
                    __ldg(reinterpret_cast<const uint4*>(wo) + i);
            }
            PROFH(38);
            named_bar_sync(3, 352);
            if (ht == 32) prefetch_l2(w2 + blockIdx.x * (DM * FF / 128), DM * FF / 64);
            if (ht == 0) {
                flag_signal(&g_flags.qkv_stored[rb]);
                flag_wait(&g_flags.qkv_stored[rb], 8, 200);
            }
            named_bar_sync(7, 96);
            PROFH(39);
#pragma unroll 1
            for (int i = warp - 9; i < 16; i += 3) {
                const int hd = j * 4 + (i >> 2), key = (i & 3) * 32 + lane;
                const uint8_t* p = g_QKV + (size_t)hd * KV_HEAD_BYTES + (rb * 16 + (key >> 3)) * KV_GROUP_BYTES + (key & 7) * 16;
                const uint4 a = __ldcg(reinterpret_cast<const uint4*>(p)), b = __ldcg(reinterpret_cast<const uint4*>(p + 128));
                float n = sumsq2(__ldcg(reinterpret_cast<const uint32_t*>(p + 512))) + sumsq8(a) + sumsq8(b);
                if ((POLY_MASK >> (key >> 3)) & 1) n *= 0.25f;
#pragma unroll
                for (int o = 16; o; o >>= 1) n = fmaxf(n, __shfl_xor_sync(~0u, n, o));
                if (lane == 0) g_kmax[hd * 64 + rb * 4 + (i & 3)] = n;
            }
            named_bar_sync(7, 96);
            PROFH(40);
            if (ht == 0) {
                flag_signal(&g_flags.kv_ready);
                flag_wait(&g_flags.kv_ready, 128, 300);
                mbar_wait_sleep(bar0 + B_XNDEAD * 8, 300);
            }
            named_bar_sync(7, 96);
            PROFH(41);
            float kmax2;
            {
                const float2 v = __ldcg(reinterpret_cast<const float2*>(g_kmax + head * 64 + lane * 2));
                kmax2 = fmaxf(v.x, v.y);
#pragma unroll
                for (int o = 16; o; o >>= 1) kmax2 = fmaxf(kmax2, __shfl_xor_sync(~0u, kmax2, o));
            }
            asm volatile("fence.proxy.async;" ::: "memory");
            int chunk = warp - 9;
#pragma unroll 1
            for (int r = ht; r < 512; r += 96) {
                if (lane == 0 && chunk < 11) {
                    mbar_expect(bar0 + (B_KV + chunk) * 8, CHUNK_BYTES);
                    bulk_load(sb + SM_KV + chunk * CHUNK_BYTES, kvsrc + chunk * CHUNK_BYTES, CHUNK_BYTES, bar0 + (B_KV + chunk) * 8);
                }
                chunk += 3;
                const uint8_t* p = kvsrc + Q_OFFSET + (quarter * 64 + (((r >> 3) + rot * 16) & 63)) * KV_GROUP_BYTES + (r & 7) * 16;
                const uint4 a = __ldcg(reinterpret_cast<const uint4*>(p)), b = __ldcg(reinterpret_cast<const uint4*>(p + 128));
                const uint32_t e = __ldcg(reinterpret_cast<const uint32_t*>(p + 256));
                const float cc = sqrtf((sumsq2(e) + sumsq8(a) + sumsq8(b)) * kmax2) * 1.02f;
                if (!(cc <= 58.f)) *slow_flag = 1;
                uint4* dst = reinterpret_cast<uint4*>(smem + SM_Q + (r >> 3) * 512 + (r & 7) * 16);
                dst[0] = a;
                dst[8] = b;
                dst[16] = make_uint4(e, pack_bf16(-cc, 768.f), 0u, 0u);
                dst[24] = make_uint4(0u, POLY_MODE ? 0xBFFF0000u : 0xC0000000u, 0u, 0u);
            }
            named_bar_sync(7, 96);
            if (*slow_flag) {
#pragma unroll 1
                for (int r = ht; r < 512; r += 96) {
                    uint32_t* dst = reinterpret_cast<uint32_t*>(smem + SM_Q + (r >> 3) * 512 + (r & 7) * 16);
                    dst[65] = 0u;
                    dst[97] = 0u;
                }
            }
            fence_proxy_async();
            __syncwarp();
            if (lane == 0) mbar_arrive(bar0 + B_QRDY * 8);
            PROFH(42);
            if (ht == 0) {
                mbar_wait_sleep(bar0 + B_FFN * 8, 300);
                flag_signal(&g_flags.ffn_done[rb]);
                flag_wait(&g_flags.ffn_done[rt >> 1], 8, 300);
            }
            named_bar_sync(7, 96);
            {
                const int w3 = warp - 9;
                const uint32_t rbar = bar0 + (B_RED + w3 * 2) * 8, rbuf = SM_RED + w3 * 8192;
                const int u0 = ((rt >> 1) * 36 + ct * 9) * 256 + (rt & 1) * 128;
                mbar_wait_sleep(bar0 + (B_KV + 15) * 8, 500);
                asm volatile("fence.proxy.async;" ::: "memory");
#pragma unroll 1
                for (int i = -2; i < 12; i++) {
                    if (i >= 0) {
                        __nanosleep(400);
                        mbar_wait(rbar + (i & 1) * 8, (i >> 1) & 1);
                        const uint4* sp = reinterpret_cast<const uint4*>(smem + rbuf + (i & 1) * 4096) + lane;
                        const uint4 v = hadd8_bf16(hadd8_bf16(hadd8_bf16(sp[0], sp[32]), hadd8_bf16(sp[64], sp[96])),
                                                   hadd8_bf16(hadd8_bf16(sp[128], sp[160]), hadd8_bf16(sp[192], sp[224])));
                        const int bx = i * 3 + w3;
                        uint2* fp = g_ffn + (blockIdx.x * 18 + (bx >> 2) * 2) * 128 + (bx & 3) * 32 + lane;
                        fp[0] = make_uint2(v.x, v.y);
                        fp[128] = make_uint2(v.z, v.w);
                    }
                    __syncwarp();
                    if (lane == 0 && i < 10) {
                        const int bx = (i + 2) * 3 + w3;
                        mbar_expect(rbar + (i & 1) * 8, 4096);
                        tma2d(sb + rbuf + (i & 1) * 4096, &tmP, (u0 + (bx >> 2) * 256 + (bx & 3) * 32) * 2, 0, rbar + (i & 1) * 8);
                    }
                }
            }
            __syncwarp();
            if (lane == 0) mbar_arrive(bar0 + B_BASE * 8);
            PROFH(43);
            if (ht == 0 || ht == 64) {
                const int w = ht >> 6;
#pragma unroll 1
                for (int p = 0; p < 4; p++) {
                    if (p == 3) mbar_wait_sleep(bar0 + (B_FREE + 6) * 8, 300);
                    mbar_wait_sleep(bar0 + (B_OS + p * 2 + w) * 8, p == 3 ? 20 : 300);
                    flag_signal(&g_flags.o_done[quarter * 8 + ((p + rot) & 3) * 2 + w][p == 3]);
                }
            } else if (ht == 32) {
                const uint8_t* osrc = reinterpret_cast<const uint8_t*>(g_O) + rt * 73728;
                mbar_wait_sleep(bar0 + B_BASE * 8, 500);
                mbar_wait_sleep(bar0 + B_FREE * 8, 500);
                flag_wait(&g_flags.o_done[rt][0], 24, 100);
                asm volatile("fence.proxy.async;" ::: "memory");
#pragma unroll 1
                for (int p = 0; p < 9; p++) {
                    if (p > 1) mbar_wait_sleep(bar0 + (B_FREE + p - 1) * 8, 40);
                    const int k = ks0 + p * 3 >= 36 ? ks0 + p * 3 - 36 : ks0 + p * 3;
                    mbar_expect(bar0 + (B_WO + p) * 8, 6144);
                    bulk_load(sb + 13824 + (p == 0 ? sm_piece(0) : (p == 1 ? sm_piece(1) : SM_KV + (p - 2) * PIECE)), osrc + k * 2048, 6144, bar0 + (B_WO + p) * 8);
                }
                mbar_expect(bar0 + B_LATE * 8, 9 * 2048);
                mbar_wait(bar0 + B_EARLY * 8, 0);
                flag_wait(&g_flags.o_done[rt][1], 8, 0);
                asm volatile("fence.proxy.async;" ::: "memory");
                bulk_load(sb + sm_ostep(27), osrc + (ks0 == 0 ? 27 : ks0 - 9) * 2048, 9 * 2048, bar0 + B_LATE * 8);
                if (atomicAdd(&g_flags.exited, 1u) == gridDim.x - 1) {
                    unsigned int* f = reinterpret_cast<unsigned int*>(&g_flags);
#pragma unroll 1
                    for (int i = 0; i < (int)(sizeof(Flags) / 4); i++) f[i] = 0;
                }
            }
        }
    }
}

typedef CUresult (*EncodeFn)(CUtensorMap*, CUtensorMapDataType, cuuint32_t, void*, const cuuint64_t*, const cuuint64_t*, const cuuint32_t*,
                             const cuuint32_t*, CUtensorMapInterleave, CUtensorMapSwizzle, CUtensorMapL2promotion, CUtensorMapFloatOOBfill);

void make_map(EncodeFn fn, CUtensorMap* m, const void* base, int rank, const cuuint64_t* dims, const cuuint64_t* strides, const cuuint32_t* box) {
    cuuint32_t es[4] = {1, 1, 1, 1};
    fn(m, CU_TENSOR_MAP_DATA_TYPE_BFLOAT16, rank, const_cast<void*>(base), dims, strides, box, es, CU_TENSOR_MAP_INTERLEAVE_NONE,
       CU_TENSOR_MAP_SWIZZLE_128B, CU_TENSOR_MAP_L2_PROMOTION_L2_256B, CU_TENSOR_MAP_FLOAT_OOB_FILL_NONE);
}

}

extern "C" void kernel_launch(void* const* d_in, const int* in_sizes, int n_in, void* d_out, int out_size) {
    const __nv_bfloat16* x = (const __nv_bfloat16*)d_in[0];
    const __nv_bfloat16* wqkv = (const __nv_bfloat16*)d_in[1];
    const __nv_bfloat16* wo = (const __nv_bfloat16*)d_in[2];
    const __nv_bfloat16* w1 = (const __nv_bfloat16*)d_in[4];
    const __nv_bfloat16* b1 = (const __nv_bfloat16*)d_in[5];
    const __nv_bfloat16* w2 = (const __nv_bfloat16*)d_in[6];
    const __nv_bfloat16* b2 = (const __nv_bfloat16*)d_in[7];
    __nv_bfloat16* out = (__nv_bfloat16*)d_out;

    EncodeFn fn = nullptr;
    cudaDriverEntryPointQueryResult qr;
    cudaGetDriverEntryPoint("cuTensorMapEncodeTiled", (void**)&fn, cudaEnableDefault, &qr);
    CUtensorMap tmX, tmQ3, tmQ1, tm1, tm2, tmP, tmOut;
    {
        cuuint64_t d[2] = {DM, SEQ}, s[1] = {DM * 2};
        cuuint32_t b[2] = {72, 64}, es[2] = {1, 1};
        fn(&tmOut, CU_TENSOR_MAP_DATA_TYPE_BFLOAT16, 2, out, d, s, b, es, CU_TENSOR_MAP_INTERLEAVE_NONE, CU_TENSOR_MAP_SWIZZLE_NONE,
           CU_TENSOR_MAP_L2_PROMOTION_NONE, CU_TENSOR_MAP_FLOAT_OOB_FILL_NONE);
    }
    {
        void* gp = nullptr;
        cudaGetSymbolAddress(&gp, g_part);
        cuuint64_t d[2] = {SLAB * 2, 8}, s[1] = {SLAB * 16};
        cuuint32_t b[2] = {64, 8}, es[2] = {1, 1};
        fn(&tmP, CU_TENSOR_MAP_DATA_TYPE_INT64, 2, gp, d, s, b, es, CU_TENSOR_MAP_INTERLEAVE_NONE, CU_TENSOR_MAP_SWIZZLE_NONE,
           CU_TENSOR_MAP_L2_PROMOTION_NONE, CU_TENSOR_MAP_FLOAT_OOB_FILL_NONE);
    }
    {
        cuuint64_t d[4] = {64, 8, 9, SEQ / 8}, s[3] = {DM * 2, 128, DM * 2 * 8};
        cuuint32_t b[4] = {64, 8, 3, 2};
        make_map(fn, &tmX, x, 4, d, s, b);
    }
    {
        cuuint64_t d[3] = {3 * DM, DM, 3}, s[2] = {3 * DM * 2, 128};
        cuuint32_t b[3] = {64, 16, 3};
        make_map(fn, &tmQ3, wqkv, 3, d, s, b);
        make_map(fn, &tmQ1, wqkv, 2, d, s, b);
    }
    {
        cuuint64_t d[2] = {FF, DM}, s[1] = {FF * 2};
        cuuint32_t b[2] = {64, 64};
        make_map(fn, &tm1, w1, 2, d, s, b);
        cuuint64_t d2[2] = {DM, FF}, s2[1] = {DM * 2};
        make_map(fn, &tm2, w2, 2, d2, s2, b);
    }
    cudaFuncSetAttribute(fused_kernel, cudaFuncAttributeMaxDynamicSharedMemorySize, K1_SMEM);
    fused_kernel<<<128, 384, K1_SMEM, cudaStreamPerThread>>>(tmX, tmQ3, tmQ1, tm1, tm2, tmP, tmOut, b1, wqkv, w1, w2, wo, x, b2, 0ull);
}
```

```cpp
#include <cuda_runtime.h>
#include <cuda_bf16.h>
#include <cuda.h>
#include <stdint.h>

#define PROF(i) do { } while (0)
#define PROFT(i) do { } while (0)
#define PROFH(i) do { } while (0)
#define PROFWT(i) do { } while (0)
#define PROF_WG 0

namespace {

constexpr int SEQ = 2048, DM = 576, FF = 4608, NH = 32, DH = 18;

constexpr int KV_GROUP_BYTES = 5 * 128;
constexpr int KV_HEAD_BYTES = (SEQ / 8) * KV_GROUP_BYTES;
constexpr int Q_OFFSET = NH * KV_HEAD_BYTES;
#define POLY_MASK 0xB6B6
__device__ __align__(1024) uint8_t g_QKV[2 * NH * KV_HEAD_BYTES];
__device__ __align__(1024) float g_kmax[NH * 64];
constexpr int SLAB = 16 * 36 * 256;
__device__ __align__(1024) uint4 g_part[8 * SLAB];
__device__ __align__(1024) uint2 g_ffn[128 * 18 * 128];
__device__ __align__(1024) uint32_t g_O[SEQ * DM / 2];
struct Flags {
    unsigned int qkv_stored[16];
    unsigned int ffn_done[16];
    unsigned int o_done[32];
    unsigned int kv_ready;
    unsigned int exited;
};
__device__ Flags g_flags;
__device__ __align__(1024) uint4 g_Olate[32 * 9 * 128];
constexpr uint32_t O_EMPTY = 0xFFFFFFFFu;
constexpr int WO_TILE_BYTES = DM * 144 * 2;
__device__ __align__(1024) uint8_t g_Wo[4 * WO_TILE_BYTES];

__device__ __forceinline__ uint32_t s2u(const void* p) { return (uint32_t)__cvta_generic_to_shared(p); }
__device__ __forceinline__ void mbar_init(uint32_t b, int c) { asm volatile("mbarrier.init.shared::cta.b64 [%0], %1;" ::"r"(b), "r"(c) : "memory"); }
__device__ __forceinline__ void mbar_expect(uint32_t b, uint32_t bytes) {
    asm volatile("mbarrier.arrive.expect_tx.shared::cta.b64 _, [%0], %1;" ::"r"(b), "r"(bytes) : "memory");
}
__device__ __forceinline__ void mbar_wait(uint32_t b, uint32_t parity) {
    asm volatile(
        "{\n.reg .pred p;\n.reg .u32 c;\n"
        "mov.u32 c, 0;\n"
        "LOOP:\n"
        "mbarrier.try_wait.parity.shared::cta.b64 p, [%0], %1;\n"
        "@p bra DONE;\n"
        "add.u32 c, c, 1;\n"
        "setp.lt.u32 p, c, 4194304;\n"
        "@p bra LOOP;\n"
        "trap;\n"
        "DONE:\n}\n" ::"r"(b), "r"(parity) : "memory");
}
__device__ __forceinline__ void fence_barrier_init() { asm volatile("fence.mbarrier_init.release.cluster;" ::: "memory"); }
__device__ __forceinline__ void fence_proxy_async() { asm volatile("fence.proxy.async.shared::cta;" ::: "memory"); }
__device__ __forceinline__ void cluster_arrive() { asm volatile("barrier.cluster.arrive.relaxed.aligned;" ::: "memory"); }
__device__ __forceinline__ void cluster_wait() { asm volatile("barrier.cluster.wait.aligned;" ::: "memory"); }
__device__ __forceinline__ void named_bar_sync(int id, int n) { asm volatile("bar.sync %0, %1;" ::"r"(id), "r"(n) : "memory"); }

__device__ __forceinline__ void tma3d_mc(uint32_t dst, const CUtensorMap* tm, int c0, int c1, int c2, uint32_t bar, uint16_t mask) {
    asm volatile("cp.async.bulk.tensor.3d.shared::cluster.global.mbarrier::complete_tx::bytes.multicast::cluster [%0], [%1, {%3, %4, %5}], [%2], %6;"
                 ::"r"(dst), "l"(tm), "r"(bar), "r"(c0), "r"(c1), "r"(c2), "h"(mask) : "memory");
}
__device__ __forceinline__ void tma2d_mc(uint32_t dst, const CUtensorMap* tm, int c0, int c1, uint32_t bar, uint16_t mask) {
    asm volatile("cp.async.bulk.tensor.2d.shared::cluster.global.mbarrier::complete_tx::bytes.multicast::cluster [%0], [%1, {%3, %4}], [%2], %5;"
                 ::"r"(dst), "l"(tm), "r"(bar), "r"(c0), "r"(c1), "h"(mask) : "memory");
}
__device__ __forceinline__ void tma4d(uint32_t dst, const CUtensorMap* tm, int c0, int c1, int c2, int c3, uint32_t bar) {
    asm volatile("cp.async.bulk.tensor.4d.shared::cluster.global.mbarrier::complete_tx::bytes [%0], [%1, {%3, %4, %5, %6}], [%2];"
                 ::"r"(dst), "l"(tm), "r"(bar), "r"(c0), "r"(c1), "r"(c2), "r"(c3) : "memory");
}
__device__ __forceinline__ void tma2d(uint32_t dst, const CUtensorMap* tm, int c0, int c1, uint32_t bar) {
    asm volatile("cp.async.bulk.tensor.2d.shared::cluster.global.mbarrier::complete_tx::bytes [%0], [%1, {%3, %4}], [%2];"
                 ::"r"(dst), "l"(tm), "r"(bar), "r"(c0), "r"(c1) : "memory");
}
__device__ __forceinline__ void bulk_load(uint32_t dst, const void* src, uint32_t bytes, uint32_t bar) {
    asm volatile("cp.async.bulk.shared::cluster.global.mbarrier::complete_tx::bytes [%0], [%1], %2, [%3];"
                 ::"r"(dst), "l"(src), "r"(bytes), "r"(bar) : "memory");
}
__device__ __forceinline__ void prefetch_l2(const void* p, uint32_t bytes) {
    asm volatile("cp.async.bulk.prefetch.L2.global [%0], %1;" ::"l"(p), "r"(bytes) : "memory");
}
__device__ __forceinline__ void prefetch_tmap(const CUtensorMap* tm) { asm volatile("prefetch.tensormap [%0];" ::"l"(tm) : "memory"); }

__device__ __forceinline__ void wg_fence() { asm volatile("wgmma.fence.sync.aligned;" ::: "memory"); }
__device__ __forceinline__ void wg_commit() { asm volatile("wgmma.commit_group.sync.aligned;" ::: "memory"); }
template <int N> __device__ __forceinline__ void wg_wait() { asm volatile("wgmma.wait_group.sync.aligned %0;" ::"n"(N) : "memory"); }
template <int N> __device__ __forceinline__ void reg_fence(float (&d)[N]) {
#pragma unroll
    for (int i = 0; i < N; i++) asm volatile("" : "+f"(d[i])::"memory");
}
template <int N> __device__ __forceinline__ void reg_fence(uint32_t (&d)[N]) {
#pragma unroll
    for (int i = 0; i < N; i++) asm volatile("" : "+r"(d[i])::"memory");
}
template <int R> __device__ __forceinline__ void reg_alloc() { asm volatile("setmaxnreg.inc.sync.aligned.u32 %0;" ::"n"(R)); }
template <int R> __device__ __forceinline__ void reg_dealloc() { asm volatile("setmaxnreg.dec.sync.aligned.u32 %0;" ::"n"(R)); }

__device__ __forceinline__ uint64_t mk_desc(uint64_t z, uint32_t addr, uint32_t lbo, uint32_t sbo, uint32_t swz) {
    return z + ((uint64_t)(((addr & 0x3FFFF) >> 4) | ((lbo >> 4) << 16)) | ((uint64_t)((sbo >> 4) | (swz << 30)) << 32));
}
__device__ __forceinline__ uint32_t pack_bf16(float lo, float hi) {
    uint32_t r;
    asm("cvt.rn.bf16x2.f32 %0, %1, %2;" : "=r"(r) : "f"(hi), "f"(lo));
    return r;
}
__device__ __forceinline__ float bf_lo(uint32_t w) { return __uint_as_float(w << 16); }
__device__ __forceinline__ float bf_hi(uint32_t w) { return __uint_as_float(w & 0xFFFF0000u); }
__device__ __forceinline__ float ex2(float x) {
    float r;
    asm("ex2.approx.ftz.f32 %0, %1;" : "=f"(r) : "f"(x));
    return r;
}
__device__ __forceinline__ float tanh_fast(float x) {
    float r;
    asm("tanh.approx.f32 %0, %1;" : "=f"(r) : "f"(x));
    return r;
}
__device__ __forceinline__ uint32_t hfma2_bf16(uint32_t a, uint32_t b, uint32_t c) {
    uint32_t r;
    asm("fma.rn.bf16x2 %0, %1, %2, %3;" : "=r"(r) : "r"(a), "r"(b), "r"(c));
    return r;
}
__device__ __forceinline__ uint32_t hadd2_bf16(uint32_t a, uint32_t b) {
    uint32_t r;
    asm("add.rn.bf16x2 %0, %1, %2;" : "=r"(r) : "r"(a), "r"(b));
    return r;
}
__device__ __forceinline__ void ldsm4(uint32_t (&a)[4], uint32_t addr) {
    asm volatile("ldmatrix.sync.aligned.m8n8.x4.shared.b16 {%0, %1, %2, %3}, [%4];" : "=r"(a[0]), "=r"(a[1]), "=r"(a[2]), "=r"(a[3]) : "r"(addr) : "memory");
}
__device__ __forceinline__ void stsm4(uint32_t addr, const uint32_t (&a)[4]) {
    asm volatile("stmatrix.sync.aligned.m8n8.x4.shared.b16 [%0], {%1, %2, %3, %4};" ::"r"(addr), "r"(a[0]), "r"(a[1]), "r"(a[2]), "r"(a[3]) : "memory");
}
__device__ __forceinline__ void mma16816(float (&c)[4], const uint32_t (&a)[4], uint32_t b0, uint32_t b1) {
    asm("mma.sync.aligned.m16n8k16.row.col.f32.bf16.bf16.f32 {%0, %1, %2, %3}, {%4, %5, %6, %7}, {%8, %9}, {%0, %1, %2, %3};"
        : "+f"(c[0]), "+f"(c[1]), "+f"(c[2]), "+f"(c[3]) : "r"(a[0]), "r"(a[1]), "r"(a[2]), "r"(a[3]), "r"(b0), "r"(b1));
}
__device__ __forceinline__ float gelu2(float u) {
    const float w = fmaf(u * u, 0.0356774081f, 0.7978845608f);
    return fmaf(u, tanh_fast(u * w), u);
}

template<int TB, int AOFF, int BOFF> __device__ __forceinline__ void wgmma_ss_n216(float (&d)[108], uint64_t da, uint64_t db, int sd) {
    asm volatile("{\n.reg .pred p;\n.reg .b64 ta, tb;\nsetp.ne.b32 p, %110, 0;\nadd.s64 ta, %108, %112;\nadd.s64 tb, %109, %113;\n"
      "wgmma.mma_async.sync.aligned.m64n216k16.f32.bf16.bf16 {%0, %1, %2, %3, %4, %5, %6, %7, %8, %9, %10, %11, %12, %13, %14, %15, %16, %17, %18, %19, %20, %21, %22, %23, %24, %25, %26, %27, %28, %29, %30, %31, %32, %33, %34, %35, %36, %37, %38, %39, %40, %41, %42, %43, %44, %45, %46, %47, %48, %49, %50, %51, %52, %53, %54, %55, %56, %57, %58, %59, %60, %61, %62, %63, %64, %65, %66, %67, %68, %69, %70, %71, %72, %73, %74, %75, %76, %77, %78, %79, %80, %81, %82, %83, %84, %85, %86, %87, %88, %89, %90, %91, %92, %93, %94, %95, %96, %97, %98, %99, %100, %101, %102, %103, %104, %105, %106, %107}, ta, tb, p, 1, 1, 0, %111;\n}\n"
      : "+f"(d[0]), "+f"(d[1]), "+f"(d[2]), "+f"(d[3]), "+f"(d[4]), "+f"(d[5]), "+f"(d[6]), "+f"(d[7]), "+f"(d[8]), "+f"(d[9]), "+f"(d[10]), "+f"(d[11]), "+f"(d[12]), "+f"(d[13]), "+f"(d[14]), "+f"(d[15]), "+f"(d[16]), "+f"(d[17]), "+f"(d[18]), "+f"(d[19]), "+f"(d[20]), "+f"(d[21]), "+f"(d[22]), "+f"(d[23]), "+f"(d[24]), "+f"(d[25]), "+f"(d[26]), "+f"(d[27]), "+f"(d[28]), "+f"(d[29]), "+f"(d[30]), "+f"(d[31]), "+f"(d[32]), "+f"(d[33]), "+f"(d[34]), "+f"(d[35]), "+f"(d[36]), "+f"(d[37]), "+f"(d[38]), "+f"(d[39]), "+f"(d[40]), "+f"(d[41]), "+f"(d[42]), "+f"(d[43]), "+f"(d[44]), "+f"(d[45]), "+f"(d[46]), "+f"(d[47]), "+f"(d[48]), "+f"(d[49]), "+f"(d[50]), "+f"(d[51]), "+f"(d[52]), "+f"(d[53]), "+f"(d[54]), "+f"(d[55]), "+f"(d[56]), "+f"(d[57]), "+f"(d[58]), "+f"(d[59]), "+f"(d[60]), "+f"(d[61]), "+f"(d[62]), "+f"(d[63]), "+f"(d[64]), "+f"(d[65]), "+f"(d[66]), "+f"(d[67]), "+f"(d[68]), "+f"(d[69]), "+f"(d[70]), "+f"(d[71]), "+f"(d[72]), "+f"(d[73]), "+f"(d[74]), "+f"(d[75]), "+f"(d[76]), "+f"(d[77]), "+f"(d[78]), "+f"(d[79]), "+f"(d[80]), "+f"(d[81]), "+f"(d[82]), "+f"(d[83]), "+f"(d[84]), "+f"(d[85]), "+f"(d[86]), "+f"(d[87]), "+f"(d[88]), "+f"(d[89]), "+f"(d[90]), "+f"(d[91]), "+f"(d[92]), "+f"(d[93]), "+f"(d[94]), "+f"(d[95]), "+f"(d[96]), "+f"(d[97]), "+f"(d[98]), "+f"(d[99]), "+f"(d[100]), "+f"(d[101]), "+f"(d[102]), "+f"(d[103]), "+f"(d[104]), "+f"(d[105]), "+f"(d[106]), "+f"(d[107])
      : "l"(da), "l"(db), "r"(sd), "n"(TB), "n"(AOFF), "n"(BOFF));
}

template<int TB, int AOFF, int BOFF> __device__ __forceinline__ void wgmma_ss_n64(float (&d)[32], uint64_t da, uint64_t db, int sd) {
    asm volatile("{\n.reg .pred p;\n.reg .b64 ta, tb;\nsetp.ne.b32 p, %34, 0;\nadd.s64 ta, %32, %36;\nadd.s64 tb, %33, %37;\n"
      "wgmma.mma_async.sync.aligned.m64n64k16.f32.bf16.bf16 {%0, %1, %2, %3, %4, %5, %6, %7, %8, %9, %10, %11, %12, %13, %14, %15, %16, %17, %18, %19, %20, %21, %22, %23, %24, %25, %26, %27, %28, %29, %30, %31}, ta, tb, p, 1, 1, 0, %35;\n}\n"
      : "+f"(d[0]), "+f"(d[1]), "+f"(d[2]), "+f"(d[3]), "+f"(d[4]), "+f"(d[5]), "+f"(d[6]), "+f"(d[7]), "+f"(d[8]), "+f"(d[9]), "+f"(d[10]), "+f"(d[11]), "+f"(d[12]), "+f"(d[13]), "+f"(d[14]), "+f"(d[15]), "+f"(d[16]), "+f"(d[17]), "+f"(d[18]), "+f"(d[19]), "+f"(d[20]), "+f"(d[21]), "+f"(d[22]), "+f"(d[23]), "+f"(d[24]), "+f"(d[25]), "+f"(d[26]), "+f"(d[27]), "+f"(d[28]), "+f"(d[29]), "+f"(d[30]), "+f"(d[31])
      : "l"(da), "l"(db), "r"(sd), "n"(TB), "n"(AOFF), "n"(BOFF));
}

template<int TB, int AOFF, int BOFF> __device__ __forceinline__ void wgmma_ss_n128(float (&d)[64], uint64_t da, uint64_t db, int sd) {
    asm volatile("{\n.reg .pred p;\n.reg .b64 ta, tb;\nsetp.ne.b32 p, %66, 0;\nadd.s64 ta, %64, %68;\nadd.s64 tb, %65, %69;\n"
      "wgmma.mma_async.sync.aligned.m64n128k16.f32.bf16.bf16 {%0, %1, %2, %3, %4, %5, %6, %7, %8, %9, %10, %11, %12, %13, %14, %15, %16, %17, %18, %19, %20, %21, %22, %23, %24, %25, %26, %27, %28, %29, %30, %31, %32, %33, %34, %35, %36, %37, %38, %39, %40, %41, %42, %43, %44, %45, %46, %47, %48, %49, %50, %51, %52, %53, %54, %55, %56, %57, %58, %59, %60, %61, %62, %63}, ta, tb, p, 1, 1, 0, %67;\n}\n"
      : "+f"(d[0]), "+f"(d[1]), "+f"(d[2]), "+f"(d[3]), "+f"(d[4]), "+f"(d[5]), "+f"(d[6]), "+f"(d[7]), "+f"(d[8]), "+f"(d[9]), "+f"(d[10]), "+f"(d[11]), "+f"(d[12]), "+f"(d[13]), "+f"(d[14]), "+f"(d[15]), "+f"(d[16]), "+f"(d[17]), "+f"(d[18]), "+f"(d[19]), "+f"(d[20]), "+f"(d[21]), "+f"(d[22]), "+f"(d[23]), "+f"(d[24]), "+f"(d[25]), "+f"(d[26]), "+f"(d[27]), "+f"(d[28]), "+f"(d[29]), "+f"(d[30]), "+f"(d[31]), "+f"(d[32]), "+f"(d[33]), "+f"(d[34]), "+f"(d[35]), "+f"(d[36]), "+f"(d[37]), "+f"(d[38]), "+f"(d[39]), "+f"(d[40]), "+f"(d[41]), "+f"(d[42]), "+f"(d[43]), "+f"(d[44]), "+f"(d[45]), "+f"(d[46]), "+f"(d[47]), "+f"(d[48]), "+f"(d[49]), "+f"(d[50]), "+f"(d[51]), "+f"(d[52]), "+f"(d[53]), "+f"(d[54]), "+f"(d[55]), "+f"(d[56]), "+f"(d[57]), "+f"(d[58]), "+f"(d[59]), "+f"(d[60]), "+f"(d[61]), "+f"(d[62]), "+f"(d[63])
      : "l"(da), "l"(db), "r"(sd), "n"(TB), "n"(AOFF), "n"(BOFF));
}

template<int TB, int AOFF, int BOFF> __device__ __forceinline__ void wgmma_ss_n72(float (&d)[36], uint64_t da, uint64_t db, int sd) {
    asm volatile("{\n.reg .pred p;\n.reg .b64 ta, tb;\nsetp.ne.b32 p, %38, 0;\nadd.s64 ta, %36, %40;\nadd.s64 tb, %37, %41;\n"
      "wgmma.mma_async.sync.aligned.m64n72k16.f32.bf16.bf16 {%0, %1, %2, %3, %4, %5, %6, %7, %8, %9, %10, %11, %12, %13, %14, %15, %16, %17, %18, %19, %20, %21, %22, %23, %24, %25, %26, %27, %28, %29, %30, %31, %32, %33, %34, %35}, ta, tb, p, 1, 1, 0, %39;\n}\n"
      : "+f"(d[0]), "+f"(d[1]), "+f"(d[2]), "+f"(d[3]), "+f"(d[4]), "+f"(d[5]), "+f"(d[6]), "+f"(d[7]), "+f"(d[8]), "+f"(d[9]), "+f"(d[10]), "+f"(d[11]), "+f"(d[12]), "+f"(d[13]), "+f"(d[14]), "+f"(d[15]), "+f"(d[16]), "+f"(d[17]), "+f"(d[18]), "+f"(d[19]), "+f"(d[20]), "+f"(d[21]), "+f"(d[22]), "+f"(d[23]), "+f"(d[24]), "+f"(d[25]), "+f"(d[26]), "+f"(d[27]), "+f"(d[28]), "+f"(d[29]), "+f"(d[30]), "+f"(d[31]), "+f"(d[32]), "+f"(d[33]), "+f"(d[34]), "+f"(d[35])
      : "l"(da), "l"(db), "r"(sd), "n"(TB), "n"(AOFF), "n"(BOFF));
}

template<int TB, int BOFF> __device__ __forceinline__ void wgmma_rs_n64(float (&d)[32], uint32_t a0, uint32_t a1, uint32_t a2, uint32_t a3, uint64_t db, int sd) {
    asm volatile("{\n.reg .pred p;\n.reg .b64 tb;\nsetp.ne.b32 p, %37, 0;\nadd.s64 tb, %36, %39;\n"
      "wgmma.mma_async.sync.aligned.m64n64k16.f32.bf16.bf16 {%0, %1, %2, %3, %4, %5, %6, %7, %8, %9, %10, %11, %12, %13, %14, %15, %16, %17, %18, %19, %20, %21, %22, %23, %24, %25, %26, %27, %28, %29, %30, %31}, {%32, %33, %34, %35}, tb, p, 1, 1, %38;\n}\n"
      : "+f"(d[0]), "+f"(d[1]), "+f"(d[2]), "+f"(d[3]), "+f"(d[4]), "+f"(d[5]), "+f"(d[6]), "+f"(d[7]), "+f"(d[8]), "+f"(d[9]), "+f"(d[10]), "+f"(d[11]), "+f"(d[12]), "+f"(d[13]), "+f"(d[14]), "+f"(d[15]), "+f"(d[16]), "+f"(d[17]), "+f"(d[18]), "+f"(d[19]), "+f"(d[20]), "+f"(d[21]), "+f"(d[22]), "+f"(d[23]), "+f"(d[24]), "+f"(d[25]), "+f"(d[26]), "+f"(d[27]), "+f"(d[28]), "+f"(d[29]), "+f"(d[30]), "+f"(d[31])
      : "r"(a0), "r"(a1), "r"(a2), "r"(a3), "l"(db), "r"(sd), "n"(TB), "n"(BOFF));
}

template<int TB, int BOFF> __device__ __forceinline__ void wgmma_rs_n24(float (&d)[12], uint32_t a0, uint32_t a1, uint32_t a2, uint32_t a3, uint64_t db, int sd) {
    asm volatile("{\n.reg .pred p;\n.reg .b64 tb;\nsetp.ne.b32 p, %17, 0;\nadd.s64 tb, %16, %19;\n"
      "wgmma.mma_async.sync.aligned.m64n24k16.f32.bf16.bf16 {%0, %1, %2, %3, %4, %5, %6, %7, %8, %9, %10, %11}, {%12, %13, %14, %15}, tb, p, 1, 1, %18;\n}\n"
      : "+f"(d[0]), "+f"(d[1]), "+f"(d[2]), "+f"(d[3]), "+f"(d[4]), "+f"(d[5]), "+f"(d[6]), "+f"(d[7]), "+f"(d[8]), "+f"(d[9]), "+f"(d[10]), "+f"(d[11])
      : "r"(a0), "r"(a1), "r"(a2), "r"(a3), "l"(db), "r"(sd), "n"(TB), "n"(BOFF));
}

template<int TB, int BOFF> __device__ __forceinline__ void wgmma_rs_n72(float (&d)[36], uint32_t a0, uint32_t a1, uint32_t a2, uint32_t a3, uint64_t db, int sd) {
    asm volatile("{\n.reg .pred p;\n.reg .b64 tb;\nsetp.ne.b32 p, %41, 0;\nadd.s64 tb, %40, %43;\n"
      "wgmma.mma_async.sync.aligned.m64n72k16.f32.bf16.bf16 {%0, %1, %2, %3, %4, %5, %6, %7, %8, %9, %10, %11, %12, %13, %14, %15, %16, %17, %18, %19, %20, %21, %22, %23, %24, %25, %26, %27, %28, %29, %30, %31, %32, %33, %34, %35}, {%36, %37, %38, %39}, tb, p, 1, 1, %42;\n}\n"
      : "+f"(d[0]), "+f"(d[1]), "+f"(d[2]), "+f"(d[3]), "+f"(d[4]), "+f"(d[5]), "+f"(d[6]), "+f"(d[7]), "+f"(d[8]), "+f"(d[9]), "+f"(d[10]), "+f"(d[11]), "+f"(d[12]), "+f"(d[13]), "+f"(d[14]), "+f"(d[15]), "+f"(d[16]), "+f"(d[17]), "+f"(d[18]), "+f"(d[19]), "+f"(d[20]), "+f"(d[21]), "+f"(d[22]), "+f"(d[23]), "+f"(d[24]), "+f"(d[25]), "+f"(d[26]), "+f"(d[27]), "+f"(d[28]), "+f"(d[29]), "+f"(d[30]), "+f"(d[31]), "+f"(d[32]), "+f"(d[33]), "+f"(d[34]), "+f"(d[35])
      : "r"(a0), "r"(a1), "r"(a2), "r"(a3), "l"(db), "r"(sd), "n"(TB), "n"(BOFF));
}

constexpr int K1_XN_BYTES = 16 * 9216;
constexpr int K1_OFF_RING = K1_XN_BYTES;
constexpr int K1_OFF_BIAS = K1_OFF_RING + 10 * 8192;
constexpr int K1_OFF_BAR = K1_OFF_BIAS + 576 * 2;
constexpr int K1_SMEM = K1_OFF_BAR + 800;
constexpr float QSCALE = 0.23570226039551584f * 1.4426950408889634f;

struct K1Ctx {
    uint32_t full0;
    uint32_t rel_addr;
    uint64_t descA, descB;
    uint32_t phase;
    __device__ __forceinline__ void begin_stage(int s) {
        mbar_wait(full0 + s * 8, phase);
        wg_fence();
    }
    __device__ __forceinline__ void release(int s) {
        if (rel_addr) asm volatile("mbarrier.arrive.shared::cluster.b64 _, [%0];" ::"r"(rel_addr + s * 8) : "memory");
    }
    __device__ __forceinline__ void end_stage(int s) {
        wg_commit();
        wg_wait<1>();
        release(s == 0 ? 8 : s - 1);
    }
};

__host__ __device__ constexpr int a_off(int ks) { return ((ks / 12) * 49152 + ((ks >> 2) % 3) * 1024 + (ks & 3) * 32) >> 4; }

template <int V> struct IC { static constexpr int value = V; };
template <int I, int N, class F> __device__ __forceinline__ void static_for(F&& f) {
    if constexpr (I < N) { f(IC<I>{}); static_for<I + 1, N>(f); }
}

template <bool A_RS, bool B_RS, class Epi>
__device__ __forceinline__ void tile_pair(K1Ctx& c, float (&accA)[32], float (&accB)[32], uint32_t (&h)[144], Epi&& epi) {
    static_for<0, 9>([&](auto sc) {
        constexpr int s = decltype(sc)::value;
        c.begin_stage(s);
        static_for<0, 8>([&](auto tc) {
            constexpr int kk = s * 8 + decltype(tc)::value, ks = kk % 36;
            constexpr int bo = (ks * 2048) >> 4;
            if constexpr (kk < 36) {
                if constexpr (A_RS) wgmma_rs_n64<1, bo>(accA, h[ks * 4], h[ks * 4 + 1], h[ks * 4 + 2], h[ks * 4 + 3], c.descB, ks != 0);
                else wgmma_ss_n64<1, a_off(ks), bo>(accA, c.descA, c.descB, ks != 0);
            } else {
                if constexpr (B_RS) wgmma_rs_n64<1, bo>(accB, h[ks * 4], h[ks * 4 + 1], h[ks * 4 + 2], h[ks * 4 + 3], c.descB, ks != 0);
                else wgmma_ss_n64<1, a_off(ks), bo>(accB, c.descA, c.descB, ks != 0);
            }
        });
        c.end_stage(s);
        epi(sc);
    });
    c.phase ^= 1;
}

template <int B0, int NB, int HOFF>
__device__ __forceinline__ void gelu_blocks(const float (&acc)[32], uint32_t (&h)[144], const uint32_t (&bq)[8], float rs0, float rs1) {
#pragma unroll
    for (int b = B0; b < B0 + NB; b++) {
        const float b0 = bf_lo(bq[b]), b1 = bf_hi(bq[b]);
        h[HOFF + b * 2 + 0] = pack_bf16(gelu2(fmaf(acc[b * 4 + 0], rs0, b0)), gelu2(fmaf(acc[b * 4 + 1], rs0, b1)));
        h[HOFF + b * 2 + 1] = pack_bf16(gelu2(fmaf(acc[b * 4 + 2], rs1, b0)), gelu2(fmaf(acc[b * 4 + 3], rs1, b1)));
    }
#pragma unroll
    for (int i = HOFF + B0 * 2; i < HOFF + (B0 + NB) * 2; i++) asm volatile("" : "+r"(h[i]));
}
__device__ __forceinline__ void load_bias(uint32_t (&bq)[8], uint32_t addr) {
    asm volatile("ld.shared.v4.u32 {%0, %1, %2, %3}, [%4];" : "=r"(bq[0]), "=r"(bq[1]), "=r"(bq[2]), "=r"(bq[3]) : "r"(addr));
    asm volatile("ld.shared.v4.u32 {%0, %1, %2, %3}, [%4 + 16];" : "=r"(bq[4]), "=r"(bq[5]), "=r"(bq[6]), "=r"(bq[7]) : "r"(addr));
}
template <int S> __device__ __forceinline__ void store_part(const float (&o)[32], uint4* p) {
    uint4 v;
    v.x = pack_bf16(o[S * 8 + 0], o[S * 8 + 1]); v.y = pack_bf16(o[S * 8 + 2], o[S * 8 + 3]);
    v.z = pack_bf16(o[S * 8 + 4], o[S * 8 + 5]); v.w = pack_bf16(o[S * 8 + 6], o[S * 8 + 7]);
    p[S * 256] = v;
}

constexpr int NCHUNK = 16;
constexpr int CHUNK_BYTES = KV_HEAD_BYTES / NCHUNK;
constexpr int SM_Q = 0;
constexpr int SM_KV = 32768;
constexpr int PIECE = 19968;
__host__ __device__ constexpr int sm_piece(int p) { return p == 0 ? 209408 : (p == 1 ? 0 : SM_KV + (p - 2) * PIECE); }
__host__ __device__ constexpr int sm_wstep(int k) { return k < 27 ? sm_piece(k / 3) + (k % 3) * 4608 : (k < 35 ? SM_KV + 7 * PIECE + (k - 27) * 4608 : PIECE); }
__host__ __device__ constexpr int sm_ostep(int k) { return sm_piece(k / 3) + 13824 + (k % 3) * 2048; }
constexpr int SM_RED = SM_KV + KV_HEAD_BYTES;

__device__ __forceinline__ float exp2_fixed(float y) {
    const float u = __uint_as_float(__float_as_uint(y) & 0xFF807FFFu) - 512.02545f;
    float t = fmaf(u, 0.019497588f, 0.114550486f);
    t = fmaf(t, u, -0.29839927f);
    return fmaf(t, u, y);
}
__device__ __forceinline__ uint32_t pack_fixed(float lo, float hi) { return __byte_perm(__float_as_uint(lo), __float_as_uint(hi), 0x6521); }

#define PV_GROUP 4
#define POLY_MODE 1
__device__ __forceinline__ uint32_t exp2_packed(float y0, float y1, uint32_t one2) {
    const uint32_t w = pack_fixed(y0, y1);
    uint32_t m;
    asm("lop3.b32 %0, %1, 0x007F007F, %2, 0xEA;" : "=r"(m) : "r"(w), "r"(one2));
    const uint32_t d = hfma2_bf16(m, 0x3EF93EF9u, 0xBF38BF38u);
    const uint32_t e = hfma2_bf16(d, d, 0xBD71BD71u);
    return hfma2_bf16(w, e, w);
}
constexpr int KV_TILE = CHUNK_BYTES / 16;
template <int OFF> __device__ __forceinline__ void issue_qk(float (&s)[64], uint64_t qd, uint64_t kd) {
    wgmma_ss_n128<0, 0, OFF + (8 << 16)>(s, qd, kd, 0);
    wgmma_ss_n128<0, 16, OFF + 32>(s, qd, kd, 1);
}
template <int OFF> __device__ __forceinline__ void issue_pv(float (&o)[12], const uint32_t (&p)[32], uint64_t vd) {
    static_for<0, 8>([&](auto kc) {
        constexpr int k = decltype(kc)::value;
        wgmma_rs_n24<1, OFF + k * (2 * KV_GROUP_BYTES / 16)>(o, p[k * 4], p[k * 4 + 1], p[k * 4 + 2], p[k * 4 + 3], vd, 1);
    });
}
template <int OFF>
__device__ __forceinline__ void softmax_pv(const float (&s)[64], uint32_t (&p)[32], float (&o)[12], uint64_t vd, uint32_t one2) {
    static_for<0, 8 / PV_GROUP>([&](auto gc) {
        constexpr int g0 = decltype(gc)::value * PV_GROUP;
#pragma unroll
        for (int b = g0 * 2; b < (g0 + PV_GROUP) * 2; b++) {
            if ((POLY_MASK >> b) & 1) {
                p[b * 2 + 0] = exp2_packed(s[b * 4 + 0], s[b * 4 + 1], one2);
                p[b * 2 + 1] = exp2_packed(s[b * 4 + 2], s[b * 4 + 3], one2);
            } else {
                p[b * 2 + 0] = pack_bf16(ex2(s[b * 4 + 0]), ex2(s[b * 4 + 1]));
                p[b * 2 + 1] = pack_bf16(ex2(s[b * 4 + 2]), ex2(s[b * 4 + 3]));
            }
        }
#pragma unroll
        for (int i = g0 * 4; i < (g0 + PV_GROUP) * 4; i++) asm volatile("" : "+r"(p[i])::"memory");
        wg_fence();
        static_for<g0, g0 + PV_GROUP>([&](auto kc) {
            constexpr int k = decltype(kc)::value;
            wgmma_rs_n24<1, OFF + k * (2 * KV_GROUP_BYTES / 16)>(o, p[k * 4], p[k * 4 + 1], p[k * 4 + 2], p[k * 4 + 3], vd, 1);
        });
    });
    wg_commit();
}
template <bool LATE> __device__ __forceinline__ void store_o(float (&o)[12], int rt, int head, int wq, int lane) {
    const int g = lane >> 2, q = lane & 3;
    const float i0 = __fdividef(1.0f, __shfl_sync(~0u, o[8], lane | 3)), i1 = __fdividef(1.0f, __shfl_sync(~0u, o[10], lane | 3));
#pragma unroll
    for (int i = 0; i < 3; i++) {
        const uint32_t w0 = pack_bf16(o[i * 4] * i0, o[i * 4 + 1] * i0), w1 = pack_bf16(o[i * 4 + 2] * i1, o[i * 4 + 3] * i1);
        if (i < 2 || q == 2) {
            if constexpr (LATE) {
                const int pc = (head & 7) * 9 + (i < 2 ? i * 4 + q : 8);
                uint32_t* op = reinterpret_cast<uint32_t*>(g_Olate) + (((rt * 9 + (pc >> 3)) * 128 + wq * 32 + g * 4 + (pc & 3)) * 4 + ((pc >> 2) & 1) * 2);
                asm volatile("st.relaxed.gpu.global.v2.u32 [%0], {%1, %2};" ::"l"(op), "r"(w0), "r"(w1) : "memory");
            } else {
                const int pc = head * 9 + (i < 2 ? i * 4 + q : 8);
                uint32_t* op = g_O + ((rt * 72 + (pc >> 2)) * 8 + wq * 2) * 32 + g * 4 + (pc & 3);
                op[0] = w0;
                op[32] = w1;
            }
        }
    }
#pragma unroll
    for (int i = 0; i < 12; i++) o[i] = 0.f;
}
__device__ __forceinline__ void mbar_arrive(uint32_t b) { asm volatile("mbarrier.arrive.shared::cta.b64 _, [%0];" ::"r"(b) : "memory"); }
__device__ __forceinline__ void mbar_wait_sleep(uint32_t b, uint32_t ns) {
    uint32_t ok, spins = 0;
    while (true) {
        asm volatile("{\n.reg .pred p;\nmbarrier.try_wait.parity.shared::cta.b64 p, [%1], 0;\nselp.u32 %0, 1, 0, p;\n}\n" : "=r"(ok) : "r"(b) : "memory");
        if (ok) break;
        __nanosleep(ns);
        if (++spins > (1u << 21)) __trap();
    }
}
__device__ __forceinline__ void flag_signal(unsigned int* f) {
    __threadfence();
    atomicAdd(f, 1u);
}
__device__ __forceinline__ void flag_wait(const unsigned int* f, unsigned int target, unsigned int sleep_ns) {
    uint32_t v, spins = 0;
    while (true) {
        asm volatile("ld.acquire.gpu.global.u32 %0, [%1];" : "=r"(v) : "l"(f) : "memory");
        if (v >= target) break;
        if (sleep_ns) __nanosleep(sleep_ns);
        if (++spins > (1u << 21)) __trap();
    }
}
__device__ __forceinline__ uint4 hadd8_bf16(const uint4 a, const uint4 b) {
    return make_uint4(hadd2_bf16(a.x, b.x), hadd2_bf16(a.y, b.y), hadd2_bf16(a.z, b.z), hadd2_bf16(a.w, b.w));
}
__device__ __forceinline__ float sumsq2(uint32_t w) { return fmaf(bf_lo(w), bf_lo(w), bf_hi(w) * bf_hi(w)); }
__device__ __forceinline__ float sumsq8(const uint4 v) { return (sumsq2(v.x) + sumsq2(v.y)) + (sumsq2(v.z) + sumsq2(v.w)); }

enum { B_FULL = 0, B_EMPTY = 9, B_BASE = 18, B_XNDEAD = 19, B_QRDY = 20, B_FFN = 21, B_KV = 22, B_FREE = 38, B_WO = 46, B_RED = 55, B_X = 61, B_EARLY = 85, B_OS = 86, B_LATE = 94, B_END = 95 };

__global__ void __cluster_dims__(2, 1, 1) __launch_bounds__(384, 1)
fused_kernel(const __grid_constant__ CUtensorMap tmX, const __grid_constant__ CUtensorMap tmQ3, const __grid_constant__ CUtensorMap tmQ1,
          const __grid_constant__ CUtensorMap tm1, const __grid_constant__ CUtensorMap tm2, const __grid_constant__ CUtensorMap tmP,
          const __grid_constant__ CUtensorMap tmOut, const __grid_constant__ CUtensorMap tmXo, const __nv_bfloat16* __restrict__ b1,
          const __nv_bfloat16* __restrict__ wqkv, const __nv_bfloat16* __restrict__ w1, const __nv_bfloat16* __restrict__ w2,
          const __nv_bfloat16* __restrict__ wo, const __nv_bfloat16* __restrict__ b2,
          const uint64_t zero) {
    extern __shared__ __align__(1024) uint8_t smem[];
    const uint32_t sb = s2u(smem);
    const int tid = threadIdx.x, lane = tid & 31;
    const int warp = __shfl_sync(~0u, tid >> 5, 0);
    const uint32_t rank = blockIdx.x & 1;
    const int cl = blockIdx.x >> 1;
    const int rb = (cl & 7) * 2 + rank;
    const int j = cl >> 3;
    const uint32_t bar0 = sb + K1_OFF_BAR;
    const uint32_t full0 = bar0 + B_FULL * 8, empty0 = bar0 + B_EMPTY * 8, xbar0 = bar0 + B_X * 8;
    const int head = blockIdx.x >> 2, quarter = blockIdx.x & 3;
    const int rt = quarter * 8 + (head >> 2), ct = head & 3;
    const int rot = head >> 3;
    const int ks0 = ((((head >> 3) + 2) & 3) * 9);
    volatile uint32_t* slow_flag = reinterpret_cast<volatile uint32_t*>(smem + K1_OFF_BAR + B_END * 8);

    if (warp < 8) {
        PROF(0);
        PROFT(48);
        if (lane == 0) {
#pragma unroll
            for (int i = 0; i < 3; i++) mbar_init(xbar0 + (warp * 3 + i) * 8, 1);
            fence_barrier_init();
#pragma unroll 1
            for (int i = 0; i < 3; i++) {
                const uint32_t xb = xbar0 + (warp * 3 + i) * 8;
                mbar_expect(xb, 6144);
                tma4d(sb + i * 49152 + warp * 6144, &tmX, 0, 0, i * 3, rb * 16 + warp * 2, xb);
            }
        }
        __syncwarp();
        cluster_arrive();
        PROF(22);
        reg_alloc<240>();
        PROF(23);
        float rs0, rs1;
        {
            const uint32_t la = sb + (warp * 2 + ((lane >> 3) & 1)) * 3072 + (lane & 7) * 128;
            uint32_t off[4];
#pragma unroll
            for (int i = 0; i < 4; i++) off[i] = la + (((i * 2 + (lane >> 4)) ^ (lane & 7)) << 4);
            float c1[4] = {0.f, 0.f, 0.f, 0.f}, c2[4] = {0.f, 0.f, 0.f, 0.f}, c3[4] = {0.f, 0.f, 0.f, 0.f};
            uint32_t a[36][4];
#pragma unroll
            for (int t = 0; t < 3; t++) {
                mbar_wait(xbar0 + (warp * 3 + t) * 8, 0);
                PROF(24 + t);
#pragma unroll
                for (int i = 0; i < 12; i++) ldsm4(a[t * 12 + i], off[i & 3] + t * 49152 + (i >> 2) * 1024);
#pragma unroll
                for (int i = t * 12; i < t * 12 + 12; i++) {
                    mma16816(c3, a[i], 0x3F803F80u, 0x3F803F80u);
                    mma16816(c1, a[i], a[i][0], a[i][2]);
                    mma16816(c2, a[i], a[i][1], a[i][3]);
                }
            }
            PROF(27);
            const int gg = lane >> 2, src = (lane & ~3) | (gg >> 1);
            const float m0 = c3[0] * (1.0f / DM), m1 = c3[2] * (1.0f / DM);
            const uint32_t mc0 = pack_bf16(-m0, -m0), mc1 = pack_bf16(-m1, -m1);
#pragma unroll
            for (int i = 0; i < 36; i++) {
#pragma unroll
                for (int k = 0; k < 4; k++) a[i][k] = hadd2_bf16(a[i][k], (k & 1) ? mc1 : mc0);
                stsm4(off[i & 3] + (i / 12) * 49152 + ((i >> 2) % 3) * 1024, a[i]);
            }
            const float q0 = __shfl_sync(~0u, (gg & 1) ? c1[1] : c1[0], src), q1 = __shfl_sync(~0u, (gg & 1) ? c2[3] : c2[2], src);
            rs0 = rsqrtf(fmaxf(fmaf(-m0, m0, q0 * (1.0f / DM)), 0.f) + 1e-5f);
            rs1 = rsqrtf(fmaxf(fmaf(-m1, m1, q1 * (1.0f / DM)), 0.f) + 1e-5f);
            if (__any_sync(~0u, fabsf(m0) * rs0 > 0.25f || fabsf(m1) * rs1 > 0.25f)) {
                const float d0 = -m0 - bf_lo(mc0), d1 = -m1 - bf_lo(mc1);
                const uint32_t md0 = pack_bf16(d0, d0), md1 = pack_bf16(d1, d1);
#pragma unroll 1
                for (int i = 0; i < 9; i++) {
#pragma unroll
                    for (int k4 = 0; k4 < 4; k4++) {
                        const uint32_t ad = off[k4] + (i / 3) * 49152 + (i % 3) * 1024;
                        uint32_t b[4];
                        ldsm4(b, ad);
#pragma unroll
                        for (int k = 0; k < 4; k++) b[k] = hadd2_bf16(b[k], (k & 1) ? md1 : md0);
                        stsm4(ad, b);
                    }
                }
            }
        }
        PROF(28);
        const int wg = warp >> 2, wq = warp & 3;
        fence_proxy_async();
        named_bar_sync(1 + wg, 128);
        cluster_wait();
        PROF(1);

        const int g = lane >> 2, q = lane & 3;
        K1Ctx c;
        c.full0 = full0;
        c.rel_addr = 0;
        c.descA = mk_desc(zero, sb + wg * 8 * 3072, 16, 3072, 1);
        c.descB = mk_desc(zero, sb + K1_OFF_RING, 2048, 1024, 1);
        c.phase = 0;
        uint32_t biasq = sb + K1_OFF_BIAS + q * 32;
        uint32_t bq[8];

        uint32_t h[144];
        float accA[32], accB[32];
        {
            float accQ[108];
            uint32_t rel = 0;
            if (lane == 0 && wq < 2) asm("mapa.shared::cluster.u32 %0, %1, %2;" : "=r"(rel) : "r"(empty0), "r"(wq));
#pragma unroll 1
            for (int r = 0; r < 2; r++) {
                static_for<0, 9>([&](auto sc) {
                    constexpr int s = decltype(sc)::value;
                    c.begin_stage(s);
                    const uint64_t da = c.descA + (r ? a_off(18 + 2 * s) : a_off(2 * s));
                    wgmma_ss_n216<1, 0, ((2 * s) % 9) * 512>(accQ, da, c.descB, (r | s) != 0);
                    wgmma_ss_n216<1, 2, ((2 * s + 1) % 9) * 512>(accQ, da, c.descB, 1);
                    c.end_stage(s);
                    c.rel_addr = rel;
                });
                c.phase ^= 1;
            }
            PROF(2); PROFWT(54);
            uint32_t rel9[9];
#pragma unroll
            for (int i9 = 0; i9 < 9; i9++) {
                const int p = 4 * i9 + q, hh = (p * 57) >> 9, r = p - 9 * hh;
                rel9[i9] = hh * KV_HEAD_BYTES + (r < 8 ? (r >> 2) * 128 + (r & 3) * 4 : 0);
            }
            uint32_t gb = 0, o2 = 0;
            float scl0 = 1.f, scl1 = 1.f;
            tile_pair<false, false>(c, accA, accB, h, [&](auto sc) {
                constexpr int s = decltype(sc)::value;
                if constexpr (s == 0) reg_fence(accQ);
                if constexpr (s < 6) {
                    constexpr int grp = s / 2, part = s % 2;
                    if constexpr (part == 0) {
                        const int G = 3 * j + grp, type = G >> 3;
                        gb = (G & 7) * 4 * KV_HEAD_BYTES + (rb * 16 + warp * 2) * KV_GROUP_BYTES + g * 16 + (type == 0 ? Q_OFFSET : (type == 2 ? 256 : 0));
                        o2 = type == 0 ? 256 : (type == 2 ? 264 : 512);
                        scl0 = rs0 * (type == 0 ? QSCALE : ((type == 1 && ((POLY_MASK >> (warp * 2)) & 1)) ? 2.f : 1.f));
                        scl1 = rs1 * (type == 0 ? QSCALE : ((type == 1 && ((POLY_MASK >> (warp * 2 + 1)) & 1)) ? 2.f : 1.f));
                    }
#pragma unroll
                    for (int i9 = part * 5; i9 < (part ? 9 : 5); i9++) {
                        const int b = grp * 9 + i9;
                        uint32_t off = gb + rel9[i9];
                        if (i9 >= 2 && (i9 & 1) == 0) off += (q == i9 / 2 - 1) ? o2 : 0;
                        *reinterpret_cast<uint32_t*>(g_QKV + off) = pack_bf16(accQ[b * 4] * scl0, accQ[b * 4 + 1] * scl0);
                        *reinterpret_cast<uint32_t*>(g_QKV + off + KV_GROUP_BYTES) = pack_bf16(accQ[b * 4 + 2] * scl1, accQ[b * 4 + 3] * scl1);
                    }
                    if constexpr (s == 5) asm volatile("bar.arrive 3, 352;" ::: "memory");
                }
                if constexpr (s == 4) { named_bar_sync(4, 352); load_bias(bq, biasq); }
                if constexpr (s == 5) reg_fence(accA);
                if constexpr (s >= 5) gelu_blocks<(s - 5) * 2, 2, 96>(accA, h, bq, rs0, rs1);
                if constexpr (s == 8) load_bias(bq, biasq + 128);
            });
        }
        PROF(3); PROFWT(55);
#pragma unroll
        for (int i = 32; i < 96; i++) asm volatile("mov.u32 %0, 0;" : "=r"(h[i]));
#pragma unroll 1
        for (int p = 1; p < 4; p++) {
            biasq += 256;
            tile_pair<false, false>(c, accA, accB, h, [&](auto sc) {
                constexpr int s = decltype(sc)::value;
                if constexpr (s == 0) {
                    reg_fence(accB);
#pragma unroll
                    for (int i = 0; i < 80; i++) h[i] = h[i + 32];
                }
                if constexpr (s < 4) gelu_blocks<s * 2, 2, 80>(accB, h, bq, rs0, rs1);
                if constexpr (s == 4) load_bias(bq, biasq);
                if constexpr (s == 5) reg_fence(accA);
                if constexpr (s >= 5) gelu_blocks<(s - 5) * 2, 2, 96>(accA, h, bq, rs0, rs1);
                if constexpr (s == 8) load_bias(bq, biasq + 128);
            });
        }
        PROF(4); PROFWT(56);
        tile_pair<false, true>(c, accA, accB, h, [&](auto sc) {
            constexpr int s = decltype(sc)::value;
            if constexpr (s == 0) reg_fence(accB);
            if constexpr (s < 4) gelu_blocks<s * 2, 2, 112>(accB, h, bq, rs0, rs1);
            if constexpr (s == 4) load_bias(bq, biasq + 256);
            if constexpr (s == 5) { reg_fence(accA); if (tid == wg * 128) mbar_arrive(bar0 + B_XNDEAD * 8); }
            if constexpr (s == 5 || s == 6) gelu_blocks<(s - 5) * 3, 3, 128>(accA, h, bq, rs0, rs1);
            if constexpr (s == 7) gelu_blocks<6, 2, 128>(accA, h, bq, rs0, rs1);
            if constexpr (s == 3 || s == 7) reg_fence(h);
        });
        PROF(5); PROFWT(57);
        uint4* pout = g_part + j * SLAB + rb * 36 * 256 + tid;
#pragma unroll 1
        for (int p = 0; p < 4; p++) {
            tile_pair<true, true>(c, accA, accB, h, [&](auto sc) {
                constexpr int s = decltype(sc)::value;
                if constexpr (s == 0) reg_fence(accB);
                if constexpr (s < 4) store_part<s>(accB, pout);
                if constexpr (s == 5) reg_fence(accA);
                if constexpr (s >= 5) store_part<s - 5>(accA, pout + 1024);
            });
            pout += 2048;
            PROF(6 + p);
        }
        wg_wait<0>();
        c.release(8);
        reg_fence(accB);
        store_part<0>(accB, pout); store_part<1>(accB, pout); store_part<2>(accB, pout); store_part<3>(accB, pout);
        __syncwarp();
        if (lane == 0) mbar_arrive(bar0 + B_FFN * 8);
        PROF(10); PROFWT(58);
        PROFT(49);

        mbar_wait(bar0 + B_QRDY * 8, 0);
        const uint32_t slow = __any_sync(~0u, *slow_flag != 0);
        const uint64_t kd0 = mk_desc(zero, sb + SM_KV, 0, KV_GROUP_BYTES, 0);
        const uint64_t vd0 = mk_desc(zero, sb + SM_KV + 256, KV_GROUP_BYTES, 128, 0);
        const uint64_t qd0 = mk_desc(zero, sb + SM_Q + wg * 4096, 128, 512, 0);
        const uint32_t kvbar = bar0 + B_KV * 8;
        float o[12];
#pragma unroll
        for (int i = 0; i < 12; i++) o[i] = 0.f;
        PROF(16);
        PROFT(50);
        if (!slow) {
            const uint32_t one2 = 0x3F803F80u + (uint32_t)zero;
            float s0[64], s1[64];
            uint32_t p0[32], p1[32];
            mbar_wait(kvbar, 0);
            reg_fence(o);
            wg_fence();
            issue_qk<0>(s0, qd0, kd0);
            wg_commit();
            wg_commit();
            uint64_t qd = qd0;
            const uint32_t fre = (tid == wg * 128) ? bar0 + B_FREE * 8 - 8 : 0;
#pragma unroll 1
            for (int pass = 0; pass < 4; pass++) {
                uint64_t vd = vd0, kd = kd0;
                uint32_t bn = kvbar + 8;
#pragma unroll 1
                for (int it = 0; it < 8; it++) {
                    mbar_wait(bn, 0);
                    if (it == 0 && pass != 0) {
                        wg_wait<0>();
                        reg_fence(o);
                        store_o<false>(o, quarter * 8 + ((pass - 1 + rot) & 3) * 2 + wg, head, wq, lane);
                        reg_fence(o);
                        __syncwarp();
                        if (lane == 0) mbar_arrive(bar0 + (B_OS + pass * 2 - 2 + wg) * 8);
                    }
                    wg_wait<1>();
                    reg_fence(s0);
                    wg_fence();
                    issue_qk<KV_TILE>(s1, qd, kd);
                    wg_commit();
                    if (pass == 3 && it > 0 && fre) mbar_arrive(fre + it * 8);
                    softmax_pv<0>(s0, p0, o, vd, one2);
                    kd += 2 * KV_TILE; bn += 8;
                    if (it == 7) { kd = kd0; bn = kvbar; qd += 512; }
                    mbar_wait(bn, 0);
                    wg_wait<1>();
                    reg_fence(s1);
                    wg_fence();
                    issue_qk<0>(s0, qd, kd);
                    wg_commit();
                    softmax_pv<KV_TILE>(s1, p1, o, vd, one2);
                    vd += 2 * KV_TILE; bn += 8;
                }
                if (pass == 0) PROF(17);
            }
            wg_wait<0>();
            reg_fence(o);
            reg_fence(s0);
            reg_fence(s1);
            store_o<true>(o, quarter * 8 + ((3 + rot) & 3) * 2 + wg, head, wq, lane);
        } else {
#pragma unroll 1
            for (int pass = 0; pass < 4; pass++) {
                float m0 = -INFINITY, m1 = -INFINITY;
                float s[64];
                uint32_t p[32];
#pragma unroll 1
                for (int t = 0; t < 16; t++) {
                    mbar_wait(kvbar + t * 8, 0);
                    wg_fence();
                    issue_qk<0>(s, qd0 + pass * 512, kd0 + t * KV_TILE);
                    wg_commit();
                    wg_wait<0>();
                    reg_fence(s);
                    float a0 = m0, a1 = m1;
#pragma unroll
                    for (int k = 0; k < 16; k++) {
                        if ((POLY_MASK >> k) & 1) {
#pragma unroll
                            for (int i = 0; i < 4; i++) s[k * 4 + i] *= 0.5f;
                        }
                        a0 = fmaxf(a0, fmaxf(s[k * 4 + 0], s[k * 4 + 1]));
                        a1 = fmaxf(a1, fmaxf(s[k * 4 + 2], s[k * 4 + 3]));
                    }
                    a0 = fmaxf(a0, __shfl_xor_sync(~0u, a0, 1)); a1 = fmaxf(a1, __shfl_xor_sync(~0u, a1, 1));
                    a0 = fmaxf(a0, __shfl_xor_sync(~0u, a0, 2)); a1 = fmaxf(a1, __shfl_xor_sync(~0u, a1, 2));
                    const float r0 = ex2(m0 - a0), r1 = ex2(m1 - a1);
                    m0 = a0; m1 = a1;
#pragma unroll
                    for (int i = 0; i < 3; i++) { o[i * 4] *= r0; o[i * 4 + 1] *= r0; o[i * 4 + 2] *= r1; o[i * 4 + 3] *= r1; }
#pragma unroll
                    for (int k = 0; k < 16; k++) {
                        p[k * 2 + 0] = pack_bf16(ex2(s[k * 4 + 0] - m0), ex2(s[k * 4 + 1] - m0));
                        p[k * 2 + 1] = pack_bf16(ex2(s[k * 4 + 2] - m1), ex2(s[k * 4 + 3] - m1));
                    }
                    reg_fence(p);
                    reg_fence(o);
                    wg_fence();
                    issue_pv<0>(o, p, vd0 + t * KV_TILE);
                    wg_commit();
                    wg_wait<0>();
                    reg_fence(o);
                }
                if (pass < 3) {
                    store_o<false>(o, quarter * 8 + ((pass + rot) & 3) * 2 + wg, head, wq, lane);
                    __syncwarp();
                    if (lane == 0) mbar_arrive(bar0 + (B_OS + pass * 2 + wg) * 8);
                }
            }
            store_o<true>(o, quarter * 8 + ((3 + rot) & 3) * 2 + wg, head, wq, lane);
            if (tid == wg * 128)
                for (int i = 0; i < 7; i++) mbar_arrive(bar0 + (B_FREE + i) * 8);
        }
        PROF(18);
        PROFT(51);

        if (tid == wg * 128) mbar_arrive(bar0 + (B_FREE + 7) * 8);
        const int t128 = tid & 127;
        uint32_t bv[9];
        uint2 fv[9];
        mbar_wait(bar0 + B_BASE * 8, 0);
#pragma unroll
        for (int i = 0; i < 9; i++) {
            bv[i] = __ldg(reinterpret_cast<const uint32_t*>(b2 + ct * 144 + wg * 72 + q * 2) + i * 4);
            fv[i] = __ldcg(g_ffn + (blockIdx.x * 18 + wg * 9 + i) * 128 + t128);
        }
        float acc[36];
        const uint64_t od = mk_desc(zero, sb, 1024, 128, 0), wd = mk_desc(zero, sb + wg * 9 * 128, 2304, 128, 0);
        static_for<0, 9>([&](auto pc) {
            constexpr int p = decltype(pc)::value;
            mbar_wait(bar0 + (B_WO + p) * 8, 0);
            wg_fence();
            wgmma_ss_n72<1, sm_ostep(p * 3) / 16, sm_wstep(p * 3) / 16>(acc, od, wd, p != 0);
            wgmma_ss_n72<1, sm_ostep(p * 3 + 1) / 16, sm_wstep(p * 3 + 1) / 16>(acc, od, wd, 1);
            wgmma_ss_n72<1, sm_ostep(p * 3 + 2) / 16, sm_wstep(p * 3 + 2) / 16>(acc, od, wd, 1);
            wg_commit();
            if constexpr (p == 1) {
                wg_wait<1>();
                if (t128 == 0) mbar_arrive(bar0 + B_EARLY * 8);
            }
        });
        wg_wait<0>();
        reg_fence(acc);
        PROF(29);
        uint4 al[9];
        {
            const uint4* ap = g_Olate + rt * 9 * 128 + t128;
            uint32_t spins = 0;
            bool ok;
            do {
                ok = true;
#pragma unroll
                for (int k = 0; k < 9; k++)
                    asm volatile("ld.relaxed.gpu.global.v4.u32 {%0, %1, %2, %3}, [%4];" : "=r"(al[k].x), "=r"(al[k].y), "=r"(al[k].z), "=r"(al[k].w) : "l"(ap + k * 128) : "memory");
#pragma unroll
                for (int k = 0; k < 9; k++) ok = ok && al[k].x != O_EMPTY && al[k].y != O_EMPTY && al[k].z != O_EMPTY && al[k].w != O_EMPTY;
                if (++spins > (1u << 20)) __trap();
            } while (!__all_sync(~0u, ok));
        }
        PROF(19);
        mbar_wait(bar0 + B_LATE * 8, 0);
        PROF(20);
        wg_fence();
        static_for<27, 36>([&](auto kc) {
            constexpr int k = decltype(kc)::value;
            wgmma_rs_n72<1, sm_wstep(k) / 16>(acc, al[k - 27].x, al[k - 27].y, al[k - 27].z, al[k - 27].w, wd, 1);
        });
        wg_commit();
        PROF(31);
        uint32_t* st = reinterpret_cast<uint32_t*>(smem + sm_piece(0) + wg * 9216) + (wq * 16 + g) * 36 + q;
        float bs[36];
#pragma unroll
        for (int i = 0; i < 9; i++) {
            const uint32_t x0 = st[i * 4], x1 = st[i * 4 + 288];
            bs[i * 4 + 0] = fmaf(bf_lo(fv[i].x), 0.5f, bf_lo(x0) + bf_lo(bv[i]));
            bs[i * 4 + 1] = fmaf(bf_hi(fv[i].x), 0.5f, bf_hi(x0) + bf_hi(bv[i]));
            bs[i * 4 + 2] = fmaf(bf_lo(fv[i].y), 0.5f, bf_lo(x1) + bf_lo(bv[i]));
            bs[i * 4 + 3] = fmaf(bf_hi(fv[i].y), 0.5f, bf_hi(x1) + bf_hi(bv[i]));
        }
        reg_fence(bs);
        wg_wait<0>();
        reg_fence(acc);
        PROF(32);
#pragma unroll
        for (int i = 0; i < 9; i++) {
            st[i * 4] = pack_bf16(acc[i * 4] + bs[i * 4], acc[i * 4 + 1] + bs[i * 4 + 1]);
            st[i * 4 + 288] = pack_bf16(acc[i * 4 + 2] + bs[i * 4 + 2], acc[i * 4 + 3] + bs[i * 4 + 3]);
        }
        fence_proxy_async();
        named_bar_sync(1 + wg, 128);
        if (t128 == 0) {
            asm volatile("cp.async.bulk.tensor.2d.global.shared::cta.bulk_group [%0, {%2, %3}], [%1];"
                         ::"l"(&tmOut), "r"(sb + sm_piece(0) + wg * 9216), "r"(ct * 144 + wg * 72), "r"(rt * 64) : "memory");
            asm volatile("cp.async.bulk.commit_group;" ::: "memory");
            asm volatile("cp.async.bulk.wait_group.read 0;" ::: "memory");
        }
        PROF(21);
        PROFT(52);
    } else {
        reg_dealloc<24>();
        if (warp == 8 && lane == 0) {
            prefetch_tmap(&tmQ3); prefetch_tmap(&tmQ1); prefetch_tmap(&tm1); prefetch_tmap(&tm2);
            #pragma unroll 1
            for (int i = 0; i < 9; i++) { mbar_init(full0 + i * 8, 1); mbar_init(empty0 + i * 8, 4); mbar_init(bar0 + (B_WO + i) * 8, 2); }
            mbar_init(bar0 + B_BASE * 8, 3); mbar_init(bar0 + B_XNDEAD * 8, 2); mbar_init(bar0 + B_QRDY * 8, 3); mbar_init(bar0 + B_FFN * 8, 8); mbar_init(bar0 + B_EARLY * 8, 2); mbar_init(bar0 + B_LATE * 8, 2);
#pragma unroll 1
            for (int i = 0; i < 16; i++) { mbar_init(bar0 + (B_KV + i) * 8, 1); mbar_init(bar0 + (B_FREE + (i & 7)) * 8, 2); if (i < 6) mbar_init(bar0 + (B_RED + i) * 8, 1); if (i < 6) mbar_init(bar0 + (B_OS + i) * 8, 4); }
            *slow_flag = 0;
            fence_barrier_init();
        }
        __syncwarp();
        cluster_arrive();
        cluster_wait();
        const uint8_t* kvsrc = g_QKV + (size_t)head * KV_HEAD_BYTES;
        if (warp == 8) {
            if (lane == 0) {
                int st = 0, u = rank, tile = -4;
                int es = 5;
                uint32_t eph = 1;
#pragma unroll 1
                for (int n = 0; n < 99; n++) {
                    mbar_wait(empty0 + es * 8, eph);
                    const uint32_t fb = full0 + st * 8, dst = sb + K1_OFF_RING + u * 8192;
                    mbar_expect(fb, 16384);
                    if (tile < 0) {
                        tma3d_mc(dst, &tmQ3, j * 216, n * 32 + rank * 16, 0, fb, 3);
                        tma2d_mc(dst + 6144, &tmQ1, j * 216 + 192, n * 32 + rank * 16, fb, 3);
                    } else if (tile < 9) {
                        tma2d_mc(dst, &tm1, j * 576 + tile * 64, u * 64, fb, 3);
                    } else {
                        tma2d_mc(dst, &tm2, (tile - 9) * 64, j * 576 + u * 64, fb, 3);
                    }
                    u += 2;
                    if (u >= 9) { u -= 9; tile++; }
                    if (++st == 9) st = 0;
                    if (++es == 9) { es = 0; eph ^= 1; }
                }
                mbar_wait(empty0 + 8 * 8, 0);
                mbar_wait(bar0 + B_QRDY * 8, 0);
                asm volatile("fence.proxy.async;" ::: "memory");
#pragma unroll 1
                for (int i = 11; i < NCHUNK; i++) {
                    mbar_expect(bar0 + (B_KV + i) * 8, CHUNK_BYTES);
                    bulk_load(sb + SM_KV + i * CHUNK_BYTES, kvsrc + i * CHUNK_BYTES, CHUNK_BYTES, bar0 + (B_KV + i) * 8);
                }
                const uint8_t* wsrc = g_Wo + ct * WO_TILE_BYTES;
                prefetch_tmap(&tmOut);
                mbar_wait_sleep(bar0 + B_BASE * 8, 500);
#pragma unroll 1
                for (int p = 0; p < 9; p++) {
                    if (p > 0) mbar_wait_sleep(bar0 + (B_FREE + p - 1) * 8, p == 1 ? 500 : 40);
                    const int k = ks0 + p * 3 >= 36 ? ks0 + p * 3 - 36 : ks0 + p * 3;
                    mbar_expect(bar0 + (B_WO + p) * 8, 13824);
                    bulk_load(sb + (p == 0 ? sm_piece(0) : (p == 1 ? sm_piece(1) : SM_KV + (p - 2) * PIECE)), wsrc + k * 4608, 13824, bar0 + (B_WO + p) * 8);
                }
                const int kl = ks0 == 0 ? 27 : ks0 - 9;
                mbar_expect(bar0 + B_LATE * 8, 9 * 4608);
                bulk_load(sb + sm_wstep(27), wsrc + kl * 4608, 8 * 4608, bar0 + B_LATE * 8);
                bulk_load(sb + sm_wstep(35), wsrc + (kl + 8) * 4608, 4608, bar0 + B_LATE * 8);
            }
        } else {
            const int ht = tid - 288;
            if (ht == 64) prefetch_l2(wqkv + blockIdx.x * (DM * 3 * DM / 128), DM * 3 * DM / 64);
            if (ht < 72) {
                const uint4 v = __ldg(reinterpret_cast<const uint4*>(b1 + j * 576) + ht);
                uint32_t* sbias = reinterpret_cast<uint32_t*>(smem + K1_OFF_BIAS) + (ht >> 3) * 32 + (ht & 7);
                sbias[0] = v.x; sbias[8] = v.y; sbias[16] = v.z; sbias[24] = v.w;
            }
            asm volatile("bar.arrive 4, 352;" ::: "memory");
            PROFH(37);
#pragma unroll
            for (int i = 0; i < 3; i++) g_Olate[blockIdx.x * 288 + i * 96 + ht] = make_uint4(O_EMPTY, O_EMPTY, O_EMPTY, O_EMPTY);
#pragma unroll 1
            for (int i = ht; i < 512; i += 96) {
                const int key = i & 127;
                uint8_t* p = g_QKV + (size_t)(j * 4 + (i >> 7)) * KV_HEAD_BYTES + (rb * 16 + (key >> 3)) * KV_GROUP_BYTES + 512 + (key & 7) * 16;
                *reinterpret_cast<uint32_t*>(p + 4) = ((POLY_MASK >> (key >> 3)) & 1) ? 0x3F804000u : 0x00003F80u;
                *reinterpret_cast<uint32_t*>(p + 12) = 0x00003F80u;
            }
            if (ht == 32) prefetch_l2(w1 + blockIdx.x * (DM * FF / 128), DM * FF / 64);
#pragma unroll 2
            for (int i = blockIdx.x * 324 + ht; i < blockIdx.x * 324 + 324; i += 96) {
                const int k = i / 72, nc = i - k * 72, c4 = nc / 18;
                *reinterpret_cast<uint4*>(g_Wo + c4 * WO_TILE_BYTES + (k >> 3) * 2304 + (nc - c4 * 18) * 128 + (k & 7) * 16) =
                    __ldg(reinterpret_cast<const uint4*>(wo) + i);
            }
            PROFH(38);
            named_bar_sync(3, 352);
            if (ht == 32) prefetch_l2(w2 + blockIdx.x * (DM * FF / 128), DM * FF / 64);
            if (ht == 0) {
                flag_signal(&g_flags.qkv_stored[rb]);
                flag_wait(&g_flags.qkv_stored[rb], 8, 200);
            }
            named_bar_sync(7, 96);
            PROFH(39);
#pragma unroll 1
            for (int i = warp - 9; i < 16; i += 3) {
                const int hd = j * 4 + (i >> 2), key = (i & 3) * 32 + lane;
                const uint8_t* p = g_QKV + (size_t)hd * KV_HEAD_BYTES + (rb * 16 + (key >> 3)) * KV_GROUP_BYTES + (key & 7) * 16;
                const uint4 a = __ldcg(reinterpret_cast<const uint4*>(p)), b = __ldcg(reinterpret_cast<const uint4*>(p + 128));
                float n = sumsq2(__ldcg(reinterpret_cast<const uint32_t*>(p + 512))) + sumsq8(a) + sumsq8(b);
                if ((POLY_MASK >> (key >> 3)) & 1) n *= 0.25f;
#pragma unroll
                for (int o = 16; o; o >>= 1) n = fmaxf(n, __shfl_xor_sync(~0u, n, o));
                if (lane == 0) g_kmax[hd * 64 + rb * 4 + (i & 3)] = n;
            }
            named_bar_sync(7, 96);
            PROFH(40);
            if (ht == 0) {
                flag_signal(&g_flags.kv_ready);
                flag_wait(&g_flags.kv_ready, 128, 300);
                mbar_wait_sleep(bar0 + B_XNDEAD * 8, 300);
            }
            named_bar_sync(7, 96);
            PROFH(41);
            float kmax2;
            {
                const float2 v = __ldcg(reinterpret_cast<const float2*>(g_kmax + head * 64 + lane * 2));
                kmax2 = fmaxf(v.x, v.y);
#pragma unroll
                for (int o = 16; o; o >>= 1) kmax2 = fmaxf(kmax2, __shfl_xor_sync(~0u, kmax2, o));
            }
            asm volatile("fence.proxy.async;" ::: "memory");
            int chunk = warp - 9;
#pragma unroll 1
            for (int r = ht; r < 512; r += 96) {
                if (lane == 0 && chunk < 11) {
                    mbar_expect(bar0 + (B_KV + chunk) * 8, CHUNK_BYTES);
                    bulk_load(sb + SM_KV + chunk * CHUNK_BYTES, kvsrc + chunk * CHUNK_BYTES, CHUNK_BYTES, bar0 + (B_KV + chunk) * 8);
                }
                chunk += 3;
                const uint8_t* p = kvsrc + Q_OFFSET + (quarter * 64 + (((r >> 3) + rot * 16) & 63)) * KV_GROUP_BYTES + (r & 7) * 16;
                const uint4 a = __ldcg(reinterpret_cast<const uint4*>(p)), b = __ldcg(reinterpret_cast<const uint4*>(p + 128));
                const uint32_t e = __ldcg(reinterpret_cast<const uint32_t*>(p + 256));
                const float cc = sqrtf((sumsq2(e) + sumsq8(a) + sumsq8(b)) * kmax2) * 1.02f;
                if (!(cc <= 58.f)) *slow_flag = 1;
                uint4* dst = reinterpret_cast<uint4*>(smem + SM_Q + (r >> 3) * 512 + (r & 7) * 16);
                dst[0] = a;
                dst[8] = b;
                dst[16] = make_uint4(e, pack_bf16(-cc, 768.f), 0u, 0u);
                dst[24] = make_uint4(0u, POLY_MODE ? 0xBFFF0000u : 0xC0000000u, 0u, 0u);
            }
            named_bar_sync(7, 96);
            if (*slow_flag) {
#pragma unroll 1
                for (int r = ht; r < 512; r += 96) {
                    uint32_t* dst = reinterpret_cast<uint32_t*>(smem + SM_Q + (r >> 3) * 512 + (r & 7) * 16);
                    dst[65] = 0u;
                    dst[97] = 0u;
                }
            }
            fence_proxy_async();
            __syncwarp();
            if (lane == 0) mbar_arrive(bar0 + B_QRDY * 8);
            PROFH(42);
            if (ht == 0) {
                mbar_wait_sleep(bar0 + B_FFN * 8, 300);
                flag_signal(&g_flags.ffn_done[rb]);
                flag_wait(&g_flags.ffn_done[rt >> 1], 8, 300);
            }
            named_bar_sync(7, 96);
            {
                const int w3 = warp - 9;
                const uint32_t rbar = bar0 + (B_RED + w3 * 2) * 8, rbuf = SM_RED + w3 * 8192;
                const int u0 = ((rt >> 1) * 36 + ct * 9) * 256 + (rt & 1) * 128;
                mbar_wait_sleep(bar0 + (B_KV + 15) * 8, 500);
                asm volatile("fence.proxy.async;" ::: "memory");
#pragma unroll 1
                for (int i = -2; i < 12; i++) {
                    if (i >= 0) {
                        __nanosleep(400);
                        mbar_wait(rbar + (i & 1) * 8, (i >> 1) & 1);
                        const uint4* sp = reinterpret_cast<const uint4*>(smem + rbuf + (i & 1) * 4096) + lane;
                        const uint4 v = hadd8_bf16(hadd8_bf16(hadd8_bf16(sp[0], sp[32]), hadd8_bf16(sp[64], sp[96])),
                                                   hadd8_bf16(hadd8_bf16(sp[128], sp[160]), hadd8_bf16(sp[192], sp[224])));
                        const int bx = i * 3 + w3;
                        uint2* fp = g_ffn + (blockIdx.x * 18 + (bx >> 2) * 2) * 128 + (bx & 3) * 32 + lane;
                        fp[0] = make_uint2(v.x, v.y);
                        fp[128] = make_uint2(v.z, v.w);
                    }
                    __syncwarp();
                    if (lane == 0 && i < 10) {
                        const int bx = (i + 2) * 3 + w3;
                        mbar_expect(rbar + (i & 1) * 8, 4096);
                        tma2d(sb + rbuf + (i & 1) * 4096, &tmP, (u0 + (bx >> 2) * 256 + (bx & 3) * 32) * 2, 0, rbar + (i & 1) * 8);
                    }
                }
            }
            __syncwarp();
            if (lane == 0) mbar_arrive(bar0 + B_BASE * 8);
            PROFH(43);
            if (ht == 0) {
#pragma unroll 1
                for (int i = 0; i < 6; i++) {
                    mbar_wait_sleep(bar0 + (B_OS + i) * 8, 200);
                    flag_signal(&g_flags.o_done[quarter * 8 + (((i >> 1) + rot) & 3) * 2 + (i & 1)]);
                }
            } else if (ht == 32) {
                const uint8_t* osrc = reinterpret_cast<const uint8_t*>(g_O) + rt * 73728;
                mbar_wait_sleep(bar0 + B_BASE * 8, 500);
                mbar_wait_sleep(bar0 + B_FREE * 8, 500);
                flag_wait(&g_flags.o_done[rt], 24, 100);
                if (atomicAdd(&g_flags.exited, 1u) == gridDim.x - 1) {
                    unsigned int* f = reinterpret_cast<unsigned int*>(&g_flags);
#pragma unroll 1
                    for (int i = 0; i < (int)(sizeof(Flags) / 4); i++) f[i] = 0;
                }
                prefetch_tmap(&tmXo);
                asm volatile("fence.proxy.async;" ::: "memory");
#pragma unroll 1
                for (int p = 0; p < 9; p++) {
                    if (p > 1) mbar_wait_sleep(bar0 + (B_FREE + p - 1) * 8, 40);
                    const int k = ks0 + p * 3 >= 36 ? ks0 + p * 3 - 36 : ks0 + p * 3;
                    mbar_expect(bar0 + (B_WO + p) * 8, 6144);
                    bulk_load(sb + 13824 + (p == 0 ? sm_piece(0) : (p == 1 ? sm_piece(1) : SM_KV + (p - 2) * PIECE)), osrc + k * 2048, 6144, bar0 + (B_WO + p) * 8);
                }
                mbar_expect(bar0 + B_LATE * 8, 2 * 9216);
                mbar_wait(bar0 + B_EARLY * 8, 0);
                tma2d(sb + sm_piece(0), &tmXo, ct * 144, rt * 64, bar0 + B_LATE * 8);
                tma2d(sb + sm_piece(0) + 9216, &tmXo, ct * 144 + 72, rt * 64, bar0 + B_LATE * 8);
            }
        }
    }
}

typedef CUresult (*EncodeFn)(CUtensorMap*, CUtensorMapDataType, cuuint32_t, void*, const cuuint64_t*, const cuuint64_t*, const cuuint32_t*,
                             const cuuint32_t*, CUtensorMapInterleave, CUtensorMapSwizzle, CUtensorMapL2promotion, CUtensorMapFloatOOBfill);

void make_map(EncodeFn fn, CUtensorMap* m, const void* base, int rank, const cuuint64_t* dims, const cuuint64_t* strides, const cuuint32_t* box) {
    cuuint32_t es[4] = {1, 1, 1, 1};
    fn(m, CU_TENSOR_MAP_DATA_TYPE_BFLOAT16, rank, const_cast<void*>(base), dims, strides, box, es, CU_TENSOR_MAP_INTERLEAVE_NONE,
       CU_TENSOR_MAP_SWIZZLE_128B, CU_TENSOR_MAP_L2_PROMOTION_L2_256B, CU_TENSOR_MAP_FLOAT_OOB_FILL_NONE);
}

}

extern "C" void kernel_launch(void* const* d_in, const int* in_sizes, int n_in, void* d_out, int out_size) {
    const __nv_bfloat16* x = (const __nv_bfloat16*)d_in[0];
    const __nv_bfloat16* wqkv = (const __nv_bfloat16*)d_in[1];
    const __nv_bfloat16* wo = (const __nv_bfloat16*)d_in[2];
    const __nv_bfloat16* w1 = (const __nv_bfloat16*)d_in[4];
    const __nv_bfloat16* b1 = (const __nv_bfloat16*)d_in[5];
    const __nv_bfloat16* w2 = (const __nv_bfloat16*)d_in[6];
    const __nv_bfloat16* b2 = (const __nv_bfloat16*)d_in[7];
    __nv_bfloat16* out = (__nv_bfloat16*)d_out;

    EncodeFn fn = nullptr;
    cudaDriverEntryPointQueryResult qr;
    cudaGetDriverEntryPoint("cuTensorMapEncodeTiled", (void**)&fn, cudaEnableDefault, &qr);
    CUtensorMap tmX, tmQ3, tmQ1, tm1, tm2, tmP, tmOut, tmXo;
    {
        cuuint64_t d[2] = {DM, SEQ}, s[1] = {DM * 2};
        cuuint32_t b[2] = {72, 64}, es[2] = {1, 1};
        fn(&tmOut, CU_TENSOR_MAP_DATA_TYPE_BFLOAT16, 2, out, d, s, b, es, CU_TENSOR_MAP_INTERLEAVE_NONE, CU_TENSOR_MAP_SWIZZLE_NONE,
           CU_TENSOR_MAP_L2_PROMOTION_NONE, CU_TENSOR_MAP_FLOAT_OOB_FILL_NONE);
        fn(&tmXo, CU_TENSOR_MAP_DATA_TYPE_BFLOAT16, 2, const_cast<__nv_bfloat16*>(x), d, s, b, es, CU_TENSOR_MAP_INTERLEAVE_NONE,
           CU_TENSOR_MAP_SWIZZLE_NONE, CU_TENSOR_MAP_L2_PROMOTION_NONE, CU_TENSOR_MAP_FLOAT_OOB_FILL_NONE);
    }
    {
        void* gp = nullptr;
        cudaGetSymbolAddress(&gp, g_part);
        cuuint64_t d[2] = {SLAB * 2, 8}, s[1] = {SLAB * 16};
        cuuint32_t b[2] = {64, 8}, es[2] = {1, 1};
        fn(&tmP, CU_TENSOR_MAP_DATA_TYPE_INT64, 2, gp, d, s, b, es, CU_TENSOR_MAP_INTERLEAVE_NONE, CU_TENSOR_MAP_SWIZZLE_NONE,
           CU_TENSOR_MAP_L2_PROMOTION_NONE, CU_TENSOR_MAP_FLOAT_OOB_FILL_NONE);
    }
    {
        cuuint64_t d[4] = {64, 8, 9, SEQ / 8}, s[3] = {DM * 2, 128, DM * 2 * 8};
        cuuint32_t b[4] = {64, 8, 3, 2};
        make_map(fn, &tmX, x, 4, d, s, b);
    }
    {
        cuuint64_t d[3] = {3 * DM, DM, 3}, s[2] = {3 * DM * 2, 128};
        cuuint32_t b[3] = {64, 16, 3};
        make_map(fn, &tmQ3, wqkv, 3, d, s, b);
        make_map(fn, &tmQ1, wqkv, 2, d, s, b);
    }
    {
        cuuint64_t d[2] = {FF, DM}, s[1] = {FF * 2};
        cuuint32_t b[2] = {64, 64};
        make_map(fn, &tm1, w1, 2, d, s, b);
        cuuint64_t d2[2] = {DM, FF}, s2[1] = {DM * 2};
        make_map(fn, &tm2, w2, 2, d2, s2, b);
    }
    cudaFuncSetAttribute(fused_kernel, cudaFuncAttributeMaxDynamicSharedMemorySize, K1_SMEM);
    fused_kernel<<<128, 384, K1_SMEM, cudaStreamPerThread>>>(tmX, tmQ3, tmQ1, tm1, tm2, tmP, tmOut, tmXo, b1, wqkv, w1, w2, wo, b2, 0ull);
}
```

```cpp
#include <cuda_runtime.h>
#include <cuda_bf16.h>
#include <cuda.h>
#include <stdint.h>

#define PROF(i) do { } while (0)
#define PROFT(i) do { } while (0)
#define PROFH(i) do { } while (0)
#define PROFWT(i) do { } while (0)
#define PROF_WG 0

namespace {

constexpr int SEQ = 2048, DM = 576, FF = 4608, NH = 32, DH = 18;

constexpr int KV_GROUP_BYTES = 5 * 128;
constexpr int KV_HEAD_BYTES = (SEQ / 8) * KV_GROUP_BYTES;
constexpr int Q_OFFSET = NH * KV_HEAD_BYTES;
#define POLY_MASK 0xB6B6
__device__ __align__(1024) uint8_t g_QKV[2 * NH * KV_HEAD_BYTES];
__device__ __align__(1024) float g_kmax[NH * 64];
constexpr int SLAB = 16 * 36 * 256;
__device__ __align__(1024) uint4 g_part[8 * SLAB];
__device__ __align__(1024) uint2 g_ffn[128 * 18 * 128];
__device__ __align__(1024) uint32_t g_O[SEQ * DM / 2];
struct Flags {
    unsigned int qkv_stored[16];
    unsigned int ffn_done[16];
    unsigned int o_done[32];
    unsigned int kv_ready;
    unsigned int exited;
};
__device__ Flags g_flags;
__device__ __align__(1024) uint4 g_Olate[32 * 9 * 128];
constexpr uint32_t O_EMPTY = 0xFFFFFFFFu;
constexpr int WO_TILE_BYTES = DM * 144 * 2;
__device__ __align__(1024) uint8_t g_Wo[4 * WO_TILE_BYTES];

__device__ __forceinline__ uint32_t s2u(const void* p) { return (uint32_t)__cvta_generic_to_shared(p); }
__device__ __forceinline__ void mbar_init(uint32_t b, int c) { asm volatile("mbarrier.init.shared::cta.b64 [%0], %1;" ::"r"(b), "r"(c) : "memory"); }
__device__ __forceinline__ void mbar_expect(uint32_t b, uint32_t bytes) {
    asm volatile("mbarrier.arrive.expect_tx.shared::cta.b64 _, [%0], %1;" ::"r"(b), "r"(bytes) : "memory");
}
__device__ __forceinline__ void mbar_wait(uint32_t b, uint32_t parity) {
    asm volatile(
        "{\n.reg .pred p;\n.reg .u32 c;\n"
        "mov.u32 c, 0;\n"
        "LOOP:\n"
        "mbarrier.try_wait.parity.shared::cta.b64 p, [%0], %1;\n"
        "@p bra DONE;\n"
        "add.u32 c, c, 1;\n"
        "setp.lt.u32 p, c, 4194304;\n"
        "@p bra LOOP;\n"
        "trap;\n"
        "DONE:\n}\n" ::"r"(b), "r"(parity) : "memory");
}
__device__ __forceinline__ void fence_barrier_init() { asm volatile("fence.mbarrier_init.release.cluster;" ::: "memory"); }
__device__ __forceinline__ void fence_proxy_async() { asm volatile("fence.proxy.async.shared::cta;" ::: "memory"); }
__device__ __forceinline__ void cluster_arrive() { asm volatile("barrier.cluster.arrive.relaxed.aligned;" ::: "memory"); }
__device__ __forceinline__ void cluster_wait() { asm volatile("barrier.cluster.wait.aligned;" ::: "memory"); }
__device__ __forceinline__ void named_bar_sync(int id, int n) { asm volatile("bar.sync %0, %1;" ::"r"(id), "r"(n) : "memory"); }

__device__ __forceinline__ void tma3d_mc(uint32_t dst, const CUtensorMap* tm, int c0, int c1, int c2, uint32_t bar, uint16_t mask) {
    asm volatile("cp.async.bulk.tensor.3d.shared::cluster.global.mbarrier::complete_tx::bytes.multicast::cluster [%0], [%1, {%3, %4, %5}], [%2], %6;"
                 ::"r"(dst), "l"(tm), "r"(bar), "r"(c0), "r"(c1), "r"(c2), "h"(mask) : "memory");
}
__device__ __forceinline__ void tma2d_mc(uint32_t dst, const CUtensorMap* tm, int c0, int c1, uint32_t bar, uint16_t mask) {
    asm volatile("cp.async.bulk.tensor.2d.shared::cluster.global.mbarrier::complete_tx::bytes.multicast::cluster [%0], [%1, {%3, %4}], [%2], %5;"
                 ::"r"(dst), "l"(tm), "r"(bar), "r"(c0), "r"(c1), "h"(mask) : "memory");
}
__device__ __forceinline__ void tma4d(uint32_t dst, const CUtensorMap* tm, int c0, int c1, int c2, int c3, uint32_t bar) {
    asm volatile("cp.async.bulk.tensor.4d.shared::cluster.global.mbarrier::complete_tx::bytes [%0], [%1, {%3, %4, %5, %6}], [%2];"
                 ::"r"(dst), "l"(tm), "r"(bar), "r"(c0), "r"(c1), "r"(c2), "r"(c3) : "memory");
}
__device__ __forceinline__ void tma2d(uint32_t dst, const CUtensorMap* tm, int c0, int c1, uint32_t bar) {
    asm volatile("cp.async.bulk.tensor.2d.shared::cluster.global.mbarrier::complete_tx::bytes [%0], [%1, {%3, %4}], [%2];"
                 ::"r"(dst), "l"(tm), "r"(bar), "r"(c0), "r"(c1) : "memory");
}
__device__ __forceinline__ void bulk_load(uint32_t dst, const void* src, uint32_t bytes, uint32_t bar) {
    asm volatile("cp.async.bulk.shared::cluster.global.mbarrier::complete_tx::bytes [%0], [%1], %2, [%3];"
                 ::"r"(dst), "l"(src), "r"(bytes), "r"(bar) : "memory");
}
__device__ __forceinline__ void prefetch_l2(const void* p, uint32_t bytes) {
    asm volatile("cp.async.bulk.prefetch.L2.global [%0], %1;" ::"l"(p), "r"(bytes) : "memory");
}
__device__ __forceinline__ void prefetch_tmap(const CUtensorMap* tm) { asm volatile("prefetch.tensormap [%0];" ::"l"(tm) : "memory"); }

__device__ __forceinline__ void wg_fence() { asm volatile("wgmma.fence.sync.aligned;" ::: "memory"); }
__device__ __forceinline__ void wg_commit() { asm volatile("wgmma.commit_group.sync.aligned;" ::: "memory"); }
template <int N> __device__ __forceinline__ void wg_wait() { asm volatile("wgmma.wait_group.sync.aligned %0;" ::"n"(N) : "memory"); }
template <int N> __device__ __forceinline__ void reg_fence(float (&d)[N]) {
#pragma unroll
    for (int i = 0; i < N; i++) asm volatile("" : "+f"(d[i])::"memory");
}
template <int N> __device__ __forceinline__ void reg_fence(uint32_t (&d)[N]) {
#pragma unroll
    for (int i = 0; i < N; i++) asm volatile("" : "+r"(d[i])::"memory");
}
template <int R> __device__ __forceinline__ void reg_alloc() { asm volatile("setmaxnreg.inc.sync.aligned.u32 %0;" ::"n"(R)); }
template <int R> __device__ __forceinline__ void reg_dealloc() { asm volatile("setmaxnreg.dec.sync.aligned.u32 %0;" ::"n"(R)); }

__device__ __forceinline__ uint64_t mk_desc(uint64_t z, uint32_t addr, uint32_t lbo, uint32_t sbo, uint32_t swz) {
    return z + ((uint64_t)(((addr & 0x3FFFF) >> 4) | ((lbo >> 4) << 16)) | ((uint64_t)((sbo >> 4) | (swz << 30)) << 32));
}
__device__ __forceinline__ uint32_t pack_bf16(float lo, float hi) {
    uint32_t r;
    asm("cvt.rn.bf16x2.f32 %0, %1, %2;" : "=r"(r) : "f"(hi), "f"(lo));
    return r;
}
__device__ __forceinline__ float bf_lo(uint32_t w) { return __uint_as_float(w << 16); }
__device__ __forceinline__ float bf_hi(uint32_t w) { return __uint_as_float(w & 0xFFFF0000u); }
__device__ __forceinline__ float ex2(float x) {
    float r;
    asm("ex2.approx.ftz.f32 %0, %1;" : "=f"(r) : "f"(x));
    return r;
}
__device__ __forceinline__ float tanh_fast(float x) {
    float r;
    asm("tanh.approx.f32 %0, %1;" : "=f"(r) : "f"(x));
    return r;
}
__device__ __forceinline__ uint32_t hfma2_bf16(uint32_t a, uint32_t b, uint32_t c) {
    uint32_t r;
    asm("fma.rn.bf16x2 %0, %1, %2, %3;" : "=r"(r) : "r"(a), "r"(b), "r"(c));
    return r;
}
__device__ __forceinline__ uint32_t hadd2_bf16(uint32_t a, uint32_t b) {
    uint32_t r;
    asm("add.rn.bf16x2 %0, %1, %2;" : "=r"(r) : "r"(a), "r"(b));
    return r;
}
__device__ __forceinline__ void ldsm4(uint32_t (&a)[4], uint32_t addr) {
    asm volatile("ldmatrix.sync.aligned.m8n8.x4.shared.b16 {%0, %1, %2, %3}, [%4];" : "=r"(a[0]), "=r"(a[1]), "=r"(a[2]), "=r"(a[3]) : "r"(addr) : "memory");
}
__device__ __forceinline__ void stsm4(uint32_t addr, const uint32_t (&a)[4]) {
    asm volatile("stmatrix.sync.aligned.m8n8.x4.shared.b16 [%0], {%1, %2, %3, %4};" ::"r"(addr), "r"(a[0]), "r"(a[1]), "r"(a[2]), "r"(a[3]) : "memory");
}
__device__ __forceinline__ void mma16816(float (&c)[4], const uint32_t (&a)[4], uint32_t b0, uint32_t b1) {
    asm("mma.sync.aligned.m16n8k16.row.col.f32.bf16.bf16.f32 {%0, %1, %2, %3}, {%4, %5, %6, %7}, {%8, %9}, {%0, %1, %2, %3};"
        : "+f"(c[0]), "+f"(c[1]), "+f"(c[2]), "+f"(c[3]) : "r"(a[0]), "r"(a[1]), "r"(a[2]), "r"(a[3]), "r"(b0), "r"(b1));
}
__device__ __forceinline__ float gelu2(float u) {
    const float w = fmaf(u * u, 0.0356774081f, 0.7978845608f);
    return fmaf(u, tanh_fast(u * w), u);
}

template<int TB, int AOFF, int BOFF> __device__ __forceinline__ void wgmma_ss_n216(float (&d)[108], uint64_t da, uint64_t db, int sd) {
    asm volatile("{\n.reg .pred p;\n.reg .b64 ta, tb;\nsetp.ne.b32 p, %110, 0;\nadd.s64 ta, %108, %112;\nadd.s64 tb, %109, %113;\n"
      "wgmma.mma_async.sync.aligned.m64n216k16.f32.bf16.bf16 {%0, %1, %2, %3, %4, %5, %6, %7, %8, %9, %10, %11, %12, %13, %14, %15, %16, %17, %18, %19, %20, %21, %22, %23, %24, %25, %26, %27, %28, %29, %30, %31, %32, %33, %34, %35, %36, %37, %38, %39, %40, %41, %42, %43, %44, %45, %46, %47, %48, %49, %50, %51, %52, %53, %54, %55, %56, %57, %58, %59, %60, %61, %62, %63, %64, %65, %66, %67, %68, %69, %70, %71, %72, %73, %74, %75, %76, %77, %78, %79, %80, %81, %82, %83, %84, %85, %86, %87, %88, %89, %90, %91, %92, %93, %94, %95, %96, %97, %98, %99, %100, %101, %102, %103, %104, %105, %106, %107}, ta, tb, p, 1, 1, 0, %111;\n}\n"
      : "+f"(d[0]), "+f"(d[1]), "+f"(d[2]), "+f"(d[3]), "+f"(d[4]), "+f"(d[5]), "+f"(d[6]), "+f"(d[7]), "+f"(d[8]), "+f"(d[9]), "+f"(d[10]), "+f"(d[11]), "+f"(d[12]), "+f"(d[13]), "+f"(d[14]), "+f"(d[15]), "+f"(d[16]), "+f"(d[17]), "+f"(d[18]), "+f"(d[19]), "+f"(d[20]), "+f"(d[21]), "+f"(d[22]), "+f"(d[23]), "+f"(d[24]), "+f"(d[25]), "+f"(d[26]), "+f"(d[27]), "+f"(d[28]), "+f"(d[29]), "+f"(d[30]), "+f"(d[31]), "+f"(d[32]), "+f"(d[33]), "+f"(d[34]), "+f"(d[35]), "+f"(d[36]), "+f"(d[37]), "+f"(d[38]), "+f"(d[39]), "+f"(d[40]), "+f"(d[41]), "+f"(d[42]), "+f"(d[43]), "+f"(d[44]), "+f"(d[45]), "+f"(d[46]), "+f"(d[47]), "+f"(d[48]), "+f"(d[49]), "+f"(d[50]), "+f"(d[51]), "+f"(d[52]), "+f"(d[53]), "+f"(d[54]), "+f"(d[55]), "+f"(d[56]), "+f"(d[57]), "+f"(d[58]), "+f"(d[59]), "+f"(d[60]), "+f"(d[61]), "+f"(d[62]), "+f"(d[63]), "+f"(d[64]), "+f"(d[65]), "+f"(d[66]), "+f"(d[67]), "+f"(d[68]), "+f"(d[69]), "+f"(d[70]), "+f"(d[71]), "+f"(d[72]), "+f"(d[73]), "+f"(d[74]), "+f"(d[75]), "+f"(d[76]), "+f"(d[77]), "+f"(d[78]), "+f"(d[79]), "+f"(d[80]), "+f"(d[81]), "+f"(d[82]), "+f"(d[83]), "+f"(d[84]), "+f"(d[85]), "+f"(d[86]), "+f"(d[87]), "+f"(d[88]), "+f"(d[89]), "+f"(d[90]), "+f"(d[91]), "+f"(d[92]), "+f"(d[93]), "+f"(d[94]), "+f"(d[95]), "+f"(d[96]), "+f"(d[97]), "+f"(d[98]), "+f"(d[99]), "+f"(d[100]), "+f"(d[101]), "+f"(d[102]), "+f"(d[103]), "+f"(d[104]), "+f"(d[105]), "+f"(d[106]), "+f"(d[107])
      : "l"(da), "l"(db), "r"(sd), "n"(TB), "n"(AOFF), "n"(BOFF));
}

template<int TB, int AOFF, int BOFF> __device__ __forceinline__ void wgmma_ss_n64(float (&d)[32], uint64_t da, uint64_t db, int sd) {
    asm volatile("{\n.reg .pred p;\n.reg .b64 ta, tb;\nsetp.ne.b32 p, %34, 0;\nadd.s64 ta, %32, %36;\nadd.s64 tb, %33, %37;\n"
      "wgmma.mma_async.sync.aligned.m64n64k16.f32.bf16.bf16 {%0, %1, %2, %3, %4, %5, %6, %7, %8, %9, %10, %11, %12, %13, %14, %15, %16, %17, %18, %19, %20, %21, %22, %23, %24, %25, %26, %27, %28, %29, %30, %31}, ta, tb, p, 1, 1, 0, %35;\n}\n"
      : "+f"(d[0]), "+f"(d[1]), "+f"(d[2]), "+f"(d[3]), "+f"(d[4]), "+f"(d[5]), "+f"(d[6]), "+f"(d[7]), "+f"(d[8]), "+f"(d[9]), "+f"(d[10]), "+f"(d[11]), "+f"(d[12]), "+f"(d[13]), "+f"(d[14]), "+f"(d[15]), "+f"(d[16]), "+f"(d[17]), "+f"(d[18]), "+f"(d[19]), "+f"(d[20]), "+f"(d[21]), "+f"(d[22]), "+f"(d[23]), "+f"(d[24]), "+f"(d[25]), "+f"(d[26]), "+f"(d[27]), "+f"(d[28]), "+f"(d[29]), "+f"(d[30]), "+f"(d[31])
      : "l"(da), "l"(db), "r"(sd), "n"(TB), "n"(AOFF), "n"(BOFF));
}

template<int TB, int AOFF, int BOFF> __device__ __forceinline__ void wgmma_ss_n128(float (&d)[64], uint64_t da, uint64_t db, int sd) {
    asm volatile("{\n.reg .pred p;\n.reg .b64 ta, tb;\nsetp.ne.b32 p, %66, 0;\nadd.s64 ta, %64, %68;\nadd.s64 tb, %65, %69;\n"
      "wgmma.mma_async.sync.aligned.m64n128k16.f32.bf16.bf16 {%0, %1, %2, %3, %4, %5, %6, %7, %8, %9, %10, %11, %12, %13, %14, %15, %16, %17, %18, %19, %20, %21, %22, %23, %24, %25, %26, %27, %28, %29, %30, %31, %32, %33, %34, %35, %36, %37, %38, %39, %40, %41, %42, %43, %44, %45, %46, %47, %48, %49, %50, %51, %52, %53, %54, %55, %56, %57, %58, %59, %60, %61, %62, %63}, ta, tb, p, 1, 1, 0, %67;\n}\n"
      : "+f"(d[0]), "+f"(d[1]), "+f"(d[2]), "+f"(d[3]), "+f"(d[4]), "+f"(d[5]), "+f"(d[6]), "+f"(d[7]), "+f"(d[8]), "+f"(d[9]), "+f"(d[10]), "+f"(d[11]), "+f"(d[12]), "+f"(d[13]), "+f"(d[14]), "+f"(d[15]), "+f"(d[16]), "+f"(d[17]), "+f"(d[18]), "+f"(d[19]), "+f"(d[20]), "+f"(d[21]), "+f"(d[22]), "+f"(d[23]), "+f"(d[24]), "+f"(d[25]), "+f"(d[26]), "+f"(d[27]), "+f"(d[28]), "+f"(d[29]), "+f"(d[30]), "+f"(d[31]), "+f"(d[32]), "+f"(d[33]), "+f"(d[34]), "+f"(d[35]), "+f"(d[36]), "+f"(d[37]), "+f"(d[38]), "+f"(d[39]), "+f"(d[40]), "+f"(d[41]), "+f"(d[42]), "+f"(d[43]), "+f"(d[44]), "+f"(d[45]), "+f"(d[46]), "+f"(d[47]), "+f"(d[48]), "+f"(d[49]), "+f"(d[50]), "+f"(d[51]), "+f"(d[52]), "+f"(d[53]), "+f"(d[54]), "+f"(d[55]), "+f"(d[56]), "+f"(d[57]), "+f"(d[58]), "+f"(d[59]), "+f"(d[60]), "+f"(d[61]), "+f"(d[62]), "+f"(d[63])
      : "l"(da), "l"(db), "r"(sd), "n"(TB), "n"(AOFF), "n"(BOFF));
}

template<int TB, int AOFF, int BOFF> __device__ __forceinline__ void wgmma_ss_n72(float (&d)[36], uint64_t da, uint64_t db, int sd) {
    asm volatile("{\n.reg .pred p;\n.reg .b64 ta, tb;\nsetp.ne.b32 p, %38, 0;\nadd.s64 ta, %36, %40;\nadd.s64 tb, %37, %41;\n"
      "wgmma.mma_async.sync.aligned.m64n72k16.f32.bf16.bf16 {%0, %1, %2, %3, %4, %5, %6, %7, %8, %9, %10, %11, %12, %13, %14, %15, %16, %17, %18, %19, %20, %21, %22, %23, %24, %25, %26, %27, %28, %29, %30, %31, %32, %33, %34, %35}, ta, tb, p, 1, 1, 0, %39;\n}\n"
      : "+f"(d[0]), "+f"(d[1]), "+f"(d[2]), "+f"(d[3]), "+f"(d[4]), "+f"(d[5]), "+f"(d[6]), "+f"(d[7]), "+f"(d[8]), "+f"(d[9]), "+f"(d[10]), "+f"(d[11]), "+f"(d[12]), "+f"(d[13]), "+f"(d[14]), "+f"(d[15]), "+f"(d[16]), "+f"(d[17]), "+f"(d[18]), "+f"(d[19]), "+f"(d[20]), "+f"(d[21]), "+f"(d[22]), "+f"(d[23]), "+f"(d[24]), "+f"(d[25]), "+f"(d[26]), "+f"(d[27]), "+f"(d[28]), "+f"(d[29]), "+f"(d[30]), "+f"(d[31]), "+f"(d[32]), "+f"(d[33]), "+f"(d[34]), "+f"(d[35])
      : "l"(da), "l"(db), "r"(sd), "n"(TB), "n"(AOFF), "n"(BOFF));
}

template<int TB, int BOFF> __device__ __forceinline__ void wgmma_rs_n64(float (&d)[32], uint32_t a0, uint32_t a1, uint32_t a2, uint32_t a3, uint64_t db, int sd) {
    asm volatile("{\n.reg .pred p;\n.reg .b64 tb;\nsetp.ne.b32 p, %37, 0;\nadd.s64 tb, %36, %39;\n"
      "wgmma.mma_async.sync.aligned.m64n64k16.f32.bf16.bf16 {%0, %1, %2, %3, %4, %5, %6, %7, %8, %9, %10, %11, %12, %13, %14, %15, %16, %17, %18, %19, %20, %21, %22, %23, %24, %25, %26, %27, %28, %29, %30, %31}, {%32, %33, %34, %35}, tb, p, 1, 1, %38;\n}\n"
      : "+f"(d[0]), "+f"(d[1]), "+f"(d[2]), "+f"(d[3]), "+f"(d[4]), "+f"(d[5]), "+f"(d[6]), "+f"(d[7]), "+f"(d[8]), "+f"(d[9]), "+f"(d[10]), "+f"(d[11]), "+f"(d[12]), "+f"(d[13]), "+f"(d[14]), "+f"(d[15]), "+f"(d[16]), "+f"(d[17]), "+f"(d[18]), "+f"(d[19]), "+f"(d[20]), "+f"(d[21]), "+f"(d[22]), "+f"(d[23]), "+f"(d[24]), "+f"(d[25]), "+f"(d[26]), "+f"(d[27]), "+f"(d[28]), "+f"(d[29]), "+f"(d[30]), "+f"(d[31])
      : "r"(a0), "r"(a1), "r"(a2), "r"(a3), "l"(db), "r"(sd), "n"(TB), "n"(BOFF));
}

template<int TB, int BOFF> __device__ __forceinline__ void wgmma_rs_n24(float (&d)[12], uint32_t a0, uint32_t a1, uint32_t a2, uint32_t a3, uint64_t db, int sd) {
    asm volatile("{\n.reg .pred p;\n.reg .b64 tb;\nsetp.ne.b32 p, %17, 0;\nadd.s64 tb, %16, %19;\n"
      "wgmma.mma_async.sync.aligned.m64n24k16.f32.bf16.bf16 {%0, %1, %2, %3, %4, %5, %6, %7, %8, %9, %10, %11}, {%12, %13, %14, %15}, tb, p, 1, 1, %18;\n}\n"
      : "+f"(d[0]), "+f"(d[1]), "+f"(d[2]), "+f"(d[3]), "+f"(d[4]), "+f"(d[5]), "+f"(d[6]), "+f"(d[7]), "+f"(d[8]), "+f"(d[9]), "+f"(d[10]), "+f"(d[11])
      : "r"(a0), "r"(a1), "r"(a2), "r"(a3), "l"(db), "r"(sd), "n"(TB), "n"(BOFF));
}

template<int TB, int BOFF> __device__ __forceinline__ void wgmma_rs_n72(float (&d)[36], uint32_t a0, uint32_t a1, uint32_t a2, uint32_t a3, uint64_t db, int sd) {
    asm volatile("{\n.reg .pred p;\n.reg .b64 tb;\nsetp.ne.b32 p, %41, 0;\nadd.s64 tb, %40, %43;\n"
      "wgmma.mma_async.sync.aligned.m64n72k16.f32.bf16.bf16 {%0, %1, %2, %3, %4, %5, %6, %7, %8, %9, %10, %11, %12, %13, %14, %15, %16, %17, %18, %19, %20, %21, %22, %23, %24, %25, %26, %27, %28, %29, %30, %31, %32, %33, %34, %35}, {%36, %37, %38, %39}, tb, p, 1, 1, %42;\n}\n"
      : "+f"(d[0]), "+f"(d[1]), "+f"(d[2]), "+f"(d[3]), "+f"(d[4]), "+f"(d[5]), "+f"(d[6]), "+f"(d[7]), "+f"(d[8]), "+f"(d[9]), "+f"(d[10]), "+f"(d[11]), "+f"(d[12]), "+f"(d[13]), "+f"(d[14]), "+f"(d[15]), "+f"(d[16]), "+f"(d[17]), "+f"(d[18]), "+f"(d[19]), "+f"(d[20]), "+f"(d[21]), "+f"(d[22]), "+f"(d[23]), "+f"(d[24]), "+f"(d[25]), "+f"(d[26]), "+f"(d[27]), "+f"(d[28]), "+f"(d[29]), "+f"(d[30]), "+f"(d[31]), "+f"(d[32]), "+f"(d[33]), "+f"(d[34]), "+f"(d[35])
      : "r"(a0), "r"(a1), "r"(a2), "r"(a3), "l"(db), "r"(sd), "n"(TB), "n"(BOFF));
}

constexpr int K1_XN_BYTES = 16 * 9216;
constexpr int K1_OFF_RING = K1_XN_BYTES;
constexpr int K1_OFF_BIAS = K1_OFF_RING + 10 * 8192;
constexpr int K1_OFF_BAR = K1_OFF_BIAS + 576 * 2;
constexpr int K1_SMEM = K1_OFF_BAR + 800;
constexpr float QSCALE = 0.23570226039551584f * 1.4426950408889634f;

struct K1Ctx {
    uint32_t full0;
    uint32_t rel_addr;
    uint64_t descA, descB;
    uint32_t phase;
    __device__ __forceinline__ void begin_stage(int s) {
        mbar_wait(full0 + s * 8, phase);
        wg_fence();
    }
    __device__ __forceinline__ void release(int s) {
        if (rel_addr) asm volatile("mbarrier.arrive.shared::cluster.b64 _, [%0];" ::"r"(rel_addr + s * 8) : "memory");
    }
    __device__ __forceinline__ void end_stage(int s) {
        wg_commit();
        wg_wait<1>();
        release(s == 0 ? 8 : s - 1);
    }
};

__host__ __device__ constexpr int a_off(int ks) { return ((ks / 12) * 49152 + ((ks >> 2) % 3) * 1024 + (ks & 3) * 32) >> 4; }

#define SPLIT_T 1
template <int V> struct IC { static constexpr int value = V; };
template <int I, int N, class F> __device__ __forceinline__ void static_for(F&& f) {
    if constexpr (I < N) { f(IC<I>{}); static_for<I + 1, N>(f); }
}

template <bool A_RS, bool B_RS, class Epi>
__device__ __forceinline__ void tile_pair(K1Ctx& c, float (&accA)[32], float (&accB)[32], uint32_t (&h)[144], Epi&& epi) {
    static_for<0, 9>([&](auto sc) {
        constexpr int s = decltype(sc)::value;
        c.begin_stage(s);
        static_for<0, 8>([&](auto tc) {
            constexpr int t = decltype(tc)::value, kk = s * 8 + t, ks = kk % 36;
            constexpr int bo = (ks * 2048) >> 4;
            if constexpr (kk < 36) {
                if constexpr (A_RS) wgmma_rs_n64<1, bo>(accA, h[ks * 4], h[ks * 4 + 1], h[ks * 4 + 2], h[ks * 4 + 3], c.descB, ks != 0);
                else wgmma_ss_n64<1, a_off(ks), bo>(accA, c.descA, c.descB, ks != 0);
            } else {
                if constexpr (B_RS) wgmma_rs_n64<1, bo>(accB, h[ks * 4], h[ks * 4 + 1], h[ks * 4 + 2], h[ks * 4 + 3], c.descB, ks != 0);
                else wgmma_ss_n64<1, a_off(ks), bo>(accB, c.descA, c.descB, ks != 0);
            }
            if constexpr (t == SPLIT_T) {
                c.end_stage(s);
                epi(sc);
            }
        });
        if constexpr (SPLIT_T < 7) wg_commit();
    });
    c.phase ^= 1;
}

template <int B0, int NB, int HOFF>
__device__ __forceinline__ void gelu_blocks(const float (&acc)[32], uint32_t (&h)[144], const uint32_t (&bq)[8], float rs0, float rs1) {
#pragma unroll
    for (int b = B0; b < B0 + NB; b++) {
        const float b0 = bf_lo(bq[b]), b1 = bf_hi(bq[b]);
        h[HOFF + b * 2 + 0] = pack_bf16(gelu2(fmaf(acc[b * 4 + 0], rs0, b0)), gelu2(fmaf(acc[b * 4 + 1], rs0, b1)));
        h[HOFF + b * 2 + 1] = pack_bf16(gelu2(fmaf(acc[b * 4 + 2], rs1, b0)), gelu2(fmaf(acc[b * 4 + 3], rs1, b1)));
    }
#pragma unroll
    for (int i = HOFF + B0 * 2; i < HOFF + (B0 + NB) * 2; i++) asm volatile("" : "+r"(h[i]));
}
__device__ __forceinline__ void load_bias(uint32_t (&bq)[8], uint32_t addr) {
    asm volatile("ld.shared.v4.u32 {%0, %1, %2, %3}, [%4];" : "=r"(bq[0]), "=r"(bq[1]), "=r"(bq[2]), "=r"(bq[3]) : "r"(addr));
    asm volatile("ld.shared.v4.u32 {%0, %1, %2, %3}, [%4 + 16];" : "=r"(bq[4]), "=r"(bq[5]), "=r"(bq[6]), "=r"(bq[7]) : "r"(addr));
}
template <int S> __device__ __forceinline__ void store_part(const float (&o)[32], uint4* p) {
    uint4 v;
    v.x = pack_bf16(o[S * 8 + 0], o[S * 8 + 1]); v.y = pack_bf16(o[S * 8 + 2], o[S * 8 + 3]);
    v.z = pack_bf16(o[S * 8 + 4], o[S * 8 + 5]); v.w = pack_bf16(o[S * 8 + 6], o[S * 8 + 7]);
    p[S * 256] = v;
}

constexpr int NCHUNK = 16;
constexpr int CHUNK_BYTES = KV_HEAD_BYTES / NCHUNK;
constexpr int SM_Q = 0;
constexpr int SM_KV = 32768;
constexpr int PIECE = 19968;
__host__ __device__ constexpr int sm_piece(int p) { return p == 0 ? 209408 : (p == 1 ? 0 : SM_KV + (p - 2) * PIECE); }
__host__ __device__ constexpr int sm_wstep(int k) { return k < 27 ? sm_piece(k / 3) + (k % 3) * 4608 : (k < 35 ? SM_KV + 7 * PIECE + (k - 27) * 4608 : PIECE); }
__host__ __device__ constexpr int sm_ostep(int k) { return sm_piece(k / 3) + 13824 + (k % 3) * 2048; }
constexpr int SM_RED = SM_KV + KV_HEAD_BYTES;

__device__ __forceinline__ float exp2_fixed(float y) {
    const float u = __uint_as_float(__float_as_uint(y) & 0xFF807FFFu) - 512.02545f;
    float t = fmaf(u, 0.019497588f, 0.114550486f);
    t = fmaf(t, u, -0.29839927f);
    return fmaf(t, u, y);
}
__device__ __forceinline__ uint32_t pack_fixed(float lo, float hi) { return __byte_perm(__float_as_uint(lo), __float_as_uint(hi), 0x6521); }

#define PV_GROUP 4
#define POLY_MODE 1
__device__ __forceinline__ uint32_t exp2_packed(float y0, float y1, uint32_t one2) {
    const uint32_t w = pack_fixed(y0, y1);
    uint32_t m;
    asm("lop3.b32 %0, %1, 0x007F007F, %2, 0xEA;" : "=r"(m) : "r"(w), "r"(one2));
    const uint32_t d = hfma2_bf16(m, 0x3EF93EF9u, 0xBF38BF38u);
    const uint32_t e = hfma2_bf16(d, d, 0xBD71BD71u);
    return hfma2_bf16(w, e, w);
}
constexpr int KV_TILE = CHUNK_BYTES / 16;
template <int OFF> __device__ __forceinline__ void issue_qk(float (&s)[64], uint64_t qd, uint64_t kd) {
    wgmma_ss_n128<0, 0, OFF + (8 << 16)>(s, qd, kd, 0);
    wgmma_ss_n128<0, 16, OFF + 32>(s, qd, kd, 1);
}
template <int OFF> __device__ __forceinline__ void issue_pv(float (&o)[12], const uint32_t (&p)[32], uint64_t vd) {
    static_for<0, 8>([&](auto kc) {
        constexpr int k = decltype(kc)::value;
        wgmma_rs_n24<1, OFF + k * (2 * KV_GROUP_BYTES / 16)>(o, p[k * 4], p[k * 4 + 1], p[k * 4 + 2], p[k * 4 + 3], vd, 1);
    });
}
template <int OFF>
__device__ __forceinline__ void softmax_pv(const float (&s)[64], uint32_t (&p)[32], float (&o)[12], uint64_t vd, uint32_t one2) {
    static_for<0, 8 / PV_GROUP>([&](auto gc) {
        constexpr int g0 = decltype(gc)::value * PV_GROUP;
#pragma unroll
        for (int b = g0 * 2; b < (g0 + PV_GROUP) * 2; b++) {
            if ((POLY_MASK >> b) & 1) {
                p[b * 2 + 0] = exp2_packed(s[b * 4 + 0], s[b * 4 + 1], one2);
                p[b * 2 + 1] = exp2_packed(s[b * 4 + 2], s[b * 4 + 3], one2);
            } else {
                p[b * 2 + 0] = pack_bf16(ex2(s[b * 4 + 0]), ex2(s[b * 4 + 1]));
                p[b * 2 + 1] = pack_bf16(ex2(s[b * 4 + 2]), ex2(s[b * 4 + 3]));
            }
        }
#pragma unroll
        for (int i = g0 * 4; i < (g0 + PV_GROUP) * 4; i++) asm volatile("" : "+r"(p[i])::"memory");
        wg_fence();
        static_for<g0, g0 + PV_GROUP>([&](auto kc) {
            constexpr int k = decltype(kc)::value;
            wgmma_rs_n24<1, OFF + k * (2 * KV_GROUP_BYTES / 16)>(o, p[k * 4], p[k * 4 + 1], p[k * 4 + 2], p[k * 4 + 3], vd, 1);
        });
    });
    wg_commit();
}
template <bool LATE> __device__ __forceinline__ void store_o(float (&o)[12], int rt, int head, int wq, int lane) {
    const int g = lane >> 2, q = lane & 3;
    const float i0 = __fdividef(1.0f, __shfl_sync(~0u, o[8], lane | 3)), i1 = __fdividef(1.0f, __shfl_sync(~0u, o[10], lane | 3));
#pragma unroll
    for (int i = 0; i < 3; i++) {
        const uint32_t w0 = pack_bf16(o[i * 4] * i0, o[i * 4 + 1] * i0), w1 = pack_bf16(o[i * 4 + 2] * i1, o[i * 4 + 3] * i1);
        if (i < 2 || q == 2) {
            if constexpr (LATE) {
                const int pc = (head & 7) * 9 + (i < 2 ? i * 4 + q : 8);
                uint32_t* op = reinterpret_cast<uint32_t*>(g_Olate) + (((rt * 9 + (pc >> 3)) * 128 + wq * 32 + g * 4 + (pc & 3)) * 4 + ((pc >> 2) & 1) * 2);
                asm volatile("st.relaxed.gpu.global.v2.u32 [%0], {%1, %2};" ::"l"(op), "r"(w0), "r"(w1) : "memory");
            } else {
                const int pc = head * 9 + (i < 2 ? i * 4 + q : 8);
                uint32_t* op = g_O + ((rt * 72 + (pc >> 2)) * 8 + wq * 2) * 32 + g * 4 + (pc & 3);
                op[0] = w0;
                op[32] = w1;
            }
        }
    }
#pragma unroll
    for (int i = 0; i < 12; i++) o[i] = 0.f;
}
__device__ __forceinline__ void mbar_arrive(uint32_t b) { asm volatile("mbarrier.arrive.shared::cta.b64 _, [%0];" ::"r"(b) : "memory"); }
__device__ __forceinline__ void mbar_wait_sleep(uint32_t b, uint32_t ns) {
    uint32_t ok, spins = 0;
    while (true) {
        asm volatile("{\n.reg .pred p;\nmbarrier.try_wait.parity.shared::cta.b64 p, [%1], 0;\nselp.u32 %0, 1, 0, p;\n}\n" : "=r"(ok) : "r"(b) : "memory");
        if (ok) break;
        __nanosleep(ns);
        if (++spins > (1u << 21)) __trap();
    }
}
__device__ __forceinline__ void flag_signal(unsigned int* f) {
    __threadfence();
    atomicAdd(f, 1u);
}
__device__ __forceinline__ void flag_wait(const unsigned int* f, unsigned int target, unsigned int sleep_ns) {
    uint32_t v, spins = 0;
    while (true) {
        asm volatile("ld.acquire.gpu.global.u32 %0, [%1];" : "=r"(v) : "l"(f) : "memory");
        if (v >= target) break;
        if (sleep_ns) __nanosleep(sleep_ns);
        if (++spins > (1u << 21)) __trap();
    }
}
__device__ __forceinline__ uint4 hadd8_bf16(const uint4 a, const uint4 b) {
    return make_uint4(hadd2_bf16(a.x, b.x), hadd2_bf16(a.y, b.y), hadd2_bf16(a.z, b.z), hadd2_bf16(a.w, b.w));
}
__device__ __forceinline__ float sumsq2(uint32_t w) { return fmaf(bf_lo(w), bf_lo(w), bf_hi(w) * bf_hi(w)); }
__device__ __forceinline__ float sumsq8(const uint4 v) { return (sumsq2(v.x) + sumsq2(v.y)) + (sumsq2(v.z) + sumsq2(v.w)); }

enum { B_FULL = 0, B_EMPTY = 9, B_BASE = 18, B_XNDEAD = 19, B_QRDY = 20, B_FFN = 21, B_KV = 22, B_FREE = 38, B_WO = 46, B_RED = 55, B_X = 61, B_EARLY = 85, B_OS = 86, B_LATE = 94, B_END = 95 };

__global__ void __cluster_dims__(2, 1, 1) __launch_bounds__(384, 1)
fused_kernel(const __grid_constant__ CUtensorMap tmX, const __grid_constant__ CUtensorMap tmQ3, const __grid_constant__ CUtensorMap tmQ1,
          const __grid_constant__ CUtensorMap tm1, const __grid_constant__ CUtensorMap tm2, const __grid_constant__ CUtensorMap tmP,
          const __grid_constant__ CUtensorMap tmOut, const __grid_constant__ CUtensorMap tmXo, const __nv_bfloat16* __restrict__ b1,
          const __nv_bfloat16* __restrict__ wqkv, const __nv_bfloat16* __restrict__ w1, const __nv_bfloat16* __restrict__ w2,
          const __nv_bfloat16* __restrict__ wo, const __nv_bfloat16* __restrict__ b2,
          const uint64_t zero) {
    extern __shared__ __align__(1024) uint8_t smem[];
    const uint32_t sb = s2u(smem);
    const int tid = threadIdx.x, lane = tid & 31;
    const int warp = __shfl_sync(~0u, tid >> 5, 0);
    const uint32_t rank = blockIdx.x & 1;
    const int cl = blockIdx.x >> 1;
    const int rb = (cl & 7) * 2 + rank;
    const int j = cl >> 3;
    const uint32_t bar0 = sb + K1_OFF_BAR;
    const uint32_t full0 = bar0 + B_FULL * 8, empty0 = bar0 + B_EMPTY * 8, xbar0 = bar0 + B_X * 8;
    const int head = blockIdx.x >> 2, quarter = blockIdx.x & 3;
    const int rt = quarter * 8 + (head >> 2), ct = head & 3;
    const int rot = head >> 3;
    const int ks0 = ((((head >> 3) + 2) & 3) * 9);
    volatile uint32_t* slow_flag = reinterpret_cast<volatile uint32_t*>(smem + K1_OFF_BAR + B_END * 8);

    if (warp < 8) {
        PROF(0);
        PROFT(48);
        if (lane == 0) {
#pragma unroll
            for (int i = 0; i < 3; i++) mbar_init(xbar0 + (warp * 3 + i) * 8, 1);
            fence_barrier_init();
#pragma unroll 1
            for (int i = 0; i < 3; i++) {
                const uint32_t xb = xbar0 + (warp * 3 + i) * 8;
                mbar_expect(xb, 6144);
                tma4d(sb + i * 49152 + warp * 6144, &tmX, 0, 0, i * 3, rb * 16 + warp * 2, xb);
            }
        }
        __syncwarp();
        cluster_arrive();
        PROF(22);
        reg_alloc<240>();
        PROF(23);
        float rs0, rs1;
        {
            const uint32_t la = sb + (warp * 2 + ((lane >> 3) & 1)) * 3072 + (lane & 7) * 128;
            uint32_t off[4];
#pragma unroll
            for (int i = 0; i < 4; i++) off[i] = la + (((i * 2 + (lane >> 4)) ^ (lane & 7)) << 4);
            float c1[4] = {0.f, 0.f, 0.f, 0.f}, c2[4] = {0.f, 0.f, 0.f, 0.f}, c3[4] = {0.f, 0.f, 0.f, 0.f};
            uint32_t a[36][4];
#pragma unroll
            for (int t = 0; t < 3; t++) {
                mbar_wait(xbar0 + (warp * 3 + t) * 8, 0);
                PROF(24 + t);
#pragma unroll
                for (int i = 0; i < 12; i++) ldsm4(a[t * 12 + i], off[i & 3] + t * 49152 + (i >> 2) * 1024);
#pragma unroll
                for (int i = t * 12; i < t * 12 + 12; i++) {
                    mma16816(c3, a[i], 0x3F803F80u, 0x3F803F80u);
                    mma16816(c1, a[i], a[i][0], a[i][2]);
                    mma16816(c2, a[i], a[i][1], a[i][3]);
                }
            }
            PROF(27);
            const int gg = lane >> 2, src = (lane & ~3) | (gg >> 1);
            const float m0 = c3[0] * (1.0f / DM), m1 = c3[2] * (1.0f / DM);
            const uint32_t mc0 = pack_bf16(-m0, -m0), mc1 = pack_bf16(-m1, -m1);
#pragma unroll
            for (int i = 0; i < 36; i++) {
#pragma unroll
                for (int k = 0; k < 4; k++) a[i][k] = hadd2_bf16(a[i][k], (k & 1) ? mc1 : mc0);
                stsm4(off[i & 3] + (i / 12) * 49152 + ((i >> 2) % 3) * 1024, a[i]);
            }
            const float q0 = __shfl_sync(~0u, (gg & 1) ? c1[1] : c1[0], src), q1 = __shfl_sync(~0u, (gg & 1) ? c2[3] : c2[2], src);
            rs0 = rsqrtf(fmaxf(fmaf(-m0, m0, q0 * (1.0f / DM)), 0.f) + 1e-5f);
            rs1 = rsqrtf(fmaxf(fmaf(-m1, m1, q1 * (1.0f / DM)), 0.f) + 1e-5f);
            if (__any_sync(~0u, fabsf(m0) * rs0 > 0.25f || fabsf(m1) * rs1 > 0.25f)) {
                const float d0 = -m0 - bf_lo(mc0), d1 = -m1 - bf_lo(mc1);
                const uint32_t md0 = pack_bf16(d0, d0), md1 = pack_bf16(d1, d1);
#pragma unroll 1
                for (int i = 0; i < 9; i++) {
#pragma unroll
                    for (int k4 = 0; k4 < 4; k4++) {
                        const uint32_t ad = off[k4] + (i / 3) * 49152 + (i % 3) * 1024;
                        uint32_t b[4];
                        ldsm4(b, ad);
#pragma unroll
                        for (int k = 0; k < 4; k++) b[k] = hadd2_bf16(b[k], (k & 1) ? md1 : md0);
                        stsm4(ad, b);
                    }
                }
            }
        }
        PROF(28);
        const int wg = warp >> 2, wq = warp & 3;
        fence_proxy_async();
        named_bar_sync(1 + wg, 128);
        cluster_wait();
        PROF(1);

        const int g = lane >> 2, q = lane & 3;
        K1Ctx c;
        c.full0 = full0;
        c.rel_addr = 0;
        c.descA = mk_desc(zero, sb + wg * 8 * 3072, 16, 3072, 1);
        c.descB = mk_desc(zero, sb + K1_OFF_RING, 2048, 1024, 1);
        c.phase = 0;
        uint32_t biasq = sb + K1_OFF_BIAS + q * 32;
        uint32_t bq[8];

        uint32_t h[144];
        float accA[32], accB[32];
        {
            float accQ[108];
            uint32_t rel = 0;
            if (lane == 0 && wq < 2) asm("mapa.shared::cluster.u32 %0, %1, %2;" : "=r"(rel) : "r"(empty0), "r"(wq));
#pragma unroll 1
            for (int r = 0; r < 2; r++) {
                static_for<0, 9>([&](auto sc) {
                    constexpr int s = decltype(sc)::value;
                    c.begin_stage(s);
                    const uint64_t da = c.descA + (r ? a_off(18 + 2 * s) : a_off(2 * s));
                    wgmma_ss_n216<1, 0, ((2 * s) % 9) * 512>(accQ, da, c.descB, (r | s) != 0);
                    wgmma_ss_n216<1, 2, ((2 * s + 1) % 9) * 512>(accQ, da, c.descB, 1);
                    c.end_stage(s);
                    c.rel_addr = rel;
                });
                c.phase ^= 1;
            }
            PROF(2); PROFWT(54);
            uint32_t rel9[9];
#pragma unroll
            for (int i9 = 0; i9 < 9; i9++) {
                const int p = 4 * i9 + q, hh = (p * 57) >> 9, r = p - 9 * hh;
                rel9[i9] = hh * KV_HEAD_BYTES + (r < 8 ? (r >> 2) * 128 + (r & 3) * 4 : 0);
            }
            uint32_t gb = 0, o2 = 0;
            float scl0 = 1.f, scl1 = 1.f;
            tile_pair<false, false>(c, accA, accB, h, [&](auto sc) {
                constexpr int s = decltype(sc)::value;
                if constexpr (s == 0) reg_fence(accQ);
                if constexpr (s < 6) {
                    constexpr int grp = s / 2, part = s % 2;
                    if constexpr (part == 0) {
                        const int G = 3 * j + grp, type = G >> 3;
                        gb = (G & 7) * 4 * KV_HEAD_BYTES + (rb * 16 + warp * 2) * KV_GROUP_BYTES + g * 16 + (type == 0 ? Q_OFFSET : (type == 2 ? 256 : 0));
                        o2 = type == 0 ? 256 : (type == 2 ? 264 : 512);
                        scl0 = rs0 * (type == 0 ? QSCALE : ((type == 1 && ((POLY_MASK >> (warp * 2)) & 1)) ? 2.f : 1.f));
                        scl1 = rs1 * (type == 0 ? QSCALE : ((type == 1 && ((POLY_MASK >> (warp * 2 + 1)) & 1)) ? 2.f : 1.f));
                    }
#pragma unroll
                    for (int i9 = part * 5; i9 < (part ? 9 : 5); i9++) {
                        const int b = grp * 9 + i9;
                        uint32_t off = gb + rel9[i9];
                        if (i9 >= 2 && (i9 & 1) == 0) off += (q == i9 / 2 - 1) ? o2 : 0;
                        *reinterpret_cast<uint32_t*>(g_QKV + off) = pack_bf16(accQ[b * 4] * scl0, accQ[b * 4 + 1] * scl0);
                        *reinterpret_cast<uint32_t*>(g_QKV + off + KV_GROUP_BYTES) = pack_bf16(accQ[b * 4 + 2] * scl1, accQ[b * 4 + 3] * scl1);
                    }
                    if constexpr (s == 5) asm volatile("bar.arrive 3, 352;" ::: "memory");
                }
                if constexpr (s == 4) { named_bar_sync(4, 352); load_bias(bq, biasq); }
                if constexpr (s == 5) reg_fence(accA);
                if constexpr (s >= 5) gelu_blocks<(s - 5) * 2, 2, 96>(accA, h, bq, rs0, rs1);
                if constexpr (s == 8) load_bias(bq, biasq + 128);
            });
        }
        PROF(3); PROFWT(55);
#pragma unroll
        for (int i = 32; i < 96; i++) asm volatile("mov.u32 %0, 0;" : "=r"(h[i]));
#pragma unroll 1
        for (int p = 1; p < 4; p++) {
            biasq += 256;
            tile_pair<false, false>(c, accA, accB, h, [&](auto sc) {
                constexpr int s = decltype(sc)::value;
                if constexpr (s == 0) {
                    reg_fence(accB);
#pragma unroll
                    for (int i = 0; i < 80; i++) h[i] = h[i + 32];
                }
                if constexpr (s < 4) gelu_blocks<s * 2, 2, 80>(accB, h, bq, rs0, rs1);
                if constexpr (s == 4) load_bias(bq, biasq);
                if constexpr (s == 5) reg_fence(accA);
                if constexpr (s >= 5) gelu_blocks<(s - 5) * 2, 2, 96>(accA, h, bq, rs0, rs1);
                if constexpr (s == 8) load_bias(bq, biasq + 128);
            });
        }
        PROF(4); PROFWT(56);
        tile_pair<false, true>(c, accA, accB, h, [&](auto sc) {
            constexpr int s = decltype(sc)::value;
            if constexpr (s == 0) reg_fence(accB);
            if constexpr (s < 4) gelu_blocks<s * 2, 2, 112>(accB, h, bq, rs0, rs1);
            if constexpr (s == 4) load_bias(bq, biasq + 256);
            if constexpr (s == 5) { reg_fence(accA); if (tid == wg * 128) mbar_arrive(bar0 + B_XNDEAD * 8); }
            if constexpr (s == 5 || s == 6) gelu_blocks<(s - 5) * 3, 3, 128>(accA, h, bq, rs0, rs1);
            if constexpr (s == 7) gelu_blocks<6, 2, 128>(accA, h, bq, rs0, rs1);
            if constexpr (s == 3 || s == 7) reg_fence(h);
        });
        PROF(5); PROFWT(57);
        uint4* pout = g_part + j * SLAB + rb * 36 * 256 + tid;
#pragma unroll 1
        for (int p = 0; p < 4; p++) {
            tile_pair<true, true>(c, accA, accB, h, [&](auto sc) {
                constexpr int s = decltype(sc)::value;
                if constexpr (s == 0) reg_fence(accB);
                if constexpr (s < 4) store_part<s>(accB, pout);
                if constexpr (s == 5) reg_fence(accA);
                if constexpr (s >= 5) store_part<s - 5>(accA, pout + 1024);
            });
            pout += 2048;
            PROF(6 + p);
        }
        wg_wait<0>();
        c.release(8);
        reg_fence(accB);
        store_part<0>(accB, pout); store_part<1>(accB, pout); store_part<2>(accB, pout); store_part<3>(accB, pout);
        __syncwarp();
        if (lane == 0) mbar_arrive(bar0 + B_FFN * 8);
        PROF(10); PROFWT(58);
        PROFT(49);

        mbar_wait(bar0 + B_QRDY * 8, 0);
        const uint32_t slow = __any_sync(~0u, *slow_flag != 0);
        const uint64_t kd0 = mk_desc(zero, sb + SM_KV, 0, KV_GROUP_BYTES, 0);
        const uint64_t vd0 = mk_desc(zero, sb + SM_KV + 256, KV_GROUP_BYTES, 128, 0);
        const uint64_t qd0 = mk_desc(zero, sb + SM_Q + wg * 4096, 128, 512, 0);
        const uint32_t kvbar = bar0 + B_KV * 8;
        float o[12];
#pragma unroll
        for (int i = 0; i < 12; i++) o[i] = 0.f;
        PROF(16);
        PROFT(50);
        if (!slow) {
            const uint32_t one2 = 0x3F803F80u + (uint32_t)zero;
            float s0[64], s1[64];
            uint32_t p0[32], p1[32];
            mbar_wait(kvbar, 0);
            reg_fence(o);
            wg_fence();
            issue_qk<0>(s0, qd0, kd0);
            wg_commit();
            wg_commit();
            uint64_t qd = qd0;
            const uint32_t fre = (tid == wg * 128) ? bar0 + B_FREE * 8 - 8 : 0;
#pragma unroll 1
            for (int pass = 0; pass < 4; pass++) {
                uint64_t vd = vd0, kd = kd0;
                uint32_t bn = kvbar + 8;
#pragma unroll 1
                for (int it = 0; it < 8; it++) {
                    mbar_wait(bn, 0);
                    if (it == 0 && pass != 0) {
                        wg_wait<0>();
                        reg_fence(o);
                        store_o<false>(o, quarter * 8 + ((pass - 1 + rot) & 3) * 2 + wg, head, wq, lane);
                        reg_fence(o);
                        __syncwarp();
                        if (lane == 0) mbar_arrive(bar0 + (B_OS + pass * 2 - 2 + wg) * 8);
                    }
                    wg_wait<1>();
                    reg_fence(s0);
                    wg_fence();
                    issue_qk<KV_TILE>(s1, qd, kd);
                    wg_commit();
                    if (pass == 3 && it > 0 && fre) mbar_arrive(fre + it * 8);
                    softmax_pv<0>(s0, p0, o, vd, one2);
                    kd += 2 * KV_TILE; bn += 8;
                    if (it == 7) { kd = kd0; bn = kvbar; qd += 512; }
                    mbar_wait(bn, 0);
                    wg_wait<1>();
                    reg_fence(s1);
                    wg_fence();
                    issue_qk<0>(s0, qd, kd);
                    wg_commit();
                    softmax_pv<KV_TILE>(s1, p1, o, vd, one2);
                    vd += 2 * KV_TILE; bn += 8;
                }
                if (pass == 0) PROF(17);
            }
            wg_wait<0>();
            reg_fence(o);
            reg_fence(s0);
            reg_fence(s1);
            store_o<true>(o, quarter * 8 + ((3 + rot) & 3) * 2 + wg, head, wq, lane);
        } else {
#pragma unroll 1
            for (int pass = 0; pass < 4; pass++) {
                float m0 = -INFINITY, m1 = -INFINITY;
                float s[64];
                uint32_t p[32];
#pragma unroll 1
                for (int t = 0; t < 16; t++) {
                    mbar_wait(kvbar + t * 8, 0);
                    wg_fence();
                    issue_qk<0>(s, qd0 + pass * 512, kd0 + t * KV_TILE);
                    wg_commit();
                    wg_wait<0>();
                    reg_fence(s);
                    float a0 = m0, a1 = m1;
#pragma unroll
                    for (int k = 0; k < 16; k++) {
                        if ((POLY_MASK >> k) & 1) {
#pragma unroll
                            for (int i = 0; i < 4; i++) s[k * 4 + i] *= 0.5f;
                        }
                        a0 = fmaxf(a0, fmaxf(s[k * 4 + 0], s[k * 4 + 1]));
                        a1 = fmaxf(a1, fmaxf(s[k * 4 + 2], s[k * 4 + 3]));
                    }
                    a0 = fmaxf(a0, __shfl_xor_sync(~0u, a0, 1)); a1 = fmaxf(a1, __shfl_xor_sync(~0u, a1, 1));
                    a0 = fmaxf(a0, __shfl_xor_sync(~0u, a0, 2)); a1 = fmaxf(a1, __shfl_xor_sync(~0u, a1, 2));
                    const float r0 = ex2(m0 - a0), r1 = ex2(m1 - a1);
                    m0 = a0; m1 = a1;
#pragma unroll
                    for (int i = 0; i < 3; i++) { o[i * 4] *= r0; o[i * 4 + 1] *= r0; o[i * 4 + 2] *= r1; o[i * 4 + 3] *= r1; }
#pragma unroll
                    for (int k = 0; k < 16; k++) {
                        p[k * 2 + 0] = pack_bf16(ex2(s[k * 4 + 0] - m0), ex2(s[k * 4 + 1] - m0));
                        p[k * 2 + 1] = pack_bf16(ex2(s[k * 4 + 2] - m1), ex2(s[k * 4 + 3] - m1));
                    }
                    reg_fence(p);
                    reg_fence(o);
                    wg_fence();
                    issue_pv<0>(o, p, vd0 + t * KV_TILE);
                    wg_commit();
                    wg_wait<0>();
                    reg_fence(o);
                }
                if (pass < 3) {
                    store_o<false>(o, quarter * 8 + ((pass + rot) & 3) * 2 + wg, head, wq, lane);
                    __syncwarp();
                    if (lane == 0) mbar_arrive(bar0 + (B_OS + pass * 2 + wg) * 8);
                }
            }
            store_o<true>(o, quarter * 8 + ((3 + rot) & 3) * 2 + wg, head, wq, lane);
            if (tid == wg * 128)
                for (int i = 0; i < 7; i++) mbar_arrive(bar0 + (B_FREE + i) * 8);
        }
        PROF(18);
        PROFT(51);

        if (tid == wg * 128) mbar_arrive(bar0 + (B_FREE + 7) * 8);
        const int t128 = tid & 127;
        uint32_t bv[9];
        uint2 fv[9];
        mbar_wait(bar0 + B_BASE * 8, 0);
#pragma unroll
        for (int i = 0; i < 9; i++) {
            bv[i] = __ldg(reinterpret_cast<const uint32_t*>(b2 + ct * 144 + wg * 72 + q * 2) + i * 4);
            fv[i] = __ldcg(g_ffn + (blockIdx.x * 18 + wg * 9 + i) * 128 + t128);
        }
        float acc[36];
        const uint64_t od = mk_desc(zero, sb, 1024, 128, 0), wd = mk_desc(zero, sb + wg * 9 * 128, 2304, 128, 0);
        static_for<0, 9>([&](auto pc) {
            constexpr int p = decltype(pc)::value;
            mbar_wait(bar0 + (B_WO + p) * 8, 0);
            wg_fence();
            wgmma_ss_n72<1, sm_ostep(p * 3) / 16, sm_wstep(p * 3) / 16>(acc, od, wd, p != 0);
            wgmma_ss_n72<1, sm_ostep(p * 3 + 1) / 16, sm_wstep(p * 3 + 1) / 16>(acc, od, wd, 1);
            wgmma_ss_n72<1, sm_ostep(p * 3 + 2) / 16, sm_wstep(p * 3 + 2) / 16>(acc, od, wd, 1);
            wg_commit();
            if constexpr (p == 1) {
                wg_wait<1>();
                if (t128 == 0) mbar_arrive(bar0 + B_EARLY * 8);
            }
        });
        wg_wait<0>();
        reg_fence(acc);
        PROF(29);
        uint4 al[9];
        {
            const uint4* ap = g_Olate + rt * 9 * 128 + t128;
            uint32_t spins = 0;
            bool ok;
            do {
                ok = true;
#pragma unroll
                for (int k = 0; k < 9; k++)
                    asm volatile("ld.relaxed.gpu.global.v4.u32 {%0, %1, %2, %3}, [%4];" : "=r"(al[k].x), "=r"(al[k].y), "=r"(al[k].z), "=r"(al[k].w) : "l"(ap + k * 128) : "memory");
#pragma unroll
                for (int k = 0; k < 9; k++) ok = ok && al[k].x != O_EMPTY && al[k].y != O_EMPTY && al[k].z != O_EMPTY && al[k].w != O_EMPTY;
                if (++spins > (1u << 20)) __trap();
            } while (!__all_sync(~0u, ok));
        }
        PROF(19);
        mbar_wait(bar0 + B_LATE * 8, 0);
        PROF(20);
        wg_fence();
        static_for<27, 36>([&](auto kc) {
            constexpr int k = decltype(kc)::value;
            wgmma_rs_n72<1, sm_wstep(k) / 16>(acc, al[k - 27].x, al[k - 27].y, al[k - 27].z, al[k - 27].w, wd, 1);
        });
        wg_commit();
        PROF(31);
        uint32_t* st = reinterpret_cast<uint32_t*>(smem + sm_piece(0) + wg * 9216) + (wq * 16 + g) * 36 + q;
        float bs[36];
#pragma unroll
        for (int i = 0; i < 9; i++) {
            const uint32_t x0 = st[i * 4], x1 = st[i * 4 + 288];
            bs[i * 4 + 0] = fmaf(bf_lo(fv[i].x), 0.5f, bf_lo(x0) + bf_lo(bv[i]));
            bs[i * 4 + 1] = fmaf(bf_hi(fv[i].x), 0.5f, bf_hi(x0) + bf_hi(bv[i]));
            bs[i * 4 + 2] = fmaf(bf_lo(fv[i].y), 0.5f, bf_lo(x1) + bf_lo(bv[i]));
            bs[i * 4 + 3] = fmaf(bf_hi(fv[i].y), 0.5f, bf_hi(x1) + bf_hi(bv[i]));
        }
        reg_fence(bs);
        wg_wait<0>();
        reg_fence(acc);
        PROF(32);
#pragma unroll
        for (int i = 0; i < 9; i++) {
            st[i * 4] = pack_bf16(acc[i * 4] + bs[i * 4], acc[i * 4 + 1] + bs[i * 4 + 1]);
            st[i * 4 + 288] = pack_bf16(acc[i * 4 + 2] + bs[i * 4 + 2], acc[i * 4 + 3] + bs[i * 4 + 3]);
        }
        fence_proxy_async();
        named_bar_sync(1 + wg, 128);
        if (t128 == 0) {
            asm volatile("cp.async.bulk.tensor.2d.global.shared::cta.bulk_group [%0, {%2, %3}], [%1];"
                         ::"l"(&tmOut), "r"(sb + sm_piece(0) + wg * 9216), "r"(ct * 144 + wg * 72), "r"(rt * 64) : "memory");
            asm volatile("cp.async.bulk.commit_group;" ::: "memory");
            asm volatile("cp.async.bulk.wait_group.read 0;" ::: "memory");
        }
        PROF(21);
        PROFT(52);
    } else {
        reg_dealloc<24>();
        if (warp == 8 && lane == 0) {
            prefetch_tmap(&tmQ3); prefetch_tmap(&tmQ1); prefetch_tmap(&tm1); prefetch_tmap(&tm2);
            #pragma unroll 1
            for (int i = 0; i < 9; i++) { mbar_init(full0 + i * 8, 1); mbar_init(empty0 + i * 8, 4); mbar_init(bar0 + (B_WO + i) * 8, 2); }
            mbar_init(bar0 + B_BASE * 8, 3); mbar_init(bar0 + B_XNDEAD * 8, 2); mbar_init(bar0 + B_QRDY * 8, 3); mbar_init(bar0 + B_FFN * 8, 8); mbar_init(bar0 + B_EARLY * 8, 2); mbar_init(bar0 + B_LATE * 8, 2);
#pragma unroll 1
            for (int i = 0; i < 16; i++) { mbar_init(bar0 + (B_KV + i) * 8, 1); mbar_init(bar0 + (B_FREE + (i & 7)) * 8, 2); if (i < 6) mbar_init(bar0 + (B_RED + i) * 8, 1); if (i < 6) mbar_init(bar0 + (B_OS + i) * 8, 4); }
            *slow_flag = 0;
            fence_barrier_init();
        }
        __syncwarp();
        cluster_arrive();
        cluster_wait();
        const uint8_t* kvsrc = g_QKV + (size_t)head * KV_HEAD_BYTES;
        if (warp == 8) {
            if (lane == 0) {
                int st = 0, u = rank, tile = -4;
                int es = 5;
                uint32_t eph = 1;
#pragma unroll 1
                for (int n = 0; n < 99; n++) {
                    mbar_wait(empty0 + es * 8, eph);
                    const uint32_t fb = full0 + st * 8, dst = sb + K1_OFF_RING + u * 8192;
                    mbar_expect(fb, 16384);
                    if (tile < 0) {
                        tma3d_mc(dst, &tmQ3, j * 216, n * 32 + rank * 16, 0, fb, 3);
                        tma2d_mc(dst + 6144, &tmQ1, j * 216 + 192, n * 32 + rank * 16, fb, 3);
                    } else if (tile < 9) {
                        tma2d_mc(dst, &tm1, j * 576 + tile * 64, u * 64, fb, 3);
                    } else {
                        tma2d_mc(dst, &tm2, (tile - 9) * 64, j * 576 + u * 64, fb, 3);
                    }
                    u += 2;
                    if (u >= 9) { u -= 9; tile++; }
                    if (++st == 9) st = 0;
                    if (++es == 9) { es = 0; eph ^= 1; }
                }
                mbar_wait(empty0 + 8 * 8, 0);
                mbar_wait(bar0 + B_QRDY * 8, 0);
                asm volatile("fence.proxy.async;" ::: "memory");
#pragma unroll 1
                for (int i = 11; i < NCHUNK; i++) {
                    mbar_expect(bar0 + (B_KV + i) * 8, CHUNK_BYTES);
                    bulk_load(sb + SM_KV + i * CHUNK_BYTES, kvsrc + i * CHUNK_BYTES, CHUNK_BYTES, bar0 + (B_KV + i) * 8);
                }
                const uint8_t* wsrc = g_Wo + ct * WO_TILE_BYTES;
                prefetch_tmap(&tmOut);
                mbar_wait_sleep(bar0 + B_BASE * 8, 500);
#pragma unroll 1
                for (int p = 0; p < 9; p++) {
                    if (p > 0) mbar_wait_sleep(bar0 + (B_FREE + p - 1) * 8, p == 1 ? 500 : 40);
                    const int k = ks0 + p * 3 >= 36 ? ks0 + p * 3 - 36 : ks0 + p * 3;
                    mbar_expect(bar0 + (B_WO + p) * 8, 13824);
                    bulk_load(sb + (p == 0 ? sm_piece(0) : (p == 1 ? sm_piece(1) : SM_KV + (p - 2) * PIECE)), wsrc + k * 4608, 13824, bar0 + (B_WO + p) * 8);
                }
                const int kl = ks0 == 0 ? 27 : ks0 - 9;
                mbar_expect(bar0 + B_LATE * 8, 9 * 4608);
                bulk_load(sb + sm_wstep(27), wsrc + kl * 4608, 8 * 4608, bar0 + B_LATE * 8);
                bulk_load(sb + sm_wstep(35), wsrc + (kl + 8) * 4608, 4608, bar0 + B_LATE * 8);
            }
        } else {
            const int ht = tid - 288;
            if (ht == 64) prefetch_l2(wqkv + blockIdx.x * (DM * 3 * DM / 128), DM * 3 * DM / 64);
            if (ht < 72) {
                const uint4 v = __ldg(reinterpret_cast<const uint4*>(b1 + j * 576) + ht);
                uint32_t* sbias = reinterpret_cast<uint32_t*>(smem + K1_OFF_BIAS) + (ht >> 3) * 32 + (ht & 7);
                sbias[0] = v.x; sbias[8] = v.y; sbias[16] = v.z; sbias[24] = v.w;
            }
            asm volatile("bar.arrive 4, 352;" ::: "memory");
            PROFH(37);
#pragma unroll
            for (int i = 0; i < 3; i++) g_Olate[blockIdx.x * 288 + i * 96 + ht] = make_uint4(O_EMPTY, O_EMPTY, O_EMPTY, O_EMPTY);
#pragma unroll 1
            for (int i = ht; i < 512; i += 96) {
                const int key = i & 127;
                uint8_t* p = g_QKV + (size_t)(j * 4 + (i >> 7)) * KV_HEAD_BYTES + (rb * 16 + (key >> 3)) * KV_GROUP_BYTES + 512 + (key & 7) * 16;
                *reinterpret_cast<uint32_t*>(p + 4) = ((POLY_MASK >> (key >> 3)) & 1) ? 0x3F804000u : 0x00003F80u;
                *reinterpret_cast<uint32_t*>(p + 12) = 0x00003F80u;
            }
            if (ht == 32) prefetch_l2(w1 + blockIdx.x * (DM * FF / 128), DM * FF / 64);
#pragma unroll 2
            for (int i = blockIdx.x * 324 + ht; i < blockIdx.x * 324 + 324; i += 96) {
                const int k = i / 72, nc = i - k * 72, c4 = nc / 18;
                *reinterpret_cast<uint4*>(g_Wo + c4 * WO_TILE_BYTES + (k >> 3) * 2304 + (nc - c4 * 18) * 128 + (k & 7) * 16) =
                    __ldg(reinterpret_cast<const uint4*>(wo) + i);
            }
            PROFH(38);
            named_bar_sync(3, 352);
            if (ht == 32) prefetch_l2(w2 + blockIdx.x * (DM * FF / 128), DM * FF / 64);
            if (ht == 0) {
                flag_signal(&g_flags.qkv_stored[rb]);
                flag_wait(&g_flags.qkv_stored[rb], 8, 200);
            }
            named_bar_sync(7, 96);
            PROFH(39);
#pragma unroll 1
            for (int i = warp - 9; i < 16; i += 3) {
                const int hd = j * 4 + (i >> 2), key = (i & 3) * 32 + lane;
                const uint8_t* p = g_QKV + (size_t)hd * KV_HEAD_BYTES + (rb * 16 + (key >> 3)) * KV_GROUP_BYTES + (key & 7) * 16;
                const uint4 a = __ldcg(reinterpret_cast<const uint4*>(p)), b = __ldcg(reinterpret_cast<const uint4*>(p + 128));
                float n = sumsq2(__ldcg(reinterpret_cast<const uint32_t*>(p + 512))) + sumsq8(a) + sumsq8(b);
                if ((POLY_MASK >> (key >> 3)) & 1) n *= 0.25f;
#pragma unroll
                for (int o = 16; o; o >>= 1) n = fmaxf(n, __shfl_xor_sync(~0u, n, o));
                if (lane == 0) g_kmax[hd * 64 + rb * 4 + (i & 3)] = n;
            }
            named_bar_sync(7, 96);
            PROFH(40);
            if (ht == 0) {
                flag_signal(&g_flags.kv_ready);
                flag_wait(&g_flags.kv_ready, 128, 300);
                mbar_wait_sleep(bar0 + B_XNDEAD * 8, 300);
            }
            named_bar_sync(7, 96);
            PROFH(41);
            float kmax2;
            {
                const float2 v = __ldcg(reinterpret_cast<const float2*>(g_kmax + head * 64 + lane * 2));
                kmax2 = fmaxf(v.x, v.y);
#pragma unroll
                for (int o = 16; o; o >>= 1) kmax2 = fmaxf(kmax2, __shfl_xor_sync(~0u, kmax2, o));
            }
            asm volatile("fence.proxy.async;" ::: "memory");
            int chunk = warp - 9;
#pragma unroll 1
            for (int r = ht; r < 512; r += 96) {
                if (lane == 0 && chunk < 11) {
                    mbar_expect(bar0 + (B_KV + chunk) * 8, CHUNK_BYTES);
                    bulk_load(sb + SM_KV + chunk * CHUNK_BYTES, kvsrc + chunk * CHUNK_BYTES, CHUNK_BYTES, bar0 + (B_KV + chunk) * 8);
                }
                chunk += 3;
                const uint8_t* p = kvsrc + Q_OFFSET + (quarter * 64 + (((r >> 3) + rot * 16) & 63)) * KV_GROUP_BYTES + (r & 7) * 16;
                const uint4 a = __ldcg(reinterpret_cast<const uint4*>(p)), b = __ldcg(reinterpret_cast<const uint4*>(p + 128));
                const uint32_t e = __ldcg(reinterpret_cast<const uint32_t*>(p + 256));
                const float cc = sqrtf((sumsq2(e) + sumsq8(a) + sumsq8(b)) * kmax2) * 1.02f;
                if (!(cc <= 58.f)) *slow_flag = 1;
                uint4* dst = reinterpret_cast<uint4*>(smem + SM_Q + (r >> 3) * 512 + (r & 7) * 16);
                dst[0] = a;
                dst[8] = b;
                dst[16] = make_uint4(e, pack_bf16(-cc, 768.f), 0u, 0u);
                dst[24] = make_uint4(0u, POLY_MODE ? 0xBFFF0000u : 0xC0000000u, 0u, 0u);
            }
            named_bar_sync(7, 96);
            if (*slow_flag) {
#pragma unroll 1
                for (int r = ht; r < 512; r += 96) {
                    uint32_t* dst = reinterpret_cast<uint32_t*>(smem + SM_Q + (r >> 3) * 512 + (r & 7) * 16);
                    dst[65] = 0u;
                    dst[97] = 0u;
                }
            }
            fence_proxy_async();
            __syncwarp();
            if (lane == 0) mbar_arrive(bar0 + B_QRDY * 8);
            PROFH(42);
            if (ht == 0) {
                mbar_wait_sleep(bar0 + B_FFN * 8, 300);
                flag_signal(&g_flags.ffn_done[rb]);
                flag_wait(&g_flags.ffn_done[rt >> 1], 8, 300);
            }
            named_bar_sync(7, 96);
            {
                const int w3 = warp - 9;
                const uint32_t rbar = bar0 + (B_RED + w3 * 2) * 8, rbuf = SM_RED + w3 * 8192;
                const int u0 = ((rt >> 1) * 36 + ct * 9) * 256 + (rt & 1) * 128;
                mbar_wait_sleep(bar0 + (B_KV + 15) * 8, 500);
                asm volatile("fence.proxy.async;" ::: "memory");
#pragma unroll 1
                for (int i = -2; i < 12; i++) {
                    if (i >= 0) {
                        __nanosleep(400);
                        mbar_wait(rbar + (i & 1) * 8, (i >> 1) & 1);
                        const uint4* sp = reinterpret_cast<const uint4*>(smem + rbuf + (i & 1) * 4096) + lane;
                        const uint4 v = hadd8_bf16(hadd8_bf16(hadd8_bf16(sp[0], sp[32]), hadd8_bf16(sp[64], sp[96])),
                                                   hadd8_bf16(hadd8_bf16(sp[128], sp[160]), hadd8_bf16(sp[192], sp[224])));
                        const int bx = i * 3 + w3;
                        uint2* fp = g_ffn + (blockIdx.x * 18 + (bx >> 2) * 2) * 128 + (bx & 3) * 32 + lane;
                        fp[0] = make_uint2(v.x, v.y);
                        fp[128] = make_uint2(v.z, v.w);
                    }
                    __syncwarp();
                    if (lane == 0 && i < 10) {
                        const int bx = (i + 2) * 3 + w3;
                        mbar_expect(rbar + (i & 1) * 8, 4096);
                        tma2d(sb + rbuf + (i & 1) * 4096, &tmP, (u0 + (bx >> 2) * 256 + (bx & 3) * 32) * 2, 0, rbar + (i & 1) * 8);
                    }
                }
            }
            __syncwarp();
            if (lane == 0) mbar_arrive(bar0 + B_BASE * 8);
            PROFH(43);
            if (ht == 0) {
#pragma unroll 1
                for (int i = 0; i < 6; i++) {
                    mbar_wait_sleep(bar0 + (B_OS + i) * 8, 200);
                    flag_signal(&g_flags.o_done[quarter * 8 + (((i >> 1) + rot) & 3) * 2 + (i & 1)]);
                }
            } else if (ht == 32) {
                const uint8_t* osrc = reinterpret_cast<const uint8_t*>(g_O) + rt * 73728;
                mbar_wait_sleep(bar0 + B_BASE * 8, 500);
                mbar_wait_sleep(bar0 + B_FREE * 8, 500);
                flag_wait(&g_flags.o_done[rt], 24, 100);
                if (atomicAdd(&g_flags.exited, 1u) == gridDim.x - 1) {
                    unsigned int* f = reinterpret_cast<unsigned int*>(&g_flags);
#pragma unroll 1
                    for (int i = 0; i < (int)(sizeof(Flags) / 4); i++) f[i] = 0;
                }
                prefetch_tmap(&tmXo);
                asm volatile("fence.proxy.async;" ::: "memory");
#pragma unroll 1
                for (int p = 0; p < 9; p++) {
                    if (p > 1) mbar_wait_sleep(bar0 + (B_FREE + p - 1) * 8, 40);
                    const int k = ks0 + p * 3 >= 36 ? ks0 + p * 3 - 36 : ks0 + p * 3;
                    mbar_expect(bar0 + (B_WO + p) * 8, 6144);
                    bulk_load(sb + 13824 + (p == 0 ? sm_piece(0) : (p == 1 ? sm_piece(1) : SM_KV + (p - 2) * PIECE)), osrc + k * 2048, 6144, bar0 + (B_WO + p) * 8);
                }
                mbar_expect(bar0 + B_LATE * 8, 2 * 9216);
                mbar_wait(bar0 + B_EARLY * 8, 0);
                tma2d(sb + sm_piece(0), &tmXo, ct * 144, rt * 64, bar0 + B_LATE * 8);
                tma2d(sb + sm_piece(0) + 9216, &tmXo, ct * 144 + 72, rt * 64, bar0 + B_LATE * 8);
            }
        }
    }
}

typedef CUresult (*EncodeFn)(CUtensorMap*, CUtensorMapDataType, cuuint32_t, void*, const cuuint64_t*, const cuuint64_t*, const cuuint32_t*,
                             const cuuint32_t*, CUtensorMapInterleave, CUtensorMapSwizzle, CUtensorMapL2promotion, CUtensorMapFloatOOBfill);

void make_map(EncodeFn fn, CUtensorMap* m, const void* base, int rank, const cuuint64_t* dims, const cuuint64_t* strides, const cuuint32_t* box) {
    cuuint32_t es[4] = {1, 1, 1, 1};
    fn(m, CU_TENSOR_MAP_DATA_TYPE_BFLOAT16, rank, const_cast<void*>(base), dims, strides, box, es, CU_TENSOR_MAP_INTERLEAVE_NONE,
       CU_TENSOR_MAP_SWIZZLE_128B, CU_TENSOR_MAP_L2_PROMOTION_L2_256B, CU_TENSOR_MAP_FLOAT_OOB_FILL_NONE);
}

}

extern "C" void kernel_launch(void* const* d_in, const int* in_sizes, int n_in, void* d_out, int out_size) {
    const __nv_bfloat16* x = (const __nv_bfloat16*)d_in[0];
    const __nv_bfloat16* wqkv = (const __nv_bfloat16*)d_in[1];
    const __nv_bfloat16* wo = (const __nv_bfloat16*)d_in[2];
    const __nv_bfloat16* w1 = (const __nv_bfloat16*)d_in[4];
    const __nv_bfloat16* b1 = (const __nv_bfloat16*)d_in[5];
    const __nv_bfloat16* w2 = (const __nv_bfloat16*)d_in[6];
    const __nv_bfloat16* b2 = (const __nv_bfloat16*)d_in[7];
    __nv_bfloat16* out = (__nv_bfloat16*)d_out;

    EncodeFn fn = nullptr;
    cudaDriverEntryPointQueryResult qr;
    cudaGetDriverEntryPoint("cuTensorMapEncodeTiled", (void**)&fn, cudaEnableDefault, &qr);
    CUtensorMap tmX, tmQ3, tmQ1, tm1, tm2, tmP, tmOut, tmXo;
    {
        cuuint64_t d[2] = {DM, SEQ}, s[1] = {DM * 2};
        cuuint32_t b[2] = {72, 64}, es[2] = {1, 1};
        fn(&tmOut, CU_TENSOR_MAP_DATA_TYPE_BFLOAT16, 2, out, d, s, b, es, CU_TENSOR_MAP_INTERLEAVE_NONE, CU_TENSOR_MAP_SWIZZLE_NONE,
           CU_TENSOR_MAP_L2_PROMOTION_NONE, CU_TENSOR_MAP_FLOAT_OOB_FILL_NONE);
        fn(&tmXo, CU_TENSOR_MAP_DATA_TYPE_BFLOAT16, 2, const_cast<__nv_bfloat16*>(x), d, s, b, es, CU_TENSOR_MAP_INTERLEAVE_NONE,
           CU_TENSOR_MAP_SWIZZLE_NONE, CU_TENSOR_MAP_L2_PROMOTION_NONE, CU_TENSOR_MAP_FLOAT_OOB_FILL_NONE);
    }
    {
        void* gp = nullptr;
        cudaGetSymbolAddress(&gp, g_part);
        cuuint64_t d[2] = {SLAB * 2, 8}, s[1] = {SLAB * 16};
        cuuint32_t b[2] = {64, 8}, es[2] = {1, 1};
        fn(&tmP, CU_TENSOR_MAP_DATA_TYPE_INT64, 2, gp, d, s, b, es, CU_TENSOR_MAP_INTERLEAVE_NONE, CU_TENSOR_MAP_SWIZZLE_NONE,
           CU_TENSOR_MAP_L2_PROMOTION_NONE, CU_TENSOR_MAP_FLOAT_OOB_FILL_NONE);
    }
    {
        cuuint64_t d[4] = {64, 8, 9, SEQ / 8}, s[3] = {DM * 2, 128, DM * 2 * 8};
        cuuint32_t b[4] = {64, 8, 3, 2};
        make_map(fn, &tmX, x, 4, d, s, b);
    }
    {
        cuuint64_t d[3] = {3 * DM, DM, 3}, s[2] = {3 * DM * 2, 128};
        cuuint32_t b[3] = {64, 16, 3};
        make_map(fn, &tmQ3, wqkv, 3, d, s, b);
        make_map(fn, &tmQ1, wqkv, 2, d, s, b);
    }
    {
        cuuint64_t d[2] = {FF, DM}, s[1] = {FF * 2};
        cuuint32_t b[2] = {64, 64};
        make_map(fn, &tm1, w1, 2, d, s, b);
        cuuint64_t d2[2] = {DM, FF}, s2[1] = {DM * 2};
        make_map(fn, &tm2, w2, 2, d2, s2, b);
    }
    cudaFuncSetAttribute(fused_kernel, cudaFuncAttributeMaxDynamicSharedMemorySize, K1_SMEM);
    fused_kernel<<<128, 384, K1_SMEM, cudaStreamPerThread>>>(tmX, tmQ3, tmQ1, tm1, tm2, tmP, tmOut, tmXo, b1, wqkv, w1, w2, wo, b2, 0ull);
}
```

```cpp
#include <cuda_runtime.h>
#include <cuda_bf16.h>
#include <cuda.h>
#include <stdint.h>

#define PROF(i) do { } while (0)
#define PROFT(i) do { } while (0)
#define PROFH(i) do { } while (0)
#define PROFWT(i) do { } while (0)
#define PROF_WG 0

namespace {

constexpr int SEQ = 2048, DM = 576, FF = 4608, NH = 32, DH = 18;

constexpr int KV_GROUP_BYTES = 5 * 128;
constexpr int KV_HEAD_BYTES = (SEQ / 8) * KV_GROUP_BYTES;
constexpr int Q_OFFSET = NH * KV_HEAD_BYTES;
#define POLY_MASK 0xB6B6
__device__ __align__(1024) uint8_t g_QKV[2 * NH * KV_HEAD_BYTES];
__device__ __align__(1024) float g_kmax[NH * 64];
constexpr int SLAB = 16 * 36 * 256;
__device__ __align__(1024) uint4 g_part[8 * SLAB];
__device__ __align__(1024) uint2 g_ffn[128 * 18 * 128];
__device__ __align__(1024) uint32_t g_O[SEQ * DM / 2];
struct Flags {
    unsigned int qkv_stored[16];
    unsigned int ffn_done[16];
    unsigned int o_done[32];
    unsigned int kv_ready;
    unsigned int exited;
};
__device__ Flags g_flags;
__device__ __align__(1024) uint4 g_Olate[32 * 9 * 128];
constexpr uint32_t O_EMPTY = 0xFFFFFFFFu;
constexpr int WO_TILE_BYTES = DM * 144 * 2;
__device__ __align__(1024) uint8_t g_Wo[4 * WO_TILE_BYTES];

__device__ __forceinline__ uint32_t s2u(const void* p) { return (uint32_t)__cvta_generic_to_shared(p); }
__device__ __forceinline__ void mbar_init(uint32_t b, int c) { asm volatile("mbarrier.init.shared::cta.b64 [%0], %1;" ::"r"(b), "r"(c) : "memory"); }
__device__ __forceinline__ void mbar_expect(uint32_t b, uint32_t bytes) {
    asm volatile("mbarrier.arrive.expect_tx.shared::cta.b64 _, [%0], %1;" ::"r"(b), "r"(bytes) : "memory");
}
__device__ __forceinline__ void mbar_wait(uint32_t b, uint32_t parity) {
    asm volatile(
        "{\n.reg .pred p;\n.reg .u32 c;\n"
        "mov.u32 c, 0;\n"
        "LOOP:\n"
        "mbarrier.try_wait.parity.shared::cta.b64 p, [%0], %1;\n"
        "@p bra DONE;\n"
        "add.u32 c, c, 1;\n"
        "setp.lt.u32 p, c, 4194304;\n"
        "@p bra LOOP;\n"
        "trap;\n"
        "DONE:\n}\n" ::"r"(b), "r"(parity) : "memory");
}
__device__ __forceinline__ void fence_barrier_init() { asm volatile("fence.mbarrier_init.release.cluster;" ::: "memory"); }
__device__ __forceinline__ void fence_proxy_async() { asm volatile("fence.proxy.async.shared::cta;" ::: "memory"); }
__device__ __forceinline__ void cluster_arrive() { asm volatile("barrier.cluster.arrive.relaxed.aligned;" ::: "memory"); }
__device__ __forceinline__ void cluster_wait() { asm volatile("barrier.cluster.wait.aligned;" ::: "memory"); }
__device__ __forceinline__ void named_bar_sync(int id, int n) { asm volatile("bar.sync %0, %1;" ::"r"(id), "r"(n) : "memory"); }

__device__ __forceinline__ void tma3d_mc(uint32_t dst, const CUtensorMap* tm, int c0, int c1, int c2, uint32_t bar, uint16_t mask) {
    asm volatile("cp.async.bulk.tensor.3d.shared::cluster.global.mbarrier::complete_tx::bytes.multicast::cluster [%0], [%1, {%3, %4, %5}], [%2], %6;"
                 ::"r"(dst), "l"(tm), "r"(bar), "r"(c0), "r"(c1), "r"(c2), "h"(mask) : "memory");
}
__device__ __forceinline__ void tma2d_mc(uint32_t dst, const CUtensorMap* tm, int c0, int c1, uint32_t bar, uint16_t mask) {
    asm volatile("cp.async.bulk.tensor.2d.shared::cluster.global.mbarrier::complete_tx::bytes.multicast::cluster [%0], [%1, {%3, %4}], [%2], %5;"
                 ::"r"(dst), "l"(tm), "r"(bar), "r"(c0), "r"(c1), "h"(mask) : "memory");
}
__device__ __forceinline__ void tma4d(uint32_t dst, const CUtensorMap* tm, int c0, int c1, int c2, int c3, uint32_t bar) {
    asm volatile("cp.async.bulk.tensor.4d.shared::cluster.global.mbarrier::complete_tx::bytes [%0], [%1, {%3, %4, %5, %6}], [%2];"
                 ::"r"(dst), "l"(tm), "r"(bar), "r"(c0), "r"(c1), "r"(c2), "r"(c3) : "memory");
}
__device__ __forceinline__ void tma2d(uint32_t dst, const CUtensorMap* tm, int c0, int c1, uint32_t bar) {
    asm volatile("cp.async.bulk.tensor.2d.shared::cluster.global.mbarrier::complete_tx::bytes [%0], [%1, {%3, %4}], [%2];"
                 ::"r"(dst), "l"(tm), "r"(bar), "r"(c0), "r"(c1) : "memory");
}
__device__ __forceinline__ void bulk_load(uint32_t dst, const void* src, uint32_t bytes, uint32_t bar) {
    asm volatile("cp.async.bulk.shared::cluster.global.mbarrier::complete_tx::bytes [%0], [%1], %2, [%3];"
                 ::"r"(dst), "l"(src), "r"(bytes), "r"(bar) : "memory");
}
__device__ __forceinline__ void prefetch_l2(const void* p, uint32_t bytes) {
    asm volatile("cp.async.bulk.prefetch.L2.global [%0], %1;" ::"l"(p), "r"(bytes) : "memory");
}
__device__ __forceinline__ void prefetch_tmap(const CUtensorMap* tm) { asm volatile("prefetch.tensormap [%0];" ::"l"(tm) : "memory"); }

__device__ __forceinline__ void wg_fence() { asm volatile("wgmma.fence.sync.aligned;" ::: "memory"); }
__device__ __forceinline__ void wg_commit() { asm volatile("wgmma.commit_group.sync.aligned;" ::: "memory"); }
template <int N> __device__ __forceinline__ void wg_wait() { asm volatile("wgmma.wait_group.sync.aligned %0;" ::"n"(N) : "memory"); }
template <int N> __device__ __forceinline__ void reg_fence(float (&d)[N]) {
#pragma unroll
    for (int i = 0; i < N; i++) asm volatile("" : "+f"(d[i])::"memory");
}
template <int N> __device__ __forceinline__ void reg_fence(uint32_t (&d)[N]) {
#pragma unroll
    for (int i = 0; i < N; i++) asm volatile("" : "+r"(d[i])::"memory");
}
template <int R> __device__ __forceinline__ void reg_alloc() { asm volatile("setmaxnreg.inc.sync.aligned.u32 %0;" ::"n"(R)); }
template <int R> __device__ __forceinline__ void reg_dealloc() { asm volatile("setmaxnreg.dec.sync.aligned.u32 %0;" ::"n"(R)); }

__device__ __forceinline__ uint64_t mk_desc(uint64_t z, uint32_t addr, uint32_t lbo, uint32_t sbo, uint32_t swz) {
    return z + ((uint64_t)(((addr & 0x3FFFF) >> 4) | ((lbo >> 4) << 16)) | ((uint64_t)((sbo >> 4) | (swz << 30)) << 32));
}
__device__ __forceinline__ uint32_t pack_bf16(float lo, float hi) {
    uint32_t r;
    asm("cvt.rn.bf16x2.f32 %0, %1, %2;" : "=r"(r) : "f"(hi), "f"(lo));
    return r;
}
__device__ __forceinline__ float bf_lo(uint32_t w) { return __uint_as_float(w << 16); }
__device__ __forceinline__ float bf_hi(uint32_t w) { return __uint_as_float(w & 0xFFFF0000u); }
__device__ __forceinline__ float ex2(float x) {
    float r;
    asm("ex2.approx.ftz.f32 %0, %1;" : "=f"(r) : "f"(x));
    return r;
}
__device__ __forceinline__ float tanh_fast(float x) {
    float r;
    asm("tanh.approx.f32 %0, %1;" : "=f"(r) : "f"(x));
    return r;
}
__device__ __forceinline__ uint32_t hfma2_bf16(uint32_t a, uint32_t b, uint32_t c) {
    uint32_t r;
    asm("fma.rn.bf16x2 %0, %1, %2, %3;" : "=r"(r) : "r"(a), "r"(b), "r"(c));
    return r;
}
__device__ __forceinline__ uint32_t hadd2_bf16(uint32_t a, uint32_t b) {
    uint32_t r;
    asm("add.rn.bf16x2 %0, %1, %2;" : "=r"(r) : "r"(a), "r"(b));
    return r;
}
__device__ __forceinline__ void ldsm4(uint32_t (&a)[4], uint32_t addr) {
    asm volatile("ldmatrix.sync.aligned.m8n8.x4.shared.b16 {%0, %1, %2, %3}, [%4];" : "=r"(a[0]), "=r"(a[1]), "=r"(a[2]), "=r"(a[3]) : "r"(addr) : "memory");
}
__device__ __forceinline__ void stsm4(uint32_t addr, const uint32_t (&a)[4]) {
    asm volatile("stmatrix.sync.aligned.m8n8.x4.shared.b16 [%0], {%1, %2, %3, %4};" ::"r"(addr), "r"(a[0]), "r"(a[1]), "r"(a[2]), "r"(a[3]) : "memory");
}
__device__ __forceinline__ void mma16816(float (&c)[4], const uint32_t (&a)[4], uint32_t b0, uint32_t b1) {
    asm("mma.sync.aligned.m16n8k16.row.col.f32.bf16.bf16.f32 {%0, %1, %2, %3}, {%4, %5, %6, %7}, {%8, %9}, {%0, %1, %2, %3};"
        : "+f"(c[0]), "+f"(c[1]), "+f"(c[2]), "+f"(c[3]) : "r"(a[0]), "r"(a[1]), "r"(a[2]), "r"(a[3]), "r"(b0), "r"(b1));
}
__device__ __forceinline__ float gelu2(float u) {
    const float w = fmaf(u * u, 0.0356774081f, 0.7978845608f);
    return fmaf(u, tanh_fast(u * w), u);
}

template<int TB, int AOFF, int BOFF> __device__ __forceinline__ void wgmma_ss_n216(float (&d)[108], uint64_t da, uint64_t db, int sd) {
    asm volatile("{\n.reg .pred p;\n.reg .b64 ta, tb;\nsetp.ne.b32 p, %110, 0;\nadd.s64 ta, %108, %112;\nadd.s64 tb, %109, %113;\n"
      "wgmma.mma_async.sync.aligned.m64n216k16.f32.bf16.bf16 {%0, %1, %2, %3, %4, %5, %6, %7, %8, %9, %10, %11, %12, %13, %14, %15, %16, %17, %18, %19, %20, %21, %22, %23, %24, %25, %26, %27, %28, %29, %30, %31, %32, %33, %34, %35, %36, %37, %38, %39, %40, %41, %42, %43, %44, %45, %46, %47, %48, %49, %50, %51, %52, %53, %54, %55, %56, %57, %58, %59, %60, %61, %62, %63, %64, %65, %66, %67, %68, %69, %70, %71, %72, %73, %74, %75, %76, %77, %78, %79, %80, %81, %82, %83, %84, %85, %86, %87, %88, %89, %90, %91, %92, %93, %94, %95, %96, %97, %98, %99, %100, %101, %102, %103, %104, %105, %106, %107}, ta, tb, p, 1, 1, 0, %111;\n}\n"
      : "+f"(d[0]), "+f"(d[1]), "+f"(d[2]), "+f"(d[3]), "+f"(d[4]), "+f"(d[5]), "+f"(d[6]), "+f"(d[7]), "+f"(d[8]), "+f"(d[9]), "+f"(d[10]), "+f"(d[11]), "+f"(d[12]), "+f"(d[13]), "+f"(d[14]), "+f"(d[15]), "+f"(d[16]), "+f"(d[17]), "+f"(d[18]), "+f"(d[19]), "+f"(d[20]), "+f"(d[21]), "+f"(d[22]), "+f"(d[23]), "+f"(d[24]), "+f"(d[25]), "+f"(d[26]), "+f"(d[27]), "+f"(d[28]), "+f"(d[29]), "+f"(d[30]), "+f"(d[31]), "+f"(d[32]), "+f"(d[33]), "+f"(d[34]), "+f"(d[35]), "+f"(d[36]), "+f"(d[37]), "+f"(d[38]), "+f"(d[39]), "+f"(d[40]), "+f"(d[41]), "+f"(d[42]), "+f"(d[43]), "+f"(d[44]), "+f"(d[45]), "+f"(d[46]), "+f"(d[47]), "+f"(d[48]), "+f"(d[49]), "+f"(d[50]), "+f"(d[51]), "+f"(d[52]), "+f"(d[53]), "+f"(d[54]), "+f"(d[55]), "+f"(d[56]), "+f"(d[57]), "+f"(d[58]), "+f"(d[59]), "+f"(d[60]), "+f"(d[61]), "+f"(d[62]), "+f"(d[63]), "+f"(d[64]), "+f"(d[65]), "+f"(d[66]), "+f"(d[67]), "+f"(d[68]), "+f"(d[69]), "+f"(d[70]), "+f"(d[71]), "+f"(d[72]), "+f"(d[73]), "+f"(d[74]), "+f"(d[75]), "+f"(d[76]), "+f"(d[77]), "+f"(d[78]), "+f"(d[79]), "+f"(d[80]), "+f"(d[81]), "+f"(d[82]), "+f"(d[83]), "+f"(d[84]), "+f"(d[85]), "+f"(d[86]), "+f"(d[87]), "+f"(d[88]), "+f"(d[89]), "+f"(d[90]), "+f"(d[91]), "+f"(d[92]), "+f"(d[93]), "+f"(d[94]), "+f"(d[95]), "+f"(d[96]), "+f"(d[97]), "+f"(d[98]), "+f"(d[99]), "+f"(d[100]), "+f"(d[101]), "+f"(d[102]), "+f"(d[103]), "+f"(d[104]), "+f"(d[105]), "+f"(d[106]), "+f"(d[107])
      : "l"(da), "l"(db), "r"(sd), "n"(TB), "n"(AOFF), "n"(BOFF));
}

template<int TB, int AOFF, int BOFF> __device__ __forceinline__ void wgmma_ss_n64(float (&d)[32], uint64_t da, uint64_t db, int sd) {
    asm volatile("{\n.reg .pred p;\n.reg .b64 ta, tb;\nsetp.ne.b32 p, %34, 0;\nadd.s64 ta, %32, %36;\nadd.s64 tb, %33, %37;\n"
      "wgmma.mma_async.sync.aligned.m64n64k16.f32.bf16.bf16 {%0, %1, %2, %3, %4, %5, %6, %7, %8, %9, %10, %11, %12, %13, %14, %15, %16, %17, %18, %19, %20, %21, %22, %23, %24, %25, %26, %27, %28, %29, %30, %31}, ta, tb, p, 1, 1, 0, %35;\n}\n"
      : "+f"(d[0]), "+f"(d[1]), "+f"(d[2]), "+f"(d[3]), "+f"(d[4]), "+f"(d[5]), "+f"(d[6]), "+f"(d[7]), "+f"(d[8]), "+f"(d[9]), "+f"(d[10]), "+f"(d[11]), "+f"(d[12]), "+f"(d[13]), "+f"(d[14]), "+f"(d[15]), "+f"(d[16]), "+f"(d[17]), "+f"(d[18]), "+f"(d[19]), "+f"(d[20]), "+f"(d[21]), "+f"(d[22]), "+f"(d[23]), "+f"(d[24]), "+f"(d[25]), "+f"(d[26]), "+f"(d[27]), "+f"(d[28]), "+f"(d[29]), "+f"(d[30]), "+f"(d[31])
      : "l"(da), "l"(db), "r"(sd), "n"(TB), "n"(AOFF), "n"(BOFF));
}

template<int TB, int AOFF, int BOFF> __device__ __forceinline__ void wgmma_ss_n128(float (&d)[64], uint64_t da, uint64_t db, int sd) {
    asm volatile("{\n.reg .pred p;\n.reg .b64 ta, tb;\nsetp.ne.b32 p, %66, 0;\nadd.s64 ta, %64, %68;\nadd.s64 tb, %65, %69;\n"
      "wgmma.mma_async.sync.aligned.m64n128k16.f32.bf16.bf16 {%0, %1, %2, %3, %4, %5, %6, %7, %8, %9, %10, %11, %12, %13, %14, %15, %16, %17, %18, %19, %20, %21, %22, %23, %24, %25, %26, %27, %28, %29, %30, %31, %32, %33, %34, %35, %36, %37, %38, %39, %40, %41, %42, %43, %44, %45, %46, %47, %48, %49, %50, %51, %52, %53, %54, %55, %56, %57, %58, %59, %60, %61, %62, %63}, ta, tb, p, 1, 1, 0, %67;\n}\n"
      : "+f"(d[0]), "+f"(d[1]), "+f"(d[2]), "+f"(d[3]), "+f"(d[4]), "+f"(d[5]), "+f"(d[6]), "+f"(d[7]), "+f"(d[8]), "+f"(d[9]), "+f"(d[10]), "+f"(d[11]), "+f"(d[12]), "+f"(d[13]), "+f"(d[14]), "+f"(d[15]), "+f"(d[16]), "+f"(d[17]), "+f"(d[18]), "+f"(d[19]), "+f"(d[20]), "+f"(d[21]), "+f"(d[22]), "+f"(d[23]), "+f"(d[24]), "+f"(d[25]), "+f"(d[26]), "+f"(d[27]), "+f"(d[28]), "+f"(d[29]), "+f"(d[30]), "+f"(d[31]), "+f"(d[32]), "+f"(d[33]), "+f"(d[34]), "+f"(d[35]), "+f"(d[36]), "+f"(d[37]), "+f"(d[38]), "+f"(d[39]), "+f"(d[40]), "+f"(d[41]), "+f"(d[42]), "+f"(d[43]), "+f"(d[44]), "+f"(d[45]), "+f"(d[46]), "+f"(d[47]), "+f"(d[48]), "+f"(d[49]), "+f"(d[50]), "+f"(d[51]), "+f"(d[52]), "+f"(d[53]), "+f"(d[54]), "+f"(d[55]), "+f"(d[56]), "+f"(d[57]), "+f"(d[58]), "+f"(d[59]), "+f"(d[60]), "+f"(d[61]), "+f"(d[62]), "+f"(d[63])
      : "l"(da), "l"(db), "r"(sd), "n"(TB), "n"(AOFF), "n"(BOFF));
}

template<int TB, int AOFF, int BOFF> __device__ __forceinline__ void wgmma_ss_n72(float (&d)[36], uint64_t da, uint64_t db, int sd) {
    asm volatile("{\n.reg .pred p;\n.reg .b64 ta, tb;\nsetp.ne.b32 p, %38, 0;\nadd.s64 ta, %36, %40;\nadd.s64 tb, %37, %41;\n"
      "wgmma.mma_async.sync.aligned.m64n72k16.f32.bf16.bf16 {%0, %1, %2, %3, %4, %5, %6, %7, %8, %9, %10, %11, %12, %13, %14, %15, %16, %17, %18, %19, %20, %21, %22, %23, %24, %25, %26, %27, %28, %29, %30, %31, %32, %33, %34, %35}, ta, tb, p, 1, 1, 0, %39;\n}\n"
      : "+f"(d[0]), "+f"(d[1]), "+f"(d[2]), "+f"(d[3]), "+f"(d[4]), "+f"(d[5]), "+f"(d[6]), "+f"(d[7]), "+f"(d[8]), "+f"(d[9]), "+f"(d[10]), "+f"(d[11]), "+f"(d[12]), "+f"(d[13]), "+f"(d[14]), "+f"(d[15]), "+f"(d[16]), "+f"(d[17]), "+f"(d[18]), "+f"(d[19]), "+f"(d[20]), "+f"(d[21]), "+f"(d[22]), "+f"(d[23]), "+f"(d[24]), "+f"(d[25]), "+f"(d[26]), "+f"(d[27]), "+f"(d[28]), "+f"(d[29]), "+f"(d[30]), "+f"(d[31]), "+f"(d[32]), "+f"(d[33]), "+f"(d[34]), "+f"(d[35])
      : "l"(da), "l"(db), "r"(sd), "n"(TB), "n"(AOFF), "n"(BOFF));
}

template<int TB, int BOFF> __device__ __forceinline__ void wgmma_rs_n64(float (&d)[32], uint32_t a0, uint32_t a1, uint32_t a2, uint32_t a3, uint64_t db, int sd) {
    asm volatile("{\n.reg .pred p;\n.reg .b64 tb;\nsetp.ne.b32 p, %37, 0;\nadd.s64 tb, %36, %39;\n"
      "wgmma.mma_async.sync.aligned.m64n64k16.f32.bf16.bf16 {%0, %1, %2, %3, %4, %5, %6, %7, %8, %9, %10, %11, %12, %13, %14, %15, %16, %17, %18, %19, %20, %21, %22, %23, %24, %25, %26, %27, %28, %29, %30, %31}, {%32, %33, %34, %35}, tb, p, 1, 1, %38;\n}\n"
      : "+f"(d[0]), "+f"(d[1]), "+f"(d[2]), "+f"(d[3]), "+f"(d[4]), "+f"(d[5]), "+f"(d[6]), "+f"(d[7]), "+f"(d[8]), "+f"(d[9]), "+f"(d[10]), "+f"(d[11]), "+f"(d[12]), "+f"(d[13]), "+f"(d[14]), "+f"(d[15]), "+f"(d[16]), "+f"(d[17]), "+f"(d[18]), "+f"(d[19]), "+f"(d[20]), "+f"(d[21]), "+f"(d[22]), "+f"(d[23]), "+f"(d[24]), "+f"(d[25]), "+f"(d[26]), "+f"(d[27]), "+f"(d[28]), "+f"(d[29]), "+f"(d[30]), "+f"(d[31])
      : "r"(a0), "r"(a1), "r"(a2), "r"(a3), "l"(db), "r"(sd), "n"(TB), "n"(BOFF));
}

template<int TB, int BOFF> __device__ __forceinline__ void wgmma_rs_n24(float (&d)[12], uint32_t a0, uint32_t a1, uint32_t a2, uint32_t a3, uint64_t db, int sd) {
    asm volatile("{\n.reg .pred p;\n.reg .b64 tb;\nsetp.ne.b32 p, %17, 0;\nadd.s64 tb, %16, %19;\n"
      "wgmma.mma_async.sync.aligned.m64n24k16.f32.bf16.bf16 {%0, %1, %2, %3, %4, %5, %6, %7, %8, %9, %10, %11}, {%12, %13, %14, %15}, tb, p, 1, 1, %18;\n}\n"
      : "+f"(d[0]), "+f"(d[1]), "+f"(d[2]), "+f"(d[3]), "+f"(d[4]), "+f"(d[5]), "+f"(d[6]), "+f"(d[7]), "+f"(d[8]), "+f"(d[9]), "+f"(d[10]), "+f"(d[11])
      : "r"(a0), "r"(a1), "r"(a2), "r"(a3), "l"(db), "r"(sd), "n"(TB), "n"(BOFF));
}

template<int TB, int BOFF> __device__ __forceinline__ void wgmma_rs_n72(float (&d)[36], uint32_t a0, uint32_t a1, uint32_t a2, uint32_t a3, uint64_t db, int sd) {
    asm volatile("{\n.reg .pred p;\n.reg .b64 tb;\nsetp.ne.b32 p, %41, 0;\nadd.s64 tb, %40, %43;\n"
      "wgmma.mma_async.sync.aligned.m64n72k16.f32.bf16.bf16 {%0, %1, %2, %3, %4, %5, %6, %7, %8, %9, %10, %11, %12, %13, %14, %15, %16, %17, %18, %19, %20, %21, %22, %23, %24, %25, %26, %27, %28, %29, %30, %31, %32, %33, %34, %35}, {%36, %37, %38, %39}, tb, p, 1, 1, %42;\n}\n"
      : "+f"(d[0]), "+f"(d[1]), "+f"(d[2]), "+f"(d[3]), "+f"(d[4]), "+f"(d[5]), "+f"(d[6]), "+f"(d[7]), "+f"(d[8]), "+f"(d[9]), "+f"(d[10]), "+f"(d[11]), "+f"(d[12]), "+f"(d[13]), "+f"(d[14]), "+f"(d[15]), "+f"(d[16]), "+f"(d[17]), "+f"(d[18]), "+f"(d[19]), "+f"(d[20]), "+f"(d[21]), "+f"(d[22]), "+f"(d[23]), "+f"(d[24]), "+f"(d[25]), "+f"(d[26]), "+f"(d[27]), "+f"(d[28]), "+f"(d[29]), "+f"(d[30]), "+f"(d[31]), "+f"(d[32]), "+f"(d[33]), "+f"(d[34]), "+f"(d[35])
      : "r"(a0), "r"(a1), "r"(a2), "r"(a3), "l"(db), "r"(sd), "n"(TB), "n"(BOFF));
}

constexpr int K1_XN_BYTES = 16 * 9216;
constexpr int K1_OFF_RING = K1_XN_BYTES;
constexpr int K1_OFF_BIAS = K1_OFF_RING + 10 * 8192;
constexpr int K1_OFF_BAR = K1_OFF_BIAS + 576 * 2;
constexpr int K1_SMEM = K1_OFF_BAR + 800;
constexpr float QSCALE = 0.23570226039551584f * 1.4426950408889634f;

struct K1Ctx {
    uint32_t full0;
    uint32_t rel_addr;
    uint64_t descA, descB;
    uint32_t phase;
    __device__ __forceinline__ void begin_stage(int s) {
        mbar_wait(full0 + s * 8, phase);
        wg_fence();
    }
    __device__ __forceinline__ void release(int s) {
        if (rel_addr) asm volatile("mbarrier.arrive.shared::cluster.b64 _, [%0];" ::"r"(rel_addr + s * 8) : "memory");
    }
    __device__ __forceinline__ void end_stage(int s) {
        wg_commit();
        wg_wait<1>();
        release(s == 0 ? 8 : s - 1);
    }
};

__host__ __device__ constexpr int a_off(int ks) { return ((ks / 12) * 49152 + ((ks >> 2) % 3) * 1024 + (ks & 3) * 32) >> 4; }

#define SPLIT_T 1
template <int V> struct IC { static constexpr int value = V; };
template <int I, int N, class F> __device__ __forceinline__ void static_for(F&& f) {
    if constexpr (I < N) { f(IC<I>{}); static_for<I + 1, N>(f); }
}

template <bool A_RS, bool B_RS, class Epi>
__device__ __forceinline__ void tile_pair(K1Ctx& c, float (&accA)[32], float (&accB)[32], uint32_t (&h)[144], Epi&& epi) {
    static_for<0, 9>([&](auto sc) {
        constexpr int s = decltype(sc)::value;
        c.begin_stage(s);
        static_for<0, 8>([&](auto tc) {
            constexpr int t = decltype(tc)::value, kk = s * 8 + t, ks = kk % 36;
            constexpr int bo = (ks * 2048) >> 4;
            if constexpr (kk < 36) {
                if constexpr (A_RS) wgmma_rs_n64<1, bo>(accA, h[ks * 4], h[ks * 4 + 1], h[ks * 4 + 2], h[ks * 4 + 3], c.descB, ks != 0);
                else wgmma_ss_n64<1, a_off(ks), bo>(accA, c.descA, c.descB, ks != 0);
            } else {
                if constexpr (B_RS) wgmma_rs_n64<1, bo>(accB, h[ks * 4], h[ks * 4 + 1], h[ks * 4 + 2], h[ks * 4 + 3], c.descB, ks != 0);
                else wgmma_ss_n64<1, a_off(ks), bo>(accB, c.descA, c.descB, ks != 0);
            }
            if constexpr (t == SPLIT_T) {
                c.end_stage(s);
                epi(sc);
            }
        });
        if constexpr (SPLIT_T < 7) wg_commit();
    });
    c.phase ^= 1;
}

template <class Epi>
__device__ __forceinline__ void tile_128(K1Ctx& c, float (&acc)[64], Epi&& epi) {
    static_for<0, 9>([&](auto sc) {
        constexpr int s = decltype(sc)::value;
        c.begin_stage(s);
        static_for<0, 4>([&](auto tc) {
            constexpr int t = decltype(tc)::value;
            constexpr int bo = ((((2 * s + (t >> 1)) % 9) * 8192 + (t & 1) * 2048) >> 4) + (((4096 - 2048) >> 4) << 16);
            wgmma_ss_n128<1, a_off(s * 4 + t), bo>(acc, c.descA, c.descB, (s | t) != 0);
            if constexpr (t == 0) {
                c.end_stage(s);
                epi(sc);
            }
        });
        wg_commit();
    });
    c.phase ^= 1;
}

template <int B0, int NB, int HOFF, int NA>
__device__ __forceinline__ void gelu_blocks(const float (&acc)[NA], uint32_t (&h)[144], const uint32_t (&bq)[8], float rs0, float rs1) {
#pragma unroll
    for (int b = B0; b < B0 + NB; b++) {
        const float b0 = bf_lo(bq[b & 7]), b1 = bf_hi(bq[b & 7]);
        h[HOFF + b * 2 + 0] = pack_bf16(gelu2(fmaf(acc[b * 4 + 0], rs0, b0)), gelu2(fmaf(acc[b * 4 + 1], rs0, b1)));
        h[HOFF + b * 2 + 1] = pack_bf16(gelu2(fmaf(acc[b * 4 + 2], rs1, b0)), gelu2(fmaf(acc[b * 4 + 3], rs1, b1)));
    }
#pragma unroll
    for (int i = HOFF + B0 * 2; i < HOFF + (B0 + NB) * 2; i++) asm volatile("" : "+r"(h[i]));
}
__device__ __forceinline__ void load_bias(uint32_t (&bq)[8], uint32_t addr) {
    asm volatile("ld.shared.v4.u32 {%0, %1, %2, %3}, [%4];" : "=r"(bq[0]), "=r"(bq[1]), "=r"(bq[2]), "=r"(bq[3]) : "r"(addr));
    asm volatile("ld.shared.v4.u32 {%0, %1, %2, %3}, [%4 + 16];" : "=r"(bq[4]), "=r"(bq[5]), "=r"(bq[6]), "=r"(bq[7]) : "r"(addr));
}
template <int S> __device__ __forceinline__ void store_part(const float (&o)[32], uint4* p) {
    uint4 v;
    v.x = pack_bf16(o[S * 8 + 0], o[S * 8 + 1]); v.y = pack_bf16(o[S * 8 + 2], o[S * 8 + 3]);
    v.z = pack_bf16(o[S * 8 + 4], o[S * 8 + 5]); v.w = pack_bf16(o[S * 8 + 6], o[S * 8 + 7]);
    p[S * 256] = v;
}

constexpr int NCHUNK = 16;
constexpr int CHUNK_BYTES = KV_HEAD_BYTES / NCHUNK;
constexpr int SM_Q = 0;
constexpr int SM_KV = 32768;
constexpr int PIECE = 19968;
__host__ __device__ constexpr int sm_piece(int p) { return p == 0 ? 209408 : (p == 1 ? 0 : SM_KV + (p - 2) * PIECE); }
__host__ __device__ constexpr int sm_wstep(int k) { return k < 27 ? sm_piece(k / 3) + (k % 3) * 4608 : (k < 35 ? SM_KV + 7 * PIECE + (k - 27) * 4608 : PIECE); }
__host__ __device__ constexpr int sm_ostep(int k) { return sm_piece(k / 3) + 13824 + (k % 3) * 2048; }
constexpr int SM_RED = SM_KV + KV_HEAD_BYTES;

__device__ __forceinline__ float exp2_fixed(float y) {
    const float u = __uint_as_float(__float_as_uint(y) & 0xFF807FFFu) - 512.02545f;
    float t = fmaf(u, 0.019497588f, 0.114550486f);
    t = fmaf(t, u, -0.29839927f);
    return fmaf(t, u, y);
}
__device__ __forceinline__ uint32_t pack_fixed(float lo, float hi) { return __byte_perm(__float_as_uint(lo), __float_as_uint(hi), 0x6521); }

#define PV_GROUP 4
#define POLY_MODE 1
__device__ __forceinline__ uint32_t exp2_packed(float y0, float y1, uint32_t one2) {
    const uint32_t w = pack_fixed(y0, y1);
    uint32_t m;
    asm("lop3.b32 %0, %1, 0x007F007F, %2, 0xEA;" : "=r"(m) : "r"(w), "r"(one2));
    const uint32_t d = hfma2_bf16(m, 0x3EF93EF9u, 0xBF38BF38u);
    const uint32_t e = hfma2_bf16(d, d, 0xBD71BD71u);
    return hfma2_bf16(w, e, w);
}
constexpr int KV_TILE = CHUNK_BYTES / 16;
template <int OFF> __device__ __forceinline__ void issue_qk(float (&s)[64], uint64_t qd, uint64_t kd) {
    wgmma_ss_n128<0, 0, OFF + (8 << 16)>(s, qd, kd, 0);
    wgmma_ss_n128<0, 16, OFF + 32>(s, qd, kd, 1);
}
template <int OFF> __device__ __forceinline__ void issue_pv(float (&o)[12], const uint32_t (&p)[32], uint64_t vd) {
    static_for<0, 8>([&](auto kc) {
        constexpr int k = decltype(kc)::value;
        wgmma_rs_n24<1, OFF + k * (2 * KV_GROUP_BYTES / 16)>(o, p[k * 4], p[k * 4 + 1], p[k * 4 + 2], p[k * 4 + 3], vd, 1);
    });
}
template <int OFF>
__device__ __forceinline__ void softmax_pv(const float (&s)[64], uint32_t (&p)[32], float (&o)[12], uint64_t vd, uint32_t one2) {
    static_for<0, 8 / PV_GROUP>([&](auto gc) {
        constexpr int g0 = decltype(gc)::value * PV_GROUP;
#pragma unroll
        for (int b = g0 * 2; b < (g0 + PV_GROUP) * 2; b++) {
            if ((POLY_MASK >> b) & 1) {
                p[b * 2 + 0] = exp2_packed(s[b * 4 + 0], s[b * 4 + 1], one2);
                p[b * 2 + 1] = exp2_packed(s[b * 4 + 2], s[b * 4 + 3], one2);
            } else {
                p[b * 2 + 0] = pack_bf16(ex2(s[b * 4 + 0]), ex2(s[b * 4 + 1]));
                p[b * 2 + 1] = pack_bf16(ex2(s[b * 4 + 2]), ex2(s[b * 4 + 3]));
            }
        }
#pragma unroll
        for (int i = g0 * 4; i < (g0 + PV_GROUP) * 4; i++) asm volatile("" : "+r"(p[i])::"memory");
        wg_fence();
        static_for<g0, g0 + PV_GROUP>([&](auto kc) {
            constexpr int k = decltype(kc)::value;
            wgmma_rs_n24<1, OFF + k * (2 * KV_GROUP_BYTES / 16)>(o, p[k * 4], p[k * 4 + 1], p[k * 4 + 2], p[k * 4 + 3], vd, 1);
        });
    });
    wg_commit();
}
template <bool LATE> __device__ __forceinline__ void store_o(float (&o)[12], int rt, int head, int wq, int lane) {
    const int g = lane >> 2, q = lane & 3;
    const float i0 = __fdividef(1.0f, __shfl_sync(~0u, o[8], lane | 3)), i1 = __fdividef(1.0f, __shfl_sync(~0u, o[10], lane | 3));
#pragma unroll
    for (int i = 0; i < 3; i++) {
        const uint32_t w0 = pack_bf16(o[i * 4] * i0, o[i * 4 + 1] * i0), w1 = pack_bf16(o[i * 4 + 2] * i1, o[i * 4 + 3] * i1);
        if (i < 2 || q == 2) {
            if constexpr (LATE) {
                const int pc = (head & 7) * 9 + (i < 2 ? i * 4 + q : 8);
                uint32_t* op = reinterpret_cast<uint32_t*>(g_Olate) + (((rt * 9 + (pc >> 3)) * 128 + wq * 32 + g * 4 + (pc & 3)) * 4 + ((pc >> 2) & 1) * 2);
                asm volatile("st.relaxed.gpu.global.v2.u32 [%0], {%1, %2};" ::"l"(op), "r"(w0), "r"(w1) : "memory");
            } else {
                const int pc = head * 9 + (i < 2 ? i * 4 + q : 8);
                uint32_t* op = g_O + ((rt * 72 + (pc >> 2)) * 8 + wq * 2) * 32 + g * 4 + (pc & 3);
                op[0] = w0;
                op[32] = w1;
            }
        }
    }
#pragma unroll
    for (int i = 0; i < 12; i++) o[i] = 0.f;
}
__device__ __forceinline__ void mbar_arrive(uint32_t b) { asm volatile("mbarrier.arrive.shared::cta.b64 _, [%0];" ::"r"(b) : "memory"); }
__device__ __forceinline__ void mbar_wait_sleep(uint32_t b, uint32_t ns) {
    uint32_t ok, spins = 0;
    while (true) {
        asm volatile("{\n.reg .pred p;\nmbarrier.try_wait.parity.shared::cta.b64 p, [%1], 0;\nselp.u32 %0, 1, 0, p;\n}\n" : "=r"(ok) : "r"(b) : "memory");
        if (ok) break;
        __nanosleep(ns);
        if (++spins > (1u << 21)) __trap();
    }
}
__device__ __forceinline__ void flag_signal(unsigned int* f) {
    __threadfence();
    atomicAdd(f, 1u);
}
__device__ __forceinline__ void flag_wait(const unsigned int* f, unsigned int target, unsigned int sleep_ns) {
    uint32_t v, spins = 0;
    while (true) {
        asm volatile("ld.acquire.gpu.global.u32 %0, [%1];" : "=r"(v) : "l"(f) : "memory");
        if (v >= target) break;
        if (sleep_ns) __nanosleep(sleep_ns);
        if (++spins > (1u << 21)) __trap();
    }
}
__device__ __forceinline__ uint4 hadd8_bf16(const uint4 a, const uint4 b) {
    return make_uint4(hadd2_bf16(a.x, b.x), hadd2_bf16(a.y, b.y), hadd2_bf16(a.z, b.z), hadd2_bf16(a.w, b.w));
}
__device__ __forceinline__ float sumsq2(uint32_t w) { return fmaf(bf_lo(w), bf_lo(w), bf_hi(w) * bf_hi(w)); }
__device__ __forceinline__ float sumsq8(const uint4 v) { return (sumsq2(v.x) + sumsq2(v.y)) + (sumsq2(v.z) + sumsq2(v.w)); }

enum { B_FULL = 0, B_EMPTY = 9, B_BASE = 18, B_XNDEAD = 19, B_QRDY = 20, B_FFN = 21, B_KV = 22, B_FREE = 38, B_WO = 46, B_RED = 55, B_X = 61, B_EARLY = 85, B_OS = 86, B_LATE = 94, B_BIAS = 95, B_END = 96 };

__global__ void __cluster_dims__(2, 1, 1) __launch_bounds__(384, 1)
fused_kernel(const __grid_constant__ CUtensorMap tmX, const __grid_constant__ CUtensorMap tmQ3, const __grid_constant__ CUtensorMap tmQ1,
          const __grid_constant__ CUtensorMap tm1, const __grid_constant__ CUtensorMap tm1b, const __grid_constant__ CUtensorMap tm2, const __grid_constant__ CUtensorMap tmP,
          const __grid_constant__ CUtensorMap tmOut, const __grid_constant__ CUtensorMap tmXo, const __nv_bfloat16* __restrict__ b1,
          const __nv_bfloat16* __restrict__ wqkv, const __nv_bfloat16* __restrict__ w1, const __nv_bfloat16* __restrict__ w2,
          const __nv_bfloat16* __restrict__ wo, const __nv_bfloat16* __restrict__ b2,
          const uint64_t zero) {
    extern __shared__ __align__(1024) uint8_t smem[];
    const uint32_t sb = s2u(smem);
    const int tid = threadIdx.x, lane = tid & 31;
    const int warp = __shfl_sync(~0u, tid >> 5, 0);
    const uint32_t rank = blockIdx.x & 1;
    const int cl = blockIdx.x >> 1;
    const int rb = (cl & 7) * 2 + rank;
    const int j = cl >> 3;
    const uint32_t bar0 = sb + K1_OFF_BAR;
    const uint32_t full0 = bar0 + B_FULL * 8, empty0 = bar0 + B_EMPTY * 8, xbar0 = bar0 + B_X * 8;
    const int head = blockIdx.x >> 2, quarter = blockIdx.x & 3;
    const int rt = quarter * 8 + (head >> 2), ct = head & 3;
    const int rot = head >> 3;
    const int ks0 = ((((head >> 3) + 2) & 3) * 9);
    volatile uint32_t* slow_flag = reinterpret_cast<volatile uint32_t*>(smem + K1_OFF_BAR + B_END * 8);

    if (warp < 8) {
        PROF(0);
        PROFT(48);
        if (lane == 0) {
#pragma unroll
            for (int i = 0; i < 3; i++) mbar_init(xbar0 + (warp * 3 + i) * 8, 1);
            fence_barrier_init();
#pragma unroll 1
            for (int i = 0; i < 3; i++) {
                const uint32_t xb = xbar0 + (warp * 3 + i) * 8;
                mbar_expect(xb, 6144);
                tma4d(sb + i * 49152 + warp * 6144, &tmX, 0, 0, i * 3, rb * 16 + warp * 2, xb);
            }
        }
        __syncwarp();
        cluster_arrive();
        PROF(22);
        reg_alloc<240>();
        PROF(23);
        float rs0, rs1;
        {
            const uint32_t la = sb + (warp * 2 + ((lane >> 3) & 1)) * 3072 + (lane & 7) * 128;
            uint32_t off[4];
#pragma unroll
            for (int i = 0; i < 4; i++) off[i] = la + (((i * 2 + (lane >> 4)) ^ (lane & 7)) << 4);
            float c1[4] = {0.f, 0.f, 0.f, 0.f}, c2[4] = {0.f, 0.f, 0.f, 0.f}, c3[4] = {0.f, 0.f, 0.f, 0.f};
            uint32_t a[36][4];
#pragma unroll
            for (int t = 0; t < 3; t++) {
                mbar_wait(xbar0 + (warp * 3 + t) * 8, 0);
                PROF(24 + t);
#pragma unroll
                for (int i = 0; i < 12; i++) ldsm4(a[t * 12 + i], off[i & 3] + t * 49152 + (i >> 2) * 1024);
#pragma unroll
                for (int i = t * 12; i < t * 12 + 12; i++) {
                    mma16816(c3, a[i], 0x3F803F80u, 0x3F803F80u);
                    mma16816(c1, a[i], a[i][0], a[i][2]);
                    mma16816(c2, a[i], a[i][1], a[i][3]);
                }
            }
            PROF(27);
            const int gg = lane >> 2, src = (lane & ~3) | (gg >> 1);
            const float m0 = c3[0] * (1.0f / DM), m1 = c3[2] * (1.0f / DM);
            const uint32_t mc0 = pack_bf16(-m0, -m0), mc1 = pack_bf16(-m1, -m1);
#pragma unroll
            for (int i = 0; i < 36; i++) {
#pragma unroll
                for (int k = 0; k < 4; k++) a[i][k] = hadd2_bf16(a[i][k], (k & 1) ? mc1 : mc0);
                stsm4(off[i & 3] + (i / 12) * 49152 + ((i >> 2) % 3) * 1024, a[i]);
            }
            const float q0 = __shfl_sync(~0u, (gg & 1) ? c1[1] : c1[0], src), q1 = __shfl_sync(~0u, (gg & 1) ? c2[3] : c2[2], src);
            rs0 = rsqrtf(fmaxf(fmaf(-m0, m0, q0 * (1.0f / DM)), 0.f) + 1e-5f);
            rs1 = rsqrtf(fmaxf(fmaf(-m1, m1, q1 * (1.0f / DM)), 0.f) + 1e-5f);
            if (__any_sync(~0u, fabsf(m0) * rs0 > 0.25f || fabsf(m1) * rs1 > 0.25f)) {
                const float d0 = -m0 - bf_lo(mc0), d1 = -m1 - bf_lo(mc1);
                const uint32_t md0 = pack_bf16(d0, d0), md1 = pack_bf16(d1, d1);
#pragma unroll 1
                for (int i = 0; i < 9; i++) {
#pragma unroll
                    for (int k4 = 0; k4 < 4; k4++) {
                        const uint32_t ad = off[k4] + (i / 3) * 49152 + (i % 3) * 1024;
                        uint32_t b[4];
                        ldsm4(b, ad);
#pragma unroll
                        for (int k = 0; k < 4; k++) b[k] = hadd2_bf16(b[k], (k & 1) ? md1 : md0);
                        stsm4(ad, b);
                    }
                }
            }
        }
        PROF(28);
        const int wg = warp >> 2, wq = warp & 3;
        fence_proxy_async();
        named_bar_sync(1 + wg, 128);
        cluster_wait();
        PROF(1);

        const int g = lane >> 2, q = lane & 3;
        K1Ctx c;
        c.full0 = full0;
        c.rel_addr = 0;
        c.descA = mk_desc(zero, sb + wg * 8 * 3072, 16, 3072, 1);
        c.descB = mk_desc(zero, sb + K1_OFF_RING, 2048, 1024, 1);
        c.phase = 0;
        const uint32_t biasq = sb + K1_OFF_BIAS + q * 32;
        uint32_t bq[8];

        uint32_t h[144];
        float accX[64];
        {
            float accQ[108];
            uint32_t rel = 0;
            if (lane == 0 && wq < 2) asm("mapa.shared::cluster.u32 %0, %1, %2;" : "=r"(rel) : "r"(empty0), "r"(wq));
#pragma unroll 1
            for (int r = 0; r < 2; r++) {
                static_for<0, 9>([&](auto sc) {
                    constexpr int s = decltype(sc)::value;
                    c.begin_stage(s);
                    const uint64_t da = c.descA + (r ? a_off(18 + 2 * s) : a_off(2 * s));
                    wgmma_ss_n216<1, 0, ((2 * s) % 9) * 512>(accQ, da, c.descB, (r | s) != 0);
                    wgmma_ss_n216<1, 2, ((2 * s + 1) % 9) * 512>(accQ, da, c.descB, 1);
                    c.end_stage(s);
                    c.rel_addr = rel;
                });
                c.phase ^= 1;
            }
            PROF(2); PROFWT(54);
            uint32_t rel9[9];
#pragma unroll
            for (int i9 = 0; i9 < 9; i9++) {
                const int p = 4 * i9 + q, hh = (p * 57) >> 9, r = p - 9 * hh;
                rel9[i9] = hh * KV_HEAD_BYTES + (r < 8 ? (r >> 2) * 128 + (r & 3) * 4 : 0);
            }
            uint32_t gb = 0, o2 = 0;
            float scl0 = 1.f, scl1 = 1.f;
            tile_128(c, accX, [&](auto sc) {
                constexpr int s = decltype(sc)::value;
                if constexpr (s == 0) reg_fence(accQ);
                constexpr int grp = s / 3, part = s % 3;
                if constexpr (part == 0) {
                    const int G = 3 * j + grp, type = G >> 3;
                    gb = (G & 7) * 4 * KV_HEAD_BYTES + (rb * 16 + warp * 2) * KV_GROUP_BYTES + g * 16 + (type == 0 ? Q_OFFSET : (type == 2 ? 256 : 0));
                    o2 = type == 0 ? 256 : (type == 2 ? 264 : 512);
                    scl0 = rs0 * (type == 0 ? QSCALE : ((type == 1 && ((POLY_MASK >> (warp * 2)) & 1)) ? 2.f : 1.f));
                    scl1 = rs1 * (type == 0 ? QSCALE : ((type == 1 && ((POLY_MASK >> (warp * 2 + 1)) & 1)) ? 2.f : 1.f));
                }
#pragma unroll
                for (int i9 = part * 3; i9 < part * 3 + 3; i9++) {
                    const int b = grp * 9 + i9;
                    uint32_t off = gb + rel9[i9];
                    if (i9 >= 2 && (i9 & 1) == 0) off += (q == i9 / 2 - 1) ? o2 : 0;
                    *reinterpret_cast<uint32_t*>(g_QKV + off) = pack_bf16(accQ[b * 4] * scl0, accQ[b * 4 + 1] * scl0);
                    *reinterpret_cast<uint32_t*>(g_QKV + off + KV_GROUP_BYTES) = pack_bf16(accQ[b * 4 + 2] * scl1, accQ[b * 4 + 3] * scl1);
                }
                if constexpr (s == 8) {
                    asm volatile("bar.arrive 3, 352;" ::: "memory");
                    mbar_wait(bar0 + B_BIAS * 8, 0);
                    load_bias(bq, biasq);
                }
            });
        }
        PROF(3); PROFWT(55);
        {
            float accY[64];
            tile_128(c, accY, [&](auto sc) {
                constexpr int s = decltype(sc)::value;
                if constexpr (s == 0) reg_fence(accX);
                if constexpr (s < 4) gelu_blocks<s * 2, 2, 0>(accX, h, bq, rs0, rs1);
                if constexpr (s == 4) load_bias(bq, biasq + 128);
                if constexpr (s > 4) gelu_blocks<s * 2 - 2, 2, 0>(accX, h, bq, rs0, rs1);
                if constexpr (s == 8) load_bias(bq, biasq + 256);
            });
            tile_128(c, accX, [&](auto sc) {
                constexpr int s = decltype(sc)::value;
                if constexpr (s == 0) reg_fence(accY);
                if constexpr (s < 4) gelu_blocks<s * 2, 2, 32>(accY, h, bq, rs0, rs1);
                if constexpr (s == 4) load_bias(bq, biasq + 384);
                if constexpr (s > 4) gelu_blocks<s * 2 - 2, 2, 32>(accY, h, bq, rs0, rs1);
                if constexpr (s == 8) load_bias(bq, biasq + 512);
            });
        }
        float accA[32], accB[32];
        tile_pair<false, false>(c, accA, accB, h, [&](auto sc) {
            constexpr int s = decltype(sc)::value;
            if constexpr (s == 0) reg_fence(accX);
            if constexpr (s < 2) gelu_blocks<s * 4, 4, 64>(accX, h, bq, rs0, rs1);
            if constexpr (s == 1) load_bias(bq, biasq + 640);
            if constexpr (s == 2 || s == 3) gelu_blocks<s * 4, 4, 64>(accX, h, bq, rs0, rs1);
            if constexpr (s == 4) load_bias(bq, biasq + 768);
            if constexpr (s == 5) reg_fence(accA);
            if constexpr (s >= 5) gelu_blocks<(s - 5) * 2, 2, 96>(accA, h, bq, rs0, rs1);
            if constexpr (s == 8) load_bias(bq, biasq + 896);
        });
        PROF(4); PROFWT(56);
        tile_pair<false, true>(c, accA, accB, h, [&](auto sc) {
            constexpr int s = decltype(sc)::value;
            if constexpr (s == 0) reg_fence(accB);
            if constexpr (s < 4) gelu_blocks<s * 2, 2, 112>(accB, h, bq, rs0, rs1);
            if constexpr (s == 4) load_bias(bq, biasq + 1024);
            if constexpr (s == 5) { reg_fence(accA); if (tid == wg * 128) mbar_arrive(bar0 + B_XNDEAD * 8); }
            if constexpr (s == 5 || s == 6) gelu_blocks<(s - 5) * 3, 3, 128>(accA, h, bq, rs0, rs1);
            if constexpr (s == 7) gelu_blocks<6, 2, 128>(accA, h, bq, rs0, rs1);
            if constexpr (s == 3 || s == 7) reg_fence(h);
        });
        PROF(5); PROFWT(57);
        uint4* pout = g_part + j * SLAB + rb * 36 * 256 + tid;
#pragma unroll 1
        for (int p = 0; p < 4; p++) {
            tile_pair<true, true>(c, accA, accB, h, [&](auto sc) {
                constexpr int s = decltype(sc)::value;
                if constexpr (s == 0) reg_fence(accB);
                if constexpr (s < 4) store_part<s>(accB, pout);
                if constexpr (s == 5) reg_fence(accA);
                if constexpr (s >= 5) store_part<s - 5>(accA, pout + 1024);
            });
            pout += 2048;
            PROF(6 + p);
        }
        wg_wait<0>();
        c.release(8);
        reg_fence(accB);
        store_part<0>(accB, pout); store_part<1>(accB, pout); store_part<2>(accB, pout); store_part<3>(accB, pout);
        __syncwarp();
        if (lane == 0) mbar_arrive(bar0 + B_FFN * 8);
        PROF(10); PROFWT(58);
        PROFT(49);

        mbar_wait(bar0 + B_QRDY * 8, 0);
        const uint32_t slow = __any_sync(~0u, *slow_flag != 0);
        const uint64_t kd0 = mk_desc(zero, sb + SM_KV, 0, KV_GROUP_BYTES, 0);
        const uint64_t vd0 = mk_desc(zero, sb + SM_KV + 256, KV_GROUP_BYTES, 128, 0);
        const uint64_t qd0 = mk_desc(zero, sb + SM_Q + wg * 4096, 128, 512, 0);
        const uint32_t kvbar = bar0 + B_KV * 8;
        float o[12];
#pragma unroll
        for (int i = 0; i < 12; i++) o[i] = 0.f;
        PROF(16);
        PROFT(50);
        if (!slow) {
            const uint32_t one2 = 0x3F803F80u + (uint32_t)zero;
            float s0[64], s1[64];
            uint32_t p0[32], p1[32];
            mbar_wait(kvbar, 0);
            reg_fence(o);
            wg_fence();
            issue_qk<0>(s0, qd0, kd0);
            wg_commit();
            wg_commit();
            uint64_t qd = qd0;
            const uint32_t fre = (tid == wg * 128) ? bar0 + B_FREE * 8 - 8 : 0;
#pragma unroll 1
            for (int pass = 0; pass < 4; pass++) {
                uint64_t vd = vd0, kd = kd0;
                uint32_t bn = kvbar + 8;
#pragma unroll 1
                for (int it = 0; it < 8; it++) {
                    mbar_wait(bn, 0);
                    if (it == 0 && pass != 0) {
                        wg_wait<0>();
                        reg_fence(o);
                        store_o<false>(o, quarter * 8 + ((pass - 1 + rot) & 3) * 2 + wg, head, wq, lane);
                        reg_fence(o);
                        __syncwarp();
                        if (lane == 0) mbar_arrive(bar0 + (B_OS + pass * 2 - 2 + wg) * 8);
                    }
                    wg_wait<1>();
                    reg_fence(s0);
                    wg_fence();
                    issue_qk<KV_TILE>(s1, qd, kd);
                    wg_commit();
                    if (pass == 3 && it > 0 && fre) mbar_arrive(fre + it * 8);
                    softmax_pv<0>(s0, p0, o, vd, one2);
                    kd += 2 * KV_TILE; bn += 8;
                    if (it == 7) { kd = kd0; bn = kvbar; qd += 512; }
                    mbar_wait(bn, 0);
                    wg_wait<1>();
                    reg_fence(s1);
                    wg_fence();
                    issue_qk<0>(s0, qd, kd);
                    wg_commit();
                    softmax_pv<KV_TILE>(s1, p1, o, vd, one2);
                    vd += 2 * KV_TILE; bn += 8;
                }
                if (pass == 0) PROF(17);
            }
            wg_wait<0>();
            reg_fence(o);
            reg_fence(s0);
            reg_fence(s1);
            store_o<true>(o, quarter * 8 + ((3 + rot) & 3) * 2 + wg, head, wq, lane);
        } else {
#pragma unroll 1
            for (int pass = 0; pass < 4; pass++) {
                float m0 = -INFINITY, m1 = -INFINITY;
                float s[64];
                uint32_t p[32];
#pragma unroll 1
                for (int t = 0; t < 16; t++) {
                    mbar_wait(kvbar + t * 8, 0);
                    wg_fence();
                    issue_qk<0>(s, qd0 + pass * 512, kd0 + t * KV_TILE);
                    wg_commit();
                    wg_wait<0>();
                    reg_fence(s);
                    float a0 = m0, a1 = m1;
#pragma unroll
                    for (int k = 0; k < 16; k++) {
                        if ((POLY_MASK >> k) & 1) {
#pragma unroll
                            for (int i = 0; i < 4; i++) s[k * 4 + i] *= 0.5f;
                        }
                        a0 = fmaxf(a0, fmaxf(s[k * 4 + 0], s[k * 4 + 1]));
                        a1 = fmaxf(a1, fmaxf(s[k * 4 + 2], s[k * 4 + 3]));
                    }
                    a0 = fmaxf(a0, __shfl_xor_sync(~0u, a0, 1)); a1 = fmaxf(a1, __shfl_xor_sync(~0u, a1, 1));
                    a0 = fmaxf(a0, __shfl_xor_sync(~0u, a0, 2)); a1 = fmaxf(a1, __shfl_xor_sync(~0u, a1, 2));
                    const float r0 = ex2(m0 - a0), r1 = ex2(m1 - a1);
                    m0 = a0; m1 = a1;
#pragma unroll
                    for (int i = 0; i < 3; i++) { o[i * 4] *= r0; o[i * 4 + 1] *= r0; o[i * 4 + 2] *= r1; o[i * 4 + 3] *= r1; }
#pragma unroll
                    for (int k = 0; k < 16; k++) {
                        p[k * 2 + 0] = pack_bf16(ex2(s[k * 4 + 0] - m0), ex2(s[k * 4 + 1] - m0));
                        p[k * 2 + 1] = pack_bf16(ex2(s[k * 4 + 2] - m1), ex2(s[k * 4 + 3] - m1));
                    }
                    reg_fence(p);
                    reg_fence(o);
                    wg_fence();
                    issue_pv<0>(o, p, vd0 + t * KV_TILE);
                    wg_commit();
                    wg_wait<0>();
                    reg_fence(o);
                }
                if (pass < 3) {
                    store_o<false>(o, quarter * 8 + ((pass + rot) & 3) * 2 + wg, head, wq, lane);
                    __syncwarp();
                    if (lane == 0) mbar_arrive(bar0 + (B_OS + pass * 2 + wg) * 8);
                }
            }
            store_o<true>(o, quarter * 8 + ((3 + rot) & 3) * 2 + wg, head, wq, lane);
            if (tid == wg * 128)
                for (int i = 0; i < 7; i++) mbar_arrive(bar0 + (B_FREE + i) * 8);
        }
        PROF(18);
        PROFT(51);

        if (tid == wg * 128) mbar_arrive(bar0 + (B_FREE + 7) * 8);
        const int t128 = tid & 127;
        uint32_t bv[9];
        uint2 fv[9];
        mbar_wait(bar0 + B_BASE * 8, 0);
#pragma unroll
        for (int i = 0; i < 9; i++) {
            bv[i] = __ldg(reinterpret_cast<const uint32_t*>(b2 + ct * 144 + wg * 72 + q * 2) + i * 4);
            fv[i] = __ldcg(g_ffn + (blockIdx.x * 18 + wg * 9 + i) * 128 + t128);
        }
        float acc[36];
        const uint64_t od = mk_desc(zero, sb, 1024, 128, 0), wd = mk_desc(zero, sb + wg * 9 * 128, 2304, 128, 0);
        static_for<0, 9>([&](auto pc) {
            constexpr int p = decltype(pc)::value;
            mbar_wait(bar0 + (B_WO + p) * 8, 0);
            wg_fence();
            wgmma_ss_n72<1, sm_ostep(p * 3) / 16, sm_wstep(p * 3) / 16>(acc, od, wd, p != 0);
            wgmma_ss_n72<1, sm_ostep(p * 3 + 1) / 16, sm_wstep(p * 3 + 1) / 16>(acc, od, wd, 1);
            wgmma_ss_n72<1, sm_ostep(p * 3 + 2) / 16, sm_wstep(p * 3 + 2) / 16>(acc, od, wd, 1);
            wg_commit();
            if constexpr (p == 1) {
                wg_wait<1>();
                if (t128 == 0) mbar_arrive(bar0 + B_EARLY * 8);
            }
        });
        wg_wait<0>();
        reg_fence(acc);
        PROF(29);
        uint4 al[9];
        {
            const uint4* ap = g_Olate + rt * 9 * 128 + t128;
            uint32_t spins = 0;
            bool ok;
            do {
                ok = true;
#pragma unroll
                for (int k = 0; k < 9; k++)
                    asm volatile("ld.relaxed.gpu.global.v4.u32 {%0, %1, %2, %3}, [%4];" : "=r"(al[k].x), "=r"(al[k].y), "=r"(al[k].z), "=r"(al[k].w) : "l"(ap + k * 128) : "memory");
#pragma unroll
                for (int k = 0; k < 9; k++) ok = ok && al[k].x != O_EMPTY && al[k].y != O_EMPTY && al[k].z != O_EMPTY && al[k].w != O_EMPTY;
                if (++spins > (1u << 20)) __trap();
            } while (!__all_sync(~0u, ok));
        }
        PROF(19);
        mbar_wait(bar0 + B_LATE * 8, 0);
        PROF(20);
        wg_fence();
        static_for<27, 36>([&](auto kc) {
            constexpr int k = decltype(kc)::value;
            wgmma_rs_n72<1, sm_wstep(k) / 16>(acc, al[k - 27].x, al[k - 27].y, al[k - 27].z, al[k - 27].w, wd, 1);
        });
        wg_commit();
        PROF(31);
        uint32_t* st = reinterpret_cast<uint32_t*>(smem + sm_piece(0) + wg * 9216) + (wq * 16 + g) * 36 + q;
        float bs[36];
#pragma unroll
        for (int i = 0; i < 9; i++) {
            const uint32_t x0 = st[i * 4], x1 = st[i * 4 + 288];
            bs[i * 4 + 0] = fmaf(bf_lo(fv[i].x), 0.5f, bf_lo(x0) + bf_lo(bv[i]));
            bs[i * 4 + 1] = fmaf(bf_hi(fv[i].x), 0.5f, bf_hi(x0) + bf_hi(bv[i]));
            bs[i * 4 + 2] = fmaf(bf_lo(fv[i].y), 0.5f, bf_lo(x1) + bf_lo(bv[i]));
            bs[i * 4 + 3] = fmaf(bf_hi(fv[i].y), 0.5f, bf_hi(x1) + bf_hi(bv[i]));
        }
        reg_fence(bs);
        wg_wait<0>();
        reg_fence(acc);
        PROF(32);
#pragma unroll
        for (int i = 0; i < 9; i++) {
            st[i * 4] = pack_bf16(acc[i * 4] + bs[i * 4], acc[i * 4 + 1] + bs[i * 4 + 1]);
            st[i * 4 + 288] = pack_bf16(acc[i * 4 + 2] + bs[i * 4 + 2], acc[i * 4 + 3] + bs[i * 4 + 3]);
        }
        fence_proxy_async();
        named_bar_sync(1 + wg, 128);
        if (t128 == 0) {
            asm volatile("cp.async.bulk.tensor.2d.global.shared::cta.bulk_group [%0, {%2, %3}], [%1];"
                         ::"l"(&tmOut), "r"(sb + sm_piece(0) + wg * 9216), "r"(ct * 144 + wg * 72), "r"(rt * 64) : "memory");
            asm volatile("cp.async.bulk.commit_group;" ::: "memory");
            asm volatile("cp.async.bulk.wait_group.read 0;" ::: "memory");
        }
        PROF(21);
        PROFT(52);
    } else {
        reg_dealloc<24>();
        if (warp == 8 && lane == 0) {
            prefetch_tmap(&tmQ3); prefetch_tmap(&tmQ1); prefetch_tmap(&tm1); prefetch_tmap(&tm1b); prefetch_tmap(&tm2);
            #pragma unroll 1
            for (int i = 0; i < 9; i++) { mbar_init(full0 + i * 8, 1); mbar_init(empty0 + i * 8, 4); mbar_init(bar0 + (B_WO + i) * 8, 2); }
            mbar_init(bar0 + B_BASE * 8, 3); mbar_init(bar0 + B_XNDEAD * 8, 2); mbar_init(bar0 + B_QRDY * 8, 3); mbar_init(bar0 + B_FFN * 8, 8); mbar_init(bar0 + B_EARLY * 8, 2); mbar_init(bar0 + B_LATE * 8, 2); mbar_init(bar0 + B_BIAS * 8, 96);
#pragma unroll 1
            for (int i = 0; i < 16; i++) { mbar_init(bar0 + (B_KV + i) * 8, 1); mbar_init(bar0 + (B_FREE + (i & 7)) * 8, 2); if (i < 6) mbar_init(bar0 + (B_RED + i) * 8, 1); if (i < 6) mbar_init(bar0 + (B_OS + i) * 8, 4); }
            *slow_flag = 0;
            fence_barrier_init();
        }
        __syncwarp();
        cluster_arrive();
        cluster_wait();
        const uint8_t* kvsrc = g_QKV + (size_t)head * KV_HEAD_BYTES;
        if (warp == 8) {
            if (lane == 0) {
                int st = 0, u = rank, tile = -4;
                int es = 5;
                uint32_t eph = 1;
#pragma unroll 1
                for (int n = 0; n < 99; n++) {
                    mbar_wait(empty0 + es * 8, eph);
                    const uint32_t fb = full0 + st * 8, dst = sb + K1_OFF_RING + u * 8192;
                    mbar_expect(fb, 16384);
                    if (tile < 0) {
                        tma3d_mc(dst, &tmQ3, j * 216, n * 32 + rank * 16, 0, fb, 3);
                        tma2d_mc(dst + 6144, &tmQ1, j * 216 + 192, n * 32 + rank * 16, fb, 3);
                    } else if (n < 45) {
                        const int rnd = (n - 18) / 9;
                        tma3d_mc(dst, &tm1b, 0, st * 64 + rank * 32, j * 9 + rnd * 2, fb, 3);
                    } else if (tile < 9) {
                        tma2d_mc(dst, &tm1, j * 576 + tile * 64, u * 64, fb, 3);
                    } else {
                        tma2d_mc(dst, &tm2, (tile - 9) * 64, j * 576 + u * 64, fb, 3);
                    }
                    u += 2;
                    if (u >= 9) { u -= 9; tile++; }
                    if (++st == 9) st = 0;
                    if (++es == 9) { es = 0; eph ^= 1; }
                }
                mbar_wait(empty0 + 8 * 8, 0);
                mbar_wait(bar0 + B_QRDY * 8, 0);
                asm volatile("fence.proxy.async;" ::: "memory");
#pragma unroll 1
                for (int i = 11; i < NCHUNK; i++) {
                    mbar_expect(bar0 + (B_KV + i) * 8, CHUNK_BYTES);
                    bulk_load(sb + SM_KV + i * CHUNK_BYTES, kvsrc + i * CHUNK_BYTES, CHUNK_BYTES, bar0 + (B_KV + i) * 8);
                }
                const uint8_t* wsrc = g_Wo + ct * WO_TILE_BYTES;
                prefetch_tmap(&tmOut);
                mbar_wait_sleep(bar0 + B_BASE * 8, 500);
#pragma unroll 1
                for (int p = 0; p < 9; p++) {
                    if (p > 0) mbar_wait_sleep(bar0 + (B_FREE + p - 1) * 8, p == 1 ? 500 : 40);
                    const int k = ks0 + p * 3 >= 36 ? ks0 + p * 3 - 36 : ks0 + p * 3;
                    mbar_expect(bar0 + (B_WO + p) * 8, 13824);
                    bulk_load(sb + (p == 0 ? sm_piece(0) : (p == 1 ? sm_piece(1) : SM_KV + (p - 2) * PIECE)), wsrc + k * 4608, 13824, bar0 + (B_WO + p) * 8);
                }
                const int kl = ks0 == 0 ? 27 : ks0 - 9;
                mbar_expect(bar0 + B_LATE * 8, 9 * 4608);
                bulk_load(sb + sm_wstep(27), wsrc + kl * 4608, 8 * 4608, bar0 + B_LATE * 8);
                bulk_load(sb + sm_wstep(35), wsrc + (kl + 8) * 4608, 4608, bar0 + B_LATE * 8);
            }
        } else {
            const int ht = tid - 288;
            if (ht == 64) prefetch_l2(wqkv + blockIdx.x * (DM * 3 * DM / 128), DM * 3 * DM / 64);
            if (ht < 72) {
                const uint4 v = __ldg(reinterpret_cast<const uint4*>(b1 + j * 576) + ht);
                uint32_t* sbias = reinterpret_cast<uint32_t*>(smem + K1_OFF_BIAS) + (ht >> 3) * 32 + (ht & 7);
                sbias[0] = v.x; sbias[8] = v.y; sbias[16] = v.z; sbias[24] = v.w;
            }
            mbar_arrive(bar0 + B_BIAS * 8);
            PROFH(37);
#pragma unroll
            for (int i = 0; i < 3; i++) g_Olate[blockIdx.x * 288 + i * 96 + ht] = make_uint4(O_EMPTY, O_EMPTY, O_EMPTY, O_EMPTY);
#pragma unroll 1
            for (int i = ht; i < 512; i += 96) {
                const int key = i & 127;
                uint8_t* p = g_QKV + (size_t)(j * 4 + (i >> 7)) * KV_HEAD_BYTES + (rb * 16 + (key >> 3)) * KV_GROUP_BYTES + 512 + (key & 7) * 16;
                *reinterpret_cast<uint32_t*>(p + 4) = ((POLY_MASK >> (key >> 3)) & 1) ? 0x3F804000u : 0x00003F80u;
                *reinterpret_cast<uint32_t*>(p + 12) = 0x00003F80u;
            }
            if (ht == 32) prefetch_l2(w1 + blockIdx.x * (DM * FF / 128), DM * FF / 64);
#pragma unroll 2
            for (int i = blockIdx.x * 324 + ht; i < blockIdx.x * 324 + 324; i += 96) {
                const int k = i / 72, nc = i - k * 72, c4 = nc / 18;
                *reinterpret_cast<uint4*>(g_Wo + c4 * WO_TILE_BYTES + (k >> 3) * 2304 + (nc - c4 * 18) * 128 + (k & 7) * 16) =
                    __ldg(reinterpret_cast<const uint4*>(wo) + i);
            }
            PROFH(38);
            named_bar_sync(3, 352);
            if (ht == 32) prefetch_l2(w2 + blockIdx.x * (DM * FF / 128), DM * FF / 64);
            if (ht == 0) {
                flag_signal(&g_flags.qkv_stored[rb]);
                flag_wait(&g_flags.qkv_stored[rb], 8, 200);
            }
            named_bar_sync(7, 96);
            PROFH(39);
#pragma unroll 1
            for (int i = warp - 9; i < 16; i += 3) {
                const int hd = j * 4 + (i >> 2), key = (i & 3) * 32 + lane;
                const uint8_t* p = g_QKV + (size_t)hd * KV_HEAD_BYTES + (rb * 16 + (key >> 3)) * KV_GROUP_BYTES + (key & 7) * 16;
                const uint4 a = __ldcg(reinterpret_cast<const uint4*>(p)), b = __ldcg(reinterpret_cast<const uint4*>(p + 128));
                float n = sumsq2(__ldcg(reinterpret_cast<const uint32_t*>(p + 512))) + sumsq8(a) + sumsq8(b);
                if ((POLY_MASK >> (key >> 3)) & 1) n *= 0.25f;
#pragma unroll
                for (int o = 16; o; o >>= 1) n = fmaxf(n, __shfl_xor_sync(~0u, n, o));
                if (lane == 0) g_kmax[hd * 64 + rb * 4 + (i & 3)] = n;
            }
            named_bar_sync(7, 96);
            PROFH(40);
            if (ht == 0) {
                flag_signal(&g_flags.kv_ready);
                flag_wait(&g_flags.kv_ready, 128, 300);
                mbar_wait_sleep(bar0 + B_XNDEAD * 8, 300);
            }
            named_bar_sync(7, 96);
            PROFH(41);
            float kmax2;
            {
                const float2 v = __ldcg(reinterpret_cast<const float2*>(g_kmax + head * 64 + lane * 2));
                kmax2 = fmaxf(v.x, v.y);
#pragma unroll
                for (int o = 16; o; o >>= 1) kmax2 = fmaxf(kmax2, __shfl_xor_sync(~0u, kmax2, o));
            }
            asm volatile("fence.proxy.async;" ::: "memory");
            int chunk = warp - 9;
#pragma unroll 1
            for (int r = ht; r < 512; r += 96) {
                if (lane == 0 && chunk < 11) {
                    mbar_expect(bar0 + (B_KV + chunk) * 8, CHUNK_BYTES);
                    bulk_load(sb + SM_KV + chunk * CHUNK_BYTES, kvsrc + chunk * CHUNK_BYTES, CHUNK_BYTES, bar0 + (B_KV + chunk) * 8);
                }
                chunk += 3;
                const uint8_t* p = kvsrc + Q_OFFSET + (quarter * 64 + (((r >> 3) + rot * 16) & 63)) * KV_GROUP_BYTES + (r & 7) * 16;
                const uint4 a = __ldcg(reinterpret_cast<const uint4*>(p)), b = __ldcg(reinterpret_cast<const uint4*>(p + 128));
                const uint32_t e = __ldcg(reinterpret_cast<const uint32_t*>(p + 256));
                const float cc = sqrtf((sumsq2(e) + sumsq8(a) + sumsq8(b)) * kmax2) * 1.02f;
                if (!(cc <= 58.f)) *slow_flag = 1;
                uint4* dst = reinterpret_cast<uint4*>(smem + SM_Q + (r >> 3) * 512 + (r & 7) * 16);
                dst[0] = a;
                dst[8] = b;
                dst[16] = make_uint4(e, pack_bf16(-cc, 768.f), 0u, 0u);
                dst[24] = make_uint4(0u, POLY_MODE ? 0xBFFF0000u : 0xC0000000u, 0u, 0u);
            }
            named_bar_sync(7, 96);
            if (*slow_flag) {
#pragma unroll 1
                for (int r = ht; r < 512; r += 96) {
                    uint32_t* dst = reinterpret_cast<uint32_t*>(smem + SM_Q + (r >> 3) * 512 + (r & 7) * 16);
                    dst[65] = 0u;
                    dst[97] = 0u;
                }
            }
            fence_proxy_async();
            __syncwarp();
            if (lane == 0) mbar_arrive(bar0 + B_QRDY * 8);
            PROFH(42);
            if (ht == 0) {
                mbar_wait_sleep(bar0 + B_FFN * 8, 300);
                flag_signal(&g_flags.ffn_done[rb]);
                flag_wait(&g_flags.ffn_done[rt >> 1], 8, 300);
            }
            named_bar_sync(7, 96);
            {
                const int w3 = warp - 9;
                const uint32_t rbar = bar0 + (B_RED + w3 * 2) * 8, rbuf = SM_RED + w3 * 8192;
                const int u0 = ((rt >> 1) * 36 + ct * 9) * 256 + (rt & 1) * 128;
                mbar_wait_sleep(bar0 + (B_KV + 15) * 8, 500);
                asm volatile("fence.proxy.async;" ::: "memory");
#pragma unroll 1
                for (int i = -2; i < 12; i++) {
                    if (i >= 0) {
                        __nanosleep(400);
                        mbar_wait(rbar + (i & 1) * 8, (i >> 1) & 1);
                        const uint4* sp = reinterpret_cast<const uint4*>(smem + rbuf + (i & 1) * 4096) + lane;
                        const uint4 v = hadd8_bf16(hadd8_bf16(hadd8_bf16(sp[0], sp[32]), hadd8_bf16(sp[64], sp[96])),
                                                   hadd8_bf16(hadd8_bf16(sp[128], sp[160]), hadd8_bf16(sp[192], sp[224])));
                        const int bx = i * 3 + w3;
                        uint2* fp = g_ffn + (blockIdx.x * 18 + (bx >> 2) * 2) * 128 + (bx & 3) * 32 + lane;
                        fp[0] = make_uint2(v.x, v.y);
                        fp[128] = make_uint2(v.z, v.w);
                    }
                    __syncwarp();
                    if (lane == 0 && i < 10) {
                        const int bx = (i + 2) * 3 + w3;
                        mbar_expect(rbar + (i & 1) * 8, 4096);
                        tma2d(sb + rbuf + (i & 1) * 4096, &tmP, (u0 + (bx >> 2) * 256 + (bx & 3) * 32) * 2, 0, rbar + (i & 1) * 8);
                    }
                }
            }
            __syncwarp();
            if (lane == 0) mbar_arrive(bar0 + B_BASE * 8);
            PROFH(43);
            if (ht == 0) {
#pragma unroll 1
                for (int i = 0; i < 6; i++) {
                    mbar_wait_sleep(bar0 + (B_OS + i) * 8, 200);
                    flag_signal(&g_flags.o_done[quarter * 8 + (((i >> 1) + rot) & 3) * 2 + (i & 1)]);
                }
            } else if (ht == 32) {
                const uint8_t* osrc = reinterpret_cast<const uint8_t*>(g_O) + rt * 73728;
                mbar_wait_sleep(bar0 + B_BASE * 8, 500);
                mbar_wait_sleep(bar0 + B_FREE * 8, 500);
                flag_wait(&g_flags.o_done[rt], 24, 100);
                if (atomicAdd(&g_flags.exited, 1u) == gridDim.x - 1) {
                    unsigned int* f = reinterpret_cast<unsigned int*>(&g_flags);
#pragma unroll 1
                    for (int i = 0; i < (int)(sizeof(Flags) / 4); i++) f[i] = 0;
                }
                prefetch_tmap(&tmXo);
                asm volatile("fence.proxy.async;" ::: "memory");
#pragma unroll 1
                for (int p = 0; p < 9; p++) {
                    if (p > 1) mbar_wait_sleep(bar0 + (B_FREE + p - 1) * 8, 40);
                    const int k = ks0 + p * 3 >= 36 ? ks0 + p * 3 - 36 : ks0 + p * 3;
                    mbar_expect(bar0 + (B_WO + p) * 8, 6144);
                    bulk_load(sb + 13824 + (p == 0 ? sm_piece(0) : (p == 1 ? sm_piece(1) : SM_KV + (p - 2) * PIECE)), osrc + k * 2048, 6144, bar0 + (B_WO + p) * 8);
                }
                mbar_expect(bar0 + B_LATE * 8, 2 * 9216);
                mbar_wait(bar0 + B_EARLY * 8, 0);
                tma2d(sb + sm_piece(0), &tmXo, ct * 144, rt * 64, bar0 + B_LATE * 8);
                tma2d(sb + sm_piece(0) + 9216, &tmXo, ct * 144 + 72, rt * 64, bar0 + B_LATE * 8);
            }
        }
    }
}

typedef CUresult (*EncodeFn)(CUtensorMap*, CUtensorMapDataType, cuuint32_t, void*, const cuuint64_t*, const cuuint64_t*, const cuuint32_t*,
                             const cuuint32_t*, CUtensorMapInterleave, CUtensorMapSwizzle, CUtensorMapL2promotion, CUtensorMapFloatOOBfill);

void make_map(EncodeFn fn, CUtensorMap* m, const void* base, int rank, const cuuint64_t* dims, const cuuint64_t* strides, const cuuint32_t* box) {
    cuuint32_t es[4] = {1, 1, 1, 1};
    fn(m, CU_TENSOR_MAP_DATA_TYPE_BFLOAT16, rank, const_cast<void*>(base), dims, strides, box, es, CU_TENSOR_MAP_INTERLEAVE_NONE,
       CU_TENSOR_MAP_SWIZZLE_128B, CU_TENSOR_MAP_L2_PROMOTION_L2_256B, CU_TENSOR_MAP_FLOAT_OOB_FILL_NONE);
}

}

extern "C" void kernel_launch(void* const* d_in, const int* in_sizes, int n_in, void* d_out, int out_size) {
    const __nv_bfloat16* x = (const __nv_bfloat16*)d_in[0];
    const __nv_bfloat16* wqkv = (const __nv_bfloat16*)d_in[1];
    const __nv_bfloat16* wo = (const __nv_bfloat16*)d_in[2];
    const __nv_bfloat16* w1 = (const __nv_bfloat16*)d_in[4];
    const __nv_bfloat16* b1 = (const __nv_bfloat16*)d_in[5];
    const __nv_bfloat16* w2 = (const __nv_bfloat16*)d_in[6];
    const __nv_bfloat16* b2 = (const __nv_bfloat16*)d_in[7];
    __nv_bfloat16* out = (__nv_bfloat16*)d_out;

    EncodeFn fn = nullptr;
    cudaDriverEntryPointQueryResult qr;
    cudaGetDriverEntryPoint("cuTensorMapEncodeTiled", (void**)&fn, cudaEnableDefault, &qr);
    CUtensorMap tmX, tmQ3, tmQ1, tm1, tm2, tmP, tmOut, tmXo, tm1b;
    {
        cuuint64_t d[2] = {DM, SEQ}, s[1] = {DM * 2};
        cuuint32_t b[2] = {72, 64}, es[2] = {1, 1};
        fn(&tmOut, CU_TENSOR_MAP_DATA_TYPE_BFLOAT16, 2, out, d, s, b, es, CU_TENSOR_MAP_INTERLEAVE_NONE, CU_TENSOR_MAP_SWIZZLE_NONE,
           CU_TENSOR_MAP_L2_PROMOTION_NONE, CU_TENSOR_MAP_FLOAT_OOB_FILL_NONE);
        fn(&tmXo, CU_TENSOR_MAP_DATA_TYPE_BFLOAT16, 2, const_cast<__nv_bfloat16*>(x), d, s, b, es, CU_TENSOR_MAP_INTERLEAVE_NONE,
           CU_TENSOR_MAP_SWIZZLE_NONE, CU_TENSOR_MAP_L2_PROMOTION_NONE, CU_TENSOR_MAP_FLOAT_OOB_FILL_NONE);
    }
    {
        void* gp = nullptr;
        cudaGetSymbolAddress(&gp, g_part);
        cuuint64_t d[2] = {SLAB * 2, 8}, s[1] = {SLAB * 16};
        cuuint32_t b[2] = {64, 8}, es[2] = {1, 1};
        fn(&tmP, CU_TENSOR_MAP_DATA_TYPE_INT64, 2, gp, d, s, b, es, CU_TENSOR_MAP_INTERLEAVE_NONE, CU_TENSOR_MAP_SWIZZLE_NONE,
           CU_TENSOR_MAP_L2_PROMOTION_NONE, CU_TENSOR_MAP_FLOAT_OOB_FILL_NONE);
    }
    {
        cuuint64_t d[4] = {64, 8, 9, SEQ / 8}, s[3] = {DM * 2, 128, DM * 2 * 8};
        cuuint32_t b[4] = {64, 8, 3, 2};
        make_map(fn, &tmX, x, 4, d, s, b);
    }
    {
        cuuint64_t d[3] = {3 * DM, DM, 3}, s[2] = {3 * DM * 2, 128};
        cuuint32_t b[3] = {64, 16, 3};
        make_map(fn, &tmQ3, wqkv, 3, d, s, b);
        make_map(fn, &tmQ1, wqkv, 2, d, s, b);
    }
    {
        cuuint64_t d[2] = {FF, DM}, s[1] = {FF * 2};
        cuuint32_t b[2] = {64, 64};
        make_map(fn, &tm1, w1, 2, d, s, b);
        cuuint64_t d3[3] = {64, DM, FF / 64}, s3[2] = {FF * 2, 128};
        cuuint32_t b3[3] = {64, 32, 2};
        make_map(fn, &tm1b, w1, 3, d3, s3, b3);
        cuuint64_t d2[2] = {DM, FF}, s2[1] = {DM * 2};
        make_map(fn, &tm2, w2, 2, d2, s2, b);
    }
    cudaFuncSetAttribute(fused_kernel, cudaFuncAttributeMaxDynamicSharedMemorySize, K1_SMEM);
    fused_kernel<<<128, 384, K1_SMEM, cudaStreamPerThread>>>(tmX, tmQ3, tmQ1, tm1, tm1b, tm2, tmP, tmOut, tmXo, b1, wqkv, w1, w2, wo, b2, 0ull);
}
```

```cpp
#include <cuda_runtime.h>
#include <cuda_bf16.h>
#include <cuda.h>
#include <stdint.h>

#define PROF(i) do { } while (0)
#define PROFT(i) do { } while (0)
#define PROFH(i) do { } while (0)
#define PROFWT(i) do { } while (0)
#define PROF_WG 0

namespace {

constexpr int SEQ = 2048, DM = 576, FF = 4608, NH = 32, DH = 18;

constexpr int KV_GROUP_BYTES = 5 * 128;
constexpr int KV_HEAD_BYTES = (SEQ / 8) * KV_GROUP_BYTES;
constexpr int Q_OFFSET = NH * KV_HEAD_BYTES;
#define POLY_MASK 0xB6B6
__device__ __align__(1024) uint8_t g_QKV[2 * NH * KV_HEAD_BYTES];
__device__ __align__(1024) float g_kmax[NH * 64];
constexpr int SLAB = 16 * 36 * 256;
__device__ __align__(1024) uint4 g_part[8 * SLAB];
__device__ __align__(1024) uint2 g_ffn[128 * 18 * 128];
__device__ __align__(1024) uint32_t g_O[SEQ * DM / 2];
struct Flags {
    unsigned int qkv_stored[16];
    unsigned int ffn_done[16];
    unsigned int o_done[32];
    unsigned int kv_ready;
    unsigned int exited;
};
__device__ Flags g_flags;
__device__ __align__(1024) uint4 g_Olate[32 * 9 * 128];
constexpr uint32_t O_EMPTY = 0xFFFFFFFFu;
constexpr int WO_TILE_BYTES = DM * 144 * 2;
__device__ __align__(1024) uint8_t g_Wo[4 * WO_TILE_BYTES];

__device__ __forceinline__ uint32_t s2u(const void* p) { return (uint32_t)__cvta_generic_to_shared(p); }
__device__ __forceinline__ void mbar_init(uint32_t b, int c) { asm volatile("mbarrier.init.shared::cta.b64 [%0], %1;" ::"r"(b), "r"(c) : "memory"); }
__device__ __forceinline__ void mbar_expect(uint32_t b, uint32_t bytes) {
    asm volatile("mbarrier.arrive.expect_tx.shared::cta.b64 _, [%0], %1;" ::"r"(b), "r"(bytes) : "memory");
}
__device__ __forceinline__ void mbar_wait(uint32_t b, uint32_t parity) {
    asm volatile(
        "{\n.reg .pred p;\n.reg .u32 c;\n"
        "mov.u32 c, 0;\n"
        "LOOP:\n"
        "mbarrier.try_wait.parity.shared::cta.b64 p, [%0], %1;\n"
        "@p bra DONE;\n"
        "add.u32 c, c, 1;\n"
        "setp.lt.u32 p, c, 4194304;\n"
        "@p bra LOOP;\n"
        "trap;\n"
        "DONE:\n}\n" ::"r"(b), "r"(parity) : "memory");
}
__device__ __forceinline__ void fence_barrier_init() { asm volatile("fence.mbarrier_init.release.cluster;" ::: "memory"); }
__device__ __forceinline__ void fence_proxy_async() { asm volatile("fence.proxy.async.shared::cta;" ::: "memory"); }
__device__ __forceinline__ void cluster_arrive() { asm volatile("barrier.cluster.arrive.relaxed.aligned;" ::: "memory"); }
__device__ __forceinline__ void cluster_wait() { asm volatile("barrier.cluster.wait.aligned;" ::: "memory"); }
__device__ __forceinline__ void named_bar_sync(int id, int n) { asm volatile("bar.sync %0, %1;" ::"r"(id), "r"(n) : "memory"); }

__device__ __forceinline__ void tma3d_mc(uint32_t dst, const CUtensorMap* tm, int c0, int c1, int c2, uint32_t bar, uint16_t mask) {
    asm volatile("cp.async.bulk.tensor.3d.shared::cluster.global.mbarrier::complete_tx::bytes.multicast::cluster [%0], [%1, {%3, %4, %5}], [%2], %6;"
                 ::"r"(dst), "l"(tm), "r"(bar), "r"(c0), "r"(c1), "r"(c2), "h"(mask) : "memory");
}
__device__ __forceinline__ void tma2d_mc(uint32_t dst, const CUtensorMap* tm, int c0, int c1, uint32_t bar, uint16_t mask) {
    asm volatile("cp.async.bulk.tensor.2d.shared::cluster.global.mbarrier::complete_tx::bytes.multicast::cluster [%0], [%1, {%3, %4}], [%2], %5;"
                 ::"r"(dst), "l"(tm), "r"(bar), "r"(c0), "r"(c1), "h"(mask) : "memory");
}
__device__ __forceinline__ void tma4d(uint32_t dst, const CUtensorMap* tm, int c0, int c1, int c2, int c3, uint32_t bar) {
    asm volatile("cp.async.bulk.tensor.4d.shared::cluster.global.mbarrier::complete_tx::bytes [%0], [%1, {%3, %4, %5, %6}], [%2];"
                 ::"r"(dst), "l"(tm), "r"(bar), "r"(c0), "r"(c1), "r"(c2), "r"(c3) : "memory");
}
__device__ __forceinline__ void tma2d(uint32_t dst, const CUtensorMap* tm, int c0, int c1, uint32_t bar) {
    asm volatile("cp.async.bulk.tensor.2d.shared::cluster.global.mbarrier::complete_tx::bytes [%0], [%1, {%3, %4}], [%2];"
                 ::"r"(dst), "l"(tm), "r"(bar), "r"(c0), "r"(c1) : "memory");
}
__device__ __forceinline__ void bulk_load(uint32_t dst, const void* src, uint32_t bytes, uint32_t bar) {
    asm volatile("cp.async.bulk.shared::cluster.global.mbarrier::complete_tx::bytes [%0], [%1], %2, [%3];"
                 ::"r"(dst), "l"(src), "r"(bytes), "r"(bar) : "memory");
}
__device__ __forceinline__ void prefetch_l2(const void* p, uint32_t bytes) {
    asm volatile("cp.async.bulk.prefetch.L2.global [%0], %1;" ::"l"(p), "r"(bytes) : "memory");
}
__device__ __forceinline__ void prefetch_tmap(const CUtensorMap* tm) { asm volatile("prefetch.tensormap [%0];" ::"l"(tm) : "memory"); }

__device__ __forceinline__ void wg_fence() { asm volatile("wgmma.fence.sync.aligned;" ::: "memory"); }
__device__ __forceinline__ void wg_commit() { asm volatile("wgmma.commit_group.sync.aligned;" ::: "memory"); }
template <int N> __device__ __forceinline__ void wg_wait() { asm volatile("wgmma.wait_group.sync.aligned %0;" ::"n"(N) : "memory"); }
template <int N> __device__ __forceinline__ void reg_fence(float (&d)[N]) {
#pragma unroll
    for (int i = 0; i < N; i++) asm volatile("" : "+f"(d[i])::"memory");
}
template <int N> __device__ __forceinline__ void reg_fence(uint32_t (&d)[N]) {
#pragma unroll
    for (int i = 0; i < N; i++) asm volatile("" : "+r"(d[i])::"memory");
}
template <int R> __device__ __forceinline__ void reg_alloc() { asm volatile("setmaxnreg.inc.sync.aligned.u32 %0;" ::"n"(R)); }
template <int R> __device__ __forceinline__ void reg_dealloc() { asm volatile("setmaxnreg.dec.sync.aligned.u32 %0;" ::"n"(R)); }

__device__ __forceinline__ uint64_t mk_desc(uint64_t z, uint32_t addr, uint32_t lbo, uint32_t sbo, uint32_t swz) {
    return z + ((uint64_t)(((addr & 0x3FFFF) >> 4) | ((lbo >> 4) << 16)) | ((uint64_t)((sbo >> 4) | (swz << 30)) << 32));
}
__device__ __forceinline__ uint32_t pack_bf16(float lo, float hi) {
    uint32_t r;
    asm("cvt.rn.bf16x2.f32 %0, %1, %2;" : "=r"(r) : "f"(hi), "f"(lo));
    return r;
}
__device__ __forceinline__ float bf_lo(uint32_t w) { return __uint_as_float(w << 16); }
__device__ __forceinline__ float bf_hi(uint32_t w) { return __uint_as_float(w & 0xFFFF0000u); }
__device__ __forceinline__ float ex2(float x) {
    float r;
    asm("ex2.approx.ftz.f32 %0, %1;" : "=f"(r) : "f"(x));
    return r;
}
__device__ __forceinline__ float tanh_fast(float x) {
    float r;
    asm("tanh.approx.f32 %0, %1;" : "=f"(r) : "f"(x));
    return r;
}
__device__ __forceinline__ uint32_t hfma2_bf16(uint32_t a, uint32_t b, uint32_t c) {
    uint32_t r;
    asm("fma.rn.bf16x2 %0, %1, %2, %3;" : "=r"(r) : "r"(a), "r"(b), "r"(c));
    return r;
}
__device__ __forceinline__ uint32_t hadd2_bf16(uint32_t a, uint32_t b) {
    uint32_t r;
    asm("add.rn.bf16x2 %0, %1, %2;" : "=r"(r) : "r"(a), "r"(b));
    return r;
}
__device__ __forceinline__ void ldsm4(uint32_t (&a)[4], uint32_t addr) {
    asm volatile("ldmatrix.sync.aligned.m8n8.x4.shared.b16 {%0, %1, %2, %3}, [%4];" : "=r"(a[0]), "=r"(a[1]), "=r"(a[2]), "=r"(a[3]) : "r"(addr) : "memory");
}
__device__ __forceinline__ void stsm4(uint32_t addr, const uint32_t (&a)[4]) {
    asm volatile("stmatrix.sync.aligned.m8n8.x4.shared.b16 [%0], {%1, %2, %3, %4};" ::"r"(addr), "r"(a[0]), "r"(a[1]), "r"(a[2]), "r"(a[3]) : "memory");
}
__device__ __forceinline__ void mma16816(float (&c)[4], const uint32_t (&a)[4], uint32_t b0, uint32_t b1) {
    asm("mma.sync.aligned.m16n8k16.row.col.f32.bf16.bf16.f32 {%0, %1, %2, %3}, {%4, %5, %6, %7}, {%8, %9}, {%0, %1, %2, %3};"
        : "+f"(c[0]), "+f"(c[1]), "+f"(c[2]), "+f"(c[3]) : "r"(a[0]), "r"(a[1]), "r"(a[2]), "r"(a[3]), "r"(b0), "r"(b1));
}
__device__ __forceinline__ float gelu2(float u) {
    const float w = fmaf(u * u, 0.0356774081f, 0.7978845608f);
    return fmaf(u, tanh_fast(u * w), u);
}

template<int TB, int AOFF, int BOFF> __device__ __forceinline__ void wgmma_ss_n216(float (&d)[108], uint64_t da, uint64_t db, int sd) {
    asm volatile("{\n.reg .pred p;\n.reg .b64 ta, tb;\nsetp.ne.b32 p, %110, 0;\nadd.s64 ta, %108, %112;\nadd.s64 tb, %109, %113;\n"
      "wgmma.mma_async.sync.aligned.m64n216k16.f32.bf16.bf16 {%0, %1, %2, %3, %4, %5, %6, %7, %8, %9, %10, %11, %12, %13, %14, %15, %16, %17, %18, %19, %20, %21, %22, %23, %24, %25, %26, %27, %28, %29, %30, %31, %32, %33, %34, %35, %36, %37, %38, %39, %40, %41, %42, %43, %44, %45, %46, %47, %48, %49, %50, %51, %52, %53, %54, %55, %56, %57, %58, %59, %60, %61, %62, %63, %64, %65, %66, %67, %68, %69, %70, %71, %72, %73, %74, %75, %76, %77, %78, %79, %80, %81, %82, %83, %84, %85, %86, %87, %88, %89, %90, %91, %92, %93, %94, %95, %96, %97, %98, %99, %100, %101, %102, %103, %104, %105, %106, %107}, ta, tb, p, 1, 1, 0, %111;\n}\n"
      : "+f"(d[0]), "+f"(d[1]), "+f"(d[2]), "+f"(d[3]), "+f"(d[4]), "+f"(d[5]), "+f"(d[6]), "+f"(d[7]), "+f"(d[8]), "+f"(d[9]), "+f"(d[10]), "+f"(d[11]), "+f"(d[12]), "+f"(d[13]), "+f"(d[14]), "+f"(d[15]), "+f"(d[16]), "+f"(d[17]), "+f"(d[18]), "+f"(d[19]), "+f"(d[20]), "+f"(d[21]), "+f"(d[22]), "+f"(d[23]), "+f"(d[24]), "+f"(d[25]), "+f"(d[26]), "+f"(d[27]), "+f"(d[28]), "+f"(d[29]), "+f"(d[30]), "+f"(d[31]), "+f"(d[32]), "+f"(d[33]), "+f"(d[34]), "+f"(d[35]), "+f"(d[36]), "+f"(d[37]), "+f"(d[38]), "+f"(d[39]), "+f"(d[40]), "+f"(d[41]), "+f"(d[42]), "+f"(d[43]), "+f"(d[44]), "+f"(d[45]), "+f"(d[46]), "+f"(d[47]), "+f"(d[48]), "+f"(d[49]), "+f"(d[50]), "+f"(d[51]), "+f"(d[52]), "+f"(d[53]), "+f"(d[54]), "+f"(d[55]), "+f"(d[56]), "+f"(d[57]), "+f"(d[58]), "+f"(d[59]), "+f"(d[60]), "+f"(d[61]), "+f"(d[62]), "+f"(d[63]), "+f"(d[64]), "+f"(d[65]), "+f"(d[66]), "+f"(d[67]), "+f"(d[68]), "+f"(d[69]), "+f"(d[70]), "+f"(d[71]), "+f"(d[72]), "+f"(d[73]), "+f"(d[74]), "+f"(d[75]), "+f"(d[76]), "+f"(d[77]), "+f"(d[78]), "+f"(d[79]), "+f"(d[80]), "+f"(d[81]), "+f"(d[82]), "+f"(d[83]), "+f"(d[84]), "+f"(d[85]), "+f"(d[86]), "+f"(d[87]), "+f"(d[88]), "+f"(d[89]), "+f"(d[90]), "+f"(d[91]), "+f"(d[92]), "+f"(d[93]), "+f"(d[94]), "+f"(d[95]), "+f"(d[96]), "+f"(d[97]), "+f"(d[98]), "+f"(d[99]), "+f"(d[100]), "+f"(d[101]), "+f"(d[102]), "+f"(d[103]), "+f"(d[104]), "+f"(d[105]), "+f"(d[106]), "+f"(d[107])
      : "l"(da), "l"(db), "r"(sd), "n"(TB), "n"(AOFF), "n"(BOFF));
}

template<int TB, int AOFF, int BOFF> __device__ __forceinline__ void wgmma_ss_n128(float (&d)[64], uint64_t da, uint64_t db, int sd) {
    asm volatile("{\n.reg .pred p;\n.reg .b64 ta, tb;\nsetp.ne.b32 p, %66, 0;\nadd.s64 ta, %64, %68;\nadd.s64 tb, %65, %69;\n"
      "wgmma.mma_async.sync.aligned.m64n128k16.f32.bf16.bf16 {%0, %1, %2, %3, %4, %5, %6, %7, %8, %9, %10, %11, %12, %13, %14, %15, %16, %17, %18, %19, %20, %21, %22, %23, %24, %25, %26, %27, %28, %29, %30, %31, %32, %33, %34, %35, %36, %37, %38, %39, %40, %41, %42, %43, %44, %45, %46, %47, %48, %49, %50, %51, %52, %53, %54, %55, %56, %57, %58, %59, %60, %61, %62, %63}, ta, tb, p, 1, 1, 0, %67;\n}\n"
      : "+f"(d[0]), "+f"(d[1]), "+f"(d[2]), "+f"(d[3]), "+f"(d[4]), "+f"(d[5]), "+f"(d[6]), "+f"(d[7]), "+f"(d[8]), "+f"(d[9]), "+f"(d[10]), "+f"(d[11]), "+f"(d[12]), "+f"(d[13]), "+f"(d[14]), "+f"(d[15]), "+f"(d[16]), "+f"(d[17]), "+f"(d[18]), "+f"(d[19]), "+f"(d[20]), "+f"(d[21]), "+f"(d[22]), "+f"(d[23]), "+f"(d[24]), "+f"(d[25]), "+f"(d[26]), "+f"(d[27]), "+f"(d[28]), "+f"(d[29]), "+f"(d[30]), "+f"(d[31]), "+f"(d[32]), "+f"(d[33]), "+f"(d[34]), "+f"(d[35]), "+f"(d[36]), "+f"(d[37]), "+f"(d[38]), "+f"(d[39]), "+f"(d[40]), "+f"(d[41]), "+f"(d[42]), "+f"(d[43]), "+f"(d[44]), "+f"(d[45]), "+f"(d[46]), "+f"(d[47]), "+f"(d[48]), "+f"(d[49]), "+f"(d[50]), "+f"(d[51]), "+f"(d[52]), "+f"(d[53]), "+f"(d[54]), "+f"(d[55]), "+f"(d[56]), "+f"(d[57]), "+f"(d[58]), "+f"(d[59]), "+f"(d[60]), "+f"(d[61]), "+f"(d[62]), "+f"(d[63])
      : "l"(da), "l"(db), "r"(sd), "n"(TB), "n"(AOFF), "n"(BOFF));
}

template<int TB, int AOFF, int BOFF> __device__ __forceinline__ void wgmma_ss_n72(float (&d)[36], uint64_t da, uint64_t db, int sd) {
    asm volatile("{\n.reg .pred p;\n.reg .b64 ta, tb;\nsetp.ne.b32 p, %38, 0;\nadd.s64 ta, %36, %40;\nadd.s64 tb, %37, %41;\n"
      "wgmma.mma_async.sync.aligned.m64n72k16.f32.bf16.bf16 {%0, %1, %2, %3, %4, %5, %6, %7, %8, %9, %10, %11, %12, %13, %14, %15, %16, %17, %18, %19, %20, %21, %22, %23, %24, %25, %26, %27, %28, %29, %30, %31, %32, %33, %34, %35}, ta, tb, p, 1, 1, 0, %39;\n}\n"
      : "+f"(d[0]), "+f"(d[1]), "+f"(d[2]), "+f"(d[3]), "+f"(d[4]), "+f"(d[5]), "+f"(d[6]), "+f"(d[7]), "+f"(d[8]), "+f"(d[9]), "+f"(d[10]), "+f"(d[11]), "+f"(d[12]), "+f"(d[13]), "+f"(d[14]), "+f"(d[15]), "+f"(d[16]), "+f"(d[17]), "+f"(d[18]), "+f"(d[19]), "+f"(d[20]), "+f"(d[21]), "+f"(d[22]), "+f"(d[23]), "+f"(d[24]), "+f"(d[25]), "+f"(d[26]), "+f"(d[27]), "+f"(d[28]), "+f"(d[29]), "+f"(d[30]), "+f"(d[31]), "+f"(d[32]), "+f"(d[33]), "+f"(d[34]), "+f"(d[35])
      : "l"(da), "l"(db), "r"(sd), "n"(TB), "n"(AOFF), "n"(BOFF));
}

template<int TB, int BOFF> __device__ __forceinline__ void wgmma_rs_n24(float (&d)[12], uint32_t a0, uint32_t a1, uint32_t a2, uint32_t a3, uint64_t db, int sd) {
    asm volatile("{\n.reg .pred p;\n.reg .b64 tb;\nsetp.ne.b32 p, %17, 0;\nadd.s64 tb, %16, %19;\n"
      "wgmma.mma_async.sync.aligned.m64n24k16.f32.bf16.bf16 {%0, %1, %2, %3, %4, %5, %6, %7, %8, %9, %10, %11}, {%12, %13, %14, %15}, tb, p, 1, 1, %18;\n}\n"
      : "+f"(d[0]), "+f"(d[1]), "+f"(d[2]), "+f"(d[3]), "+f"(d[4]), "+f"(d[5]), "+f"(d[6]), "+f"(d[7]), "+f"(d[8]), "+f"(d[9]), "+f"(d[10]), "+f"(d[11])
      : "r"(a0), "r"(a1), "r"(a2), "r"(a3), "l"(db), "r"(sd), "n"(TB), "n"(BOFF));
}

template<int TB, int BOFF> __device__ __forceinline__ void wgmma_rs_n72(float (&d)[36], uint32_t a0, uint32_t a1, uint32_t a2, uint32_t a3, uint64_t db, int sd) {
    asm volatile("{\n.reg .pred p;\n.reg .b64 tb;\nsetp.ne.b32 p, %41, 0;\nadd.s64 tb, %40, %43;\n"
      "wgmma.mma_async.sync.aligned.m64n72k16.f32.bf16.bf16 {%0, %1, %2, %3, %4, %5, %6, %7, %8, %9, %10, %11, %12, %13, %14, %15, %16, %17, %18, %19, %20, %21, %22, %23, %24, %25, %26, %27, %28, %29, %30, %31, %32, %33, %34, %35}, {%36, %37, %38, %39}, tb, p, 1, 1, %42;\n}\n"
      : "+f"(d[0]), "+f"(d[1]), "+f"(d[2]), "+f"(d[3]), "+f"(d[4]), "+f"(d[5]), "+f"(d[6]), "+f"(d[7]), "+f"(d[8]), "+f"(d[9]), "+f"(d[10]), "+f"(d[11]), "+f"(d[12]), "+f"(d[13]), "+f"(d[14]), "+f"(d[15]), "+f"(d[16]), "+f"(d[17]), "+f"(d[18]), "+f"(d[19]), "+f"(d[20]), "+f"(d[21]), "+f"(d[22]), "+f"(d[23]), "+f"(d[24]), "+f"(d[25]), "+f"(d[26]), "+f"(d[27]), "+f"(d[28]), "+f"(d[29]), "+f"(d[30]), "+f"(d[31]), "+f"(d[32]), "+f"(d[33]), "+f"(d[34]), "+f"(d[35])
      : "r"(a0), "r"(a1), "r"(a2), "r"(a3), "l"(db), "r"(sd), "n"(TB), "n"(BOFF));
}

template<int TB, int AINC, int BINC> __device__ __forceinline__ void wgmma_ss_n64_pi(float (&d)[32], uint64_t& da, uint64_t& db, int sd) {
    asm volatile("{\n.reg .pred p;\nsetp.ne.b32 p, %34, 0;\n"
      "wgmma.mma_async.sync.aligned.m64n64k16.f32.bf16.bf16 {%0, %1, %2, %3, %4, %5, %6, %7, %8, %9, %10, %11, %12, %13, %14, %15, %16, %17, %18, %19, %20, %21, %22, %23, %24, %25, %26, %27, %28, %29, %30, %31}, %32, %33, p, 1, 1, 0, %35;\n"
      "add.s64 %32, %32, %36;\nadd.s64 %33, %33, %37;\n}\n"
      : "+f"(d[0]), "+f"(d[1]), "+f"(d[2]), "+f"(d[3]), "+f"(d[4]), "+f"(d[5]), "+f"(d[6]), "+f"(d[7]), "+f"(d[8]), "+f"(d[9]), "+f"(d[10]), "+f"(d[11]), "+f"(d[12]), "+f"(d[13]), "+f"(d[14]), "+f"(d[15]), "+f"(d[16]), "+f"(d[17]), "+f"(d[18]), "+f"(d[19]), "+f"(d[20]), "+f"(d[21]), "+f"(d[22]), "+f"(d[23]), "+f"(d[24]), "+f"(d[25]), "+f"(d[26]), "+f"(d[27]), "+f"(d[28]), "+f"(d[29]), "+f"(d[30]), "+f"(d[31]), "+l"(da), "+l"(db)
      : "r"(sd), "n"(TB), "n"(AINC), "n"(BINC));
}

template<int TB, int BINC> __device__ __forceinline__ void wgmma_rs_n64_pi(float (&d)[32], uint32_t a0, uint32_t a1, uint32_t a2, uint32_t a3, uint64_t& db, int sd) {
    asm volatile("{\n.reg .pred p;\nsetp.ne.b32 p, %37, 0;\n"
      "wgmma.mma_async.sync.aligned.m64n64k16.f32.bf16.bf16 {%0, %1, %2, %3, %4, %5, %6, %7, %8, %9, %10, %11, %12, %13, %14, %15, %16, %17, %18, %19, %20, %21, %22, %23, %24, %25, %26, %27, %28, %29, %30, %31}, {%33, %34, %35, %36}, %32, p, 1, 1, %38;\n"
      "add.s64 %32, %32, %39;\n}\n"
      : "+f"(d[0]), "+f"(d[1]), "+f"(d[2]), "+f"(d[3]), "+f"(d[4]), "+f"(d[5]), "+f"(d[6]), "+f"(d[7]), "+f"(d[8]), "+f"(d[9]), "+f"(d[10]), "+f"(d[11]), "+f"(d[12]), "+f"(d[13]), "+f"(d[14]), "+f"(d[15]), "+f"(d[16]), "+f"(d[17]), "+f"(d[18]), "+f"(d[19]), "+f"(d[20]), "+f"(d[21]), "+f"(d[22]), "+f"(d[23]), "+f"(d[24]), "+f"(d[25]), "+f"(d[26]), "+f"(d[27]), "+f"(d[28]), "+f"(d[29]), "+f"(d[30]), "+f"(d[31]), "+l"(db)
      : "r"(a0), "r"(a1), "r"(a2), "r"(a3), "r"(sd), "n"(TB), "n"(BINC));
}

constexpr int K1_XN_BYTES = 16 * 9216;
constexpr int K1_OFF_RING = K1_XN_BYTES;
constexpr int K1_OFF_BIAS = K1_OFF_RING + 10 * 8192;
constexpr int K1_OFF_BAR = K1_OFF_BIAS + 576 * 2;
constexpr int K1_SMEM = K1_OFF_BAR + 800;
constexpr float QSCALE = 0.23570226039551584f * 1.4426950408889634f;

struct K1Ctx {
    uint32_t full0;
    uint32_t rel_addr;
    uint64_t descA, descB;
    uint32_t phase;
    __device__ __forceinline__ void begin_stage(int s) {
        mbar_wait(full0 + s * 8, phase);
        wg_fence();
    }
    __device__ __forceinline__ void release(int s) {
        if (rel_addr) asm volatile("mbarrier.arrive.shared::cluster.b64 _, [%0];" ::"r"(rel_addr + s * 8) : "memory");
    }
    __device__ __forceinline__ void end_stage(int s) {
        wg_commit();
        wg_wait<1>();
        release(s == 0 ? 8 : s - 1);
    }
};

__host__ __device__ constexpr int a_off(int ks) { return ((ks / 12) * 49152 + ((ks >> 2) % 3) * 1024 + (ks & 3) * 32) >> 4; }

template <int V> struct IC { static constexpr int value = V; };
template <int I, int N, class F> __device__ __forceinline__ void static_for(F&& f) {
    if constexpr (I < N) { f(IC<I>{}); static_for<I + 1, N>(f); }
}

template <bool A_RS, bool B_RS, class Epi>
__device__ __forceinline__ void tile_pair(K1Ctx& c, float (&accA)[32], float (&accB)[32], uint32_t (&h)[144], Epi&& epi) {
    static_for<0, 9>([&](auto sc) {
        constexpr int s = decltype(sc)::value;
        c.begin_stage(s);
        static_for<0, 8>([&](auto tc) {
            constexpr int t = decltype(tc)::value, kk = s * 8 + t, ks = kk % 36;
            constexpr int db = ks == 35 ? -35 * 128 : 128, da = a_off((ks + 1) % 36) - a_off(ks);
            if constexpr (kk < 36) {
                if constexpr (A_RS) wgmma_rs_n64_pi<1, db>(accA, h[ks * 4], h[ks * 4 + 1], h[ks * 4 + 2], h[ks * 4 + 3], c.descB, ks != 0);
                else wgmma_ss_n64_pi<1, da, db>(accA, c.descA, c.descB, ks != 0);
            } else {
                if constexpr (B_RS) wgmma_rs_n64_pi<1, db>(accB, h[ks * 4], h[ks * 4 + 1], h[ks * 4 + 2], h[ks * 4 + 3], c.descB, ks != 0);
                else wgmma_ss_n64_pi<1, da, db>(accB, c.descA, c.descB, ks != 0);
            }
            if constexpr (t == 0) {
                c.end_stage(s);
                epi(sc);
                wg_fence();
            }
        });
        wg_commit();
    });
    c.phase ^= 1;
}

template <int B0, int NB, int HOFF>
__device__ __forceinline__ void gelu_blocks(const float (&acc)[32], uint32_t (&h)[144], const uint32_t (&bq)[8], float rs0, float rs1) {
#pragma unroll
    for (int b = B0; b < B0 + NB; b++) {
        const float b0 = bf_lo(bq[b]), b1 = bf_hi(bq[b]);
        h[HOFF + b * 2 + 0] = pack_bf16(gelu2(fmaf(acc[b * 4 + 0], rs0, b0)), gelu2(fmaf(acc[b * 4 + 1], rs0, b1)));
        h[HOFF + b * 2 + 1] = pack_bf16(gelu2(fmaf(acc[b * 4 + 2], rs1, b0)), gelu2(fmaf(acc[b * 4 + 3], rs1, b1)));
    }
#pragma unroll
    for (int i = HOFF + B0 * 2; i < HOFF + (B0 + NB) * 2; i++) asm volatile("" : "+r"(h[i]));
}
__device__ __forceinline__ void load_bias(uint32_t (&bq)[8], uint32_t addr) {
    asm volatile("ld.shared.v4.u32 {%0, %1, %2, %3}, [%4];" : "=r"(bq[0]), "=r"(bq[1]), "=r"(bq[2]), "=r"(bq[3]) : "r"(addr));
    asm volatile("ld.shared.v4.u32 {%0, %1, %2, %3}, [%4 + 16];" : "=r"(bq[4]), "=r"(bq[5]), "=r"(bq[6]), "=r"(bq[7]) : "r"(addr));
}
template <int S> __device__ __forceinline__ void store_part(const float (&o)[32], uint4* p) {
    uint4 v;
    v.x = pack_bf16(o[S * 8 + 0], o[S * 8 + 1]); v.y = pack_bf16(o[S * 8 + 2], o[S * 8 + 3]);
    v.z = pack_bf16(o[S * 8 + 4], o[S * 8 + 5]); v.w = pack_bf16(o[S * 8 + 6], o[S * 8 + 7]);
    p[S * 256] = v;
}

constexpr int NCHUNK = 16;
constexpr int CHUNK_BYTES = KV_HEAD_BYTES / NCHUNK;
constexpr int SM_Q = 0;
constexpr int SM_KV = 32768;
constexpr int PIECE = 19968;
__host__ __device__ constexpr int sm_piece(int p) { return p == 0 ? 209408 : (p == 1 ? 0 : SM_KV + (p - 2) * PIECE); }
__host__ __device__ constexpr int sm_wstep(int k) { return k < 27 ? sm_piece(k / 3) + (k % 3) * 4608 : (k < 35 ? SM_KV + 7 * PIECE + (k - 27) * 4608 : PIECE); }
__host__ __device__ constexpr int sm_ostep(int k) { return sm_piece(k / 3) + 13824 + (k % 3) * 2048; }
constexpr int SM_RED = SM_KV + KV_HEAD_BYTES;

__device__ __forceinline__ float exp2_fixed(float y) {
    const float u = __uint_as_float(__float_as_uint(y) & 0xFF807FFFu) - 512.02545f;
    float t = fmaf(u, 0.019497588f, 0.114550486f);
    t = fmaf(t, u, -0.29839927f);
    return fmaf(t, u, y);
}
__device__ __forceinline__ uint32_t pack_fixed(float lo, float hi) { return __byte_perm(__float_as_uint(lo), __float_as_uint(hi), 0x6521); }

#define PV_GROUP 4
#define POLY_MODE 1
__device__ __forceinline__ uint32_t exp2_packed(float y0, float y1, uint32_t one2) {
    const uint32_t w = pack_fixed(y0, y1);
    uint32_t m;
    asm("lop3.b32 %0, %1, 0x007F007F, %2, 0xEA;" : "=r"(m) : "r"(w), "r"(one2));
    const uint32_t d = hfma2_bf16(m, 0x3EF93EF9u, 0xBF38BF38u);
    const uint32_t e = hfma2_bf16(d, d, 0xBD71BD71u);
    return hfma2_bf16(w, e, w);
}
constexpr int KV_TILE = CHUNK_BYTES / 16;
template <int OFF> __device__ __forceinline__ void issue_qk(float (&s)[64], uint64_t qd, uint64_t kd) {
    wgmma_ss_n128<0, 0, OFF + (8 << 16)>(s, qd, kd, 0);
    wgmma_ss_n128<0, 16, OFF + 32>(s, qd, kd, 1);
}
template <int OFF> __device__ __forceinline__ void issue_pv(float (&o)[12], const uint32_t (&p)[32], uint64_t vd) {
    static_for<0, 8>([&](auto kc) {
        constexpr int k = decltype(kc)::value;
        wgmma_rs_n24<1, OFF + k * (2 * KV_GROUP_BYTES / 16)>(o, p[k * 4], p[k * 4 + 1], p[k * 4 + 2], p[k * 4 + 3], vd, 1);
    });
}
template <int OFF>
__device__ __forceinline__ void softmax_pv(const float (&s)[64], uint32_t (&p)[32], float (&o)[12], uint64_t vd, uint32_t one2) {
    static_for<0, 8 / PV_GROUP>([&](auto gc) {
        constexpr int g0 = decltype(gc)::value * PV_GROUP;
#pragma unroll
        for (int b = g0 * 2; b < (g0 + PV_GROUP) * 2; b++) {
            if ((POLY_MASK >> b) & 1) {
                p[b * 2 + 0] = exp2_packed(s[b * 4 + 0], s[b * 4 + 1], one2);
                p[b * 2 + 1] = exp2_packed(s[b * 4 + 2], s[b * 4 + 3], one2);
            } else {
                p[b * 2 + 0] = pack_bf16(ex2(s[b * 4 + 0]), ex2(s[b * 4 + 1]));
                p[b * 2 + 1] = pack_bf16(ex2(s[b * 4 + 2]), ex2(s[b * 4 + 3]));
            }
        }
#pragma unroll
        for (int i = g0 * 4; i < (g0 + PV_GROUP) * 4; i++) asm volatile("" : "+r"(p[i])::"memory");
        wg_fence();
        static_for<g0, g0 + PV_GROUP>([&](auto kc) {
            constexpr int k = decltype(kc)::value;
            wgmma_rs_n24<1, OFF + k * (2 * KV_GROUP_BYTES / 16)>(o, p[k * 4], p[k * 4 + 1], p[k * 4 + 2], p[k * 4 + 3], vd, 1);
        });
    });
    wg_commit();
}
template <bool LATE> __device__ __forceinline__ void store_o(float (&o)[12], int rt, int head, int wq, int lane) {
    const int g = lane >> 2, q = lane & 3;
    const float i0 = __fdividef(1.0f, __shfl_sync(~0u, o[8], lane | 3)), i1 = __fdividef(1.0f, __shfl_sync(~0u, o[10], lane | 3));
#pragma unroll
    for (int i = 0; i < 3; i++) {
        const uint32_t w0 = pack_bf16(o[i * 4] * i0, o[i * 4 + 1] * i0), w1 = pack_bf16(o[i * 4 + 2] * i1, o[i * 4 + 3] * i1);
        if (i < 2 || q == 2) {
            if constexpr (LATE) {
                const int pc = (head & 7) * 9 + (i < 2 ? i * 4 + q : 8);
                uint32_t* op = reinterpret_cast<uint32_t*>(g_Olate) + (((rt * 9 + (pc >> 3)) * 128 + wq * 32 + g * 4 + (pc & 3)) * 4 + ((pc >> 2) & 1) * 2);
                asm volatile("st.relaxed.gpu.global.v2.u32 [%0], {%1, %2};" ::"l"(op), "r"(w0), "r"(w1) : "memory");
            } else {
                const int pc = head * 9 + (i < 2 ? i * 4 + q : 8);
                uint32_t* op = g_O + ((rt * 72 + (pc >> 2)) * 8 + wq * 2) * 32 + g * 4 + (pc & 3);
                op[0] = w0;
                op[32] = w1;
            }
        }
    }
#pragma unroll
    for (int i = 0; i < 12; i++) o[i] = 0.f;
}
__device__ __forceinline__ void mbar_arrive(uint32_t b) { asm volatile("mbarrier.arrive.shared::cta.b64 _, [%0];" ::"r"(b) : "memory"); }
__device__ __forceinline__ void mbar_wait_sleep(uint32_t b, uint32_t ns) {
    uint32_t ok, spins = 0;
    while (true) {
        asm volatile("{\n.reg .pred p;\nmbarrier.try_wait.parity.shared::cta.b64 p, [%1], 0;\nselp.u32 %0, 1, 0, p;\n}\n" : "=r"(ok) : "r"(b) : "memory");
        if (ok) break;
        __nanosleep(ns);
        if (++spins > (1u << 21)) __trap();
    }
}
__device__ __forceinline__ void flag_signal(unsigned int* f) {
    __threadfence();
    atomicAdd(f, 1u);
}
__device__ __forceinline__ void flag_wait(const unsigned int* f, unsigned int target, unsigned int sleep_ns) {
    uint32_t v, spins = 0;
    while (true) {
        asm volatile("ld.acquire.gpu.global.u32 %0, [%1];" : "=r"(v) : "l"(f) : "memory");
        if (v >= target) break;
        if (sleep_ns) __nanosleep(sleep_ns);
        if (++spins > (1u << 21)) __trap();
    }
}
__device__ __forceinline__ uint4 hadd8_bf16(const uint4 a, const uint4 b) {
    return make_uint4(hadd2_bf16(a.x, b.x), hadd2_bf16(a.y, b.y), hadd2_bf16(a.z, b.z), hadd2_bf16(a.w, b.w));
}
__device__ __forceinline__ float sumsq2(uint32_t w) { return fmaf(bf_lo(w), bf_lo(w), bf_hi(w) * bf_hi(w)); }
__device__ __forceinline__ float sumsq8(const uint4 v) { return (sumsq2(v.x) + sumsq2(v.y)) + (sumsq2(v.z) + sumsq2(v.w)); }

enum { B_FULL = 0, B_EMPTY = 9, B_BASE = 18, B_XNDEAD = 19, B_QRDY = 20, B_FFN = 21, B_KV = 22, B_FREE = 38, B_WO = 46, B_RED = 55, B_X = 61, B_EARLY = 85, B_OS = 86, B_LATE = 94, B_BIAS = 95, B_END = 96 };

__global__ void __cluster_dims__(2, 1, 1) __launch_bounds__(384, 1)
fused_kernel(const __grid_constant__ CUtensorMap tmX, const __grid_constant__ CUtensorMap tmQ3, const __grid_constant__ CUtensorMap tmQ1,
          const __grid_constant__ CUtensorMap tm1, const __grid_constant__ CUtensorMap tm2, const __grid_constant__ CUtensorMap tmP,
          const __grid_constant__ CUtensorMap tmOut, const __grid_constant__ CUtensorMap tmXo, const __nv_bfloat16* __restrict__ b1,
          const __nv_bfloat16* __restrict__ wqkv, const __nv_bfloat16* __restrict__ w1, const __nv_bfloat16* __restrict__ w2,
          const __nv_bfloat16* __restrict__ wo, const __nv_bfloat16* __restrict__ b2,
          const uint64_t zero) {
    extern __shared__ __align__(1024) uint8_t smem[];
    const uint32_t sb = s2u(smem);
    const int tid = threadIdx.x, lane = tid & 31;
    const int warp = __shfl_sync(~0u, tid >> 5, 0);
    const uint32_t rank = blockIdx.x & 1;
    const int cl = blockIdx.x >> 1;
    const int rb = (cl & 7) * 2 + rank;
    const int j = cl >> 3;
    const uint32_t bar0 = sb + K1_OFF_BAR;
    const uint32_t full0 = bar0 + B_FULL * 8, empty0 = bar0 + B_EMPTY * 8, xbar0 = bar0 + B_X * 8;
    const int head = blockIdx.x >> 2, quarter = blockIdx.x & 3;
    const int rt = quarter * 8 + (head >> 2), ct = head & 3;
    const int rot = head >> 3;
    const int ks0 = ((((head >> 3) + 2) & 3) * 9);
    volatile uint32_t* slow_flag = reinterpret_cast<volatile uint32_t*>(smem + K1_OFF_BAR + B_END * 8);

    if (warp < 8) {
        PROF(0);
        PROFT(48);
        if (lane == 0) {
#pragma unroll
            for (int i = 0; i < 3; i++) mbar_init(xbar0 + (warp * 3 + i) * 8, 1);
            fence_barrier_init();
#pragma unroll 1
            for (int i = 0; i < 3; i++) {
                const uint32_t xb = xbar0 + (warp * 3 + i) * 8;
                mbar_expect(xb, 6144);
                tma4d(sb + i * 49152 + warp * 6144, &tmX, 0, 0, i * 3, rb * 16 + warp * 2, xb);
            }
        }
        __syncwarp();
        cluster_arrive();
        PROF(22);
        reg_alloc<240>();
        PROF(23);
        float rs0, rs1;
        {
            const uint32_t la = sb + (warp * 2 + ((lane >> 3) & 1)) * 3072 + (lane & 7) * 128;
            uint32_t off[4];
#pragma unroll
            for (int i = 0; i < 4; i++) off[i] = la + (((i * 2 + (lane >> 4)) ^ (lane & 7)) << 4);
            float c1[4] = {0.f, 0.f, 0.f, 0.f}, c2[4] = {0.f, 0.f, 0.f, 0.f}, c3[4] = {0.f, 0.f, 0.f, 0.f};
            uint32_t a[36][4];
#pragma unroll
            for (int t = 0; t < 3; t++) {
                mbar_wait(xbar0 + (warp * 3 + t) * 8, 0);
                PROF(24 + t);
#pragma unroll
                for (int i = 0; i < 12; i++) ldsm4(a[t * 12 + i], off[i & 3] + t * 49152 + (i >> 2) * 1024);
#pragma unroll
                for (int i = t * 12; i < t * 12 + 12; i++) {
                    mma16816(c3, a[i], 0x3F803F80u, 0x3F803F80u);
                    mma16816(c1, a[i], a[i][0], a[i][2]);
                    mma16816(c2, a[i], a[i][1], a[i][3]);
                }
            }
            PROF(27);
            const int gg = lane >> 2, src = (lane & ~3) | (gg >> 1);
            const float m0 = c3[0] * (1.0f / DM), m1 = c3[2] * (1.0f / DM);
            const uint32_t mc0 = pack_bf16(-m0, -m0), mc1 = pack_bf16(-m1, -m1);
#pragma unroll
            for (int i = 0; i < 36; i++) {
#pragma unroll
                for (int k = 0; k < 4; k++) a[i][k] = hadd2_bf16(a[i][k], (k & 1) ? mc1 : mc0);
                stsm4(off[i & 3] + (i / 12) * 49152 + ((i >> 2) % 3) * 1024, a[i]);
            }
            const float q0 = __shfl_sync(~0u, (gg & 1) ? c1[1] : c1[0], src), q1 = __shfl_sync(~0u, (gg & 1) ? c2[3] : c2[2], src);
            rs0 = rsqrtf(fmaxf(fmaf(-m0, m0, q0 * (1.0f / DM)), 0.f) + 1e-5f);
            rs1 = rsqrtf(fmaxf(fmaf(-m1, m1, q1 * (1.0f / DM)), 0.f) + 1e-5f);
            if (__any_sync(~0u, fabsf(m0) * rs0 > 0.25f || fabsf(m1) * rs1 > 0.25f)) {
                const float d0 = -m0 - bf_lo(mc0), d1 = -m1 - bf_lo(mc1);
                const uint32_t md0 = pack_bf16(d0, d0), md1 = pack_bf16(d1, d1);
#pragma unroll 1
                for (int i = 0; i < 9; i++) {
#pragma unroll
                    for (int k4 = 0; k4 < 4; k4++) {
                        const uint32_t ad = off[k4] + (i / 3) * 49152 + (i % 3) * 1024;
                        uint32_t b[4];
                        ldsm4(b, ad);
#pragma unroll
                        for (int k = 0; k < 4; k++) b[k] = hadd2_bf16(b[k], (k & 1) ? md1 : md0);
                        stsm4(ad, b);
                    }
                }
            }
        }
        PROF(28);
        const int wg = warp >> 2, wq = warp & 3;
        fence_proxy_async();
        named_bar_sync(1 + wg, 128);
        cluster_wait();
        PROF(1);

        const int g = lane >> 2, q = lane & 3;
        K1Ctx c;
        c.full0 = full0;
        c.rel_addr = 0;
        c.descA = mk_desc(zero, sb + wg * 8 * 3072, 16, 3072, 1);
        c.descB = mk_desc(zero, sb + K1_OFF_RING, 2048, 1024, 1);
        c.phase = 0;
        uint32_t biasq = sb + K1_OFF_BIAS + q * 32;
        uint32_t bq[8];

        uint32_t h[144];
        float accA[32], accB[32];
        {
            float accQ[108];
            uint32_t rel = 0;
            if (lane == 0 && wq < 2) asm("mapa.shared::cluster.u32 %0, %1, %2;" : "=r"(rel) : "r"(empty0), "r"(wq));
#pragma unroll 1
            for (int r = 0; r < 2; r++) {
                static_for<0, 9>([&](auto sc) {
                    constexpr int s = decltype(sc)::value;
                    c.begin_stage(s);
                    const uint64_t da = c.descA + (r ? a_off(18 + 2 * s) : a_off(2 * s));
                    wgmma_ss_n216<1, 0, ((2 * s) % 9) * 512>(accQ, da, c.descB, (r | s) != 0);
                    wgmma_ss_n216<1, 2, ((2 * s + 1) % 9) * 512>(accQ, da, c.descB, 1);
                    c.end_stage(s);
                    c.rel_addr = rel;
                });
                c.phase ^= 1;
            }
            PROF(2); PROFWT(54);
            mbar_wait(bar0 + B_BIAS * 8, 0);
            uint32_t rel9[9];
#pragma unroll
            for (int i9 = 0; i9 < 9; i9++) {
                const int p = 4 * i9 + q, hh = (p * 57) >> 9, r = p - 9 * hh;
                rel9[i9] = hh * KV_HEAD_BYTES + (r < 8 ? (r >> 2) * 128 + (r & 3) * 4 : 0);
            }
            wg_wait<0>();
            reg_fence(accQ);
#pragma unroll
            for (int grp = 0; grp < 3; grp++) {
                const int G = 3 * j + grp, type = G >> 3;
                const uint32_t gb = (G & 7) * 4 * KV_HEAD_BYTES + (rb * 16 + warp * 2) * KV_GROUP_BYTES + g * 16 + (type == 0 ? Q_OFFSET : (type == 2 ? 256 : 0));
                const uint32_t o2 = type == 0 ? 256 : (type == 2 ? 264 : 512);
                const float scl0 = rs0 * (type == 0 ? QSCALE : ((type == 1 && ((POLY_MASK >> (warp * 2)) & 1)) ? 2.f : 1.f));
                const float scl1 = rs1 * (type == 0 ? QSCALE : ((type == 1 && ((POLY_MASK >> (warp * 2 + 1)) & 1)) ? 2.f : 1.f));
#pragma unroll
                for (int i9 = 0; i9 < 9; i9++) {
                    const int b = grp * 9 + i9;
                    uint32_t off = gb + rel9[i9];
                    if (i9 >= 2 && (i9 & 1) == 0) off += (q == i9 / 2 - 1) ? o2 : 0;
                    *reinterpret_cast<uint32_t*>(g_QKV + off) = pack_bf16(accQ[b * 4] * scl0, accQ[b * 4 + 1] * scl0);
                    *reinterpret_cast<uint32_t*>(g_QKV + off + KV_GROUP_BYTES) = pack_bf16(accQ[b * 4 + 2] * scl1, accQ[b * 4 + 3] * scl1);
                }
            }
            asm volatile("bar.arrive 3, 352;" ::: "memory");
        }
        PROF(3); PROFWT(55);
#pragma unroll
        for (int i = 32; i < 112; i++) asm volatile("mov.u32 %0, 0;" : "=r"(h[i]));
#pragma unroll
        for (int i = 0; i < 32; i++) asm volatile("mov.f32 %0, 0f00000000;" : "=f"(accB[i]));
#pragma unroll
        for (int i = 0; i < 8; i++) bq[i] = 0;
#pragma unroll 1
        for (int p = 0; p < 4; p++) {
            tile_pair<false, false>(c, accA, accB, h, [&](auto sc) {
                constexpr int s = decltype(sc)::value;
                if constexpr (s == 0) {
                    reg_fence(accB);
#pragma unroll
                    for (int i = 0; i < 80; i++) h[i] = h[i + 32];
                }
                if constexpr (s < 4) gelu_blocks<s * 2, 2, 80>(accB, h, bq, rs0, rs1);
                if constexpr (s == 4) load_bias(bq, biasq);
                if constexpr (s == 5) reg_fence(accA);
                if constexpr (s >= 5) gelu_blocks<(s - 5) * 2, 2, 96>(accA, h, bq, rs0, rs1);
                if constexpr (s == 8) load_bias(bq, biasq + 128);
            });
            biasq += 256;
        }
        PROF(4); PROFWT(56);
        tile_pair<false, true>(c, accA, accB, h, [&](auto sc) {
            constexpr int s = decltype(sc)::value;
            if constexpr (s == 0) reg_fence(accB);
            if constexpr (s < 4) gelu_blocks<s * 2, 2, 112>(accB, h, bq, rs0, rs1);
            if constexpr (s == 4) load_bias(bq, biasq);
            if constexpr (s == 5) { reg_fence(accA); if (tid == wg * 128) mbar_arrive(bar0 + B_XNDEAD * 8); }
            if constexpr (s == 5 || s == 6) gelu_blocks<(s - 5) * 3, 3, 128>(accA, h, bq, rs0, rs1);
            if constexpr (s == 7) gelu_blocks<6, 2, 128>(accA, h, bq, rs0, rs1);
            if constexpr (s == 3 || s == 7) reg_fence(h);
        });
        PROF(5); PROFWT(57);
        uint4* pout = g_part + j * SLAB + rb * 36 * 256 + tid;
#pragma unroll 1
        for (int p = 0; p < 4; p++) {
            tile_pair<true, true>(c, accA, accB, h, [&](auto sc) {
                constexpr int s = decltype(sc)::value;
                if constexpr (s == 0) reg_fence(accB);
                if constexpr (s < 4) store_part<s>(accB, pout);
                if constexpr (s == 5) reg_fence(accA);
                if constexpr (s >= 5) store_part<s - 5>(accA, pout + 1024);
            });
            pout += 2048;
            PROF(6 + p);
        }
        wg_wait<0>();
        c.release(8);
        reg_fence(accB);
        store_part<0>(accB, pout); store_part<1>(accB, pout); store_part<2>(accB, pout); store_part<3>(accB, pout);
        __syncwarp();
        if (lane == 0) mbar_arrive(bar0 + B_FFN * 8);
        PROF(10); PROFWT(58);
        PROFT(49);

        mbar_wait(bar0 + B_QRDY * 8, 0);
        const uint32_t slow = __any_sync(~0u, *slow_flag != 0);
        const uint64_t kd0 = mk_desc(zero, sb + SM_KV, 0, KV_GROUP_BYTES, 0);
        const uint64_t vd0 = mk_desc(zero, sb + SM_KV + 256, KV_GROUP_BYTES, 128, 0);
        const uint64_t qd0 = mk_desc(zero, sb + SM_Q + wg * 4096, 128, 512, 0);
        const uint32_t kvbar = bar0 + B_KV * 8;
        float o[12];
#pragma unroll
        for (int i = 0; i < 12; i++) o[i] = 0.f;
        PROF(16);
        PROFT(50);
        if (!slow) {
            const uint32_t one2 = 0x3F803F80u + (uint32_t)zero;
            float s0[64], s1[64];
            uint32_t p0[32], p1[32];
            mbar_wait(kvbar, 0);
            reg_fence(o);
            wg_fence();
            issue_qk<0>(s0, qd0, kd0);
            wg_commit();
            wg_commit();
            uint64_t qd = qd0;
            const uint32_t fre = (tid == wg * 128) ? bar0 + B_FREE * 8 - 8 : 0;
#pragma unroll 1
            for (int pass = 0; pass < 4; pass++) {
                uint64_t vd = vd0, kd = kd0;
                uint32_t bn = kvbar + 8;
#pragma unroll 1
                for (int it = 0; it < 8; it++) {
                    mbar_wait(bn, 0);
                    if (it == 0 && pass != 0) {
                        wg_wait<0>();
                        reg_fence(o);
                        store_o<false>(o, quarter * 8 + ((pass - 1 + rot) & 3) * 2 + wg, head, wq, lane);
                        reg_fence(o);
                        __syncwarp();
                        if (lane == 0) mbar_arrive(bar0 + (B_OS + pass * 2 - 2 + wg) * 8);
                    }
                    wg_wait<1>();
                    reg_fence(s0);
                    wg_fence();
                    issue_qk<KV_TILE>(s1, qd, kd);
                    wg_commit();
                    if (pass == 3 && it > 0 && fre) mbar_arrive(fre + it * 8);
                    softmax_pv<0>(s0, p0, o, vd, one2);
                    kd += 2 * KV_TILE; bn += 8;
                    if (it == 7) { kd = kd0; bn = kvbar; qd += 512; }
                    mbar_wait(bn, 0);
                    wg_wait<1>();
                    reg_fence(s1);
                    wg_fence();
                    issue_qk<0>(s0, qd, kd);
                    wg_commit();
                    softmax_pv<KV_TILE>(s1, p1, o, vd, one2);
                    vd += 2 * KV_TILE; bn += 8;
                }
                if (pass == 0) PROF(17);
            }
            wg_wait<0>();
            reg_fence(o);
            reg_fence(s0);
            reg_fence(s1);
            store_o<true>(o, quarter * 8 + ((3 + rot) & 3) * 2 + wg, head, wq, lane);
        } else {
#pragma unroll 1
            for (int pass = 0; pass < 4; pass++) {
                float m0 = -INFINITY, m1 = -INFINITY;
                float s[64];
                uint32_t p[32];
#pragma unroll 1
                for (int t = 0; t < 16; t++) {
                    mbar_wait(kvbar + t * 8, 0);
                    wg_fence();
                    issue_qk<0>(s, qd0 + pass * 512, kd0 + t * KV_TILE);
                    wg_commit();
                    wg_wait<0>();
                    reg_fence(s);
                    float a0 = m0, a1 = m1;
#pragma unroll
                    for (int k = 0; k < 16; k++) {
                        if ((POLY_MASK >> k) & 1) {
#pragma unroll
                            for (int i = 0; i < 4; i++) s[k * 4 + i] *= 0.5f;
                        }
                        a0 = fmaxf(a0, fmaxf(s[k * 4 + 0], s[k * 4 + 1]));
                        a1 = fmaxf(a1, fmaxf(s[k * 4 + 2], s[k * 4 + 3]));
                    }
                    a0 = fmaxf(a0, __shfl_xor_sync(~0u, a0, 1)); a1 = fmaxf(a1, __shfl_xor_sync(~0u, a1, 1));
                    a0 = fmaxf(a0, __shfl_xor_sync(~0u, a0, 2)); a1 = fmaxf(a1, __shfl_xor_sync(~0u, a1, 2));
                    const float r0 = ex2(m0 - a0), r1 = ex2(m1 - a1);
                    m0 = a0; m1 = a1;
#pragma unroll
                    for (int i = 0; i < 3; i++) { o[i * 4] *= r0; o[i * 4 + 1] *= r0; o[i * 4 + 2] *= r1; o[i * 4 + 3] *= r1; }
#pragma unroll
                    for (int k = 0; k < 16; k++) {
                        p[k * 2 + 0] = pack_bf16(ex2(s[k * 4 + 0] - m0), ex2(s[k * 4 + 1] - m0));
                        p[k * 2 + 1] = pack_bf16(ex2(s[k * 4 + 2] - m1), ex2(s[k * 4 + 3] - m1));
                    }
                    reg_fence(p);
                    reg_fence(o);
                    wg_fence();
                    issue_pv<0>(o, p, vd0 + t * KV_TILE);
                    wg_commit();
                    wg_wait<0>();
                    reg_fence(o);
                }
                if (pass < 3) {
                    store_o<false>(o, quarter * 8 + ((pass + rot) & 3) * 2 + wg, head, wq, lane);
                    __syncwarp();
                    if (lane == 0) mbar_arrive(bar0 + (B_OS + pass * 2 + wg) * 8);
                }
            }
            store_o<true>(o, quarter * 8 + ((3 + rot) & 3) * 2 + wg, head, wq, lane);
            if (tid == wg * 128)
                for (int i = 0; i < 7; i++) mbar_arrive(bar0 + (B_FREE + i) * 8);
        }
        PROF(18);
        PROFT(51);

        if (tid == wg * 128) mbar_arrive(bar0 + (B_FREE + 7) * 8);
        const int t128 = tid & 127;
        uint32_t bv[9];
        uint2 fv[9];
        mbar_wait(bar0 + B_BASE * 8, 0);
#pragma unroll
        for (int i = 0; i < 9; i++) {
            bv[i] = __ldg(reinterpret_cast<const uint32_t*>(b2 + ct * 144 + wg * 72 + q * 2) + i * 4);
            fv[i] = __ldcg(g_ffn + (blockIdx.x * 18 + wg * 9 + i) * 128 + t128);
        }
        float acc[36];
        const uint64_t od = mk_desc(zero, sb, 1024, 128, 0), wd = mk_desc(zero, sb + wg * 9 * 128, 2304, 128, 0);
        static_for<0, 9>([&](auto pc) {
            constexpr int p = decltype(pc)::value;
            mbar_wait(bar0 + (B_WO + p) * 8, 0);
            wg_fence();
            wgmma_ss_n72<1, sm_ostep(p * 3) / 16, sm_wstep(p * 3) / 16>(acc, od, wd, p != 0);
            wgmma_ss_n72<1, sm_ostep(p * 3 + 1) / 16, sm_wstep(p * 3 + 1) / 16>(acc, od, wd, 1);
            wgmma_ss_n72<1, sm_ostep(p * 3 + 2) / 16, sm_wstep(p * 3 + 2) / 16>(acc, od, wd, 1);
            wg_commit();
            if constexpr (p == 1) {
                wg_wait<1>();
                if (t128 == 0) mbar_arrive(bar0 + B_EARLY * 8);
            }
        });
        wg_wait<0>();
        reg_fence(acc);
        PROF(29);
        uint4 al[9];
        {
            const uint4* ap = g_Olate + rt * 9 * 128 + t128;
            uint32_t spins = 0;
            bool ok;
            do {
                ok = true;
#pragma unroll
                for (int k = 0; k < 9; k++)
                    asm volatile("ld.relaxed.gpu.global.v4.u32 {%0, %1, %2, %3}, [%4];" : "=r"(al[k].x), "=r"(al[k].y), "=r"(al[k].z), "=r"(al[k].w) : "l"(ap + k * 128) : "memory");
#pragma unroll
                for (int k = 0; k < 9; k++) ok = ok && al[k].x != O_EMPTY && al[k].y != O_EMPTY && al[k].z != O_EMPTY && al[k].w != O_EMPTY;
                if (++spins > (1u << 20)) __trap();
            } while (!__all_sync(~0u, ok));
        }
        PROF(19);
        mbar_wait(bar0 + B_LATE * 8, 0);
        PROF(20);
        wg_fence();
        static_for<27, 36>([&](auto kc) {
            constexpr int k = decltype(kc)::value;
            wgmma_rs_n72<1, sm_wstep(k) / 16>(acc, al[k - 27].x, al[k - 27].y, al[k - 27].z, al[k - 27].w, wd, 1);
        });
        wg_commit();
        PROF(31);
        uint32_t* st = reinterpret_cast<uint32_t*>(smem + sm_piece(0) + wg * 9216) + (wq * 16 + g) * 36 + q;
        float bs[36];
#pragma unroll
        for (int i = 0; i < 9; i++) {
            const uint32_t x0 = st[i * 4], x1 = st[i * 4 + 288];
            bs[i * 4 + 0] = fmaf(bf_lo(fv[i].x), 0.5f, bf_lo(x0) + bf_lo(bv[i]));
            bs[i * 4 + 1] = fmaf(bf_hi(fv[i].x), 0.5f, bf_hi(x0) + bf_hi(bv[i]));
            bs[i * 4 + 2] = fmaf(bf_lo(fv[i].y), 0.5f, bf_lo(x1) + bf_lo(bv[i]));
            bs[i * 4 + 3] = fmaf(bf_hi(fv[i].y), 0.5f, bf_hi(x1) + bf_hi(bv[i]));
        }
        reg_fence(bs);
        wg_wait<0>();
        reg_fence(acc);
        PROF(32);
#pragma unroll
        for (int i = 0; i < 9; i++) {
            st[i * 4] = pack_bf16(acc[i * 4] + bs[i * 4], acc[i * 4 + 1] + bs[i * 4 + 1]);
            st[i * 4 + 288] = pack_bf16(acc[i * 4 + 2] + bs[i * 4 + 2], acc[i * 4 + 3] + bs[i * 4 + 3]);
        }
        fence_proxy_async();
        named_bar_sync(1 + wg, 128);
        if (t128 == 0) {
            asm volatile("cp.async.bulk.tensor.2d.global.shared::cta.bulk_group [%0, {%2, %3}], [%1];"
                         ::"l"(&tmOut), "r"(sb + sm_piece(0) + wg * 9216), "r"(ct * 144 + wg * 72), "r"(rt * 64) : "memory");
            asm volatile("cp.async.bulk.commit_group;" ::: "memory");
            asm volatile("cp.async.bulk.wait_group.read 0;" ::: "memory");
        }
        PROF(21);
        PROFT(52);
    } else {
        reg_dealloc<24>();
        if (warp == 8 && lane == 0) {
            prefetch_tmap(&tmQ3); prefetch_tmap(&tmQ1); prefetch_tmap(&tm1); prefetch_tmap(&tm2);
            #pragma unroll 1
            for (int i = 0; i < 9; i++) { mbar_init(full0 + i * 8, 1); mbar_init(empty0 + i * 8, 4); mbar_init(bar0 + (B_WO + i) * 8, 2); }
            mbar_init(bar0 + B_BASE * 8, 3); mbar_init(bar0 + B_XNDEAD * 8, 2); mbar_init(bar0 + B_QRDY * 8, 3); mbar_init(bar0 + B_FFN * 8, 8); mbar_init(bar0 + B_EARLY * 8, 2); mbar_init(bar0 + B_LATE * 8, 2); mbar_init(bar0 + B_BIAS * 8, 96);
#pragma unroll 1
            for (int i = 0; i < 16; i++) { mbar_init(bar0 + (B_KV + i) * 8, 1); mbar_init(bar0 + (B_FREE + (i & 7)) * 8, 2); if (i < 6) mbar_init(bar0 + (B_RED + i) * 8, 1); if (i < 6) mbar_init(bar0 + (B_OS + i) * 8, 4); }
            *slow_flag = 0;
            fence_barrier_init();
        }
        __syncwarp();
        cluster_arrive();
        cluster_wait();
        const uint8_t* kvsrc = g_QKV + (size_t)head * KV_HEAD_BYTES;
        if (warp == 8) {
            if (lane == 0) {
                int st = 0, u = rank, tile = -4;
                int es = 5;
                uint32_t eph = 1;
#pragma unroll 1
                for (int n = 0; n < 99; n++) {
                    mbar_wait(empty0 + es * 8, eph);
                    const uint32_t fb = full0 + st * 8, dst = sb + K1_OFF_RING + u * 8192;
                    mbar_expect(fb, 16384);
                    if (tile < 0) {
                        tma3d_mc(dst, &tmQ3, j * 216, n * 32 + rank * 16, 0, fb, 3);
                        tma2d_mc(dst + 6144, &tmQ1, j * 216 + 192, n * 32 + rank * 16, fb, 3);
                    } else if (tile < 9) {
                        tma2d_mc(dst, &tm1, j * 576 + tile * 64, u * 64, fb, 3);
                    } else {
                        tma2d_mc(dst, &tm2, (tile - 9) * 64, j * 576 + u * 64, fb, 3);
                    }
                    u += 2;
                    if (u >= 9) { u -= 9; tile++; }
                    if (++st == 9) st = 0;
                    if (++es == 9) { es = 0; eph ^= 1; }
                }
                mbar_wait(empty0 + 8 * 8, 0);
                mbar_wait(bar0 + B_QRDY * 8, 0);
                asm volatile("fence.proxy.async;" ::: "memory");
#pragma unroll 1
                for (int i = 11; i < NCHUNK; i++) {
                    mbar_expect(bar0 + (B_KV + i) * 8, CHUNK_BYTES);
                    bulk_load(sb + SM_KV + i * CHUNK_BYTES, kvsrc + i * CHUNK_BYTES, CHUNK_BYTES, bar0 + (B_KV + i) * 8);
                }
                const uint8_t* wsrc = g_Wo + ct * WO_TILE_BYTES;
                prefetch_tmap(&tmOut);
                mbar_wait_sleep(bar0 + B_BASE * 8, 500);
#pragma unroll 1
                for (int p = 0; p < 9; p++) {
                    if (p > 0) mbar_wait_sleep(bar0 + (B_FREE + p - 1) * 8, p == 1 ? 500 : 40);
                    const int k = ks0 + p * 3 >= 36 ? ks0 + p * 3 - 36 : ks0 + p * 3;
                    mbar_expect(bar0 + (B_WO + p) * 8, 13824);
                    bulk_load(sb + (p == 0 ? sm_piece(0) : (p == 1 ? sm_piece(1) : SM_KV + (p - 2) * PIECE)), wsrc + k * 4608, 13824, bar0 + (B_WO + p) * 8);
                }
                const int kl = ks0 == 0 ? 27 : ks0 - 9;
                mbar_expect(bar0 + B_LATE * 8, 9 * 4608);
                bulk_load(sb + sm_wstep(27), wsrc + kl * 4608, 8 * 4608, bar0 + B_LATE * 8);
                bulk_load(sb + sm_wstep(35), wsrc + (kl + 8) * 4608, 4608, bar0 + B_LATE * 8);
            }
        } else {
            const int ht = tid - 288;
            if (ht == 64) prefetch_l2(wqkv + blockIdx.x * (DM * 3 * DM / 128), DM * 3 * DM / 64);
            if (ht < 72) {
                const uint4 v = __ldg(reinterpret_cast<const uint4*>(b1 + j * 576) + ht);
                uint32_t* sbias = reinterpret_cast<uint32_t*>(smem + K1_OFF_BIAS) + (ht >> 3) * 32 + (ht & 7);
                sbias[0] = v.x; sbias[8] = v.y; sbias[16] = v.z; sbias[24] = v.w;
            }
            mbar_arrive(bar0 + B_BIAS * 8);
            PROFH(37);
#pragma unroll
            for (int i = 0; i < 3; i++) g_Olate[blockIdx.x * 288 + i * 96 + ht] = make_uint4(O_EMPTY, O_EMPTY, O_EMPTY, O_EMPTY);
#pragma unroll 1
            for (int i = ht; i < 512; i += 96) {
                const int key = i & 127;
                uint8_t* p = g_QKV + (size_t)(j * 4 + (i >> 7)) * KV_HEAD_BYTES + (rb * 16 + (key >> 3)) * KV_GROUP_BYTES + 512 + (key & 7) * 16;
                *reinterpret_cast<uint32_t*>(p + 4) = ((POLY_MASK >> (key >> 3)) & 1) ? 0x3F804000u : 0x00003F80u;
                *reinterpret_cast<uint32_t*>(p + 12) = 0x00003F80u;
            }
            if (ht == 32) prefetch_l2(w1 + blockIdx.x * (DM * FF / 128), DM * FF / 64);
#pragma unroll 2
            for (int i = blockIdx.x * 324 + ht; i < blockIdx.x * 324 + 324; i += 96) {
                const int k = i / 72, nc = i - k * 72, c4 = nc / 18;
                *reinterpret_cast<uint4*>(g_Wo + c4 * WO_TILE_BYTES + (k >> 3) * 2304 + (nc - c4 * 18) * 128 + (k & 7) * 16) =
                    __ldg(reinterpret_cast<const uint4*>(wo) + i);
            }
            PROFH(38);
            named_bar_sync(3, 352);
            if (ht == 32) prefetch_l2(w2 + blockIdx.x * (DM * FF / 128), DM * FF / 64);
            if (ht == 0) {
                flag_signal(&g_flags.qkv_stored[rb]);
                flag_wait(&g_flags.qkv_stored[rb], 8, 200);
            }
            named_bar_sync(7, 96);
            PROFH(39);
#pragma unroll 1
            for (int i = warp - 9; i < 16; i += 3) {
                const int hd = j * 4 + (i >> 2), key = (i & 3) * 32 + lane;
                const uint8_t* p = g_QKV + (size_t)hd * KV_HEAD_BYTES + (rb * 16 + (key >> 3)) * KV_GROUP_BYTES + (key & 7) * 16;
                const uint4 a = __ldcg(reinterpret_cast<const uint4*>(p)), b = __ldcg(reinterpret_cast<const uint4*>(p + 128));
                float n = sumsq2(__ldcg(reinterpret_cast<const uint32_t*>(p + 512))) + sumsq8(a) + sumsq8(b);
                if ((POLY_MASK >> (key >> 3)) & 1) n *= 0.25f;
#pragma unroll
                for (int o = 16; o; o >>= 1) n = fmaxf(n, __shfl_xor_sync(~0u, n, o));
                if (lane == 0) g_kmax[hd * 64 + rb * 4 + (i & 3)] = n;
            }
            named_bar_sync(7, 96);
            PROFH(40);
            if (ht == 0) {
                flag_signal(&g_flags.kv_ready);
                flag_wait(&g_flags.kv_ready, 128, 300);
                mbar_wait_sleep(bar0 + B_XNDEAD * 8, 300);
            }
            named_bar_sync(7, 96);
            PROFH(41);
            float kmax2;
            {
                const float2 v = __ldcg(reinterpret_cast<const float2*>(g_kmax + head * 64 + lane * 2));
                kmax2 = fmaxf(v.x, v.y);
#pragma unroll
                for (int o = 16; o; o >>= 1) kmax2 = fmaxf(kmax2, __shfl_xor_sync(~0u, kmax2, o));
            }
            asm volatile("fence.proxy.async;" ::: "memory");
            int chunk = warp - 9;
#pragma unroll 1
            for (int r = ht; r < 512; r += 96) {
                if (lane == 0 && chunk < 11) {
                    mbar_expect(bar0 + (B_KV + chunk) * 8, CHUNK_BYTES);
                    bulk_load(sb + SM_KV + chunk * CHUNK_BYTES, kvsrc + chunk * CHUNK_BYTES, CHUNK_BYTES, bar0 + (B_KV + chunk) * 8);
                }
                chunk += 3;
                const uint8_t* p = kvsrc + Q_OFFSET + (quarter * 64 + (((r >> 3) + rot * 16) & 63)) * KV_GROUP_BYTES + (r & 7) * 16;
                const uint4 a = __ldcg(reinterpret_cast<const uint4*>(p)), b = __ldcg(reinterpret_cast<const uint4*>(p + 128));
                const uint32_t e = __ldcg(reinterpret_cast<const uint32_t*>(p + 256));
                const float cc = sqrtf((sumsq2(e) + sumsq8(a) + sumsq8(b)) * kmax2) * 1.02f;
                if (!(cc <= 58.f)) *slow_flag = 1;
                uint4* dst = reinterpret_cast<uint4*>(smem + SM_Q + (r >> 3) * 512 + (r & 7) * 16);
                dst[0] = a;
                dst[8] = b;
                dst[16] = make_uint4(e, pack_bf16(-cc, 768.f), 0u, 0u);
                dst[24] = make_uint4(0u, POLY_MODE ? 0xBFFF0000u : 0xC0000000u, 0u, 0u);
            }
            named_bar_sync(7, 96);
            if (*slow_flag) {
#pragma unroll 1
                for (int r = ht; r < 512; r += 96) {
                    uint32_t* dst = reinterpret_cast<uint32_t*>(smem + SM_Q + (r >> 3) * 512 + (r & 7) * 16);
                    dst[65] = 0u;
                    dst[97] = 0u;
                }
            }
            fence_proxy_async();
            __syncwarp();
            if (lane == 0) mbar_arrive(bar0 + B_QRDY * 8);
            PROFH(42);
            if (ht == 0) {
                mbar_wait_sleep(bar0 + B_FFN * 8, 300);
                flag_signal(&g_flags.ffn_done[rb]);
                flag_wait(&g_flags.ffn_done[rt >> 1], 8, 300);
            }
            named_bar_sync(7, 96);
            {
                const int w3 = warp - 9;
                const uint32_t rbar = bar0 + (B_RED + w3 * 2) * 8, rbuf = SM_RED + w3 * 8192;
                const int u0 = ((rt >> 1) * 36 + ct * 9) * 256 + (rt & 1) * 128;
                mbar_wait_sleep(bar0 + (B_KV + 15) * 8, 500);
                asm volatile("fence.proxy.async;" ::: "memory");
#pragma unroll 1
                for (int i = -2; i < 12; i++) {
                    if (i >= 0) {
                        __nanosleep(400);
                        mbar_wait(rbar + (i & 1) * 8, (i >> 1) & 1);
                        const uint4* sp = reinterpret_cast<const uint4*>(smem + rbuf + (i & 1) * 4096) + lane;
                        const uint4 v = hadd8_bf16(hadd8_bf16(hadd8_bf16(sp[0], sp[32]), hadd8_bf16(sp[64], sp[96])),
                                                   hadd8_bf16(hadd8_bf16(sp[128], sp[160]), hadd8_bf16(sp[192], sp[224])));
                        const int bx = i * 3 + w3;
                        uint2* fp = g_ffn + (blockIdx.x * 18 + (bx >> 2) * 2) * 128 + (bx & 3) * 32 + lane;
                        fp[0] = make_uint2(v.x, v.y);
                        fp[128] = make_uint2(v.z, v.w);
                    }
                    __syncwarp();
                    if (lane == 0 && i < 10) {
                        const int bx = (i + 2) * 3 + w3;
                        mbar_expect(rbar + (i & 1) * 8, 4096);
                        tma2d(sb + rbuf + (i & 1) * 4096, &tmP, (u0 + (bx >> 2) * 256 + (bx & 3) * 32) * 2, 0, rbar + (i & 1) * 8);
                    }
                }
            }
            __syncwarp();
            if (lane == 0) mbar_arrive(bar0 + B_BASE * 8);
            PROFH(43);
            if (ht == 0) {
#pragma unroll 1
                for (int i = 0; i < 6; i++) {
                    mbar_wait_sleep(bar0 + (B_OS + i) * 8, 200);
                    flag_signal(&g_flags.o_done[quarter * 8 + (((i >> 1) + rot) & 3) * 2 + (i & 1)]);
                }
            } else if (ht == 32) {
                const uint8_t* osrc = reinterpret_cast<const uint8_t*>(g_O) + rt * 73728;
                mbar_wait_sleep(bar0 + B_BASE * 8, 500);
                mbar_wait_sleep(bar0 + B_FREE * 8, 500);
                flag_wait(&g_flags.o_done[rt], 24, 100);
                if (atomicAdd(&g_flags.exited, 1u) == gridDim.x - 1) {
                    unsigned int* f = reinterpret_cast<unsigned int*>(&g_flags);
#pragma unroll 1
                    for (int i = 0; i < (int)(sizeof(Flags) / 4); i++) f[i] = 0;
                }
                prefetch_tmap(&tmXo);
                asm volatile("fence.proxy.async;" ::: "memory");
#pragma unroll 1
                for (int p = 0; p < 9; p++) {
                    if (p > 1) mbar_wait_sleep(bar0 + (B_FREE + p - 1) * 8, 40);
                    const int k = ks0 + p * 3 >= 36 ? ks0 + p * 3 - 36 : ks0 + p * 3;
                    mbar_expect(bar0 + (B_WO + p) * 8, 6144);
                    bulk_load(sb + 13824 + (p == 0 ? sm_piece(0) : (p == 1 ? sm_piece(1) : SM_KV + (p - 2) * PIECE)), osrc + k * 2048, 6144, bar0 + (B_WO + p) * 8);
                }
                mbar_expect(bar0 + B_LATE * 8, 2 * 9216);
                mbar_wait(bar0 + B_EARLY * 8, 0);
                tma2d(sb + sm_piece(0), &tmXo, ct * 144, rt * 64, bar0 + B_LATE * 8);
                tma2d(sb + sm_piece(0) + 9216, &tmXo, ct * 144 + 72, rt * 64, bar0 + B_LATE * 8);
            }
        }
    }
}

typedef CUresult (*EncodeFn)(CUtensorMap*, CUtensorMapDataType, cuuint32_t, void*, const cuuint64_t*, const cuuint64_t*, const cuuint32_t*,
                             const cuuint32_t*, CUtensorMapInterleave, CUtensorMapSwizzle, CUtensorMapL2promotion, CUtensorMapFloatOOBfill);

void make_map(EncodeFn fn, CUtensorMap* m, const void* base, int rank, const cuuint64_t* dims, const cuuint64_t* strides, const cuuint32_t* box) {
    cuuint32_t es[4] = {1, 1, 1, 1};
    fn(m, CU_TENSOR_MAP_DATA_TYPE_BFLOAT16, rank, const_cast<void*>(base), dims, strides, box, es, CU_TENSOR_MAP_INTERLEAVE_NONE,
       CU_TENSOR_MAP_SWIZZLE_128B, CU_TENSOR_MAP_L2_PROMOTION_L2_256B, CU_TENSOR_MAP_FLOAT_OOB_FILL_NONE);
}

}

extern "C" void kernel_launch(void* const* d_in, const int* in_sizes, int n_in, void* d_out, int out_size) {
    const __nv_bfloat16* x = (const __nv_bfloat16*)d_in[0];
    const __nv_bfloat16* wqkv = (const __nv_bfloat16*)d_in[1];
    const __nv_bfloat16* wo = (const __nv_bfloat16*)d_in[2];
    const __nv_bfloat16* w1 = (const __nv_bfloat16*)d_in[4];
    const __nv_bfloat16* b1 = (const __nv_bfloat16*)d_in[5];
    const __nv_bfloat16* w2 = (const __nv_bfloat16*)d_in[6];
    const __nv_bfloat16* b2 = (const __nv_bfloat16*)d_in[7];
    __nv_bfloat16* out = (__nv_bfloat16*)d_out;

    EncodeFn fn = nullptr;
    cudaDriverEntryPointQueryResult qr;
    cudaGetDriverEntryPoint("cuTensorMapEncodeTiled", (void**)&fn, cudaEnableDefault, &qr);
    CUtensorMap tmX, tmQ3, tmQ1, tm1, tm2, tmP, tmOut, tmXo;
    {
        cuuint64_t d[2] = {DM, SEQ}, s[1] = {DM * 2};
        cuuint32_t b[2] = {72, 64}, es[2] = {1, 1};
        fn(&tmOut, CU_TENSOR_MAP_DATA_TYPE_BFLOAT16, 2, out, d, s, b, es, CU_TENSOR_MAP_INTERLEAVE_NONE, CU_TENSOR_MAP_SWIZZLE_NONE,
           CU_TENSOR_MAP_L2_PROMOTION_NONE, CU_TENSOR_MAP_FLOAT_OOB_FILL_NONE);
        fn(&tmXo, CU_TENSOR_MAP_DATA_TYPE_BFLOAT16, 2, const_cast<__nv_bfloat16*>(x), d, s, b, es, CU_TENSOR_MAP_INTERLEAVE_NONE,
           CU_TENSOR_MAP_SWIZZLE_NONE, CU_TENSOR_MAP_L2_PROMOTION_NONE, CU_TENSOR_MAP_FLOAT_OOB_FILL_NONE);
    }
    {
        void* gp = nullptr;
        cudaGetSymbolAddress(&gp, g_part);
        cuuint64_t d[2] = {SLAB * 2, 8}, s[1] = {SLAB * 16};
        cuuint32_t b[2] = {64, 8}, es[2] = {1, 1};
        fn(&tmP, CU_TENSOR_MAP_DATA_TYPE_INT64, 2, gp, d, s, b, es, CU_TENSOR_MAP_INTERLEAVE_NONE, CU_TENSOR_MAP_SWIZZLE_NONE,
           CU_TENSOR_MAP_L2_PROMOTION_NONE, CU_TENSOR_MAP_FLOAT_OOB_FILL_NONE);
    }
    {
        cuuint64_t d[4] = {64, 8, 9, SEQ / 8}, s[3] = {DM * 2, 128, DM * 2 * 8};
        cuuint32_t b[4] = {64, 8, 3, 2};
        make_map(fn, &tmX, x, 4, d, s, b);
    }
    {
        cuuint64_t d[3] = {3 * DM, DM, 3}, s[2] = {3 * DM * 2, 128};
        cuuint32_t b[3] = {64, 16, 3};
        make_map(fn, &tmQ3, wqkv, 3, d, s, b);
        make_map(fn, &tmQ1, wqkv, 2, d, s, b);
    }
    {
        cuuint64_t d[2] = {FF, DM}, s[1] = {FF * 2};
        cuuint32_t b[2] = {64, 64};
        make_map(fn, &tm1, w1, 2, d, s, b);
        cuuint64_t d2[2] = {DM, FF}, s2[1] = {DM * 2};
        make_map(fn, &tm2, w2, 2, d2, s2, b);
    }
    cudaFuncSetAttribute(fused_kernel, cudaFuncAttributeMaxDynamicSharedMemorySize, K1_SMEM);
    fused_kernel<<<128, 384, K1_SMEM, cudaStreamPerThread>>>(tmX, tmQ3, tmQ1, tm1, tm2, tmP, tmOut, tmXo, b1, wqkv, w1, w2, wo, b2, 0ull);
}
```

```cpp
#include <cuda_runtime.h>
#include <cuda_bf16.h>
#include <cuda.h>
#include <stdint.h>

#define PROF(i) do { } while (0)
#define PROFT(i) do { } while (0)
#define PROFH(i) do { } while (0)
#define PROFWT(i) do { } while (0)
#define PROF_WG 0

namespace {

constexpr int SEQ = 2048, DM = 576, FF = 4608, NH = 32, DH = 18;

constexpr int KV_GROUP_BYTES = 5 * 128;
constexpr int KV_HEAD_BYTES = (SEQ / 8) * KV_GROUP_BYTES;
constexpr int Q_OFFSET = NH * KV_HEAD_BYTES;
#define POLY_MASK 0xB6B6
__device__ __align__(1024) uint8_t g_QKV[2 * NH * KV_HEAD_BYTES];
__device__ __align__(1024) float g_kmax[NH * 64];
constexpr int SLAB = 16 * 36 * 256;
__device__ __align__(1024) uint4 g_part[8 * SLAB];
__device__ __align__(1024) uint2 g_ffn[128 * 18 * 128];
__device__ __align__(1024) uint32_t g_O[SEQ * DM / 2];
struct Flags {
    unsigned int qkv_stored[16];
    unsigned int ffn_done[16];
    unsigned int o_done[32];
    unsigned int kv_ready;
    unsigned int exited;
};
__device__ Flags g_flags;
__device__ __align__(1024) uint4 g_Olate[32 * 9 * 128];
constexpr uint32_t O_EMPTY = 0xFFFFFFFFu;
constexpr int WO_TILE_BYTES = DM * 144 * 2;
__device__ __align__(1024) uint8_t g_Wo[4 * WO_TILE_BYTES];

__device__ __forceinline__ uint32_t s2u(const void* p) { return (uint32_t)__cvta_generic_to_shared(p); }
__device__ __forceinline__ void mbar_init(uint32_t b, int c) { asm volatile("mbarrier.init.shared::cta.b64 [%0], %1;" ::"r"(b), "r"(c) : "memory"); }
__device__ __forceinline__ void mbar_expect(uint32_t b, uint32_t bytes) {
    asm volatile("mbarrier.arrive.expect_tx.shared::cta.b64 _, [%0], %1;" ::"r"(b), "r"(bytes) : "memory");
}
__device__ __forceinline__ void mbar_wait(uint32_t b, uint32_t parity) {
    asm volatile(
        "{\n.reg .pred p;\n.reg .u32 c;\n"
        "mov.u32 c, 0;\n"
        "LOOP:\n"
        "mbarrier.try_wait.parity.shared::cta.b64 p, [%0], %1;\n"
        "@p bra DONE;\n"
        "add.u32 c, c, 1;\n"
        "setp.lt.u32 p, c, 4194304;\n"
        "@p bra LOOP;\n"
        "trap;\n"
        "DONE:\n}\n" ::"r"(b), "r"(parity) : "memory");
}
__device__ __forceinline__ void fence_barrier_init() { asm volatile("fence.mbarrier_init.release.cluster;" ::: "memory"); }
__device__ __forceinline__ void fence_proxy_async() { asm volatile("fence.proxy.async.shared::cta;" ::: "memory"); }
__device__ __forceinline__ void cluster_arrive() { asm volatile("barrier.cluster.arrive.relaxed.aligned;" ::: "memory"); }
__device__ __forceinline__ void cluster_wait() { asm volatile("barrier.cluster.wait.aligned;" ::: "memory"); }
__device__ __forceinline__ void named_bar_sync(int id, int n) { asm volatile("bar.sync %0, %1;" ::"r"(id), "r"(n) : "memory"); }

__device__ __forceinline__ void tma3d_mc(uint32_t dst, const CUtensorMap* tm, int c0, int c1, int c2, uint32_t bar, uint16_t mask) {
    asm volatile("cp.async.bulk.tensor.3d.shared::cluster.global.mbarrier::complete_tx::bytes.multicast::cluster [%0], [%1, {%3, %4, %5}], [%2], %6;"
                 ::"r"(dst), "l"(tm), "r"(bar), "r"(c0), "r"(c1), "r"(c2), "h"(mask) : "memory");
}
__device__ __forceinline__ void tma2d_mc(uint32_t dst, const CUtensorMap* tm, int c0, int c1, uint32_t bar, uint16_t mask) {
    asm volatile("cp.async.bulk.tensor.2d.shared::cluster.global.mbarrier::complete_tx::bytes.multicast::cluster [%0], [%1, {%3, %4}], [%2], %5;"
                 ::"r"(dst), "l"(tm), "r"(bar), "r"(c0), "r"(c1), "h"(mask) : "memory");
}
__device__ __forceinline__ void tma4d(uint32_t dst, const CUtensorMap* tm, int c0, int c1, int c2, int c3, uint32_t bar) {
    asm volatile("cp.async.bulk.tensor.4d.shared::cluster.global.mbarrier::complete_tx::bytes [%0], [%1, {%3, %4, %5, %6}], [%2];"
                 ::"r"(dst), "l"(tm), "r"(bar), "r"(c0), "r"(c1), "r"(c2), "r"(c3) : "memory");
}
__device__ __forceinline__ void tma2d(uint32_t dst, const CUtensorMap* tm, int c0, int c1, uint32_t bar) {
    asm volatile("cp.async.bulk.tensor.2d.shared::cluster.global.mbarrier::complete_tx::bytes [%0], [%1, {%3, %4}], [%2];"
                 ::"r"(dst), "l"(tm), "r"(bar), "r"(c0), "r"(c1) : "memory");
}
__device__ __forceinline__ void bulk_load(uint32_t dst, const void* src, uint32_t bytes, uint32_t bar) {
    asm volatile("cp.async.bulk.shared::cluster.global.mbarrier::complete_tx::bytes [%0], [%1], %2, [%3];"
                 ::"r"(dst), "l"(src), "r"(bytes), "r"(bar) : "memory");
}
__device__ __forceinline__ void prefetch_l2(const void* p, uint32_t bytes) {
    asm volatile("cp.async.bulk.prefetch.L2.global [%0], %1;" ::"l"(p), "r"(bytes) : "memory");
}
__device__ __forceinline__ void prefetch_tmap(const CUtensorMap* tm) { asm volatile("prefetch.tensormap [%0];" ::"l"(tm) : "memory"); }

__device__ __forceinline__ void wg_fence() { asm volatile("wgmma.fence.sync.aligned;" ::: "memory"); }
__device__ __forceinline__ void wg_commit() { asm volatile("wgmma.commit_group.sync.aligned;" ::: "memory"); }
template <int N> __device__ __forceinline__ void wg_wait() { asm volatile("wgmma.wait_group.sync.aligned %0;" ::"n"(N) : "memory"); }
template <int N> __device__ __forceinline__ void reg_fence(float (&d)[N]) {
#pragma unroll
    for (int i = 0; i < N; i++) asm volatile("" : "+f"(d[i])::"memory");
}
template <int N> __device__ __forceinline__ void reg_fence(uint32_t (&d)[N]) {
#pragma unroll
    for (int i = 0; i < N; i++) asm volatile("" : "+r"(d[i])::"memory");
}
template <int R> __device__ __forceinline__ void reg_alloc() { asm volatile("setmaxnreg.inc.sync.aligned.u32 %0;" ::"n"(R)); }
template <int R> __device__ __forceinline__ void reg_dealloc() { asm volatile("setmaxnreg.dec.sync.aligned.u32 %0;" ::"n"(R)); }

__device__ __forceinline__ uint64_t mk_desc(uint64_t z, uint32_t addr, uint32_t lbo, uint32_t sbo, uint32_t swz) {
    return z + ((uint64_t)(((addr & 0x3FFFF) >> 4) | ((lbo >> 4) << 16)) | ((uint64_t)((sbo >> 4) | (swz << 30)) << 32));
}
__device__ __forceinline__ uint32_t pack_bf16(float lo, float hi) {
    uint32_t r;
    asm("cvt.rn.bf16x2.f32 %0, %1, %2;" : "=r"(r) : "f"(hi), "f"(lo));
    return r;
}
__device__ __forceinline__ float bf_lo(uint32_t w) { return __uint_as_float(w << 16); }
__device__ __forceinline__ float bf_hi(uint32_t w) { return __uint_as_float(w & 0xFFFF0000u); }
__device__ __forceinline__ float ex2(float x) {
    float r;
    asm("ex2.approx.ftz.f32 %0, %1;" : "=f"(r) : "f"(x));
    return r;
}
__device__ __forceinline__ float tanh_fast(float x) {
    float r;
    asm("tanh.approx.f32 %0, %1;" : "=f"(r) : "f"(x));
    return r;
}
__device__ __forceinline__ uint32_t hfma2_bf16(uint32_t a, uint32_t b, uint32_t c) {
    uint32_t r;
    asm("fma.rn.bf16x2 %0, %1, %2, %3;" : "=r"(r) : "r"(a), "r"(b), "r"(c));
    return r;
}
__device__ __forceinline__ uint32_t hadd2_bf16(uint32_t a, uint32_t b) {
    uint32_t r;
    asm("add.rn.bf16x2 %0, %1, %2;" : "=r"(r) : "r"(a), "r"(b));
    return r;
}
__device__ __forceinline__ void ldsm4(uint32_t (&a)[4], uint32_t addr) {
    asm volatile("ldmatrix.sync.aligned.m8n8.x4.shared.b16 {%0, %1, %2, %3}, [%4];" : "=r"(a[0]), "=r"(a[1]), "=r"(a[2]), "=r"(a[3]) : "r"(addr) : "memory");
}
__device__ __forceinline__ void stsm4(uint32_t addr, const uint32_t (&a)[4]) {
    asm volatile("stmatrix.sync.aligned.m8n8.x4.shared.b16 [%0], {%1, %2, %3, %4};" ::"r"(addr), "r"(a[0]), "r"(a[1]), "r"(a[2]), "r"(a[3]) : "memory");
}
__device__ __forceinline__ void mma16816(float (&c)[4], const uint32_t (&a)[4], uint32_t b0, uint32_t b1) {
    asm("mma.sync.aligned.m16n8k16.row.col.f32.bf16.bf16.f32 {%0, %1, %2, %3}, {%4, %5, %6, %7}, {%8, %9}, {%0, %1, %2, %3};"
        : "+f"(c[0]), "+f"(c[1]), "+f"(c[2]), "+f"(c[3]) : "r"(a[0]), "r"(a[1]), "r"(a[2]), "r"(a[3]), "r"(b0), "r"(b1));
}
__device__ __forceinline__ float gelu2(float u) {
    const float w = fmaf(u * u, 0.0356774081f, 0.7978845608f);
    return fmaf(u, tanh_fast(u * w), u);
}

template<int TB, int AOFF, int BOFF> __device__ __forceinline__ void wgmma_ss_n216(float (&d)[108], uint64_t da, uint64_t db, int sd) {
    asm volatile("{\n.reg .pred p;\n.reg .b64 ta, tb;\nsetp.ne.b32 p, %110, 0;\nadd.s64 ta, %108, %112;\nadd.s64 tb, %109, %113;\n"
      "wgmma.mma_async.sync.aligned.m64n216k16.f32.bf16.bf16 {%0, %1, %2, %3, %4, %5, %6, %7, %8, %9, %10, %11, %12, %13, %14, %15, %16, %17, %18, %19, %20, %21, %22, %23, %24, %25, %26, %27, %28, %29, %30, %31, %32, %33, %34, %35, %36, %37, %38, %39, %40, %41, %42, %43, %44, %45, %46, %47, %48, %49, %50, %51, %52, %53, %54, %55, %56, %57, %58, %59, %60, %61, %62, %63, %64, %65, %66, %67, %68, %69, %70, %71, %72, %73, %74, %75, %76, %77, %78, %79, %80, %81, %82, %83, %84, %85, %86, %87, %88, %89, %90, %91, %92, %93, %94, %95, %96, %97, %98, %99, %100, %101, %102, %103, %104, %105, %106, %107}, ta, tb, p, 1, 1, 0, %111;\n}\n"
      : "+f"(d[0]), "+f"(d[1]), "+f"(d[2]), "+f"(d[3]), "+f"(d[4]), "+f"(d[5]), "+f"(d[6]), "+f"(d[7]), "+f"(d[8]), "+f"(d[9]), "+f"(d[10]), "+f"(d[11]), "+f"(d[12]), "+f"(d[13]), "+f"(d[14]), "+f"(d[15]), "+f"(d[16]), "+f"(d[17]), "+f"(d[18]), "+f"(d[19]), "+f"(d[20]), "+f"(d[21]), "+f"(d[22]), "+f"(d[23]), "+f"(d[24]), "+f"(d[25]), "+f"(d[26]), "+f"(d[27]), "+f"(d[28]), "+f"(d[29]), "+f"(d[30]), "+f"(d[31]), "+f"(d[32]), "+f"(d[33]), "+f"(d[34]), "+f"(d[35]), "+f"(d[36]), "+f"(d[37]), "+f"(d[38]), "+f"(d[39]), "+f"(d[40]), "+f"(d[41]), "+f"(d[42]), "+f"(d[43]), "+f"(d[44]), "+f"(d[45]), "+f"(d[46]), "+f"(d[47]), "+f"(d[48]), "+f"(d[49]), "+f"(d[50]), "+f"(d[51]), "+f"(d[52]), "+f"(d[53]), "+f"(d[54]), "+f"(d[55]), "+f"(d[56]), "+f"(d[57]), "+f"(d[58]), "+f"(d[59]), "+f"(d[60]), "+f"(d[61]), "+f"(d[62]), "+f"(d[63]), "+f"(d[64]), "+f"(d[65]), "+f"(d[66]), "+f"(d[67]), "+f"(d[68]), "+f"(d[69]), "+f"(d[70]), "+f"(d[71]), "+f"(d[72]), "+f"(d[73]), "+f"(d[74]), "+f"(d[75]), "+f"(d[76]), "+f"(d[77]), "+f"(d[78]), "+f"(d[79]), "+f"(d[80]), "+f"(d[81]), "+f"(d[82]), "+f"(d[83]), "+f"(d[84]), "+f"(d[85]), "+f"(d[86]), "+f"(d[87]), "+f"(d[88]), "+f"(d[89]), "+f"(d[90]), "+f"(d[91]), "+f"(d[92]), "+f"(d[93]), "+f"(d[94]), "+f"(d[95]), "+f"(d[96]), "+f"(d[97]), "+f"(d[98]), "+f"(d[99]), "+f"(d[100]), "+f"(d[101]), "+f"(d[102]), "+f"(d[103]), "+f"(d[104]), "+f"(d[105]), "+f"(d[106]), "+f"(d[107])
      : "l"(da), "l"(db), "r"(sd), "n"(TB), "n"(AOFF), "n"(BOFF));
}

template<int TB, int AOFF, int BOFF> __device__ __forceinline__ void wgmma_ss_n128(float (&d)[64], uint64_t da, uint64_t db, int sd) {
    asm volatile("{\n.reg .pred p;\n.reg .b64 ta, tb;\nsetp.ne.b32 p, %66, 0;\nadd.s64 ta, %64, %68;\nadd.s64 tb, %65, %69;\n"
      "wgmma.mma_async.sync.aligned.m64n128k16.f32.bf16.bf16 {%0, %1, %2, %3, %4, %5, %6, %7, %8, %9, %10, %11, %12, %13, %14, %15, %16, %17, %18, %19, %20, %21, %22, %23, %24, %25, %26, %27, %28, %29, %30, %31, %32, %33, %34, %35, %36, %37, %38, %39, %40, %41, %42, %43, %44, %45, %46, %47, %48, %49, %50, %51, %52, %53, %54, %55, %56, %57, %58, %59, %60, %61, %62, %63}, ta, tb, p, 1, 1, 0, %67;\n}\n"
      : "+f"(d[0]), "+f"(d[1]), "+f"(d[2]), "+f"(d[3]), "+f"(d[4]), "+f"(d[5]), "+f"(d[6]), "+f"(d[7]), "+f"(d[8]), "+f"(d[9]), "+f"(d[10]), "+f"(d[11]), "+f"(d[12]), "+f"(d[13]), "+f"(d[14]), "+f"(d[15]), "+f"(d[16]), "+f"(d[17]), "+f"(d[18]), "+f"(d[19]), "+f"(d[20]), "+f"(d[21]), "+f"(d[22]), "+f"(d[23]), "+f"(d[24]), "+f"(d[25]), "+f"(d[26]), "+f"(d[27]), "+f"(d[28]), "+f"(d[29]), "+f"(d[30]), "+f"(d[31]), "+f"(d[32]), "+f"(d[33]), "+f"(d[34]), "+f"(d[35]), "+f"(d[36]), "+f"(d[37]), "+f"(d[38]), "+f"(d[39]), "+f"(d[40]), "+f"(d[41]), "+f"(d[42]), "+f"(d[43]), "+f"(d[44]), "+f"(d[45]), "+f"(d[46]), "+f"(d[47]), "+f"(d[48]), "+f"(d[49]), "+f"(d[50]), "+f"(d[51]), "+f"(d[52]), "+f"(d[53]), "+f"(d[54]), "+f"(d[55]), "+f"(d[56]), "+f"(d[57]), "+f"(d[58]), "+f"(d[59]), "+f"(d[60]), "+f"(d[61]), "+f"(d[62]), "+f"(d[63])
      : "l"(da), "l"(db), "r"(sd), "n"(TB), "n"(AOFF), "n"(BOFF));
}

template<int TB, int AOFF, int BOFF> __device__ __forceinline__ void wgmma_ss_n72(float (&d)[36], uint64_t da, uint64_t db, int sd) {
    asm volatile("{\n.reg .pred p;\n.reg .b64 ta, tb;\nsetp.ne.b32 p, %38, 0;\nadd.s64 ta, %36, %40;\nadd.s64 tb, %37, %41;\n"
      "wgmma.mma_async.sync.aligned.m64n72k16.f32.bf16.bf16 {%0, %1, %2, %3, %4, %5, %6, %7, %8, %9, %10, %11, %12, %13, %14, %15, %16, %17, %18, %19, %20, %21, %22, %23, %24, %25, %26, %27, %28, %29, %30, %31, %32, %33, %34, %35}, ta, tb, p, 1, 1, 0, %39;\n}\n"
      : "+f"(d[0]), "+f"(d[1]), "+f"(d[2]), "+f"(d[3]), "+f"(d[4]), "+f"(d[5]), "+f"(d[6]), "+f"(d[7]), "+f"(d[8]), "+f"(d[9]), "+f"(d[10]), "+f"(d[11]), "+f"(d[12]), "+f"(d[13]), "+f"(d[14]), "+f"(d[15]), "+f"(d[16]), "+f"(d[17]), "+f"(d[18]), "+f"(d[19]), "+f"(d[20]), "+f"(d[21]), "+f"(d[22]), "+f"(d[23]), "+f"(d[24]), "+f"(d[25]), "+f"(d[26]), "+f"(d[27]), "+f"(d[28]), "+f"(d[29]), "+f"(d[30]), "+f"(d[31]), "+f"(d[32]), "+f"(d[33]), "+f"(d[34]), "+f"(d[35])
      : "l"(da), "l"(db), "r"(sd), "n"(TB), "n"(AOFF), "n"(BOFF));
}

template<int TB, int BOFF> __device__ __forceinline__ void wgmma_rs_n24(float (&d)[12], uint32_t a0, uint32_t a1, uint32_t a2, uint32_t a3, uint64_t db, int sd) {
    asm volatile("{\n.reg .pred p;\n.reg .b64 tb;\nsetp.ne.b32 p, %17, 0;\nadd.s64 tb, %16, %19;\n"
      "wgmma.mma_async.sync.aligned.m64n24k16.f32.bf16.bf16 {%0, %1, %2, %3, %4, %5, %6, %7, %8, %9, %10, %11}, {%12, %13, %14, %15}, tb, p, 1, 1, %18;\n}\n"
      : "+f"(d[0]), "+f"(d[1]), "+f"(d[2]), "+f"(d[3]), "+f"(d[4]), "+f"(d[5]), "+f"(d[6]), "+f"(d[7]), "+f"(d[8]), "+f"(d[9]), "+f"(d[10]), "+f"(d[11])
      : "r"(a0), "r"(a1), "r"(a2), "r"(a3), "l"(db), "r"(sd), "n"(TB), "n"(BOFF));
}

template<int TB, int BOFF> __device__ __forceinline__ void wgmma_rs_n72(float (&d)[36], uint32_t a0, uint32_t a1, uint32_t a2, uint32_t a3, uint64_t db, int sd) {
    asm volatile("{\n.reg .pred p;\n.reg .b64 tb;\nsetp.ne.b32 p, %41, 0;\nadd.s64 tb, %40, %43;\n"
      "wgmma.mma_async.sync.aligned.m64n72k16.f32.bf16.bf16 {%0, %1, %2, %3, %4, %5, %6, %7, %8, %9, %10, %11, %12, %13, %14, %15, %16, %17, %18, %19, %20, %21, %22, %23, %24, %25, %26, %27, %28, %29, %30, %31, %32, %33, %34, %35}, {%36, %37, %38, %39}, tb, p, 1, 1, %42;\n}\n"
      : "+f"(d[0]), "+f"(d[1]), "+f"(d[2]), "+f"(d[3]), "+f"(d[4]), "+f"(d[5]), "+f"(d[6]), "+f"(d[7]), "+f"(d[8]), "+f"(d[9]), "+f"(d[10]), "+f"(d[11]), "+f"(d[12]), "+f"(d[13]), "+f"(d[14]), "+f"(d[15]), "+f"(d[16]), "+f"(d[17]), "+f"(d[18]), "+f"(d[19]), "+f"(d[20]), "+f"(d[21]), "+f"(d[22]), "+f"(d[23]), "+f"(d[24]), "+f"(d[25]), "+f"(d[26]), "+f"(d[27]), "+f"(d[28]), "+f"(d[29]), "+f"(d[30]), "+f"(d[31]), "+f"(d[32]), "+f"(d[33]), "+f"(d[34]), "+f"(d[35])
      : "r"(a0), "r"(a1), "r"(a2), "r"(a3), "l"(db), "r"(sd), "n"(TB), "n"(BOFF));
}

template<int TB, int AINC, int BINC> __device__ __forceinline__ void wgmma_ss_n64_pi(float (&d)[32], uint64_t& da, uint64_t& db, int sd) {
    asm volatile("{\n.reg .pred p;\nsetp.ne.b32 p, %34, 0;\n"
      "wgmma.mma_async.sync.aligned.m64n64k16.f32.bf16.bf16 {%0, %1, %2, %3, %4, %5, %6, %7, %8, %9, %10, %11, %12, %13, %14, %15, %16, %17, %18, %19, %20, %21, %22, %23, %24, %25, %26, %27, %28, %29, %30, %31}, %32, %33, p, 1, 1, 0, %35;\n"
      "add.s64 %32, %32, %36;\nadd.s64 %33, %33, %37;\n}\n"
      : "+f"(d[0]), "+f"(d[1]), "+f"(d[2]), "+f"(d[3]), "+f"(d[4]), "+f"(d[5]), "+f"(d[6]), "+f"(d[7]), "+f"(d[8]), "+f"(d[9]), "+f"(d[10]), "+f"(d[11]), "+f"(d[12]), "+f"(d[13]), "+f"(d[14]), "+f"(d[15]), "+f"(d[16]), "+f"(d[17]), "+f"(d[18]), "+f"(d[19]), "+f"(d[20]), "+f"(d[21]), "+f"(d[22]), "+f"(d[23]), "+f"(d[24]), "+f"(d[25]), "+f"(d[26]), "+f"(d[27]), "+f"(d[28]), "+f"(d[29]), "+f"(d[30]), "+f"(d[31]), "+l"(da), "+l"(db)
      : "r"(sd), "n"(TB), "n"(AINC), "n"(BINC));
}

template<int TB, int BINC> __device__ __forceinline__ void wgmma_rs_n64_pi(float (&d)[32], uint32_t a0, uint32_t a1, uint32_t a2, uint32_t a3, uint64_t& db, int sd) {
    asm volatile("{\n.reg .pred p;\nsetp.ne.b32 p, %37, 0;\n"
      "wgmma.mma_async.sync.aligned.m64n64k16.f32.bf16.bf16 {%0, %1, %2, %3, %4, %5, %6, %7, %8, %9, %10, %11, %12, %13, %14, %15, %16, %17, %18, %19, %20, %21, %22, %23, %24, %25, %26, %27, %28, %29, %30, %31}, {%33, %34, %35, %36}, %32, p, 1, 1, %38;\n"
      "add.s64 %32, %32, %39;\n}\n"
      : "+f"(d[0]), "+f"(d[1]), "+f"(d[2]), "+f"(d[3]), "+f"(d[4]), "+f"(d[5]), "+f"(d[6]), "+f"(d[7]), "+f"(d[8]), "+f"(d[9]), "+f"(d[10]), "+f"(d[11]), "+f"(d[12]), "+f"(d[13]), "+f"(d[14]), "+f"(d[15]), "+f"(d[16]), "+f"(d[17]), "+f"(d[18]), "+f"(d[19]), "+f"(d[20]), "+f"(d[21]), "+f"(d[22]), "+f"(d[23]), "+f"(d[24]), "+f"(d[25]), "+f"(d[26]), "+f"(d[27]), "+f"(d[28]), "+f"(d[29]), "+f"(d[30]), "+f"(d[31]), "+l"(db)
      : "r"(a0), "r"(a1), "r"(a2), "r"(a3), "r"(sd), "n"(TB), "n"(BINC));
}

constexpr int K1_XN_BYTES = 16 * 9216;
constexpr int K1_OFF_RING = K1_XN_BYTES;
constexpr int K1_OFF_BIAS = K1_OFF_RING + 10 * 8192;
constexpr int K1_OFF_BAR = K1_OFF_BIAS + 576 * 2;
constexpr int K1_SMEM = K1_OFF_BAR + 800;
constexpr float QSCALE = 0.23570226039551584f * 1.4426950408889634f;

struct K1Ctx {
    uint32_t full0;
    uint32_t rel_addr;
    uint64_t descA, descB;
    uint32_t phase;
    __device__ __forceinline__ void begin_stage(int s) {
        mbar_wait(full0 + s * 8, phase);
        wg_fence();
    }
    __device__ __forceinline__ void release(int s) {
        if (rel_addr) asm volatile("mbarrier.arrive.shared::cluster.b64 _, [%0];" ::"r"(rel_addr + s * 8) : "memory");
    }
    __device__ __forceinline__ void end_stage(int s) {
        wg_commit();
        wg_wait<1>();
        release(s == 0 ? 8 : s - 1);
    }
};

__host__ __device__ constexpr int a_off(int ks) { return ((ks / 12) * 49152 + ((ks >> 2) % 3) * 1024 + (ks & 3) * 32) >> 4; }

template <int V> struct IC { static constexpr int value = V; };
template <int I, int N, class F> __device__ __forceinline__ void static_for(F&& f) {
    if constexpr (I < N) { f(IC<I>{}); static_for<I + 1, N>(f); }
}

template <bool A_RS, bool B_RS, class Epi>
__device__ __forceinline__ void tile_pair(K1Ctx& c, float (&accA)[32], float (&accB)[32], uint32_t (&h)[144], Epi&& epi) {
    static_for<0, 9>([&](auto sc) {
        constexpr int s = decltype(sc)::value;
        c.begin_stage(s);
        static_for<0, 8>([&](auto tc) {
            constexpr int t = decltype(tc)::value, kk = s * 8 + t, ks = kk % 36;
            constexpr int db = ks == 35 ? -35 * 128 : 128, da = a_off((ks + 1) % 36) - a_off(ks);
            if constexpr (kk < 36) {
                if constexpr (A_RS) wgmma_rs_n64_pi<1, db>(accA, h[ks * 4], h[ks * 4 + 1], h[ks * 4 + 2], h[ks * 4 + 3], c.descB, ks != 0);
                else wgmma_ss_n64_pi<1, da, db>(accA, c.descA, c.descB, ks != 0);
            } else {
                if constexpr (B_RS) wgmma_rs_n64_pi<1, db>(accB, h[ks * 4], h[ks * 4 + 1], h[ks * 4 + 2], h[ks * 4 + 3], c.descB, ks != 0);
                else wgmma_ss_n64_pi<1, da, db>(accB, c.descA, c.descB, ks != 0);
            }
            if constexpr (t == 0) {
                c.end_stage(s);
                epi(sc);
                wg_fence();
            }
        });
        wg_commit();
    });
    c.phase ^= 1;
}

template <int B0, int NB, int HOFF>
__device__ __forceinline__ void gelu_blocks(const float (&acc)[32], uint32_t (&h)[144], const uint32_t (&bq)[8], float rs0, float rs1) {
#pragma unroll
    for (int b = B0; b < B0 + NB; b++) {
        const float b0 = bf_lo(bq[b]), b1 = bf_hi(bq[b]);
        h[HOFF + b * 2 + 0] = pack_bf16(gelu2(fmaf(acc[b * 4 + 0], rs0, b0)), gelu2(fmaf(acc[b * 4 + 1], rs0, b1)));
        h[HOFF + b * 2 + 1] = pack_bf16(gelu2(fmaf(acc[b * 4 + 2], rs1, b0)), gelu2(fmaf(acc[b * 4 + 3], rs1, b1)));
    }
#pragma unroll
    for (int i = HOFF + B0 * 2; i < HOFF + (B0 + NB) * 2; i++) asm volatile("" : "+r"(h[i]));
}
__device__ __forceinline__ void load_bias(uint32_t (&bq)[8], uint32_t addr) {
    asm volatile("ld.shared.v4.u32 {%0, %1, %2, %3}, [%4];" : "=r"(bq[0]), "=r"(bq[1]), "=r"(bq[2]), "=r"(bq[3]) : "r"(addr));
    asm volatile("ld.shared.v4.u32 {%0, %1, %2, %3}, [%4 + 16];" : "=r"(bq[4]), "=r"(bq[5]), "=r"(bq[6]), "=r"(bq[7]) : "r"(addr));
}
template <int S> __device__ __forceinline__ void store_part(const float (&o)[32], uint4* p) {
    uint4 v;
    v.x = pack_bf16(o[S * 8 + 0], o[S * 8 + 1]); v.y = pack_bf16(o[S * 8 + 2], o[S * 8 + 3]);
    v.z = pack_bf16(o[S * 8 + 4], o[S * 8 + 5]); v.w = pack_bf16(o[S * 8 + 6], o[S * 8 + 7]);
    p[S * 256] = v;
}

constexpr int NCHUNK = 16;
constexpr int CHUNK_BYTES = KV_HEAD_BYTES / NCHUNK;
constexpr int SM_Q = 0;
constexpr int SM_KV = 32768;
constexpr int PIECE = 19968;
__host__ __device__ constexpr int sm_piece(int p) { return p == 0 ? 209408 : (p == 1 ? 0 : SM_KV + (p - 2) * PIECE); }
__host__ __device__ constexpr int sm_wstep(int k) { return k < 27 ? sm_piece(k / 3) + (k % 3) * 4608 : (k < 35 ? SM_KV + 7 * PIECE + (k - 27) * 4608 : PIECE); }
__host__ __device__ constexpr int sm_ostep(int k) { return sm_piece(k / 3) + 13824 + (k % 3) * 2048; }
constexpr int SM_RED = SM_KV + KV_HEAD_BYTES;

__device__ __forceinline__ float exp2_fixed(float y) {
    const float u = __uint_as_float(__float_as_uint(y) & 0xFF807FFFu) - 512.02545f;
    float t = fmaf(u, 0.019497588f, 0.114550486f);
    t = fmaf(t, u, -0.29839927f);
    return fmaf(t, u, y);
}
__device__ __forceinline__ uint32_t pack_fixed(float lo, float hi) { return __byte_perm(__float_as_uint(lo), __float_as_uint(hi), 0x6521); }

#define PV_GROUP 4
#define POLY_MODE 1
__device__ __forceinline__ uint32_t exp2_packed(float y0, float y1, uint32_t one2) {
    const uint32_t w = pack_fixed(y0, y1);
    uint32_t m;
    asm("lop3.b32 %0, %1, 0x007F007F, %2, 0xEA;" : "=r"(m) : "r"(w), "r"(one2));
    const uint32_t d = hfma2_bf16(m, 0x3EF93EF9u, 0xBF38BF38u);
    const uint32_t e = hfma2_bf16(d, d, 0xBD71BD71u);
    return hfma2_bf16(w, e, w);
}
constexpr int KV_TILE = CHUNK_BYTES / 16;
template <int OFF> __device__ __forceinline__ void issue_qk(float (&s)[64], uint64_t qd, uint64_t kd) {
    wgmma_ss_n128<0, 0, OFF + (8 << 16)>(s, qd, kd, 0);
    wgmma_ss_n128<0, 16, OFF + 32>(s, qd, kd, 1);
}
template <int OFF> __device__ __forceinline__ void issue_pv(float (&o)[12], const uint32_t (&p)[32], uint64_t vd) {
    static_for<0, 8>([&](auto kc) {
        constexpr int k = decltype(kc)::value;
        wgmma_rs_n24<1, OFF + k * (2 * KV_GROUP_BYTES / 16)>(o, p[k * 4], p[k * 4 + 1], p[k * 4 + 2], p[k * 4 + 3], vd, 1);
    });
}
template <int OFF>
__device__ __forceinline__ void softmax_pv(const float (&s)[64], uint32_t (&p)[32], float (&o)[12], uint64_t vd, uint32_t one2) {
    static_for<0, 8 / PV_GROUP>([&](auto gc) {
        constexpr int g0 = decltype(gc)::value * PV_GROUP;
#pragma unroll
        for (int b = g0 * 2; b < (g0 + PV_GROUP) * 2; b++) {
            if ((POLY_MASK >> b) & 1) {
                p[b * 2 + 0] = exp2_packed(s[b * 4 + 0], s[b * 4 + 1], one2);
                p[b * 2 + 1] = exp2_packed(s[b * 4 + 2], s[b * 4 + 3], one2);
            } else {
                p[b * 2 + 0] = pack_bf16(ex2(s[b * 4 + 0]), ex2(s[b * 4 + 1]));
                p[b * 2 + 1] = pack_bf16(ex2(s[b * 4 + 2]), ex2(s[b * 4 + 3]));
            }
        }
#pragma unroll
        for (int i = g0 * 4; i < (g0 + PV_GROUP) * 4; i++) asm volatile("" : "+r"(p[i])::"memory");
        wg_fence();
        static_for<g0, g0 + PV_GROUP>([&](auto kc) {
            constexpr int k = decltype(kc)::value;
            wgmma_rs_n24<1, OFF + k * (2 * KV_GROUP_BYTES / 16)>(o, p[k * 4], p[k * 4 + 1], p[k * 4 + 2], p[k * 4 + 3], vd, 1);
        });
    });
    wg_commit();
}
__device__ __forceinline__ int head_pair(int hh, int i) {
    if (i == 8) return hh == 3 ? 0 : 8;
    const int q = i >> 1, t = (4 - hh) & 3;
    if ((i & 1) == 0) return t + q;
    return (hh == 1 || hh == 2) ? (q >= hh ? q - hh : t + 4 + q) : t + 4 + q;
}
template <bool LATE> __device__ __forceinline__ void store_o(float (&o)[12], int rt, int head, int wq, int lane) {
    const int g = lane >> 2, q = lane & 3;
    const float i0 = __fdividef(1.0f, __shfl_sync(~0u, o[8], lane | 3)), i1 = __fdividef(1.0f, __shfl_sync(~0u, o[10], lane | 3));
#pragma unroll
    for (int i = 0; i < 3; i++) {
        const uint32_t w0 = pack_bf16(o[i * 4] * i0, o[i * 4 + 1] * i0), w1 = pack_bf16(o[i * 4 + 2] * i1, o[i * 4 + 3] * i1);
        if (i < 2 || q == 2) {
            if constexpr (LATE) {
                const int pc = (head & 7) * 9 + head_pair(head & 3, i < 2 ? i * 4 + q : 8);
                uint32_t* op = reinterpret_cast<uint32_t*>(g_Olate) + (((rt * 9 + (pc >> 3)) * 128 + wq * 32 + g * 4 + (pc & 3)) * 4 + ((pc >> 2) & 1) * 2);
                asm volatile("st.relaxed.gpu.global.v2.u32 [%0], {%1, %2};" ::"l"(op), "r"(w0), "r"(w1) : "memory");
            } else {
                const int pc = head * 9 + head_pair(head & 3, i < 2 ? i * 4 + q : 8);
                uint32_t* op = g_O + ((rt * 72 + (pc >> 2)) * 8 + wq * 2) * 32 + g * 4 + (pc & 3);
                op[0] = w0;
                op[32] = w1;
            }
        }
    }
#pragma unroll
    for (int i = 0; i < 12; i++) o[i] = 0.f;
}
__device__ __forceinline__ void mbar_arrive(uint32_t b) { asm volatile("mbarrier.arrive.shared::cta.b64 _, [%0];" ::"r"(b) : "memory"); }
__device__ __forceinline__ void mbar_wait_sleep(uint32_t b, uint32_t ns) {
    uint32_t ok, spins = 0;
    while (true) {
        asm volatile("{\n.reg .pred p;\nmbarrier.try_wait.parity.shared::cta.b64 p, [%1], 0;\nselp.u32 %0, 1, 0, p;\n}\n" : "=r"(ok) : "r"(b) : "memory");
        if (ok) break;
        __nanosleep(ns);
        if (++spins > (1u << 21)) __trap();
    }
}
__device__ __forceinline__ void flag_signal(unsigned int* f) {
    __threadfence();
    atomicAdd(f, 1u);
}
__device__ __forceinline__ void flag_wait(const unsigned int* f, unsigned int target, unsigned int sleep_ns) {
    uint32_t v, spins = 0;
    while (true) {
        asm volatile("ld.acquire.gpu.global.u32 %0, [%1];" : "=r"(v) : "l"(f) : "memory");
        if (v >= target) break;
        if (sleep_ns) __nanosleep(sleep_ns);
        if (++spins > (1u << 21)) __trap();
    }
}
__device__ __forceinline__ uint4 hadd8_bf16(const uint4 a, const uint4 b) {
    return make_uint4(hadd2_bf16(a.x, b.x), hadd2_bf16(a.y, b.y), hadd2_bf16(a.z, b.z), hadd2_bf16(a.w, b.w));
}
__device__ __forceinline__ float sumsq2(uint32_t w) { return fmaf(bf_lo(w), bf_lo(w), bf_hi(w) * bf_hi(w)); }
__device__ __forceinline__ float sumsq8(const uint4 v) { return (sumsq2(v.x) + sumsq2(v.y)) + (sumsq2(v.z) + sumsq2(v.w)); }

enum { B_FULL = 0, B_EMPTY = 9, B_BASE = 18, B_XNDEAD = 19, B_QRDY = 20, B_FFN = 21, B_KV = 22, B_FREE = 38, B_WO = 46, B_RED = 55, B_X = 61, B_EARLY = 85, B_OS = 86, B_LATE = 94, B_BIAS = 95, B_END = 96 };

__global__ void __cluster_dims__(2, 1, 1) __launch_bounds__(384, 1)
fused_kernel(const __grid_constant__ CUtensorMap tmX, const __grid_constant__ CUtensorMap tmQ3, const __grid_constant__ CUtensorMap tmQ1,
          const __grid_constant__ CUtensorMap tm1, const __grid_constant__ CUtensorMap tm2, const __grid_constant__ CUtensorMap tmP,
          const __grid_constant__ CUtensorMap tmOut, const __grid_constant__ CUtensorMap tmXo, const __nv_bfloat16* __restrict__ b1,
          const __nv_bfloat16* __restrict__ wqkv, const __nv_bfloat16* __restrict__ w1, const __nv_bfloat16* __restrict__ w2,
          const __nv_bfloat16* __restrict__ wo, const __nv_bfloat16* __restrict__ b2,
          const uint64_t zero) {
    extern __shared__ __align__(1024) uint8_t smem[];
    const uint32_t sb = s2u(smem);
    const int tid = threadIdx.x, lane = tid & 31;
    const int warp = __shfl_sync(~0u, tid >> 5, 0);
    const uint32_t rank = blockIdx.x & 1;
    const int cl = blockIdx.x >> 1;
    const int rb = (cl & 7) * 2 + rank;
    const int j = cl >> 3;
    const uint32_t bar0 = sb + K1_OFF_BAR;
    const uint32_t full0 = bar0 + B_FULL * 8, empty0 = bar0 + B_EMPTY * 8, xbar0 = bar0 + B_X * 8;
    const int head = blockIdx.x >> 2, quarter = blockIdx.x & 3;
    const int rt = quarter * 8 + (head >> 2), ct = head & 3;
    const int rot = head >> 3;
    const int ks0 = ((((head >> 3) + 2) & 3) * 9);
    volatile uint32_t* slow_flag = reinterpret_cast<volatile uint32_t*>(smem + K1_OFF_BAR + B_END * 8);

    if (warp < 8) {
        PROF(0);
        PROFT(48);
        if (lane == 0) {
#pragma unroll
            for (int i = 0; i < 3; i++) mbar_init(xbar0 + (warp * 3 + i) * 8, 1);
            fence_barrier_init();
#pragma unroll 1
            for (int i = 0; i < 3; i++) {
                const uint32_t xb = xbar0 + (warp * 3 + i) * 8;
                mbar_expect(xb, 6144);
                tma4d(sb + i * 49152 + warp * 6144, &tmX, 0, 0, i * 3, rb * 16 + warp * 2, xb);
            }
        }
        __syncwarp();
        cluster_arrive();
        PROF(22);
        reg_alloc<240>();
        PROF(23);
        float rs0, rs1;
        {
            const uint32_t la = sb + (warp * 2 + ((lane >> 3) & 1)) * 3072 + (lane & 7) * 128;
            uint32_t off[4];
#pragma unroll
            for (int i = 0; i < 4; i++) off[i] = la + (((i * 2 + (lane >> 4)) ^ (lane & 7)) << 4);
            float c1[4] = {0.f, 0.f, 0.f, 0.f}, c2[4] = {0.f, 0.f, 0.f, 0.f}, c3[4] = {0.f, 0.f, 0.f, 0.f};
            uint32_t a[36][4];
#pragma unroll
            for (int t = 0; t < 3; t++) {
                mbar_wait(xbar0 + (warp * 3 + t) * 8, 0);
                PROF(24 + t);
#pragma unroll
                for (int i = 0; i < 12; i++) ldsm4(a[t * 12 + i], off[i & 3] + t * 49152 + (i >> 2) * 1024);
#pragma unroll
                for (int i = t * 12; i < t * 12 + 12; i++) {
                    mma16816(c3, a[i], 0x3F803F80u, 0x3F803F80u);
                    mma16816(c1, a[i], a[i][0], a[i][2]);
                    mma16816(c2, a[i], a[i][1], a[i][3]);
                }
            }
            PROF(27);
            const int gg = lane >> 2, src = (lane & ~3) | (gg >> 1);
            const float m0 = c3[0] * (1.0f / DM), m1 = c3[2] * (1.0f / DM);
            const uint32_t mc0 = pack_bf16(-m0, -m0), mc1 = pack_bf16(-m1, -m1);
#pragma unroll
            for (int i = 0; i < 36; i++) {
#pragma unroll
                for (int k = 0; k < 4; k++) a[i][k] = hadd2_bf16(a[i][k], (k & 1) ? mc1 : mc0);
                stsm4(off[i & 3] + (i / 12) * 49152 + ((i >> 2) % 3) * 1024, a[i]);
            }
            const float q0 = __shfl_sync(~0u, (gg & 1) ? c1[1] : c1[0], src), q1 = __shfl_sync(~0u, (gg & 1) ? c2[3] : c2[2], src);
            rs0 = rsqrtf(fmaxf(fmaf(-m0, m0, q0 * (1.0f / DM)), 0.f) + 1e-5f);
            rs1 = rsqrtf(fmaxf(fmaf(-m1, m1, q1 * (1.0f / DM)), 0.f) + 1e-5f);
            if (__any_sync(~0u, fabsf(m0) * rs0 > 0.25f || fabsf(m1) * rs1 > 0.25f)) {
                const float d0 = -m0 - bf_lo(mc0), d1 = -m1 - bf_lo(mc1);
                const uint32_t md0 = pack_bf16(d0, d0), md1 = pack_bf16(d1, d1);
#pragma unroll 1
                for (int i = 0; i < 9; i++) {
#pragma unroll
                    for (int k4 = 0; k4 < 4; k4++) {
                        const uint32_t ad = off[k4] + (i / 3) * 49152 + (i % 3) * 1024;
                        uint32_t b[4];
                        ldsm4(b, ad);
#pragma unroll
                        for (int k = 0; k < 4; k++) b[k] = hadd2_bf16(b[k], (k & 1) ? md1 : md0);
                        stsm4(ad, b);
                    }
                }
            }
        }
        PROF(28);
        const int wg = warp >> 2, wq = warp & 3;
        fence_proxy_async();
        named_bar_sync(1 + wg, 128);
        cluster_wait();
        PROF(1);

        const int g = lane >> 2, q = lane & 3;
        K1Ctx c;
        c.full0 = full0;
        c.rel_addr = 0;
        c.descA = mk_desc(zero, sb + wg * 8 * 3072, 16, 3072, 1);
        c.descB = mk_desc(zero, sb + K1_OFF_RING, 2048, 1024, 1);
        c.phase = 0;
        uint32_t biasq = sb + K1_OFF_BIAS + q * 32;
        uint32_t bq[8];

        uint32_t h[144];
        float accA[32], accB[32];
        {
            float accQ[108];
            uint32_t rel = 0;
            if (lane == 0 && wq < 2) asm("mapa.shared::cluster.u32 %0, %1, %2;" : "=r"(rel) : "r"(empty0), "r"(wq));
#pragma unroll 1
            for (int r = 0; r < 2; r++) {
                static_for<0, 9>([&](auto sc) {
                    constexpr int s = decltype(sc)::value;
                    c.begin_stage(s);
                    const uint64_t da = c.descA + (r ? a_off(18 + 2 * s) : a_off(2 * s));
                    wgmma_ss_n216<1, 0, ((2 * s) % 9) * 512>(accQ, da, c.descB, (r | s) != 0);
                    wgmma_ss_n216<1, 2, ((2 * s + 1) % 9) * 512>(accQ, da, c.descB, 1);
                    c.end_stage(s);
                    c.rel_addr = rel;
                });
                c.phase ^= 1;
            }
            PROF(2); PROFWT(54);
            mbar_wait(bar0 + B_BIAS * 8, 0);
            wg_wait<0>();
            reg_fence(accQ);
#pragma unroll
            for (int grp = 0; grp < 3; grp++) {
                const int G = 3 * j + grp, type = G >> 3;
                uint8_t* gb = g_QKV + ((G & 7) * 4 * KV_HEAD_BYTES + (rb * 16 + warp * 2) * KV_GROUP_BYTES + g * 16 + (type == 0 ? Q_OFFSET : (type == 2 ? 256 : 0)));
                uint8_t* gt = gb + q * KV_HEAD_BYTES + (type == 0 ? 256 : (type == 2 ? 264 : 512));
                gb += (q >> 1) * 128 + (q & 1) * 8;
#pragma unroll
                for (int hf = 0; hf < 2; hf++) {
                    const float sc = (hf ? rs1 : rs0) * (type == 0 ? QSCALE : ((type == 1 && ((POLY_MASK >> (warp * 2 + hf)) & 1)) ? 2.f : 1.f));
                    uint32_t w[9];
#pragma unroll
                    for (int i = 0; i < 9; i++) w[i] = pack_bf16(accQ[(grp * 9 + i) * 4 + hf * 2] * sc, accQ[(grp * 9 + i) * 4 + hf * 2 + 1] * sc);
                    uint8_t* p = gb + hf * KV_GROUP_BYTES;
                    *reinterpret_cast<uint2*>(p) = make_uint2(w[0], w[1]);
                    *reinterpret_cast<uint2*>(p + KV_HEAD_BYTES) = make_uint2(w[3], q >= 1 ? w[2] : w[4]);
                    *reinterpret_cast<uint2*>(p + 2 * KV_HEAD_BYTES) = make_uint2(w[5], q >= 2 ? w[4] : w[6]);
                    *reinterpret_cast<uint2*>(p + 3 * KV_HEAD_BYTES) = make_uint2(w[7], w[8]);
                    *reinterpret_cast<uint32_t*>(gt + hf * KV_GROUP_BYTES) = q == 0 ? w[2] : (q == 1 ? w[4] : w[6]);
                }
            }
            asm volatile("bar.arrive 3, 352;" ::: "memory");
        }
        PROF(3); PROFWT(55);
#pragma unroll
        for (int i = 32; i < 112; i++) asm volatile("mov.u32 %0, 0;" : "=r"(h[i]));
#pragma unroll
        for (int i = 0; i < 32; i++) asm volatile("mov.f32 %0, 0f00000000;" : "=f"(accB[i]));
#pragma unroll
        for (int i = 0; i < 8; i++) bq[i] = 0;
#pragma unroll 1
        for (int p = 0; p < 4; p++) {
            tile_pair<false, false>(c, accA, accB, h, [&](auto sc) {
                constexpr int s = decltype(sc)::value;
                if constexpr (s == 0) {
                    reg_fence(accB);
#pragma unroll
                    for (int i = 0; i < 80; i++) h[i] = h[i + 32];
                }
                if constexpr (s < 4) gelu_blocks<s * 2, 2, 80>(accB, h, bq, rs0, rs1);
                if constexpr (s == 4) load_bias(bq, biasq);
                if constexpr (s == 5) reg_fence(accA);
                if constexpr (s >= 5) gelu_blocks<(s - 5) * 2, 2, 96>(accA, h, bq, rs0, rs1);
                if constexpr (s == 8) load_bias(bq, biasq + 128);
            });
            biasq += 256;
        }
        PROF(4); PROFWT(56);
        tile_pair<false, true>(c, accA, accB, h, [&](auto sc) {
            constexpr int s = decltype(sc)::value;
            if constexpr (s == 0) reg_fence(accB);
            if constexpr (s < 4) gelu_blocks<s * 2, 2, 112>(accB, h, bq, rs0, rs1);
            if constexpr (s == 4) load_bias(bq, biasq);
            if constexpr (s == 5) { reg_fence(accA); if (tid == wg * 128) mbar_arrive(bar0 + B_XNDEAD * 8); }
            if constexpr (s == 5 || s == 6) gelu_blocks<(s - 5) * 3, 3, 128>(accA, h, bq, rs0, rs1);
            if constexpr (s == 7) gelu_blocks<6, 2, 128>(accA, h, bq, rs0, rs1);
            if constexpr (s == 3 || s == 7) reg_fence(h);
        });
        PROF(5); PROFWT(57);
        uint4* pout = g_part + j * SLAB + rb * 36 * 256 + tid;
#pragma unroll 1
        for (int p = 0; p < 4; p++) {
            tile_pair<true, true>(c, accA, accB, h, [&](auto sc) {
                constexpr int s = decltype(sc)::value;
                if constexpr (s == 0) reg_fence(accB);
                if constexpr (s < 4) store_part<s>(accB, pout);
                if constexpr (s == 5) reg_fence(accA);
                if constexpr (s >= 5) store_part<s - 5>(accA, pout + 1024);
            });
            pout += 2048;
            PROF(6 + p);
        }
        wg_wait<0>();
        c.release(8);
        reg_fence(accB);
        store_part<0>(accB, pout); store_part<1>(accB, pout); store_part<2>(accB, pout); store_part<3>(accB, pout);
        __syncwarp();
        if (lane == 0) mbar_arrive(bar0 + B_FFN * 8);
        PROF(10); PROFWT(58);
        PROFT(49);

        mbar_wait(bar0 + B_QRDY * 8, 0);
        const uint32_t slow = __any_sync(~0u, *slow_flag != 0);
        const uint64_t kd0 = mk_desc(zero, sb + SM_KV, 0, KV_GROUP_BYTES, 0);
        const uint64_t vd0 = mk_desc(zero, sb + SM_KV + 256, KV_GROUP_BYTES, 128, 0);
        const uint64_t qd0 = mk_desc(zero, sb + SM_Q + wg * 4096, 128, 512, 0);
        const uint32_t kvbar = bar0 + B_KV * 8;
        float o[12];
#pragma unroll
        for (int i = 0; i < 12; i++) o[i] = 0.f;
        PROF(16);
        PROFT(50);
        if (!slow) {
            const uint32_t one2 = 0x3F803F80u + (uint32_t)zero;
            float s0[64], s1[64];
            uint32_t p0[32], p1[32];
            mbar_wait(kvbar, 0);
            reg_fence(o);
            wg_fence();
            issue_qk<0>(s0, qd0, kd0);
            wg_commit();
            wg_commit();
            uint64_t qd = qd0;
            const uint32_t fre = (tid == wg * 128) ? bar0 + B_FREE * 8 - 8 : 0;
#pragma unroll 1
            for (int pass = 0; pass < 4; pass++) {
                uint64_t vd = vd0, kd = kd0;
                uint32_t bn = kvbar + 8;
#pragma unroll 1
                for (int it = 0; it < 8; it++) {
                    mbar_wait(bn, 0);
                    if (it == 0 && pass != 0) {
                        wg_wait<0>();
                        reg_fence(o);
                        store_o<false>(o, quarter * 8 + ((pass - 1 + rot) & 3) * 2 + wg, head, wq, lane);
                        reg_fence(o);
                        __syncwarp();
                        if (lane == 0) mbar_arrive(bar0 + (B_OS + pass * 2 - 2 + wg) * 8);
                    }
                    wg_wait<1>();
                    reg_fence(s0);
                    wg_fence();
                    issue_qk<KV_TILE>(s1, qd, kd);
                    wg_commit();
                    if (pass == 3 && it > 0 && fre) mbar_arrive(fre + it * 8);
                    softmax_pv<0>(s0, p0, o, vd, one2);
                    kd += 2 * KV_TILE; bn += 8;
                    if (it == 7) { kd = kd0; bn = kvbar; qd += 512; }
                    mbar_wait(bn, 0);
                    wg_wait<1>();
                    reg_fence(s1);
                    wg_fence();
                    issue_qk<0>(s0, qd, kd);
                    wg_commit();
                    softmax_pv<KV_TILE>(s1, p1, o, vd, one2);
                    vd += 2 * KV_TILE; bn += 8;
                }
                if (pass == 0) PROF(17);
            }
            wg_wait<0>();
            reg_fence(o);
            reg_fence(s0);
            reg_fence(s1);
            store_o<true>(o, quarter * 8 + ((3 + rot) & 3) * 2 + wg, head, wq, lane);
        } else {
#pragma unroll 1
            for (int pass = 0; pass < 4; pass++) {
                float m0 = -INFINITY, m1 = -INFINITY;
                float s[64];
                uint32_t p[32];
#pragma unroll 1
                for (int t = 0; t < 16; t++) {
                    mbar_wait(kvbar + t * 8, 0);
                    wg_fence();
                    issue_qk<0>(s, qd0 + pass * 512, kd0 + t * KV_TILE);
                    wg_commit();
                    wg_wait<0>();
                    reg_fence(s);
                    float a0 = m0, a1 = m1;
#pragma unroll
                    for (int k = 0; k < 16; k++) {
                        if ((POLY_MASK >> k) & 1) {
#pragma unroll
                            for (int i = 0; i < 4; i++) s[k * 4 + i] *= 0.5f;
                        }
                        a0 = fmaxf(a0, fmaxf(s[k * 4 + 0], s[k * 4 + 1]));
                        a1 = fmaxf(a1, fmaxf(s[k * 4 + 2], s[k * 4 + 3]));
                    }
                    a0 = fmaxf(a0, __shfl_xor_sync(~0u, a0, 1)); a1 = fmaxf(a1, __shfl_xor_sync(~0u, a1, 1));
                    a0 = fmaxf(a0, __shfl_xor_sync(~0u, a0, 2)); a1 = fmaxf(a1, __shfl_xor_sync(~0u, a1, 2));
                    const float r0 = ex2(m0 - a0), r1 = ex2(m1 - a1);
                    m0 = a0; m1 = a1;
#pragma unroll
                    for (int i = 0; i < 3; i++) { o[i * 4] *= r0; o[i * 4 + 1] *= r0; o[i * 4 + 2] *= r1; o[i * 4 + 3] *= r1; }
#pragma unroll
                    for (int k = 0; k < 16; k++) {
                        p[k * 2 + 0] = pack_bf16(ex2(s[k * 4 + 0] - m0), ex2(s[k * 4 + 1] - m0));
                        p[k * 2 + 1] = pack_bf16(ex2(s[k * 4 + 2] - m1), ex2(s[k * 4 + 3] - m1));
                    }
                    reg_fence(p);
                    reg_fence(o);
                    wg_fence();
                    issue_pv<0>(o, p, vd0 + t * KV_TILE);
                    wg_commit();
                    wg_wait<0>();
                    reg_fence(o);
                }
                if (pass < 3) {
                    store_o<false>(o, quarter * 8 + ((pass + rot) & 3) * 2 + wg, head, wq, lane);
                    __syncwarp();
                    if (lane == 0) mbar_arrive(bar0 + (B_OS + pass * 2 + wg) * 8);
                }
            }
            store_o<true>(o, quarter * 8 + ((3 + rot) & 3) * 2 + wg, head, wq, lane);
            if (tid == wg * 128)
                for (int i = 0; i < 7; i++) mbar_arrive(bar0 + (B_FREE + i) * 8);
        }
        PROF(18);
        PROFT(51);

        if (tid == wg * 128) mbar_arrive(bar0 + (B_FREE + 7) * 8);
        const int t128 = tid & 127;
        uint32_t bv[9];
        uint2 fv[9];
        mbar_wait(bar0 + B_BASE * 8, 0);
#pragma unroll
        for (int i = 0; i < 9; i++) {
            bv[i] = __ldg(reinterpret_cast<const uint32_t*>(b2 + ct * 144 + wg * 72 + q * 2) + i * 4);
            fv[i] = __ldcg(g_ffn + (blockIdx.x * 18 + wg * 9 + i) * 128 + t128);
        }
        float acc[36];
        const uint64_t od = mk_desc(zero, sb, 1024, 128, 0), wd = mk_desc(zero, sb + wg * 9 * 128, 2304, 128, 0);
        static_for<0, 9>([&](auto pc) {
            constexpr int p = decltype(pc)::value;
            mbar_wait(bar0 + (B_WO + p) * 8, 0);
            wg_fence();
            wgmma_ss_n72<1, sm_ostep(p * 3) / 16, sm_wstep(p * 3) / 16>(acc, od, wd, p != 0);
            wgmma_ss_n72<1, sm_ostep(p * 3 + 1) / 16, sm_wstep(p * 3 + 1) / 16>(acc, od, wd, 1);
            wgmma_ss_n72<1, sm_ostep(p * 3 + 2) / 16, sm_wstep(p * 3 + 2) / 16>(acc, od, wd, 1);
            wg_commit();
            if constexpr (p == 1) {
                wg_wait<1>();
                if (t128 == 0) mbar_arrive(bar0 + B_EARLY * 8);
            }
        });
        wg_wait<0>();
        reg_fence(acc);
        PROF(29);
        uint4 al[9];
        {
            const uint4* ap = g_Olate + rt * 9 * 128 + t128;
            uint32_t spins = 0;
            bool ok;
            do {
                ok = true;
#pragma unroll
                for (int k = 0; k < 9; k++)
                    asm volatile("ld.relaxed.gpu.global.v4.u32 {%0, %1, %2, %3}, [%4];" : "=r"(al[k].x), "=r"(al[k].y), "=r"(al[k].z), "=r"(al[k].w) : "l"(ap + k * 128) : "memory");
#pragma unroll
                for (int k = 0; k < 9; k++) ok = ok && al[k].x != O_EMPTY && al[k].y != O_EMPTY && al[k].z != O_EMPTY && al[k].w != O_EMPTY;
                if (++spins > (1u << 20)) __trap();
            } while (!__all_sync(~0u, ok));
        }
        PROF(19);
        mbar_wait(bar0 + B_LATE * 8, 0);
        PROF(20);
        wg_fence();
        static_for<27, 36>([&](auto kc) {
            constexpr int k = decltype(kc)::value;
            wgmma_rs_n72<1, sm_wstep(k) / 16>(acc, al[k - 27].x, al[k - 27].y, al[k - 27].z, al[k - 27].w, wd, 1);
        });
        wg_commit();
        PROF(31);
        uint32_t* st = reinterpret_cast<uint32_t*>(smem + sm_piece(0) + wg * 9216) + (wq * 16 + g) * 36 + q;
        float bs[36];
#pragma unroll
        for (int i = 0; i < 9; i++) {
            const uint32_t x0 = st[i * 4], x1 = st[i * 4 + 288];
            bs[i * 4 + 0] = fmaf(bf_lo(fv[i].x), 0.5f, bf_lo(x0) + bf_lo(bv[i]));
            bs[i * 4 + 1] = fmaf(bf_hi(fv[i].x), 0.5f, bf_hi(x0) + bf_hi(bv[i]));
            bs[i * 4 + 2] = fmaf(bf_lo(fv[i].y), 0.5f, bf_lo(x1) + bf_lo(bv[i]));
            bs[i * 4 + 3] = fmaf(bf_hi(fv[i].y), 0.5f, bf_hi(x1) + bf_hi(bv[i]));
        }
        reg_fence(bs);
        wg_wait<0>();
        reg_fence(acc);
        PROF(32);
#pragma unroll
        for (int i = 0; i < 9; i++) {
            st[i * 4] = pack_bf16(acc[i * 4] + bs[i * 4], acc[i * 4 + 1] + bs[i * 4 + 1]);
            st[i * 4 + 288] = pack_bf16(acc[i * 4 + 2] + bs[i * 4 + 2], acc[i * 4 + 3] + bs[i * 4 + 3]);
        }
        fence_proxy_async();
        named_bar_sync(1 + wg, 128);
        if (t128 == 0) {
            asm volatile("cp.async.bulk.tensor.2d.global.shared::cta.bulk_group [%0, {%2, %3}], [%1];"
                         ::"l"(&tmOut), "r"(sb + sm_piece(0) + wg * 9216), "r"(ct * 144 + wg * 72), "r"(rt * 64) : "memory");
            asm volatile("cp.async.bulk.commit_group;" ::: "memory");
            asm volatile("cp.async.bulk.wait_group.read 0;" ::: "memory");
        }
        PROF(21);
        PROFT(52);
    } else {
        reg_dealloc<24>();
        if (warp == 8 && lane == 0) {
            prefetch_tmap(&tmQ3); prefetch_tmap(&tmQ1); prefetch_tmap(&tm1); prefetch_tmap(&tm2);
            #pragma unroll 1
            for (int i = 0; i < 9; i++) { mbar_init(full0 + i * 8, 1); mbar_init(empty0 + i * 8, 4); mbar_init(bar0 + (B_WO + i) * 8, 2); }
            mbar_init(bar0 + B_BASE * 8, 3); mbar_init(bar0 + B_XNDEAD * 8, 2); mbar_init(bar0 + B_QRDY * 8, 3); mbar_init(bar0 + B_FFN * 8, 8); mbar_init(bar0 + B_EARLY * 8, 2); mbar_init(bar0 + B_LATE * 8, 2); mbar_init(bar0 + B_BIAS * 8, 96);
#pragma unroll 1
            for (int i = 0; i < 16; i++) { mbar_init(bar0 + (B_KV + i) * 8, 1); mbar_init(bar0 + (B_FREE + (i & 7)) * 8, 2); if (i < 6) mbar_init(bar0 + (B_RED + i) * 8, 1); if (i < 6) mbar_init(bar0 + (B_OS + i) * 8, 4); }
            *slow_flag = 0;
            fence_barrier_init();
        }
        __syncwarp();
        cluster_arrive();
        cluster_wait();
        const uint8_t* kvsrc = g_QKV + (size_t)head * KV_HEAD_BYTES;
        if (warp == 8) {
            if (lane == 0) {
                int st = 0, u = rank, tile = -4;
                int es = 5;
                uint32_t eph = 1;
#pragma unroll 1
                for (int n = 0; n < 99; n++) {
                    mbar_wait(empty0 + es * 8, eph);
                    const uint32_t fb = full0 + st * 8, dst = sb + K1_OFF_RING + u * 8192;
                    mbar_expect(fb, 16384);
                    if (tile < 0) {
                        tma3d_mc(dst, &tmQ3, j * 216, n * 32 + rank * 16, 0, fb, 3);
                        tma2d_mc(dst + 6144, &tmQ1, j * 216 + 192, n * 32 + rank * 16, fb, 3);
                    } else if (tile < 9) {
                        tma2d_mc(dst, &tm1, j * 576 + tile * 64, u * 64, fb, 3);
                    } else {
                        tma2d_mc(dst, &tm2, (tile - 9) * 64, j * 576 + u * 64, fb, 3);
                    }
                    u += 2;
                    if (u >= 9) { u -= 9; tile++; }
                    if (++st == 9) st = 0;
                    if (++es == 9) { es = 0; eph ^= 1; }
                }
                mbar_wait(empty0 + 8 * 8, 0);
                mbar_wait(bar0 + B_QRDY * 8, 0);
                asm volatile("fence.proxy.async;" ::: "memory");
#pragma unroll 1
                for (int i = 11; i < NCHUNK; i++) {
                    mbar_expect(bar0 + (B_KV + i) * 8, CHUNK_BYTES);
                    bulk_load(sb + SM_KV + i * CHUNK_BYTES, kvsrc + i * CHUNK_BYTES, CHUNK_BYTES, bar0 + (B_KV + i) * 8);
                }
                const uint8_t* wsrc = g_Wo + ct * WO_TILE_BYTES;
                prefetch_tmap(&tmOut);
                mbar_wait_sleep(bar0 + B_BASE * 8, 500);
#pragma unroll 1
                for (int p = 0; p < 9; p++) {
                    if (p > 0) mbar_wait_sleep(bar0 + (B_FREE + p - 1) * 8, p == 1 ? 500 : 40);
                    const int k = ks0 + p * 3 >= 36 ? ks0 + p * 3 - 36 : ks0 + p * 3;
                    mbar_expect(bar0 + (B_WO + p) * 8, 13824);
                    bulk_load(sb + (p == 0 ? sm_piece(0) : (p == 1 ? sm_piece(1) : SM_KV + (p - 2) * PIECE)), wsrc + k * 4608, 13824, bar0 + (B_WO + p) * 8);
                }
                const int kl = ks0 == 0 ? 27 : ks0 - 9;
                mbar_expect(bar0 + B_LATE * 8, 9 * 4608);
                bulk_load(sb + sm_wstep(27), wsrc + kl * 4608, 8 * 4608, bar0 + B_LATE * 8);
                bulk_load(sb + sm_wstep(35), wsrc + (kl + 8) * 4608, 4608, bar0 + B_LATE * 8);
            }
        } else {
            const int ht = tid - 288;
            if (ht == 64) prefetch_l2(wqkv + blockIdx.x * (DM * 3 * DM / 128), DM * 3 * DM / 64);
            if (ht < 72) {
                const uint4 v = __ldg(reinterpret_cast<const uint4*>(b1 + j * 576) + ht);
                uint32_t* sbias = reinterpret_cast<uint32_t*>(smem + K1_OFF_BIAS) + (ht >> 3) * 32 + (ht & 7);
                sbias[0] = v.x; sbias[8] = v.y; sbias[16] = v.z; sbias[24] = v.w;
            }
            mbar_arrive(bar0 + B_BIAS * 8);
            PROFH(37);
#pragma unroll
            for (int i = 0; i < 3; i++) g_Olate[blockIdx.x * 288 + i * 96 + ht] = make_uint4(O_EMPTY, O_EMPTY, O_EMPTY, O_EMPTY);
#pragma unroll 1
            for (int i = ht; i < 512; i += 96) {
                const int key = i & 127;
                uint8_t* p = g_QKV + (size_t)(j * 4 + (i >> 7)) * KV_HEAD_BYTES + (rb * 16 + (key >> 3)) * KV_GROUP_BYTES + 512 + (key & 7) * 16;
                *reinterpret_cast<uint32_t*>(p + 4) = ((POLY_MASK >> (key >> 3)) & 1) ? 0x3F804000u : 0x00003F80u;
                *reinterpret_cast<uint32_t*>(p + 12) = 0x00003F80u;
            }
            if (ht == 32) prefetch_l2(w1 + blockIdx.x * (DM * FF / 128), DM * FF / 64);
#pragma unroll 2
            for (int i = blockIdx.x * 324 + ht; i < blockIdx.x * 324 + 324; i += 96) {
                const int k = i / 72, nc = i - k * 72, c4 = nc / 18;
                *reinterpret_cast<uint4*>(g_Wo + c4 * WO_TILE_BYTES + (k >> 3) * 2304 + (nc - c4 * 18) * 128 + (k & 7) * 16) =
                    __ldg(reinterpret_cast<const uint4*>(wo) + i);
            }
            PROFH(38);
            named_bar_sync(3, 352);
            if (ht == 32) prefetch_l2(w2 + blockIdx.x * (DM * FF / 128), DM * FF / 64);
            if (ht == 0) {
                flag_signal(&g_flags.qkv_stored[rb]);
                flag_wait(&g_flags.qkv_stored[rb], 8, 200);
            }
            named_bar_sync(7, 96);
            PROFH(39);
#pragma unroll 1
            for (int i = warp - 9; i < 16; i += 3) {
                const int hd = j * 4 + (i >> 2), key = (i & 3) * 32 + lane;
                const uint8_t* p = g_QKV + (size_t)hd * KV_HEAD_BYTES + (rb * 16 + (key >> 3)) * KV_GROUP_BYTES + (key & 7) * 16;
                const uint4 a = __ldcg(reinterpret_cast<const uint4*>(p)), b = __ldcg(reinterpret_cast<const uint4*>(p + 128));
                float n = sumsq2(__ldcg(reinterpret_cast<const uint32_t*>(p + 512))) + sumsq8(a) + sumsq8(b);
                if ((POLY_MASK >> (key >> 3)) & 1) n *= 0.25f;
#pragma unroll
                for (int o = 16; o; o >>= 1) n = fmaxf(n, __shfl_xor_sync(~0u, n, o));
                if (lane == 0) g_kmax[hd * 64 + rb * 4 + (i & 3)] = n;
            }
            named_bar_sync(7, 96);
            PROFH(40);
            if (ht == 0) {
                flag_signal(&g_flags.kv_ready);
                flag_wait(&g_flags.kv_ready, 128, 300);
                mbar_wait_sleep(bar0 + B_XNDEAD * 8, 300);
            }
            named_bar_sync(7, 96);
            PROFH(41);
            float kmax2;
            {
                const float2 v = __ldcg(reinterpret_cast<const float2*>(g_kmax + head * 64 + lane * 2));
                kmax2 = fmaxf(v.x, v.y);
#pragma unroll
                for (int o = 16; o; o >>= 1) kmax2 = fmaxf(kmax2, __shfl_xor_sync(~0u, kmax2, o));
            }
            asm volatile("fence.proxy.async;" ::: "memory");
            int chunk = warp - 9;
#pragma unroll 1
            for (int r = ht; r < 512; r += 96) {
                if (lane == 0 && chunk < 11) {
                    mbar_expect(bar0 + (B_KV + chunk) * 8, CHUNK_BYTES);
                    bulk_load(sb + SM_KV + chunk * CHUNK_BYTES, kvsrc + chunk * CHUNK_BYTES, CHUNK_BYTES, bar0 + (B_KV + chunk) * 8);
                }
                chunk += 3;
                const uint8_t* p = kvsrc + Q_OFFSET + (quarter * 64 + (((r >> 3) + rot * 16) & 63)) * KV_GROUP_BYTES + (r & 7) * 16;
                const uint4 a = __ldcg(reinterpret_cast<const uint4*>(p)), b = __ldcg(reinterpret_cast<const uint4*>(p + 128));
                const uint32_t e = __ldcg(reinterpret_cast<const uint32_t*>(p + 256));
                const float cc = sqrtf((sumsq2(e) + sumsq8(a) + sumsq8(b)) * kmax2) * 1.02f;
                if (!(cc <= 58.f)) *slow_flag = 1;
                uint4* dst = reinterpret_cast<uint4*>(smem + SM_Q + (r >> 3) * 512 + (r & 7) * 16);
                dst[0] = a;
                dst[8] = b;
                dst[16] = make_uint4(e, pack_bf16(-cc, 768.f), 0u, 0u);
                dst[24] = make_uint4(0u, POLY_MODE ? 0xBFFF0000u : 0xC0000000u, 0u, 0u);
            }
            named_bar_sync(7, 96);
            if (*slow_flag) {
#pragma unroll 1
                for (int r = ht; r < 512; r += 96) {
                    uint32_t* dst = reinterpret_cast<uint32_t*>(smem + SM_Q + (r >> 3) * 512 + (r & 7) * 16);
                    dst[65] = 0u;
                    dst[97] = 0u;
                }
            }
            fence_proxy_async();
            __syncwarp();
            if (lane == 0) mbar_arrive(bar0 + B_QRDY * 8);
            PROFH(42);
            if (ht == 0) {
                mbar_wait_sleep(bar0 + B_FFN * 8, 300);
                flag_signal(&g_flags.ffn_done[rb]);
                flag_wait(&g_flags.ffn_done[rt >> 1], 8, 300);
            }
            named_bar_sync(7, 96);
            {
                const int w3 = warp - 9;
                const uint32_t rbar = bar0 + (B_RED + w3 * 2) * 8, rbuf = SM_RED + w3 * 8192;
                const int u0 = ((rt >> 1) * 36 + ct * 9) * 256 + (rt & 1) * 128;
                mbar_wait_sleep(bar0 + (B_KV + 15) * 8, 500);
                asm volatile("fence.proxy.async;" ::: "memory");
#pragma unroll 1
                for (int i = -2; i < 12; i++) {
                    if (i >= 0) {
                        __nanosleep(400);
                        mbar_wait(rbar + (i & 1) * 8, (i >> 1) & 1);
                        const uint4* sp = reinterpret_cast<const uint4*>(smem + rbuf + (i & 1) * 4096) + lane;
                        const uint4 v = hadd8_bf16(hadd8_bf16(hadd8_bf16(sp[0], sp[32]), hadd8_bf16(sp[64], sp[96])),
                                                   hadd8_bf16(hadd8_bf16(sp[128], sp[160]), hadd8_bf16(sp[192], sp[224])));
                        const int bx = i * 3 + w3;
                        uint2* fp = g_ffn + (blockIdx.x * 18 + (bx >> 2) * 2) * 128 + (bx & 3) * 32 + lane;
                        fp[0] = make_uint2(v.x, v.y);
                        fp[128] = make_uint2(v.z, v.w);
                    }
                    __syncwarp();
                    if (lane == 0 && i < 10) {
                        const int bx = (i + 2) * 3 + w3;
                        mbar_expect(rbar + (i & 1) * 8, 4096);
                        tma2d(sb + rbuf + (i & 1) * 4096, &tmP, (u0 + (bx >> 2) * 256 + (bx & 3) * 32) * 2, 0, rbar + (i & 1) * 8);
                    }
                }
            }
            __syncwarp();
            if (lane == 0) mbar_arrive(bar0 + B_BASE * 8);
            PROFH(43);
            if (ht == 0) {
#pragma unroll 1
                for (int i = 0; i < 6; i++) {
                    mbar_wait_sleep(bar0 + (B_OS + i) * 8, 200);
                    flag_signal(&g_flags.o_done[quarter * 8 + (((i >> 1) + rot) & 3) * 2 + (i & 1)]);
                }
            } else if (ht == 32) {
                const uint8_t* osrc = reinterpret_cast<const uint8_t*>(g_O) + rt * 73728;
                mbar_wait_sleep(bar0 + B_BASE * 8, 500);
                mbar_wait_sleep(bar0 + B_FREE * 8, 500);
                flag_wait(&g_flags.o_done[rt], 24, 100);
                if (atomicAdd(&g_flags.exited, 1u) == gridDim.x - 1) {
                    unsigned int* f = reinterpret_cast<unsigned int*>(&g_flags);
#pragma unroll 1
                    for (int i = 0; i < (int)(sizeof(Flags) / 4); i++) f[i] = 0;
                }
                prefetch_tmap(&tmXo);
                asm volatile("fence.proxy.async;" ::: "memory");
#pragma unroll 1
                for (int p = 0; p < 9; p++) {
                    if (p > 1) mbar_wait_sleep(bar0 + (B_FREE + p - 1) * 8, 40);
                    const int k = ks0 + p * 3 >= 36 ? ks0 + p * 3 - 36 : ks0 + p * 3;
                    mbar_expect(bar0 + (B_WO + p) * 8, 6144);
                    bulk_load(sb + 13824 + (p == 0 ? sm_piece(0) : (p == 1 ? sm_piece(1) : SM_KV + (p - 2) * PIECE)), osrc + k * 2048, 6144, bar0 + (B_WO + p) * 8);
                }
                mbar_expect(bar0 + B_LATE * 8, 2 * 9216);
                mbar_wait(bar0 + B_EARLY * 8, 0);
                tma2d(sb + sm_piece(0), &tmXo, ct * 144, rt * 64, bar0 + B_LATE * 8);
                tma2d(sb + sm_piece(0) + 9216, &tmXo, ct * 144 + 72, rt * 64, bar0 + B_LATE * 8);
            }
        }
    }
}

typedef CUresult (*EncodeFn)(CUtensorMap*, CUtensorMapDataType, cuuint32_t, void*, const cuuint64_t*, const cuuint64_t*, const cuuint32_t*,
                             const cuuint32_t*, CUtensorMapInterleave, CUtensorMapSwizzle, CUtensorMapL2promotion, CUtensorMapFloatOOBfill);

void make_map(EncodeFn fn, CUtensorMap* m, const void* base, int rank, const cuuint64_t* dims, const cuuint64_t* strides, const cuuint32_t* box) {
    cuuint32_t es[4] = {1, 1, 1, 1};
    fn(m, CU_TENSOR_MAP_DATA_TYPE_BFLOAT16, rank, const_cast<void*>(base), dims, strides, box, es, CU_TENSOR_MAP_INTERLEAVE_NONE,
       CU_TENSOR_MAP_SWIZZLE_128B, CU_TENSOR_MAP_L2_PROMOTION_L2_256B, CU_TENSOR_MAP_FLOAT_OOB_FILL_NONE);
}

}

extern "C" void kernel_launch(void* const* d_in, const int* in_sizes, int n_in, void* d_out, int out_size) {
    const __nv_bfloat16* x = (const __nv_bfloat16*)d_in[0];
    const __nv_bfloat16* wqkv = (const __nv_bfloat16*)d_in[1];
    const __nv_bfloat16* wo = (const __nv_bfloat16*)d_in[2];
    const __nv_bfloat16* w1 = (const __nv_bfloat16*)d_in[4];
    const __nv_bfloat16* b1 = (const __nv_bfloat16*)d_in[5];
    const __nv_bfloat16* w2 = (const __nv_bfloat16*)d_in[6];
    const __nv_bfloat16* b2 = (const __nv_bfloat16*)d_in[7];
    __nv_bfloat16* out = (__nv_bfloat16*)d_out;

    EncodeFn fn = nullptr;
    cudaDriverEntryPointQueryResult qr;
    cudaGetDriverEntryPoint("cuTensorMapEncodeTiled", (void**)&fn, cudaEnableDefault, &qr);
    CUtensorMap tmX, tmQ3, tmQ1, tm1, tm2, tmP, tmOut, tmXo;
    {
        cuuint64_t d[2] = {DM, SEQ}, s[1] = {DM * 2};
        cuuint32_t b[2] = {72, 64}, es[2] = {1, 1};
        fn(&tmOut, CU_TENSOR_MAP_DATA_TYPE_BFLOAT16, 2, out, d, s, b, es, CU_TENSOR_MAP_INTERLEAVE_NONE, CU_TENSOR_MAP_SWIZZLE_NONE,
           CU_TENSOR_MAP_L2_PROMOTION_NONE, CU_TENSOR_MAP_FLOAT_OOB_FILL_NONE);
        fn(&tmXo, CU_TENSOR_MAP_DATA_TYPE_BFLOAT16, 2, const_cast<__nv_bfloat16*>(x), d, s, b, es, CU_TENSOR_MAP_INTERLEAVE_NONE,
           CU_TENSOR_MAP_SWIZZLE_NONE, CU_TENSOR_MAP_L2_PROMOTION_NONE, CU_TENSOR_MAP_FLOAT_OOB_FILL_NONE);
    }
    {
        void* gp = nullptr;
        cudaGetSymbolAddress(&gp, g_part);
        cuuint64_t d[2] = {SLAB * 2, 8}, s[1] = {SLAB * 16};
        cuuint32_t b[2] = {64, 8}, es[2] = {1, 1};
        fn(&tmP, CU_TENSOR_MAP_DATA_TYPE_INT64, 2, gp, d, s, b, es, CU_TENSOR_MAP_INTERLEAVE_NONE, CU_TENSOR_MAP_SWIZZLE_NONE,
           CU_TENSOR_MAP_L2_PROMOTION_NONE, CU_TENSOR_MAP_FLOAT_OOB_FILL_NONE);
    }
    {
        cuuint64_t d[4] = {64, 8, 9, SEQ / 8}, s[3] = {DM * 2, 128, DM * 2 * 8};
        cuuint32_t b[4] = {64, 8, 3, 2};
        make_map(fn, &tmX, x, 4, d, s, b);
    }
    {
        cuuint64_t d[3] = {3 * DM, DM, 3}, s[2] = {3 * DM * 2, 128};
        cuuint32_t b[3] = {64, 16, 3};
        make_map(fn, &tmQ3, wqkv, 3, d, s, b);
        make_map(fn, &tmQ1, wqkv, 2, d, s, b);
    }
    {
        cuuint64_t d[2] = {FF, DM}, s[1] = {FF * 2};
        cuuint32_t b[2] = {64, 64};
        make_map(fn, &tm1, w1, 2, d, s, b);
        cuuint64_t d2[2] = {DM, FF}, s2[1] = {DM * 2};
        make_map(fn, &tm2, w2, 2, d2, s2, b);
    }
    cudaFuncSetAttribute(fused_kernel, cudaFuncAttributeMaxDynamicSharedMemorySize, K1_SMEM);
    fused_kernel<<<128, 384, K1_SMEM, cudaStreamPerThread>>>(tmX, tmQ3, tmQ1, tm1, tm2, tmP, tmOut, tmXo, b1, wqkv, w1, w2, wo, b2, 0ull);
}
```

```cpp
#include <cuda_runtime.h>
#include <cuda_bf16.h>
#include <cuda.h>
#include <stdint.h>

#define PROF(i) do { } while (0)
#define PROFT(i) do { } while (0)
#define PROFH(i) do { } while (0)
#define PROFWT(i) do { } while (0)
#define PROF_WG 0

namespace {

constexpr int SEQ = 2048, DM = 576, FF = 4608, NH = 32, DH = 18;

constexpr int KV_GROUP_BYTES = 5 * 128;
constexpr int KV_HEAD_BYTES = (SEQ / 8) * KV_GROUP_BYTES;
constexpr int Q_OFFSET = NH * KV_HEAD_BYTES;
#define POLY_MASK 0xB6B6
__device__ __align__(1024) uint8_t g_QKV[2 * NH * KV_HEAD_BYTES];
__device__ __align__(1024) float g_kmax[NH * 64];
constexpr int SLAB = 16 * 36 * 256;
__device__ __align__(1024) uint4 g_part[8 * SLAB];
__device__ __align__(1024) uint2 g_ffn[128 * 18 * 128];
__device__ __align__(1024) uint32_t g_O[SEQ * DM / 2];
struct Flags {
    unsigned int qkv_stored[16];
    unsigned int ffn_done[16];
    unsigned int o_done[32];
    unsigned int kv_ready;
    unsigned int exited;
};
__device__ Flags g_flags;
__device__ __align__(1024) uint4 g_Olate[32 * 9 * 128];
constexpr uint32_t O_EMPTY = 0xFFFFFFFFu;
constexpr int WO_TILE_BYTES = DM * 144 * 2;
__device__ __align__(1024) uint8_t g_Wo[4 * WO_TILE_BYTES];

__device__ __forceinline__ uint32_t s2u(const void* p) { return (uint32_t)__cvta_generic_to_shared(p); }
__device__ __forceinline__ void mbar_init(uint32_t b, int c) { asm volatile("mbarrier.init.shared::cta.b64 [%0], %1;" ::"r"(b), "r"(c) : "memory"); }
__device__ __forceinline__ void mbar_expect(uint32_t b, uint32_t bytes) {
    asm volatile("mbarrier.arrive.expect_tx.shared::cta.b64 _, [%0], %1;" ::"r"(b), "r"(bytes) : "memory");
}
__device__ __forceinline__ void mbar_wait(uint32_t b, uint32_t parity) {
    asm volatile(
        "{\n.reg .pred p;\n.reg .u32 c;\n"
        "mov.u32 c, 0;\n"
        "LOOP:\n"
        "mbarrier.try_wait.parity.shared::cta.b64 p, [%0], %1;\n"
        "@p bra DONE;\n"
        "add.u32 c, c, 1;\n"
        "setp.lt.u32 p, c, 4194304;\n"
        "@p bra LOOP;\n"
        "trap;\n"
        "DONE:\n}\n" ::"r"(b), "r"(parity) : "memory");
}
__device__ __forceinline__ void fence_barrier_init() { asm volatile("fence.mbarrier_init.release.cluster;" ::: "memory"); }
__device__ __forceinline__ void fence_proxy_async() { asm volatile("fence.proxy.async.shared::cta;" ::: "memory"); }
__device__ __forceinline__ void cluster_arrive() { asm volatile("barrier.cluster.arrive.relaxed.aligned;" ::: "memory"); }
__device__ __forceinline__ void cluster_wait() { asm volatile("barrier.cluster.wait.aligned;" ::: "memory"); }
__device__ __forceinline__ void named_bar_sync(int id, int n) { asm volatile("bar.sync %0, %1;" ::"r"(id), "r"(n) : "memory"); }

__device__ __forceinline__ void tma3d_mc(uint32_t dst, const CUtensorMap* tm, int c0, int c1, int c2, uint32_t bar, uint16_t mask) {
    asm volatile("cp.async.bulk.tensor.3d.shared::cluster.global.mbarrier::complete_tx::bytes.multicast::cluster [%0], [%1, {%3, %4, %5}], [%2], %6;"
                 ::"r"(dst), "l"(tm), "r"(bar), "r"(c0), "r"(c1), "r"(c2), "h"(mask) : "memory");
}
__device__ __forceinline__ void tma2d_mc(uint32_t dst, const CUtensorMap* tm, int c0, int c1, uint32_t bar, uint16_t mask) {
    asm volatile("cp.async.bulk.tensor.2d.shared::cluster.global.mbarrier::complete_tx::bytes.multicast::cluster [%0], [%1, {%3, %4}], [%2], %5;"
                 ::"r"(dst), "l"(tm), "r"(bar), "r"(c0), "r"(c1), "h"(mask) : "memory");
}
__device__ __forceinline__ void tma4d(uint32_t dst, const CUtensorMap* tm, int c0, int c1, int c2, int c3, uint32_t bar) {
    asm volatile("cp.async.bulk.tensor.4d.shared::cluster.global.mbarrier::complete_tx::bytes [%0], [%1, {%3, %4, %5, %6}], [%2];"
                 ::"r"(dst), "l"(tm), "r"(bar), "r"(c0), "r"(c1), "r"(c2), "r"(c3) : "memory");
}
__device__ __forceinline__ void tma2d(uint32_t dst, const CUtensorMap* tm, int c0, int c1, uint32_t bar) {
    asm volatile("cp.async.bulk.tensor.2d.shared::cluster.global.mbarrier::complete_tx::bytes [%0], [%1, {%3, %4}], [%2];"
                 ::"r"(dst), "l"(tm), "r"(bar), "r"(c0), "r"(c1) : "memory");
}
__device__ __forceinline__ void bulk_load(uint32_t dst, const void* src, uint32_t bytes, uint32_t bar) {
    asm volatile("cp.async.bulk.shared::cluster.global.mbarrier::complete_tx::bytes [%0], [%1], %2, [%3];"
                 ::"r"(dst), "l"(src), "r"(bytes), "r"(bar) : "memory");
}
__device__ __forceinline__ void prefetch_l2(const void* p, uint32_t bytes) {
    asm volatile("cp.async.bulk.prefetch.L2.global [%0], %1;" ::"l"(p), "r"(bytes) : "memory");
}
__device__ __forceinline__ void prefetch_tmap(const CUtensorMap* tm) { asm volatile("prefetch.tensormap [%0];" ::"l"(tm) : "memory"); }

__device__ __forceinline__ void wg_fence() { asm volatile("wgmma.fence.sync.aligned;" ::: "memory"); }
__device__ __forceinline__ void wg_commit() { asm volatile("wgmma.commit_group.sync.aligned;" ::: "memory"); }
template <int N> __device__ __forceinline__ void wg_wait() { asm volatile("wgmma.wait_group.sync.aligned %0;" ::"n"(N) : "memory"); }
template <int N> __device__ __forceinline__ void reg_fence(float (&d)[N]) {
#pragma unroll
    for (int i = 0; i < N; i++) asm volatile("" : "+f"(d[i])::"memory");
}
template <int N> __device__ __forceinline__ void reg_fence(uint32_t (&d)[N]) {
#pragma unroll
    for (int i = 0; i < N; i++) asm volatile("" : "+r"(d[i])::"memory");
}
template <int R> __device__ __forceinline__ void reg_alloc() { asm volatile("setmaxnreg.inc.sync.aligned.u32 %0;" ::"n"(R)); }
template <int R> __device__ __forceinline__ void reg_dealloc() { asm volatile("setmaxnreg.dec.sync.aligned.u32 %0;" ::"n"(R)); }

__device__ __forceinline__ uint64_t mk_desc(uint64_t z, uint32_t addr, uint32_t lbo, uint32_t sbo, uint32_t swz) {
    return z + ((uint64_t)(((addr & 0x3FFFF) >> 4) | ((lbo >> 4) << 16)) | ((uint64_t)((sbo >> 4) | (swz << 30)) << 32));
}
__device__ __forceinline__ uint32_t pack_bf16(float lo, float hi) {
    uint32_t r;
    asm("cvt.rn.bf16x2.f32 %0, %1, %2;" : "=r"(r) : "f"(hi), "f"(lo));
    return r;
}
__device__ __forceinline__ float bf_lo(uint32_t w) { return __uint_as_float(w << 16); }
__device__ __forceinline__ float bf_hi(uint32_t w) { return __uint_as_float(w & 0xFFFF0000u); }
__device__ __forceinline__ float ex2(float x) {
    float r;
    asm("ex2.approx.ftz.f32 %0, %1;" : "=f"(r) : "f"(x));
    return r;
}
__device__ __forceinline__ float tanh_fast(float x) {
    float r;
    asm("tanh.approx.f32 %0, %1;" : "=f"(r) : "f"(x));
    return r;
}
__device__ __forceinline__ uint32_t hfma2_bf16(uint32_t a, uint32_t b, uint32_t c) {
    uint32_t r;
    asm("fma.rn.bf16x2 %0, %1, %2, %3;" : "=r"(r) : "r"(a), "r"(b), "r"(c));
    return r;
}
__device__ __forceinline__ uint32_t hadd2_bf16(uint32_t a, uint32_t b) {
    uint32_t r;
    asm("add.rn.bf16x2 %0, %1, %2;" : "=r"(r) : "r"(a), "r"(b));
    return r;
}
__device__ __forceinline__ void ldsm4(uint32_t (&a)[4], uint32_t addr) {
    asm volatile("ldmatrix.sync.aligned.m8n8.x4.shared.b16 {%0, %1, %2, %3}, [%4];" : "=r"(a[0]), "=r"(a[1]), "=r"(a[2]), "=r"(a[3]) : "r"(addr) : "memory");
}
__device__ __forceinline__ void stsm4(uint32_t addr, const uint32_t (&a)[4]) {
    asm volatile("stmatrix.sync.aligned.m8n8.x4.shared.b16 [%0], {%1, %2, %3, %4};" ::"r"(addr), "r"(a[0]), "r"(a[1]), "r"(a[2]), "r"(a[3]) : "memory");
}
__device__ __forceinline__ void mma16816(float (&c)[4], const uint32_t (&a)[4], uint32_t b0, uint32_t b1) {
    asm("mma.sync.aligned.m16n8k16.row.col.f32.bf16.bf16.f32 {%0, %1, %2, %3}, {%4, %5, %6, %7}, {%8, %9}, {%0, %1, %2, %3};"
        : "+f"(c[0]), "+f"(c[1]), "+f"(c[2]), "+f"(c[3]) : "r"(a[0]), "r"(a[1]), "r"(a[2]), "r"(a[3]), "r"(b0), "r"(b1));
}
__device__ __forceinline__ float gelu2(float u) {
    const float w = fmaf(u * u, 0.0356774081f, 0.7978845608f);
    return fmaf(u, tanh_fast(u * w), u);
}

template<int TB, int AOFF, int BOFF> __device__ __forceinline__ void wgmma_ss_n216(float (&d)[108], uint64_t da, uint64_t db, int sd) {
    asm volatile("{\n.reg .pred p;\n.reg .b64 ta, tb;\nsetp.ne.b32 p, %110, 0;\nadd.s64 ta, %108, %112;\nadd.s64 tb, %109, %113;\n"
      "wgmma.mma_async.sync.aligned.m64n216k16.f32.bf16.bf16 {%0, %1, %2, %3, %4, %5, %6, %7, %8, %9, %10, %11, %12, %13, %14, %15, %16, %17, %18, %19, %20, %21, %22, %23, %24, %25, %26, %27, %28, %29, %30, %31, %32, %33, %34, %35, %36, %37, %38, %39, %40, %41, %42, %43, %44, %45, %46, %47, %48, %49, %50, %51, %52, %53, %54, %55, %56, %57, %58, %59, %60, %61, %62, %63, %64, %65, %66, %67, %68, %69, %70, %71, %72, %73, %74, %75, %76, %77, %78, %79, %80, %81, %82, %83, %84, %85, %86, %87, %88, %89, %90, %91, %92, %93, %94, %95, %96, %97, %98, %99, %100, %101, %102, %103, %104, %105, %106, %107}, ta, tb, p, 1, 1, 0, %111;\n}\n"
      : "+f"(d[0]), "+f"(d[1]), "+f"(d[2]), "+f"(d[3]), "+f"(d[4]), "+f"(d[5]), "+f"(d[6]), "+f"(d[7]), "+f"(d[8]), "+f"(d[9]), "+f"(d[10]), "+f"(d[11]), "+f"(d[12]), "+f"(d[13]), "+f"(d[14]), "+f"(d[15]), "+f"(d[16]), "+f"(d[17]), "+f"(d[18]), "+f"(d[19]), "+f"(d[20]), "+f"(d[21]), "+f"(d[22]), "+f"(d[23]), "+f"(d[24]), "+f"(d[25]), "+f"(d[26]), "+f"(d[27]), "+f"(d[28]), "+f"(d[29]), "+f"(d[30]), "+f"(d[31]), "+f"(d[32]), "+f"(d[33]), "+f"(d[34]), "+f"(d[35]), "+f"(d[36]), "+f"(d[37]), "+f"(d[38]), "+f"(d[39]), "+f"(d[40]), "+f"(d[41]), "+f"(d[42]), "+f"(d[43]), "+f"(d[44]), "+f"(d[45]), "+f"(d[46]), "+f"(d[47]), "+f"(d[48]), "+f"(d[49]), "+f"(d[50]), "+f"(d[51]), "+f"(d[52]), "+f"(d[53]), "+f"(d[54]), "+f"(d[55]), "+f"(d[56]), "+f"(d[57]), "+f"(d[58]), "+f"(d[59]), "+f"(d[60]), "+f"(d[61]), "+f"(d[62]), "+f"(d[63]), "+f"(d[64]), "+f"(d[65]), "+f"(d[66]), "+f"(d[67]), "+f"(d[68]), "+f"(d[69]), "+f"(d[70]), "+f"(d[71]), "+f"(d[72]), "+f"(d[73]), "+f"(d[74]), "+f"(d[75]), "+f"(d[76]), "+f"(d[77]), "+f"(d[78]), "+f"(d[79]), "+f"(d[80]), "+f"(d[81]), "+f"(d[82]), "+f"(d[83]), "+f"(d[84]), "+f"(d[85]), "+f"(d[86]), "+f"(d[87]), "+f"(d[88]), "+f"(d[89]), "+f"(d[90]), "+f"(d[91]), "+f"(d[92]), "+f"(d[93]), "+f"(d[94]), "+f"(d[95]), "+f"(d[96]), "+f"(d[97]), "+f"(d[98]), "+f"(d[99]), "+f"(d[100]), "+f"(d[101]), "+f"(d[102]), "+f"(d[103]), "+f"(d[104]), "+f"(d[105]), "+f"(d[106]), "+f"(d[107])
      : "l"(da), "l"(db), "r"(sd), "n"(TB), "n"(AOFF), "n"(BOFF));
}

template<int TB, int AOFF, int BOFF> __device__ __forceinline__ void wgmma_ss_n128(float (&d)[64], uint64_t da, uint64_t db, int sd) {
    asm volatile("{\n.reg .pred p;\n.reg .b64 ta, tb;\nsetp.ne.b32 p, %66, 0;\nadd.s64 ta, %64, %68;\nadd.s64 tb, %65, %69;\n"
      "wgmma.mma_async.sync.aligned.m64n128k16.f32.bf16.bf16 {%0, %1, %2, %3, %4, %5, %6, %7, %8, %9, %10, %11, %12, %13, %14, %15, %16, %17, %18, %19, %20, %21, %22, %23, %24, %25, %26, %27, %28, %29, %30, %31, %32, %33, %34, %35, %36, %37, %38, %39, %40, %41, %42, %43, %44, %45, %46, %47, %48, %49, %50, %51, %52, %53, %54, %55, %56, %57, %58, %59, %60, %61, %62, %63}, ta, tb, p, 1, 1, 0, %67;\n}\n"
      : "+f"(d[0]), "+f"(d[1]), "+f"(d[2]), "+f"(d[3]), "+f"(d[4]), "+f"(d[5]), "+f"(d[6]), "+f"(d[7]), "+f"(d[8]), "+f"(d[9]), "+f"(d[10]), "+f"(d[11]), "+f"(d[12]), "+f"(d[13]), "+f"(d[14]), "+f"(d[15]), "+f"(d[16]), "+f"(d[17]), "+f"(d[18]), "+f"(d[19]), "+f"(d[20]), "+f"(d[21]), "+f"(d[22]), "+f"(d[23]), "+f"(d[24]), "+f"(d[25]), "+f"(d[26]), "+f"(d[27]), "+f"(d[28]), "+f"(d[29]), "+f"(d[30]), "+f"(d[31]), "+f"(d[32]), "+f"(d[33]), "+f"(d[34]), "+f"(d[35]), "+f"(d[36]), "+f"(d[37]), "+f"(d[38]), "+f"(d[39]), "+f"(d[40]), "+f"(d[41]), "+f"(d[42]), "+f"(d[43]), "+f"(d[44]), "+f"(d[45]), "+f"(d[46]), "+f"(d[47]), "+f"(d[48]), "+f"(d[49]), "+f"(d[50]), "+f"(d[51]), "+f"(d[52]), "+f"(d[53]), "+f"(d[54]), "+f"(d[55]), "+f"(d[56]), "+f"(d[57]), "+f"(d[58]), "+f"(d[59]), "+f"(d[60]), "+f"(d[61]), "+f"(d[62]), "+f"(d[63])
      : "l"(da), "l"(db), "r"(sd), "n"(TB), "n"(AOFF), "n"(BOFF));
}

template<int TB, int AOFF, int BOFF> __device__ __forceinline__ void wgmma_ss_n72(float (&d)[36], uint64_t da, uint64_t db, int sd) {
    asm volatile("{\n.reg .pred p;\n.reg .b64 ta, tb;\nsetp.ne.b32 p, %38, 0;\nadd.s64 ta, %36, %40;\nadd.s64 tb, %37, %41;\n"
      "wgmma.mma_async.sync.aligned.m64n72k16.f32.bf16.bf16 {%0, %1, %2, %3, %4, %5, %6, %7, %8, %9, %10, %11, %12, %13, %14, %15, %16, %17, %18, %19, %20, %21, %22, %23, %24, %25, %26, %27, %28, %29, %30, %31, %32, %33, %34, %35}, ta, tb, p, 1, 1, 0, %39;\n}\n"
      : "+f"(d[0]), "+f"(d[1]), "+f"(d[2]), "+f"(d[3]), "+f"(d[4]), "+f"(d[5]), "+f"(d[6]), "+f"(d[7]), "+f"(d[8]), "+f"(d[9]), "+f"(d[10]), "+f"(d[11]), "+f"(d[12]), "+f"(d[13]), "+f"(d[14]), "+f"(d[15]), "+f"(d[16]), "+f"(d[17]), "+f"(d[18]), "+f"(d[19]), "+f"(d[20]), "+f"(d[21]), "+f"(d[22]), "+f"(d[23]), "+f"(d[24]), "+f"(d[25]), "+f"(d[26]), "+f"(d[27]), "+f"(d[28]), "+f"(d[29]), "+f"(d[30]), "+f"(d[31]), "+f"(d[32]), "+f"(d[33]), "+f"(d[34]), "+f"(d[35])
      : "l"(da), "l"(db), "r"(sd), "n"(TB), "n"(AOFF), "n"(BOFF));
}

template<int TB, int BOFF> __device__ __forceinline__ void wgmma_rs_n24(float (&d)[12], uint32_t a0, uint32_t a1, uint32_t a2, uint32_t a3, uint64_t db, int sd) {
    asm volatile("{\n.reg .pred p;\n.reg .b64 tb;\nsetp.ne.b32 p, %17, 0;\nadd.s64 tb, %16, %19;\n"
      "wgmma.mma_async.sync.aligned.m64n24k16.f32.bf16.bf16 {%0, %1, %2, %3, %4, %5, %6, %7, %8, %9, %10, %11}, {%12, %13, %14, %15}, tb, p, 1, 1, %18;\n}\n"
      : "+f"(d[0]), "+f"(d[1]), "+f"(d[2]), "+f"(d[3]), "+f"(d[4]), "+f"(d[5]), "+f"(d[6]), "+f"(d[7]), "+f"(d[8]), "+f"(d[9]), "+f"(d[10]), "+f"(d[11])
      : "r"(a0), "r"(a1), "r"(a2), "r"(a3), "l"(db), "r"(sd), "n"(TB), "n"(BOFF));
}

template<int TB, int BOFF> __device__ __forceinline__ void wgmma_rs_n72(float (&d)[36], uint32_t a0, uint32_t a1, uint32_t a2, uint32_t a3, uint64_t db, int sd) {
    asm volatile("{\n.reg .pred p;\n.reg .b64 tb;\nsetp.ne.b32 p, %41, 0;\nadd.s64 tb, %40, %43;\n"
      "wgmma.mma_async.sync.aligned.m64n72k16.f32.bf16.bf16 {%0, %1, %2, %3, %4, %5, %6, %7, %8, %9, %10, %11, %12, %13, %14, %15, %16, %17, %18, %19, %20, %21, %22, %23, %24, %25, %26, %27, %28, %29, %30, %31, %32, %33, %34, %35}, {%36, %37, %38, %39}, tb, p, 1, 1, %42;\n}\n"
      : "+f"(d[0]), "+f"(d[1]), "+f"(d[2]), "+f"(d[3]), "+f"(d[4]), "+f"(d[5]), "+f"(d[6]), "+f"(d[7]), "+f"(d[8]), "+f"(d[9]), "+f"(d[10]), "+f"(d[11]), "+f"(d[12]), "+f"(d[13]), "+f"(d[14]), "+f"(d[15]), "+f"(d[16]), "+f"(d[17]), "+f"(d[18]), "+f"(d[19]), "+f"(d[20]), "+f"(d[21]), "+f"(d[22]), "+f"(d[23]), "+f"(d[24]), "+f"(d[25]), "+f"(d[26]), "+f"(d[27]), "+f"(d[28]), "+f"(d[29]), "+f"(d[30]), "+f"(d[31]), "+f"(d[32]), "+f"(d[33]), "+f"(d[34]), "+f"(d[35])
      : "r"(a0), "r"(a1), "r"(a2), "r"(a3), "l"(db), "r"(sd), "n"(TB), "n"(BOFF));
}

template<int TB, int AINC, int BINC> __device__ __forceinline__ void wgmma_ss_n64_pi(float (&d)[32], uint64_t& da, uint64_t& db, int sd) {
    asm volatile("{\n.reg .pred p;\nsetp.ne.b32 p, %34, 0;\n"
      "wgmma.mma_async.sync.aligned.m64n64k16.f32.bf16.bf16 {%0, %1, %2, %3, %4, %5, %6, %7, %8, %9, %10, %11, %12, %13, %14, %15, %16, %17, %18, %19, %20, %21, %22, %23, %24, %25, %26, %27, %28, %29, %30, %31}, %32, %33, p, 1, 1, 0, %35;\n"
      "add.s64 %32, %32, %36;\nadd.s64 %33, %33, %37;\n}\n"
      : "+f"(d[0]), "+f"(d[1]), "+f"(d[2]), "+f"(d[3]), "+f"(d[4]), "+f"(d[5]), "+f"(d[6]), "+f"(d[7]), "+f"(d[8]), "+f"(d[9]), "+f"(d[10]), "+f"(d[11]), "+f"(d[12]), "+f"(d[13]), "+f"(d[14]), "+f"(d[15]), "+f"(d[16]), "+f"(d[17]), "+f"(d[18]), "+f"(d[19]), "+f"(d[20]), "+f"(d[21]), "+f"(d[22]), "+f"(d[23]), "+f"(d[24]), "+f"(d[25]), "+f"(d[26]), "+f"(d[27]), "+f"(d[28]), "+f"(d[29]), "+f"(d[30]), "+f"(d[31]), "+l"(da), "+l"(db)
      : "r"(sd), "n"(TB), "n"(AINC), "n"(BINC));
}

template<int TB, int BINC> __device__ __forceinline__ void wgmma_rs_n64_pi(float (&d)[32], uint32_t a0, uint32_t a1, uint32_t a2, uint32_t a3, uint64_t& db, int sd) {
    asm volatile("{\n.reg .pred p;\nsetp.ne.b32 p, %37, 0;\n"
      "wgmma.mma_async.sync.aligned.m64n64k16.f32.bf16.bf16 {%0, %1, %2, %3, %4, %5, %6, %7, %8, %9, %10, %11, %12, %13, %14, %15, %16, %17, %18, %19, %20, %21, %22, %23, %24, %25, %26, %27, %28, %29, %30, %31}, {%33, %34, %35, %36}, %32, p, 1, 1, %38;\n"
      "add.s64 %32, %32, %39;\n}\n"
      : "+f"(d[0]), "+f"(d[1]), "+f"(d[2]), "+f"(d[3]), "+f"(d[4]), "+f"(d[5]), "+f"(d[6]), "+f"(d[7]), "+f"(d[8]), "+f"(d[9]), "+f"(d[10]), "+f"(d[11]), "+f"(d[12]), "+f"(d[13]), "+f"(d[14]), "+f"(d[15]), "+f"(d[16]), "+f"(d[17]), "+f"(d[18]), "+f"(d[19]), "+f"(d[20]), "+f"(d[21]), "+f"(d[22]), "+f"(d[23]), "+f"(d[24]), "+f"(d[25]), "+f"(d[26]), "+f"(d[27]), "+f"(d[28]), "+f"(d[29]), "+f"(d[30]), "+f"(d[31]), "+l"(db)
      : "r"(a0), "r"(a1), "r"(a2), "r"(a3), "r"(sd), "n"(TB), "n"(BINC));
}

constexpr int K1_XN_BYTES = 16 * 9216;
constexpr int K1_OFF_RING = K1_XN_BYTES;
constexpr int K1_OFF_BIAS = K1_OFF_RING + 10 * 8192;
constexpr int K1_OFF_BAR = K1_OFF_BIAS + 576 * 2;
constexpr int K1_SMEM = K1_OFF_BAR + 800;
constexpr float QSCALE = 0.23570226039551584f * 1.4426950408889634f;

struct K1Ctx {
    uint32_t full0;
    uint32_t rel_addr;
    uint64_t descA, descB;
    uint32_t phase;
    __device__ __forceinline__ void begin_stage(int s) {
        mbar_wait(full0 + s * 8, phase);
        wg_fence();
    }
    __device__ __forceinline__ void release(int s) {
        if (rel_addr) asm volatile("mbarrier.arrive.shared::cluster.b64 _, [%0];" ::"r"(rel_addr + s * 8) : "memory");
    }
    __device__ __forceinline__ void end_stage(int s) {
        wg_commit();
        wg_wait<1>();
        release(s == 0 ? 8 : s - 1);
    }
};

__host__ __device__ constexpr int a_off(int ks) { return ((ks / 12) * 49152 + ((ks >> 2) % 3) * 1024 + (ks & 3) * 32) >> 4; }

template <int V> struct IC { static constexpr int value = V; };
template <int I, int N, class F> __device__ __forceinline__ void static_for(F&& f) {
    if constexpr (I < N) { f(IC<I>{}); static_for<I + 1, N>(f); }
}

template <bool A_RS, bool B_RS, class Epi>
__device__ __forceinline__ void tile_pair(K1Ctx& c, float (&accA)[32], float (&accB)[32], uint32_t (&h)[144], Epi&& epi) {
    static_for<0, 9>([&](auto sc) {
        constexpr int s = decltype(sc)::value;
        c.begin_stage(s);
        static_for<0, 8>([&](auto tc) {
            constexpr int t = decltype(tc)::value, kk = s * 8 + t, ks = kk % 36;
            constexpr int db = ks == 35 ? -35 * 128 : 128, da = a_off((ks + 1) % 36) - a_off(ks);
            if constexpr (kk < 36) {
                if constexpr (A_RS) wgmma_rs_n64_pi<1, db>(accA, h[ks * 4], h[ks * 4 + 1], h[ks * 4 + 2], h[ks * 4 + 3], c.descB, ks != 0);
                else wgmma_ss_n64_pi<1, da, db>(accA, c.descA, c.descB, ks != 0);
            } else {
                if constexpr (B_RS) wgmma_rs_n64_pi<1, db>(accB, h[ks * 4], h[ks * 4 + 1], h[ks * 4 + 2], h[ks * 4 + 3], c.descB, ks != 0);
                else wgmma_ss_n64_pi<1, da, db>(accB, c.descA, c.descB, ks != 0);
            }
            if constexpr (t == 0) {
                c.end_stage(s);
                epi(sc);
                wg_fence();
            }
        });
        wg_commit();
    });
    c.phase ^= 1;
}

template <int B0, int NB, int HOFF>
__device__ __forceinline__ void gelu_blocks(const float (&acc)[32], uint32_t (&h)[144], const uint32_t (&bq)[8], float rs0, float rs1) {
#pragma unroll
    for (int b = B0; b < B0 + NB; b++) {
        const float b0 = bf_lo(bq[b]), b1 = bf_hi(bq[b]);
        h[HOFF + b * 2 + 0] = pack_bf16(gelu2(fmaf(acc[b * 4 + 0], rs0, b0)), gelu2(fmaf(acc[b * 4 + 1], rs0, b1)));
        h[HOFF + b * 2 + 1] = pack_bf16(gelu2(fmaf(acc[b * 4 + 2], rs1, b0)), gelu2(fmaf(acc[b * 4 + 3], rs1, b1)));
    }
#pragma unroll
    for (int i = HOFF + B0 * 2; i < HOFF + (B0 + NB) * 2; i++) asm volatile("" : "+r"(h[i]));
}
__device__ __forceinline__ void load_bias(uint32_t (&bq)[8], uint32_t addr) {
    asm volatile("ld.shared.v4.u32 {%0, %1, %2, %3}, [%4];" : "=r"(bq[0]), "=r"(bq[1]), "=r"(bq[2]), "=r"(bq[3]) : "r"(addr));
    asm volatile("ld.shared.v4.u32 {%0, %1, %2, %3}, [%4 + 16];" : "=r"(bq[4]), "=r"(bq[5]), "=r"(bq[6]), "=r"(bq[7]) : "r"(addr));
}
__device__ __forceinline__ void st_pred2(bool p, void* a, uint32_t x, uint32_t y) {
    asm volatile("{\n.reg .pred p;\nsetp.ne.u32 p, %3, 0;\n@p st.global.v2.u32 [%0], {%1, %2};\n}\n" ::"l"(a), "r"(x), "r"(y), "r"((uint32_t)p) : "memory");
}
__device__ __forceinline__ void st_pred1(bool p, void* a, uint32_t x) {
    asm volatile("{\n.reg .pred p;\nsetp.ne.u32 p, %2, 0;\n@p st.global.u32 [%0], %1;\n}\n" ::"l"(a), "r"(x), "r"((uint32_t)p) : "memory");
}
template <int S> __device__ __forceinline__ void store_part(const float (&o)[32], uint4* p) {
    uint4 v;
    v.x = pack_bf16(o[S * 8 + 0], o[S * 8 + 1]); v.y = pack_bf16(o[S * 8 + 2], o[S * 8 + 3]);
    v.z = pack_bf16(o[S * 8 + 4], o[S * 8 + 5]); v.w = pack_bf16(o[S * 8 + 6], o[S * 8 + 7]);
    p[S * 256] = v;
}

constexpr int NCHUNK = 16;
constexpr int CHUNK_BYTES = KV_HEAD_BYTES / NCHUNK;
constexpr int SM_Q = 0;
constexpr int SM_KV = 32768;
constexpr int PIECE = 19968;
__host__ __device__ constexpr int sm_piece(int p) { return p == 0 ? 209408 : (p == 1 ? 0 : SM_KV + (p - 2) * PIECE); }
__host__ __device__ constexpr int sm_wstep(int k) { return k < 27 ? sm_piece(k / 3) + (k % 3) * 4608 : (k < 35 ? SM_KV + 7 * PIECE + (k - 27) * 4608 : PIECE); }
__host__ __device__ constexpr int sm_ostep(int k) { return sm_piece(k / 3) + 13824 + (k % 3) * 2048; }
constexpr int SM_RED = SM_KV + KV_HEAD_BYTES;

__device__ __forceinline__ float exp2_fixed(float y) {
    const float u = __uint_as_float(__float_as_uint(y) & 0xFF807FFFu) - 512.02545f;
    float t = fmaf(u, 0.019497588f, 0.114550486f);
    t = fmaf(t, u, -0.29839927f);
    return fmaf(t, u, y);
}
__device__ __forceinline__ uint32_t pack_fixed(float lo, float hi) { return __byte_perm(__float_as_uint(lo), __float_as_uint(hi), 0x6521); }

#define PV_GROUP 4
#define POLY_MODE 1
__device__ __forceinline__ uint32_t exp2_packed(float y0, float y1, uint32_t one2) {
    const uint32_t w = pack_fixed(y0, y1);
    uint32_t m;
    asm("lop3.b32 %0, %1, 0x007F007F, %2, 0xEA;" : "=r"(m) : "r"(w), "r"(one2));
    const uint32_t d = hfma2_bf16(m, 0x3EF93EF9u, 0xBF38BF38u);
    const uint32_t e = hfma2_bf16(d, d, 0xBD71BD71u);
    return hfma2_bf16(w, e, w);
}
constexpr int KV_TILE = CHUNK_BYTES / 16;
template <int OFF> __device__ __forceinline__ void issue_qk(float (&s)[64], uint64_t qd, uint64_t kd) {
    wgmma_ss_n128<0, 0, OFF + (8 << 16)>(s, qd, kd, 0);
    wgmma_ss_n128<0, 16, OFF + 32>(s, qd, kd, 1);
}
template <int OFF> __device__ __forceinline__ void issue_pv(float (&o)[12], const uint32_t (&p)[32], uint64_t vd) {
    static_for<0, 8>([&](auto kc) {
        constexpr int k = decltype(kc)::value;
        wgmma_rs_n24<1, OFF + k * (2 * KV_GROUP_BYTES / 16)>(o, p[k * 4], p[k * 4 + 1], p[k * 4 + 2], p[k * 4 + 3], vd, 1);
    });
}
template <int OFF>
__device__ __forceinline__ void softmax_pv(const float (&s)[64], uint32_t (&p)[32], float (&o)[12], uint64_t vd, uint32_t one2) {
    static_for<0, 8 / PV_GROUP>([&](auto gc) {
        constexpr int g0 = decltype(gc)::value * PV_GROUP;
#pragma unroll
        for (int b = g0 * 2; b < (g0 + PV_GROUP) * 2; b++) {
            if ((POLY_MASK >> b) & 1) {
                p[b * 2 + 0] = exp2_packed(s[b * 4 + 0], s[b * 4 + 1], one2);
                p[b * 2 + 1] = exp2_packed(s[b * 4 + 2], s[b * 4 + 3], one2);
            } else {
                p[b * 2 + 0] = pack_bf16(ex2(s[b * 4 + 0]), ex2(s[b * 4 + 1]));
                p[b * 2 + 1] = pack_bf16(ex2(s[b * 4 + 2]), ex2(s[b * 4 + 3]));
            }
        }
#pragma unroll
        for (int i = g0 * 4; i < (g0 + PV_GROUP) * 4; i++) asm volatile("" : "+r"(p[i])::"memory");
        wg_fence();
        static_for<g0, g0 + PV_GROUP>([&](auto kc) {
            constexpr int k = decltype(kc)::value;
            wgmma_rs_n24<1, OFF + k * (2 * KV_GROUP_BYTES / 16)>(o, p[k * 4], p[k * 4 + 1], p[k * 4 + 2], p[k * 4 + 3], vd, 1);
        });
    });
    wg_commit();
}
__device__ __forceinline__ int head_pair(int hh, int i) {
    if (i == 8) return hh == 3 ? 0 : 8;
    const int q = i >> 1, t = (4 - hh) & 3;
    if ((i & 1) == 0) return t + q;
    return (hh == 1 || hh == 2) ? (q >= hh ? q - hh : t + 4 + q) : t + 4 + q;
}
template <bool LATE> __device__ __forceinline__ void store_o(float (&o)[12], int rt, int head, int wq, int lane) {
    const int g = lane >> 2, q = lane & 3;
    const float i0 = __fdividef(1.0f, __shfl_sync(~0u, o[8], lane | 3)), i1 = __fdividef(1.0f, __shfl_sync(~0u, o[10], lane | 3));
#pragma unroll
    for (int i = 0; i < 3; i++) {
        const uint32_t w0 = pack_bf16(o[i * 4] * i0, o[i * 4 + 1] * i0), w1 = pack_bf16(o[i * 4 + 2] * i1, o[i * 4 + 3] * i1);
        if (i < 2 || q == 2) {
            if constexpr (LATE) {
                const int pc = (head & 7) * 9 + head_pair(head & 3, i < 2 ? i * 4 + q : 8);
                uint32_t* op = reinterpret_cast<uint32_t*>(g_Olate) + (((rt * 9 + (pc >> 3)) * 128 + wq * 32 + g * 4 + (pc & 3)) * 4 + ((pc >> 2) & 1) * 2);
                asm volatile("st.relaxed.gpu.global.v2.u32 [%0], {%1, %2};" ::"l"(op), "r"(w0), "r"(w1) : "memory");
            } else {
                const int pc = head * 9 + head_pair(head & 3, i < 2 ? i * 4 + q : 8);
                uint32_t* op = g_O + ((rt * 72 + (pc >> 2)) * 8 + wq * 2) * 32 + g * 4 + (pc & 3);
                op[0] = w0;
                op[32] = w1;
            }
        }
    }
#pragma unroll
    for (int i = 0; i < 12; i++) o[i] = 0.f;
}
__device__ __forceinline__ void mbar_arrive(uint32_t b) { asm volatile("mbarrier.arrive.shared::cta.b64 _, [%0];" ::"r"(b) : "memory"); }
__device__ __forceinline__ void mbar_wait_sleep(uint32_t b, uint32_t ns) {
    uint32_t ok, spins = 0;
    while (true) {
        asm volatile("{\n.reg .pred p;\nmbarrier.try_wait.parity.shared::cta.b64 p, [%1], 0;\nselp.u32 %0, 1, 0, p;\n}\n" : "=r"(ok) : "r"(b) : "memory");
        if (ok) break;
        __nanosleep(ns);
        if (++spins > (1u << 21)) __trap();
    }
}
__device__ __forceinline__ void flag_signal(unsigned int* f) {
    __threadfence();
    atomicAdd(f, 1u);
}
__device__ __forceinline__ void flag_wait(const unsigned int* f, unsigned int target, unsigned int sleep_ns) {
    uint32_t v, spins = 0;
    while (true) {
        asm volatile("ld.acquire.gpu.global.u32 %0, [%1];" : "=r"(v) : "l"(f) : "memory");
        if (v >= target) break;
        if (sleep_ns) __nanosleep(sleep_ns);
        if (++spins > (1u << 21)) __trap();
    }
}
__device__ __forceinline__ uint4 hadd8_bf16(const uint4 a, const uint4 b) {
    return make_uint4(hadd2_bf16(a.x, b.x), hadd2_bf16(a.y, b.y), hadd2_bf16(a.z, b.z), hadd2_bf16(a.w, b.w));
}
__device__ __forceinline__ float sumsq2(uint32_t w) { return fmaf(bf_lo(w), bf_lo(w), bf_hi(w) * bf_hi(w)); }
__device__ __forceinline__ float sumsq8(const uint4 v) { return (sumsq2(v.x) + sumsq2(v.y)) + (sumsq2(v.z) + sumsq2(v.w)); }

enum { B_FULL = 0, B_EMPTY = 9, B_BASE = 18, B_XNDEAD = 19, B_QRDY = 20, B_FFN = 21, B_KV = 22, B_FREE = 38, B_WO = 46, B_RED = 55, B_X = 61, B_EARLY = 85, B_OS = 86, B_LATE = 94, B_BIAS = 95, B_END = 96 };

__global__ void __cluster_dims__(2, 1, 1) __launch_bounds__(384, 1)
fused_kernel(const __grid_constant__ CUtensorMap tmX, const __grid_constant__ CUtensorMap tmQ3, const __grid_constant__ CUtensorMap tmQ1,
          const __grid_constant__ CUtensorMap tm1, const __grid_constant__ CUtensorMap tm2, const __grid_constant__ CUtensorMap tmP,
          const __grid_constant__ CUtensorMap tmOut, const __grid_constant__ CUtensorMap tmXo, const __nv_bfloat16* __restrict__ b1,
          const __nv_bfloat16* __restrict__ wqkv, const __nv_bfloat16* __restrict__ w1, const __nv_bfloat16* __restrict__ w2,
          const __nv_bfloat16* __restrict__ wo, const __nv_bfloat16* __restrict__ b2,
          const uint64_t zero) {
    extern __shared__ __align__(1024) uint8_t smem[];
    const uint32_t sb = s2u(smem);
    const int tid = threadIdx.x, lane = tid & 31;
    const int warp = __shfl_sync(~0u, tid >> 5, 0);
    const uint32_t rank = blockIdx.x & 1;
    const int cl = blockIdx.x >> 1;
    const int rb = (cl & 7) * 2 + rank;
    const int j = cl >> 3;
    const uint32_t bar0 = sb + K1_OFF_BAR;
    const uint32_t full0 = bar0 + B_FULL * 8, empty0 = bar0 + B_EMPTY * 8, xbar0 = bar0 + B_X * 8;
    const int head = blockIdx.x >> 2, quarter = blockIdx.x & 3;
    const int rt = quarter * 8 + (head >> 2), ct = head & 3;
    const int rot = head >> 3;
    const int ks0 = ((((head >> 3) + 2) & 3) * 9);
    volatile uint32_t* slow_flag = reinterpret_cast<volatile uint32_t*>(smem + K1_OFF_BAR + B_END * 8);

    if (warp < 8) {
        PROF(0);
        PROFT(48);
        if (lane == 0) {
#pragma unroll
            for (int i = 0; i < 3; i++) mbar_init(xbar0 + (warp * 3 + i) * 8, 1);
            fence_barrier_init();
#pragma unroll 1
            for (int i = 0; i < 3; i++) {
                const uint32_t xb = xbar0 + (warp * 3 + i) * 8;
                mbar_expect(xb, 6144);
                tma4d(sb + i * 49152 + warp * 6144, &tmX, 0, 0, i * 3, rb * 16 + warp * 2, xb);
            }
        }
        __syncwarp();
        cluster_arrive();
        PROF(22);
        reg_alloc<240>();
        PROF(23);
        float rs0, rs1;
        {
            const uint32_t la = sb + (warp * 2 + ((lane >> 3) & 1)) * 3072 + (lane & 7) * 128;
            uint32_t off[4];
#pragma unroll
            for (int i = 0; i < 4; i++) off[i] = la + (((i * 2 + (lane >> 4)) ^ (lane & 7)) << 4);
            float c1[4] = {0.f, 0.f, 0.f, 0.f}, c2[4] = {0.f, 0.f, 0.f, 0.f}, c3[4] = {0.f, 0.f, 0.f, 0.f};
            uint32_t a[36][4];
#pragma unroll
            for (int t = 0; t < 3; t++) {
                mbar_wait(xbar0 + (warp * 3 + t) * 8, 0);
                PROF(24 + t);
#pragma unroll
                for (int i = 0; i < 12; i++) ldsm4(a[t * 12 + i], off[i & 3] + t * 49152 + (i >> 2) * 1024);
#pragma unroll
                for (int i = t * 12; i < t * 12 + 12; i++) {
                    mma16816(c3, a[i], 0x3F803F80u, 0x3F803F80u);
                    mma16816(c1, a[i], a[i][0], a[i][2]);
                    mma16816(c2, a[i], a[i][1], a[i][3]);
                }
            }
            PROF(27);
            const int gg = lane >> 2, src = (lane & ~3) | (gg >> 1);
            const float m0 = c3[0] * (1.0f / DM), m1 = c3[2] * (1.0f / DM);
            const uint32_t mc0 = pack_bf16(-m0, -m0), mc1 = pack_bf16(-m1, -m1);
#pragma unroll
            for (int i = 0; i < 36; i++) {
#pragma unroll
                for (int k = 0; k < 4; k++) a[i][k] = hadd2_bf16(a[i][k], (k & 1) ? mc1 : mc0);
                stsm4(off[i & 3] + (i / 12) * 49152 + ((i >> 2) % 3) * 1024, a[i]);
            }
            const float q0 = __shfl_sync(~0u, (gg & 1) ? c1[1] : c1[0], src), q1 = __shfl_sync(~0u, (gg & 1) ? c2[3] : c2[2], src);
            rs0 = rsqrtf(fmaxf(fmaf(-m0, m0, q0 * (1.0f / DM)), 0.f) + 1e-5f);
            rs1 = rsqrtf(fmaxf(fmaf(-m1, m1, q1 * (1.0f / DM)), 0.f) + 1e-5f);
            if (__any_sync(~0u, fabsf(m0) * rs0 > 0.25f || fabsf(m1) * rs1 > 0.25f)) {
                const float d0 = -m0 - bf_lo(mc0), d1 = -m1 - bf_lo(mc1);
                const uint32_t md0 = pack_bf16(d0, d0), md1 = pack_bf16(d1, d1);
#pragma unroll 1
                for (int i = 0; i < 9; i++) {
#pragma unroll
                    for (int k4 = 0; k4 < 4; k4++) {
                        const uint32_t ad = off[k4] + (i / 3) * 49152 + (i % 3) * 1024;
                        uint32_t b[4];
                        ldsm4(b, ad);
#pragma unroll
                        for (int k = 0; k < 4; k++) b[k] = hadd2_bf16(b[k], (k & 1) ? md1 : md0);
                        stsm4(ad, b);
                    }
                }
            }
        }
        PROF(28);
        const int wg = warp >> 2, wq = warp & 3;
        fence_proxy_async();
        named_bar_sync(1 + wg, 128);
        cluster_wait();
        PROF(1);

        const int g = lane >> 2, q = lane & 3;
        K1Ctx c;
        c.full0 = full0;
        c.rel_addr = 0;
        c.descA = mk_desc(zero, sb + wg * 8 * 3072, 16, 3072, 1);
        c.descB = mk_desc(zero, sb + K1_OFF_RING, 2048, 1024, 1);
        c.phase = 0;
        uint32_t biasq = sb + K1_OFF_BIAS + q * 32;
        uint32_t bq[8];

        uint32_t h[144];
        float accA[32], accB[32];
        uint32_t qo[3], qt[3];
        {
            float accQ[108];
            uint32_t rel = 0;
            if (lane == 0 && wq < 2) asm("mapa.shared::cluster.u32 %0, %1, %2;" : "=r"(rel) : "r"(empty0), "r"(wq));
#pragma unroll 1
            for (int r = 0; r < 2; r++) {
                static_for<0, 9>([&](auto sc) {
                    constexpr int s = decltype(sc)::value;
                    c.begin_stage(s);
                    const uint64_t da = c.descA + (r ? a_off(18 + 2 * s) : a_off(2 * s));
                    wgmma_ss_n216<1, 0, ((2 * s) % 9) * 512>(accQ, da, c.descB, (r | s) != 0);
                    wgmma_ss_n216<1, 2, ((2 * s + 1) % 9) * 512>(accQ, da, c.descB, 1);
                    c.end_stage(s);
                    c.rel_addr = rel;
                });
                c.phase ^= 1;
            }
            PROF(2); PROFWT(54);
            mbar_wait(bar0 + B_BIAS * 8, 0);
            wg_wait<0>();
            reg_fence(accQ);
#pragma unroll
            for (int grp = 0; grp < 3; grp++) {
                const int G = 3 * j + grp, type = G >> 3;
                const uint32_t base = (G & 7) * 4 * KV_HEAD_BYTES + (rb * 16 + warp * 2) * KV_GROUP_BYTES + g * 16 + (type == 0 ? Q_OFFSET : (type == 2 ? 256 : 0));
                qo[grp] = base + (q >> 1) * 128 + (q & 1) * 8;
                qt[grp] = base + q * KV_HEAD_BYTES + (type == 0 ? 256 : (type == 2 ? 264 : 512));
#pragma unroll
                for (int hf = 0; hf < 2; hf++) {
                    const float sc = (hf ? rs1 : rs0) * (type == 0 ? QSCALE : ((type == 1 && ((POLY_MASK >> (warp * 2 + hf)) & 1)) ? 2.f : 1.f));
                    uint32_t w[9];
#pragma unroll
                    for (int i = 0; i < 9; i++) w[i] = pack_bf16(accQ[(grp * 9 + i) * 4 + hf * 2] * sc, accQ[(grp * 9 + i) * 4 + hf * 2 + 1] * sc);
                    uint32_t* d = h + 32 + hf * 32 + grp * 8;
                    d[0] = w[0]; d[1] = w[1]; d[2] = w[3]; d[3] = q >= 1 ? w[2] : w[4];
                    d[4] = w[5]; d[5] = q >= 2 ? w[4] : w[6]; d[6] = w[7]; d[7] = w[8];
                    h[32 + hf * 32 + 24 + grp] = q == 0 ? w[2] : (q == 1 ? w[4] : w[6]);
                }
            }
        }
        PROF(3); PROFWT(55);
#pragma unroll
        for (int i = 32; i < 112; i++)
            if (i >= 96 || (i & 31) >= 27) asm volatile("mov.u32 %0, 0;" : "=r"(h[i]));
#pragma unroll
        for (int i = 0; i < 32; i++) asm volatile("mov.f32 %0, 0f00000000;" : "=f"(accB[i]));
#pragma unroll
        for (int i = 0; i < 8; i++) bq[i] = 0;
#pragma unroll 1
        for (int p = 0; p < 4; p++) {
            uint8_t* const qb = g_QKV + p * KV_GROUP_BYTES;
            tile_pair<false, false>(c, accA, accB, h, [&](auto sc) {
                constexpr int s = decltype(sc)::value;
                if constexpr (s == 0) {
                    reg_fence(accB);
#pragma unroll
                    for (int i = 0; i < 80; i++) h[i] = h[i + 32];
                }
                if constexpr (s >= 1 && s <= 6) {
                    constexpr int grp = (s - 1) >> 1, k = ((s - 1) & 1) * 2;
                    st_pred2(p < 2, qb + qo[grp] + k * KV_HEAD_BYTES, h[grp * 8 + k * 2], h[grp * 8 + k * 2 + 1]);
                    st_pred2(p < 2, qb + qo[grp] + (k + 1) * KV_HEAD_BYTES, h[grp * 8 + k * 2 + 2], h[grp * 8 + k * 2 + 3]);
                    if constexpr (k == 2) st_pred1(p < 2, qb + qt[grp], h[24 + grp]);
                }
                if constexpr (s < 4) gelu_blocks<s * 2, 2, 80>(accB, h, bq, rs0, rs1);
                if constexpr (s == 4) load_bias(bq, biasq);
                if constexpr (s == 5) reg_fence(accA);
                if constexpr (s >= 5) gelu_blocks<(s - 5) * 2, 2, 96>(accA, h, bq, rs0, rs1);
                if constexpr (s == 8) load_bias(bq, biasq + 128);
            });
            if (p == 1) asm volatile("bar.arrive 3, 352;" ::: "memory");
            biasq += 256;
        }
        PROF(4); PROFWT(56);
        tile_pair<false, true>(c, accA, accB, h, [&](auto sc) {
            constexpr int s = decltype(sc)::value;
            if constexpr (s == 0) reg_fence(accB);
            if constexpr (s < 4) gelu_blocks<s * 2, 2, 112>(accB, h, bq, rs0, rs1);
            if constexpr (s == 4) load_bias(bq, biasq);
            if constexpr (s == 5) { reg_fence(accA); if (tid == wg * 128) mbar_arrive(bar0 + B_XNDEAD * 8); }
            if constexpr (s == 5 || s == 6) gelu_blocks<(s - 5) * 3, 3, 128>(accA, h, bq, rs0, rs1);
            if constexpr (s == 7) gelu_blocks<6, 2, 128>(accA, h, bq, rs0, rs1);
            if constexpr (s == 3 || s == 7) reg_fence(h);
        });
        PROF(5); PROFWT(57);
        uint4* pout = g_part + j * SLAB + rb * 36 * 256 + tid;
#pragma unroll 1
        for (int p = 0; p < 4; p++) {
            tile_pair<true, true>(c, accA, accB, h, [&](auto sc) {
                constexpr int s = decltype(sc)::value;
                if constexpr (s == 0) reg_fence(accB);
                if constexpr (s < 4) store_part<s>(accB, pout);
                if constexpr (s == 5) reg_fence(accA);
                if constexpr (s >= 5) store_part<s - 5>(accA, pout + 1024);
            });
            pout += 2048;
            PROF(6 + p);
        }
        wg_wait<0>();
        c.release(8);
        reg_fence(accB);
        store_part<0>(accB, pout); store_part<1>(accB, pout); store_part<2>(accB, pout); store_part<3>(accB, pout);
        __syncwarp();
        if (lane == 0) mbar_arrive(bar0 + B_FFN * 8);
        PROF(10); PROFWT(58);
        PROFT(49);

        mbar_wait(bar0 + B_QRDY * 8, 0);
        const uint32_t slow = __any_sync(~0u, *slow_flag != 0);
        const uint64_t kd0 = mk_desc(zero, sb + SM_KV, 0, KV_GROUP_BYTES, 0);
        const uint64_t vd0 = mk_desc(zero, sb + SM_KV + 256, KV_GROUP_BYTES, 128, 0);
        const uint64_t qd0 = mk_desc(zero, sb + SM_Q + wg * 4096, 128, 512, 0);
        const uint32_t kvbar = bar0 + B_KV * 8;
        float o[12];
#pragma unroll
        for (int i = 0; i < 12; i++) o[i] = 0.f;
        PROF(16);
        PROFT(50);
        if (!slow) {
            const uint32_t one2 = 0x3F803F80u + (uint32_t)zero;
            float s0[64], s1[64];
            uint32_t p0[32], p1[32];
            mbar_wait(kvbar, 0);
            reg_fence(o);
            wg_fence();
            issue_qk<0>(s0, qd0, kd0);
            wg_commit();
            wg_commit();
            uint64_t qd = qd0;
            const uint32_t fre = (tid == wg * 128) ? bar0 + B_FREE * 8 - 8 : 0;
#pragma unroll 1
            for (int pass = 0; pass < 4; pass++) {
                uint64_t vd = vd0, kd = kd0;
                uint32_t bn = kvbar + 8;
#pragma unroll 1
                for (int it = 0; it < 8; it++) {
                    mbar_wait(bn, 0);
                    if (it == 0 && pass != 0) {
                        wg_wait<0>();
                        reg_fence(o);
                        store_o<false>(o, quarter * 8 + ((pass - 1 + rot) & 3) * 2 + wg, head, wq, lane);
                        reg_fence(o);
                        __syncwarp();
                        if (lane == 0) mbar_arrive(bar0 + (B_OS + pass * 2 - 2 + wg) * 8);
                    }
                    wg_wait<1>();
                    reg_fence(s0);
                    wg_fence();
                    issue_qk<KV_TILE>(s1, qd, kd);
                    wg_commit();
                    if (pass == 3 && it > 0 && fre) mbar_arrive(fre + it * 8);
                    softmax_pv<0>(s0, p0, o, vd, one2);
                    kd += 2 * KV_TILE; bn += 8;
                    if (it == 7) { kd = kd0; bn = kvbar; qd += 512; }
                    mbar_wait(bn, 0);
                    wg_wait<1>();
                    reg_fence(s1);
                    wg_fence();
                    issue_qk<0>(s0, qd, kd);
                    wg_commit();
                    softmax_pv<KV_TILE>(s1, p1, o, vd, one2);
                    vd += 2 * KV_TILE; bn += 8;
                }
                if (pass == 0) PROF(17);
            }
            wg_wait<0>();
            reg_fence(o);
            reg_fence(s0);
            reg_fence(s1);
            store_o<true>(o, quarter * 8 + ((3 + rot) & 3) * 2 + wg, head, wq, lane);
        } else {
#pragma unroll 1
            for (int pass = 0; pass < 4; pass++) {
                float m0 = -INFINITY, m1 = -INFINITY;
                float s[64];
                uint32_t p[32];
#pragma unroll 1
                for (int t = 0; t < 16; t++) {
                    mbar_wait(kvbar + t * 8, 0);
                    wg_fence();
                    issue_qk<0>(s, qd0 + pass * 512, kd0 + t * KV_TILE);
                    wg_commit();
                    wg_wait<0>();
                    reg_fence(s);
                    float a0 = m0, a1 = m1;
#pragma unroll
                    for (int k = 0; k < 16; k++) {
                        if ((POLY_MASK >> k) & 1) {
#pragma unroll
                            for (int i = 0; i < 4; i++) s[k * 4 + i] *= 0.5f;
                        }
                        a0 = fmaxf(a0, fmaxf(s[k * 4 + 0], s[k * 4 + 1]));
                        a1 = fmaxf(a1, fmaxf(s[k * 4 + 2], s[k * 4 + 3]));
                    }
                    a0 = fmaxf(a0, __shfl_xor_sync(~0u, a0, 1)); a1 = fmaxf(a1, __shfl_xor_sync(~0u, a1, 1));
                    a0 = fmaxf(a0, __shfl_xor_sync(~0u, a0, 2)); a1 = fmaxf(a1, __shfl_xor_sync(~0u, a1, 2));
                    const float r0 = ex2(m0 - a0), r1 = ex2(m1 - a1);
                    m0 = a0; m1 = a1;
#pragma unroll
                    for (int i = 0; i < 3; i++) { o[i * 4] *= r0; o[i * 4 + 1] *= r0; o[i * 4 + 2] *= r1; o[i * 4 + 3] *= r1; }
#pragma unroll
                    for (int k = 0; k < 16; k++) {
                        p[k * 2 + 0] = pack_bf16(ex2(s[k * 4 + 0] - m0), ex2(s[k * 4 + 1] - m0));
                        p[k * 2 + 1] = pack_bf16(ex2(s[k * 4 + 2] - m1), ex2(s[k * 4 + 3] - m1));
                    }
                    reg_fence(p);
                    reg_fence(o);
                    wg_fence();
                    issue_pv<0>(o, p, vd0 + t * KV_TILE);
                    wg_commit();
                    wg_wait<0>();
                    reg_fence(o);
                }
                if (pass < 3) {
                    store_o<false>(o, quarter * 8 + ((pass + rot) & 3) * 2 + wg, head, wq, lane);
                    __syncwarp();
                    if (lane == 0) mbar_arrive(bar0 + (B_OS + pass * 2 + wg) * 8);
                }
            }
            store_o<true>(o, quarter * 8 + ((3 + rot) & 3) * 2 + wg, head, wq, lane);
            if (tid == wg * 128)
                for (int i = 0; i < 7; i++) mbar_arrive(bar0 + (B_FREE + i) * 8);
        }
        PROF(18);
        PROFT(51);

        if (tid == wg * 128) mbar_arrive(bar0 + (B_FREE + 7) * 8);
        const int t128 = tid & 127;
        uint32_t bv[9];
        uint2 fv[9];
        mbar_wait(bar0 + B_BASE * 8, 0);
#pragma unroll
        for (int i = 0; i < 9; i++) {
            bv[i] = __ldg(reinterpret_cast<const uint32_t*>(b2 + ct * 144 + wg * 72 + q * 2) + i * 4);
            fv[i] = __ldcg(g_ffn + (blockIdx.x * 18 + wg * 9 + i) * 128 + t128);
        }
        float acc[36];
        const uint64_t od = mk_desc(zero, sb, 1024, 128, 0), wd = mk_desc(zero, sb + wg * 9 * 128, 2304, 128, 0);
        static_for<0, 9>([&](auto pc) {
            constexpr int p = decltype(pc)::value;
            mbar_wait(bar0 + (B_WO + p) * 8, 0);
            wg_fence();
            wgmma_ss_n72<1, sm_ostep(p * 3) / 16, sm_wstep(p * 3) / 16>(acc, od, wd, p != 0);
            wgmma_ss_n72<1, sm_ostep(p * 3 + 1) / 16, sm_wstep(p * 3 + 1) / 16>(acc, od, wd, 1);
            wgmma_ss_n72<1, sm_ostep(p * 3 + 2) / 16, sm_wstep(p * 3 + 2) / 16>(acc, od, wd, 1);
            wg_commit();
            if constexpr (p == 1) {
                wg_wait<1>();
                if (t128 == 0) mbar_arrive(bar0 + B_EARLY * 8);
            }
        });
        wg_wait<0>();
        reg_fence(acc);
        PROF(29);
        uint4 al[9];
        {
            const uint4* ap = g_Olate + rt * 9 * 128 + t128;
            uint32_t spins = 0;
            bool ok;
            do {
                ok = true;
#pragma unroll
                for (int k = 0; k < 9; k++)
                    asm volatile("ld.relaxed.gpu.global.v4.u32 {%0, %1, %2, %3}, [%4];" : "=r"(al[k].x), "=r"(al[k].y), "=r"(al[k].z), "=r"(al[k].w) : "l"(ap + k * 128) : "memory");
#pragma unroll
                for (int k = 0; k < 9; k++) ok = ok && al[k].x != O_EMPTY && al[k].y != O_EMPTY && al[k].z != O_EMPTY && al[k].w != O_EMPTY;
                if (++spins > (1u << 20)) __trap();
            } while (!__all_sync(~0u, ok));
        }
        PROF(19);
        mbar_wait(bar0 + B_LATE * 8, 0);
        PROF(20);
        wg_fence();
        static_for<27, 36>([&](auto kc) {
            constexpr int k = decltype(kc)::value;
            wgmma_rs_n72<1, sm_wstep(k) / 16>(acc, al[k - 27].x, al[k - 27].y, al[k - 27].z, al[k - 27].w, wd, 1);
        });
        wg_commit();
        PROF(31);
        uint32_t* st = reinterpret_cast<uint32_t*>(smem + sm_piece(0) + wg * 9216) + (wq * 16 + g) * 36 + q;
        float bs[36];
#pragma unroll
        for (int i = 0; i < 9; i++) {
            const uint32_t x0 = st[i * 4], x1 = st[i * 4 + 288];
            bs[i * 4 + 0] = fmaf(bf_lo(fv[i].x), 0.5f, bf_lo(x0) + bf_lo(bv[i]));
            bs[i * 4 + 1] = fmaf(bf_hi(fv[i].x), 0.5f, bf_hi(x0) + bf_hi(bv[i]));
            bs[i * 4 + 2] = fmaf(bf_lo(fv[i].y), 0.5f, bf_lo(x1) + bf_lo(bv[i]));
            bs[i * 4 + 3] = fmaf(bf_hi(fv[i].y), 0.5f, bf_hi(x1) + bf_hi(bv[i]));
        }
        reg_fence(bs);
        wg_wait<0>();
        reg_fence(acc);
        PROF(32);
#pragma unroll
        for (int i = 0; i < 9; i++) {
            st[i * 4] = pack_bf16(acc[i * 4] + bs[i * 4], acc[i * 4 + 1] + bs[i * 4 + 1]);
            st[i * 4 + 288] = pack_bf16(acc[i * 4 + 2] + bs[i * 4 + 2], acc[i * 4 + 3] + bs[i * 4 + 3]);
        }
        fence_proxy_async();
        named_bar_sync(1 + wg, 128);
        if (t128 == 0) {
            asm volatile("cp.async.bulk.tensor.2d.global.shared::cta.bulk_group [%0, {%2, %3}], [%1];"
                         ::"l"(&tmOut), "r"(sb + sm_piece(0) + wg * 9216), "r"(ct * 144 + wg * 72), "r"(rt * 64) : "memory");
            asm volatile("cp.async.bulk.commit_group;" ::: "memory");
            asm volatile("cp.async.bulk.wait_group.read 0;" ::: "memory");
        }
        PROF(21);
        PROFT(52);
    } else {
        reg_dealloc<24>();
        if (warp == 8 && lane == 0) {
            prefetch_tmap(&tmQ3); prefetch_tmap(&tmQ1); prefetch_tmap(&tm1); prefetch_tmap(&tm2);
            #pragma unroll 1
            for (int i = 0; i < 9; i++) { mbar_init(full0 + i * 8, 1); mbar_init(empty0 + i * 8, 4); mbar_init(bar0 + (B_WO + i) * 8, 2); }
            mbar_init(bar0 + B_BASE * 8, 3); mbar_init(bar0 + B_XNDEAD * 8, 2); mbar_init(bar0 + B_QRDY * 8, 3); mbar_init(bar0 + B_FFN * 8, 8); mbar_init(bar0 + B_EARLY * 8, 2); mbar_init(bar0 + B_LATE * 8, 2); mbar_init(bar0 + B_BIAS * 8, 96);
#pragma unroll 1
            for (int i = 0; i < 16; i++) { mbar_init(bar0 + (B_KV + i) * 8, 1); mbar_init(bar0 + (B_FREE + (i & 7)) * 8, 2); if (i < 6) mbar_init(bar0 + (B_RED + i) * 8, 1); if (i < 6) mbar_init(bar0 + (B_OS + i) * 8, 4); }
            *slow_flag = 0;
            fence_barrier_init();
        }
        __syncwarp();
        cluster_arrive();
        cluster_wait();
        const uint8_t* kvsrc = g_QKV + (size_t)head * KV_HEAD_BYTES;
        if (warp == 8) {
            if (lane == 0) {
                int st = 0, u = rank, tile = -4;
                int es = 5;
                uint32_t eph = 1;
#pragma unroll 1
                for (int n = 0; n < 99; n++) {
                    mbar_wait(empty0 + es * 8, eph);
                    const uint32_t fb = full0 + st * 8, dst = sb + K1_OFF_RING + u * 8192;
                    mbar_expect(fb, 16384);
                    if (tile < 0) {
                        tma3d_mc(dst, &tmQ3, j * 216, n * 32 + rank * 16, 0, fb, 3);
                        tma2d_mc(dst + 6144, &tmQ1, j * 216 + 192, n * 32 + rank * 16, fb, 3);
                    } else if (tile < 9) {
                        tma2d_mc(dst, &tm1, j * 576 + tile * 64, u * 64, fb, 3);
                    } else {
                        tma2d_mc(dst, &tm2, (tile - 9) * 64, j * 576 + u * 64, fb, 3);
                    }
                    u += 2;
                    if (u >= 9) { u -= 9; tile++; }
                    if (++st == 9) st = 0;
                    if (++es == 9) { es = 0; eph ^= 1; }
                }
                mbar_wait(empty0 + 8 * 8, 0);
                mbar_wait(bar0 + B_QRDY * 8, 0);
                asm volatile("fence.proxy.async;" ::: "memory");
#pragma unroll 1
                for (int i = 11; i < NCHUNK; i++) {
                    mbar_expect(bar0 + (B_KV + i) * 8, CHUNK_BYTES);
                    bulk_load(sb + SM_KV + i * CHUNK_BYTES, kvsrc + i * CHUNK_BYTES, CHUNK_BYTES, bar0 + (B_KV + i) * 8);
                }
                const uint8_t* wsrc = g_Wo + ct * WO_TILE_BYTES;
                prefetch_tmap(&tmOut);
                mbar_wait_sleep(bar0 + B_BASE * 8, 500);
#pragma unroll 1
                for (int p = 0; p < 9; p++) {
                    if (p > 0) mbar_wait_sleep(bar0 + (B_FREE + p - 1) * 8, p == 1 ? 500 : 40);
                    const int k = ks0 + p * 3 >= 36 ? ks0 + p * 3 - 36 : ks0 + p * 3;
                    mbar_expect(bar0 + (B_WO + p) * 8, 13824);
                    bulk_load(sb + (p == 0 ? sm_piece(0) : (p == 1 ? sm_piece(1) : SM_KV + (p - 2) * PIECE)), wsrc + k * 4608, 13824, bar0 + (B_WO + p) * 8);
                }
                const int kl = ks0 == 0 ? 27 : ks0 - 9;
                mbar_expect(bar0 + B_LATE * 8, 9 * 4608);
                bulk_load(sb + sm_wstep(27), wsrc + kl * 4608, 8 * 4608, bar0 + B_LATE * 8);
                bulk_load(sb + sm_wstep(35), wsrc + (kl + 8) * 4608, 4608, bar0 + B_LATE * 8);
            }
        } else {
            const int ht = tid - 288;
            if (ht == 64) prefetch_l2(wqkv + blockIdx.x * (DM * 3 * DM / 128), DM * 3 * DM / 64);
            if (ht < 72) {
                const uint4 v = __ldg(reinterpret_cast<const uint4*>(b1 + j * 576) + ht);
                uint32_t* sbias = reinterpret_cast<uint32_t*>(smem + K1_OFF_BIAS) + (ht >> 3) * 32 + (ht & 7);
                sbias[0] = v.x; sbias[8] = v.y; sbias[16] = v.z; sbias[24] = v.w;
            }
            mbar_arrive(bar0 + B_BIAS * 8);
            PROFH(37);
#pragma unroll
            for (int i = 0; i < 3; i++) g_Olate[blockIdx.x * 288 + i * 96 + ht] = make_uint4(O_EMPTY, O_EMPTY, O_EMPTY, O_EMPTY);
#pragma unroll 1
            for (int i = ht; i < 512; i += 96) {
                const int key = i & 127;
                uint8_t* p = g_QKV + (size_t)(j * 4 + (i >> 7)) * KV_HEAD_BYTES + (rb * 16 + (key >> 3)) * KV_GROUP_BYTES + 512 + (key & 7) * 16;
                *reinterpret_cast<uint32_t*>(p + 4) = ((POLY_MASK >> (key >> 3)) & 1) ? 0x3F804000u : 0x00003F80u;
                *reinterpret_cast<uint32_t*>(p + 12) = 0x00003F80u;
            }
            if (ht == 32) prefetch_l2(w1 + blockIdx.x * (DM * FF / 128), DM * FF / 64);
#pragma unroll 2
            for (int i = blockIdx.x * 324 + ht; i < blockIdx.x * 324 + 324; i += 96) {
                const int k = i / 72, nc = i - k * 72, c4 = nc / 18;
                *reinterpret_cast<uint4*>(g_Wo + c4 * WO_TILE_BYTES + (k >> 3) * 2304 + (nc - c4 * 18) * 128 + (k & 7) * 16) =
                    __ldg(reinterpret_cast<const uint4*>(wo) + i);
            }
            PROFH(38);
            named_bar_sync(3, 352);
            if (ht == 32) prefetch_l2(w2 + blockIdx.x * (DM * FF / 128), DM * FF / 64);
            if (ht == 0) {
                flag_signal(&g_flags.qkv_stored[rb]);
                flag_wait(&g_flags.qkv_stored[rb], 8, 200);
            }
            named_bar_sync(7, 96);
            PROFH(39);
#pragma unroll 1
            for (int i = warp - 9; i < 16; i += 3) {
                const int hd = j * 4 + (i >> 2), key = (i & 3) * 32 + lane;
                const uint8_t* p = g_QKV + (size_t)hd * KV_HEAD_BYTES + (rb * 16 + (key >> 3)) * KV_GROUP_BYTES + (key & 7) * 16;
                const uint4 a = __ldcg(reinterpret_cast<const uint4*>(p)), b = __ldcg(reinterpret_cast<const uint4*>(p + 128));
                float n = sumsq2(__ldcg(reinterpret_cast<const uint32_t*>(p + 512))) + sumsq8(a) + sumsq8(b);
                if ((POLY_MASK >> (key >> 3)) & 1) n *= 0.25f;
#pragma unroll
                for (int o = 16; o; o >>= 1) n = fmaxf(n, __shfl_xor_sync(~0u, n, o));
                if (lane == 0) g_kmax[hd * 64 + rb * 4 + (i & 3)] = n;
            }
            named_bar_sync(7, 96);
            PROFH(40);
            if (ht == 0) {
                flag_signal(&g_flags.kv_ready);
                flag_wait(&g_flags.kv_ready, 128, 300);
                mbar_wait_sleep(bar0 + B_XNDEAD * 8, 300);
            }
            named_bar_sync(7, 96);
            PROFH(41);
            float kmax2;
            {
                const float2 v = __ldcg(reinterpret_cast<const float2*>(g_kmax + head * 64 + lane * 2));
                kmax2 = fmaxf(v.x, v.y);
#pragma unroll
                for (int o = 16; o; o >>= 1) kmax2 = fmaxf(kmax2, __shfl_xor_sync(~0u, kmax2, o));
            }
            asm volatile("fence.proxy.async;" ::: "memory");
            int chunk = warp - 9;
#pragma unroll 1
            for (int r = ht; r < 512; r += 96) {
                if (lane == 0 && chunk < 11) {
                    mbar_expect(bar0 + (B_KV + chunk) * 8, CHUNK_BYTES);
                    bulk_load(sb + SM_KV + chunk * CHUNK_BYTES, kvsrc + chunk * CHUNK_BYTES, CHUNK_BYTES, bar0 + (B_KV + chunk) * 8);
                }
                chunk += 3;
                const uint8_t* p = kvsrc + Q_OFFSET + (quarter * 64 + (((r >> 3) + rot * 16) & 63)) * KV_GROUP_BYTES + (r & 7) * 16;
                const uint4 a = __ldcg(reinterpret_cast<const uint4*>(p)), b = __ldcg(reinterpret_cast<const uint4*>(p + 128));
                const uint32_t e = __ldcg(reinterpret_cast<const uint32_t*>(p + 256));
                const float cc = sqrtf((sumsq2(e) + sumsq8(a) + sumsq8(b)) * kmax2) * 1.02f;
                if (!(cc <= 58.f)) *slow_flag = 1;
                uint4* dst = reinterpret_cast<uint4*>(smem + SM_Q + (r >> 3) * 512 + (r & 7) * 16);
                dst[0] = a;
                dst[8] = b;
                dst[16] = make_uint4(e, pack_bf16(-cc, 768.f), 0u, 0u);
                dst[24] = make_uint4(0u, POLY_MODE ? 0xBFFF0000u : 0xC0000000u, 0u, 0u);
            }
            named_bar_sync(7, 96);
            if (*slow_flag) {
#pragma unroll 1
                for (int r = ht; r < 512; r += 96) {
                    uint32_t* dst = reinterpret_cast<uint32_t*>(smem + SM_Q + (r >> 3) * 512 + (r & 7) * 16);
                    dst[65] = 0u;
                    dst[97] = 0u;
                }
            }
            fence_proxy_async();
            __syncwarp();
            if (lane == 0) mbar_arrive(bar0 + B_QRDY * 8);
            PROFH(42);
            if (ht == 0) {
                mbar_wait_sleep(bar0 + B_FFN * 8, 300);
                flag_signal(&g_flags.ffn_done[rb]);
                flag_wait(&g_flags.ffn_done[rt >> 1], 8, 300);
            }
            named_bar_sync(7, 96);
            {
                const int w3 = warp - 9;
                const uint32_t rbar = bar0 + (B_RED + w3 * 2) * 8, rbuf = SM_RED + w3 * 8192;
                const int u0 = ((rt >> 1) * 36 + ct * 9) * 256 + (rt & 1) * 128;
                mbar_wait_sleep(bar0 + (B_KV + 15) * 8, 500);
                asm volatile("fence.proxy.async;" ::: "memory");
#pragma unroll 1
                for (int i = -2; i < 12; i++) {
                    if (i >= 0) {
                        __nanosleep(400);
                        mbar_wait(rbar + (i & 1) * 8, (i >> 1) & 1);
                        const uint4* sp = reinterpret_cast<const uint4*>(smem + rbuf + (i & 1) * 4096) + lane;
                        const uint4 v = hadd8_bf16(hadd8_bf16(hadd8_bf16(sp[0], sp[32]), hadd8_bf16(sp[64], sp[96])),
                                                   hadd8_bf16(hadd8_bf16(sp[128], sp[160]), hadd8_bf16(sp[192], sp[224])));
                        const int bx = i * 3 + w3;
                        uint2* fp = g_ffn + (blockIdx.x * 18 + (bx >> 2) * 2) * 128 + (bx & 3) * 32 + lane;
                        fp[0] = make_uint2(v.x, v.y);
                        fp[128] = make_uint2(v.z, v.w);
                    }
                    __syncwarp();
                    if (lane == 0 && i < 10) {
                        const int bx = (i + 2) * 3 + w3;
                        mbar_expect(rbar + (i & 1) * 8, 4096);
                        tma2d(sb + rbuf + (i & 1) * 4096, &tmP, (u0 + (bx >> 2) * 256 + (bx & 3) * 32) * 2, 0, rbar + (i & 1) * 8);
                    }
                }
            }
            __syncwarp();
            if (lane == 0) mbar_arrive(bar0 + B_BASE * 8);
            PROFH(43);
            if (ht == 0) {
#pragma unroll 1
                for (int i = 0; i < 6; i++) {
                    mbar_wait_sleep(bar0 + (B_OS + i) * 8, 200);
                    flag_signal(&g_flags.o_done[quarter * 8 + (((i >> 1) + rot) & 3) * 2 + (i & 1)]);
                }
            } else if (ht == 32) {
                const uint8_t* osrc = reinterpret_cast<const uint8_t*>(g_O) + rt * 73728;
                mbar_wait_sleep(bar0 + B_BASE * 8, 500);
                mbar_wait_sleep(bar0 + B_FREE * 8, 500);
                flag_wait(&g_flags.o_done[rt], 24, 100);
                if (atomicAdd(&g_flags.exited, 1u) == gridDim.x - 1) {
                    unsigned int* f = reinterpret_cast<unsigned int*>(&g_flags);
#pragma unroll 1
                    for (int i = 0; i < (int)(sizeof(Flags) / 4); i++) f[i] = 0;
                }
                prefetch_tmap(&tmXo);
                asm volatile("fence.proxy.async;" ::: "memory");
#pragma unroll 1
                for (int p = 0; p < 9; p++) {
                    if (p > 1) mbar_wait_sleep(bar0 + (B_FREE + p - 1) * 8, 40);
                    const int k = ks0 + p * 3 >= 36 ? ks0 + p * 3 - 36 : ks0 + p * 3;
                    mbar_expect(bar0 + (B_WO + p) * 8, 6144);
                    bulk_load(sb + 13824 + (p == 0 ? sm_piece(0) : (p == 1 ? sm_piece(1) : SM_KV + (p - 2) * PIECE)), osrc + k * 2048, 6144, bar0 + (B_WO + p) * 8);
                }
                mbar_expect(bar0 + B_LATE * 8, 2 * 9216);
                mbar_wait(bar0 + B_EARLY * 8, 0);
                tma2d(sb + sm_piece(0), &tmXo, ct * 144, rt * 64, bar0 + B_LATE * 8);
                tma2d(sb + sm_piece(0) + 9216, &tmXo, ct * 144 + 72, rt * 64, bar0 + B_LATE * 8);
            }
        }
    }
}

typedef CUresult (*EncodeFn)(CUtensorMap*, CUtensorMapDataType, cuuint32_t, void*, const cuuint64_t*, const cuuint64_t*, const cuuint32_t*,
                             const cuuint32_t*, CUtensorMapInterleave, CUtensorMapSwizzle, CUtensorMapL2promotion, CUtensorMapFloatOOBfill);

void make_map(EncodeFn fn, CUtensorMap* m, const void* base, int rank, const cuuint64_t* dims, const cuuint64_t* strides, const cuuint32_t* box) {
    cuuint32_t es[4] = {1, 1, 1, 1};
    fn(m, CU_TENSOR_MAP_DATA_TYPE_BFLOAT16, rank, const_cast<void*>(base), dims, strides, box, es, CU_TENSOR_MAP_INTERLEAVE_NONE,
       CU_TENSOR_MAP_SWIZZLE_128B, CU_TENSOR_MAP_L2_PROMOTION_L2_256B, CU_TENSOR_MAP_FLOAT_OOB_FILL_NONE);
}

}

extern "C" void kernel_launch(void* const* d_in, const int* in_sizes, int n_in, void* d_out, int out_size) {
    const __nv_bfloat16* x = (const __nv_bfloat16*)d_in[0];
    const __nv_bfloat16* wqkv = (const __nv_bfloat16*)d_in[1];
    const __nv_bfloat16* wo = (const __nv_bfloat16*)d_in[2];
    const __nv_bfloat16* w1 = (const __nv_bfloat16*)d_in[4];
    const __nv_bfloat16* b1 = (const __nv_bfloat16*)d_in[5];
    const __nv_bfloat16* w2 = (const __nv_bfloat16*)d_in[6];
    const __nv_bfloat16* b2 = (const __nv_bfloat16*)d_in[7];
    __nv_bfloat16* out = (__nv_bfloat16*)d_out;

    EncodeFn fn = nullptr;
    cudaDriverEntryPointQueryResult qr;
    cudaGetDriverEntryPoint("cuTensorMapEncodeTiled", (void**)&fn, cudaEnableDefault, &qr);
    CUtensorMap tmX, tmQ3, tmQ1, tm1, tm2, tmP, tmOut, tmXo;
    {
        cuuint64_t d[2] = {DM, SEQ}, s[1] = {DM * 2};
        cuuint32_t b[2] = {72, 64}, es[2] = {1, 1};
        fn(&tmOut, CU_TENSOR_MAP_DATA_TYPE_BFLOAT16, 2, out, d, s, b, es, CU_TENSOR_MAP_INTERLEAVE_NONE, CU_TENSOR_MAP_SWIZZLE_NONE,
           CU_TENSOR_MAP_L2_PROMOTION_NONE, CU_TENSOR_MAP_FLOAT_OOB_FILL_NONE);
        fn(&tmXo, CU_TENSOR_MAP_DATA_TYPE_BFLOAT16, 2, const_cast<__nv_bfloat16*>(x), d, s, b, es, CU_TENSOR_MAP_INTERLEAVE_NONE,
           CU_TENSOR_MAP_SWIZZLE_NONE, CU_TENSOR_MAP_L2_PROMOTION_NONE, CU_TENSOR_MAP_FLOAT_OOB_FILL_NONE);
    }
    {
        void* gp = nullptr;
        cudaGetSymbolAddress(&gp, g_part);
        cuuint64_t d[2] = {SLAB * 2, 8}, s[1] = {SLAB * 16};
        cuuint32_t b[2] = {64, 8}, es[2] = {1, 1};
        fn(&tmP, CU_TENSOR_MAP_DATA_TYPE_INT64, 2, gp, d, s, b, es, CU_TENSOR_MAP_INTERLEAVE_NONE, CU_TENSOR_MAP_SWIZZLE_NONE,
           CU_TENSOR_MAP_L2_PROMOTION_NONE, CU_TENSOR_MAP_FLOAT_OOB_FILL_NONE);
    }
    {
        cuuint64_t d[4] = {64, 8, 9, SEQ / 8}, s[3] = {DM * 2, 128, DM * 2 * 8};
        cuuint32_t b[4] = {64, 8, 3, 2};
        make_map(fn, &tmX, x, 4, d, s, b);
    }
    {
        cuuint64_t d[3] = {3 * DM, DM, 3}, s[2] = {3 * DM * 2, 128};
        cuuint32_t b[3] = {64, 16, 3};
        make_map(fn, &tmQ3, wqkv, 3, d, s, b);
        make_map(fn, &tmQ1, wqkv, 2, d, s, b);
    }
    {
        cuuint64_t d[2] = {FF, DM}, s[1] = {FF * 2};
        cuuint32_t b[2] = {64, 64};
        make_map(fn, &tm1, w1, 2, d, s, b);
        cuuint64_t d2[2] = {DM, FF}, s2[1] = {DM * 2};
        make_map(fn, &tm2, w2, 2, d2, s2, b);
    }
    cudaFuncSetAttribute(fused_kernel, cudaFuncAttributeMaxDynamicSharedMemorySize, K1_SMEM);
    fused_kernel<<<128, 384, K1_SMEM, cudaStreamPerThread>>>(tmX, tmQ3, tmQ1, tm1, tm2, tmP, tmOut, tmXo, b1, wqkv, w1, w2, wo, b2, 0ull);
}
```

```cpp
#include <cuda_runtime.h>
#include <cuda_bf16.h>
#include <cuda.h>
#include <stdint.h>

#define PROF(i) do { } while (0)
#define PROFT(i) do { } while (0)
#define PROFH(i) do { } while (0)
#define PROFWT(i) do { } while (0)
#define PROF_WG 0

namespace {

constexpr int SEQ = 2048, DM = 576, FF = 4608, NH = 32, DH = 18;

constexpr int KV_GROUP_BYTES = 5 * 128;
constexpr int KV_HEAD_BYTES = (SEQ / 8) * KV_GROUP_BYTES;
constexpr int Q_OFFSET = NH * KV_HEAD_BYTES;
#define POLY_MASK 0xB6B6
__device__ __align__(1024) uint8_t g_QKV[2 * NH * KV_HEAD_BYTES];
__device__ __align__(1024) float g_kmax[NH * 64];
constexpr int SLAB = 16 * 36 * 256;
__device__ __align__(1024) uint4 g_part[8 * SLAB];
__device__ __align__(1024) uint2 g_ffn[128 * 18 * 128];
__device__ __align__(1024) uint32_t g_O[SEQ * DM / 2];
struct Flags {
    unsigned int qkv_stored[16];
    unsigned int ffn_done[16];
    unsigned int o_done[32];
    unsigned int kv_ready;
    unsigned int exited;
};
__device__ Flags g_flags;
__device__ __align__(1024) uint4 g_Olate[32 * 9 * 128];
constexpr uint32_t O_EMPTY = 0xFFFFFFFFu;
constexpr int WO_TILE_BYTES = DM * 144 * 2;
__device__ __align__(1024) uint8_t g_Wo[4 * WO_TILE_BYTES];

__device__ __forceinline__ uint32_t s2u(const void* p) { return (uint32_t)__cvta_generic_to_shared(p); }
__device__ __forceinline__ void mbar_init(uint32_t b, int c) { asm volatile("mbarrier.init.shared::cta.b64 [%0], %1;" ::"r"(b), "r"(c) : "memory"); }
__device__ __forceinline__ void mbar_expect(uint32_t b, uint32_t bytes) {
    asm volatile("mbarrier.arrive.expect_tx.shared::cta.b64 _, [%0], %1;" ::"r"(b), "r"(bytes) : "memory");
}
__device__ __forceinline__ void mbar_wait(uint32_t b, uint32_t parity) {
    asm volatile(
        "{\n.reg .pred p;\n.reg .u32 c;\n"
        "mov.u32 c, 0;\n"
        "LOOP:\n"
        "mbarrier.try_wait.parity.shared::cta.b64 p, [%0], %1;\n"
        "@p bra DONE;\n"
        "add.u32 c, c, 1;\n"
        "setp.lt.u32 p, c, 4194304;\n"
        "@p bra LOOP;\n"
        "trap;\n"
        "DONE:\n}\n" ::"r"(b), "r"(parity) : "memory");
}
__device__ __forceinline__ void fence_barrier_init() { asm volatile("fence.mbarrier_init.release.cluster;" ::: "memory"); }
__device__ __forceinline__ void fence_proxy_async() { asm volatile("fence.proxy.async.shared::cta;" ::: "memory"); }
__device__ __forceinline__ void cluster_arrive() { asm volatile("barrier.cluster.arrive.relaxed.aligned;" ::: "memory"); }
__device__ __forceinline__ void cluster_wait() { asm volatile("barrier.cluster.wait.aligned;" ::: "memory"); }
__device__ __forceinline__ void named_bar_sync(int id, int n) { asm volatile("bar.sync %0, %1;" ::"r"(id), "r"(n) : "memory"); }

__device__ __forceinline__ void tma3d_mc(uint32_t dst, const CUtensorMap* tm, int c0, int c1, int c2, uint32_t bar, uint16_t mask) {
    asm volatile("cp.async.bulk.tensor.3d.shared::cluster.global.mbarrier::complete_tx::bytes.multicast::cluster [%0], [%1, {%3, %4, %5}], [%2], %6;"
                 ::"r"(dst), "l"(tm), "r"(bar), "r"(c0), "r"(c1), "r"(c2), "h"(mask) : "memory");
}
__device__ __forceinline__ void tma2d_mc(uint32_t dst, const CUtensorMap* tm, int c0, int c1, uint32_t bar, uint16_t mask) {
    asm volatile("cp.async.bulk.tensor.2d.shared::cluster.global.mbarrier::complete_tx::bytes.multicast::cluster [%0], [%1, {%3, %4}], [%2], %5;"
                 ::"r"(dst), "l"(tm), "r"(bar), "r"(c0), "r"(c1), "h"(mask) : "memory");
}
__device__ __forceinline__ void tma4d(uint32_t dst, const CUtensorMap* tm, int c0, int c1, int c2, int c3, uint32_t bar) {
    asm volatile("cp.async.bulk.tensor.4d.shared::cluster.global.mbarrier::complete_tx::bytes [%0], [%1, {%3, %4, %5, %6}], [%2];"
                 ::"r"(dst), "l"(tm), "r"(bar), "r"(c0), "r"(c1), "r"(c2), "r"(c3) : "memory");
}
__device__ __forceinline__ void tma2d(uint32_t dst, const CUtensorMap* tm, int c0, int c1, uint32_t bar) {
    asm volatile("cp.async.bulk.tensor.2d.shared::cluster.global.mbarrier::complete_tx::bytes [%0], [%1, {%3, %4}], [%2];"
                 ::"r"(dst), "l"(tm), "r"(bar), "r"(c0), "r"(c1) : "memory");
}
__device__ __forceinline__ void bulk_load(uint32_t dst, const void* src, uint32_t bytes, uint32_t bar) {
    asm volatile("cp.async.bulk.shared::cluster.global.mbarrier::complete_tx::bytes [%0], [%1], %2, [%3];"
                 ::"r"(dst), "l"(src), "r"(bytes), "r"(bar) : "memory");
}
__device__ __forceinline__ void prefetch_l2(const void* p, uint32_t bytes) {
    asm volatile("cp.async.bulk.prefetch.L2.global [%0], %1;" ::"l"(p), "r"(bytes) : "memory");
}
__device__ __forceinline__ void prefetch_tmap(const CUtensorMap* tm) { asm volatile("prefetch.tensormap [%0];" ::"l"(tm) : "memory"); }

__device__ __forceinline__ void wg_fence() { asm volatile("wgmma.fence.sync.aligned;" ::: "memory"); }
__device__ __forceinline__ void wg_commit() { asm volatile("wgmma.commit_group.sync.aligned;" ::: "memory"); }
template <int N> __device__ __forceinline__ void wg_wait() { asm volatile("wgmma.wait_group.sync.aligned %0;" ::"n"(N) : "memory"); }
template <int N> __device__ __forceinline__ void reg_fence(float (&d)[N]) {
#pragma unroll
    for (int i = 0; i < N; i++) asm volatile("" : "+f"(d[i])::"memory");
}
template <int N> __device__ __forceinline__ void reg_fence(uint32_t (&d)[N]) {
#pragma unroll
    for (int i = 0; i < N; i++) asm volatile("" : "+r"(d[i])::"memory");
}
template <int R> __device__ __forceinline__ void reg_alloc() { asm volatile("setmaxnreg.inc.sync.aligned.u32 %0;" ::"n"(R)); }
template <int R> __device__ __forceinline__ void reg_dealloc() { asm volatile("setmaxnreg.dec.sync.aligned.u32 %0;" ::"n"(R)); }

__device__ __forceinline__ uint64_t mk_desc(uint64_t z, uint32_t addr, uint32_t lbo, uint32_t sbo, uint32_t swz) {
    return z + ((uint64_t)(((addr & 0x3FFFF) >> 4) | ((lbo >> 4) << 16)) | ((uint64_t)((sbo >> 4) | (swz << 30)) << 32));
}
__device__ __forceinline__ uint32_t pack_bf16(float lo, float hi) {
    uint32_t r;
    asm("cvt.rn.bf16x2.f32 %0, %1, %2;" : "=r"(r) : "f"(hi), "f"(lo));
    return r;
}
__device__ __forceinline__ float bf_lo(uint32_t w) { return __uint_as_float(w << 16); }
__device__ __forceinline__ float bf_hi(uint32_t w) { return __uint_as_float(w & 0xFFFF0000u); }
__device__ __forceinline__ float ex2(float x) {
    float r;
    asm("ex2.approx.ftz.f32 %0, %1;" : "=f"(r) : "f"(x));
    return r;
}
__device__ __forceinline__ float tanh_fast(float x) {
    float r;
    asm("tanh.approx.f32 %0, %1;" : "=f"(r) : "f"(x));
    return r;
}
__device__ __forceinline__ uint32_t hfma2_bf16(uint32_t a, uint32_t b, uint32_t c) {
    uint32_t r;
    asm("fma.rn.bf16x2 %0, %1, %2, %3;" : "=r"(r) : "r"(a), "r"(b), "r"(c));
    return r;
}
__device__ __forceinline__ uint32_t hadd2_bf16(uint32_t a, uint32_t b) {
    uint32_t r;
    asm("add.rn.bf16x2 %0, %1, %2;" : "=r"(r) : "r"(a), "r"(b));
    return r;
}
__device__ __forceinline__ void ldsm4(uint32_t (&a)[4], uint32_t addr) {
    asm volatile("ldmatrix.sync.aligned.m8n8.x4.shared.b16 {%0, %1, %2, %3}, [%4];" : "=r"(a[0]), "=r"(a[1]), "=r"(a[2]), "=r"(a[3]) : "r"(addr) : "memory");
}
__device__ __forceinline__ void stsm4(uint32_t addr, const uint32_t (&a)[4]) {
    asm volatile("stmatrix.sync.aligned.m8n8.x4.shared.b16 [%0], {%1, %2, %3, %4};" ::"r"(addr), "r"(a[0]), "r"(a[1]), "r"(a[2]), "r"(a[3]) : "memory");
}
__device__ __forceinline__ void mma16816(float (&c)[4], const uint32_t (&a)[4], uint32_t b0, uint32_t b1) {
    asm("mma.sync.aligned.m16n8k16.row.col.f32.bf16.bf16.f32 {%0, %1, %2, %3}, {%4, %5, %6, %7}, {%8, %9}, {%0, %1, %2, %3};"
        : "+f"(c[0]), "+f"(c[1]), "+f"(c[2]), "+f"(c[3]) : "r"(a[0]), "r"(a[1]), "r"(a[2]), "r"(a[3]), "r"(b0), "r"(b1));
}
__device__ __forceinline__ float gelu2(float u) {
    const float w = fmaf(u * u, 0.0356774081f, 0.7978845608f);
    return fmaf(u, tanh_fast(u * w), u);
}

template<int TB, int AOFF, int BOFF> __device__ __forceinline__ void wgmma_ss_n216(float (&d)[108], uint64_t da, uint64_t db, int sd) {
    asm volatile("{\n.reg .pred p;\n.reg .b64 ta, tb;\nsetp.ne.b32 p, %110, 0;\nadd.s64 ta, %108, %112;\nadd.s64 tb, %109, %113;\n"
      "wgmma.mma_async.sync.aligned.m64n216k16.f32.bf16.bf16 {%0, %1, %2, %3, %4, %5, %6, %7, %8, %9, %10, %11, %12, %13, %14, %15, %16, %17, %18, %19, %20, %21, %22, %23, %24, %25, %26, %27, %28, %29, %30, %31, %32, %33, %34, %35, %36, %37, %38, %39, %40, %41, %42, %43, %44, %45, %46, %47, %48, %49, %50, %51, %52, %53, %54, %55, %56, %57, %58, %59, %60, %61, %62, %63, %64, %65, %66, %67, %68, %69, %70, %71, %72, %73, %74, %75, %76, %77, %78, %79, %80, %81, %82, %83, %84, %85, %86, %87, %88, %89, %90, %91, %92, %93, %94, %95, %96, %97, %98, %99, %100, %101, %102, %103, %104, %105, %106, %107}, ta, tb, p, 1, 1, 0, %111;\n}\n"
      : "+f"(d[0]), "+f"(d[1]), "+f"(d[2]), "+f"(d[3]), "+f"(d[4]), "+f"(d[5]), "+f"(d[6]), "+f"(d[7]), "+f"(d[8]), "+f"(d[9]), "+f"(d[10]), "+f"(d[11]), "+f"(d[12]), "+f"(d[13]), "+f"(d[14]), "+f"(d[15]), "+f"(d[16]), "+f"(d[17]), "+f"(d[18]), "+f"(d[19]), "+f"(d[20]), "+f"(d[21]), "+f"(d[22]), "+f"(d[23]), "+f"(d[24]), "+f"(d[25]), "+f"(d[26]), "+f"(d[27]), "+f"(d[28]), "+f"(d[29]), "+f"(d[30]), "+f"(d[31]), "+f"(d[32]), "+f"(d[33]), "+f"(d[34]), "+f"(d[35]), "+f"(d[36]), "+f"(d[37]), "+f"(d[38]), "+f"(d[39]), "+f"(d[40]), "+f"(d[41]), "+f"(d[42]), "+f"(d[43]), "+f"(d[44]), "+f"(d[45]), "+f"(d[46]), "+f"(d[47]), "+f"(d[48]), "+f"(d[49]), "+f"(d[50]), "+f"(d[51]), "+f"(d[52]), "+f"(d[53]), "+f"(d[54]), "+f"(d[55]), "+f"(d[56]), "+f"(d[57]), "+f"(d[58]), "+f"(d[59]), "+f"(d[60]), "+f"(d[61]), "+f"(d[62]), "+f"(d[63]), "+f"(d[64]), "+f"(d[65]), "+f"(d[66]), "+f"(d[67]), "+f"(d[68]), "+f"(d[69]), "+f"(d[70]), "+f"(d[71]), "+f"(d[72]), "+f"(d[73]), "+f"(d[74]), "+f"(d[75]), "+f"(d[76]), "+f"(d[77]), "+f"(d[78]), "+f"(d[79]), "+f"(d[80]), "+f"(d[81]), "+f"(d[82]), "+f"(d[83]), "+f"(d[84]), "+f"(d[85]), "+f"(d[86]), "+f"(d[87]), "+f"(d[88]), "+f"(d[89]), "+f"(d[90]), "+f"(d[91]), "+f"(d[92]), "+f"(d[93]), "+f"(d[94]), "+f"(d[95]), "+f"(d[96]), "+f"(d[97]), "+f"(d[98]), "+f"(d[99]), "+f"(d[100]), "+f"(d[101]), "+f"(d[102]), "+f"(d[103]), "+f"(d[104]), "+f"(d[105]), "+f"(d[106]), "+f"(d[107])
      : "l"(da), "l"(db), "r"(sd), "n"(TB), "n"(AOFF), "n"(BOFF));
}

template<int TB, int AOFF, int BOFF> __device__ __forceinline__ void wgmma_ss_n128(float (&d)[64], uint64_t da, uint64_t db, int sd) {
    asm volatile("{\n.reg .pred p;\n.reg .b64 ta, tb;\nsetp.ne.b32 p, %66, 0;\nadd.s64 ta, %64, %68;\nadd.s64 tb, %65, %69;\n"
      "wgmma.mma_async.sync.aligned.m64n128k16.f32.bf16.bf16 {%0, %1, %2, %3, %4, %5, %6, %7, %8, %9, %10, %11, %12, %13, %14, %15, %16, %17, %18, %19, %20, %21, %22, %23, %24, %25, %26, %27, %28, %29, %30, %31, %32, %33, %34, %35, %36, %37, %38, %39, %40, %41, %42, %43, %44, %45, %46, %47, %48, %49, %50, %51, %52, %53, %54, %55, %56, %57, %58, %59, %60, %61, %62, %63}, ta, tb, p, 1, 1, 0, %67;\n}\n"
      : "+f"(d[0]), "+f"(d[1]), "+f"(d[2]), "+f"(d[3]), "+f"(d[4]), "+f"(d[5]), "+f"(d[6]), "+f"(d[7]), "+f"(d[8]), "+f"(d[9]), "+f"(d[10]), "+f"(d[11]), "+f"(d[12]), "+f"(d[13]), "+f"(d[14]), "+f"(d[15]), "+f"(d[16]), "+f"(d[17]), "+f"(d[18]), "+f"(d[19]), "+f"(d[20]), "+f"(d[21]), "+f"(d[22]), "+f"(d[23]), "+f"(d[24]), "+f"(d[25]), "+f"(d[26]), "+f"(d[27]), "+f"(d[28]), "+f"(d[29]), "+f"(d[30]), "+f"(d[31]), "+f"(d[32]), "+f"(d[33]), "+f"(d[34]), "+f"(d[35]), "+f"(d[36]), "+f"(d[37]), "+f"(d[38]), "+f"(d[39]), "+f"(d[40]), "+f"(d[41]), "+f"(d[42]), "+f"(d[43]), "+f"(d[44]), "+f"(d[45]), "+f"(d[46]), "+f"(d[47]), "+f"(d[48]), "+f"(d[49]), "+f"(d[50]), "+f"(d[51]), "+f"(d[52]), "+f"(d[53]), "+f"(d[54]), "+f"(d[55]), "+f"(d[56]), "+f"(d[57]), "+f"(d[58]), "+f"(d[59]), "+f"(d[60]), "+f"(d[61]), "+f"(d[62]), "+f"(d[63])
      : "l"(da), "l"(db), "r"(sd), "n"(TB), "n"(AOFF), "n"(BOFF));
}

template<int TB, int AOFF, int BOFF> __device__ __forceinline__ void wgmma_ss_n72(float (&d)[36], uint64_t da, uint64_t db, int sd) {
    asm volatile("{\n.reg .pred p;\n.reg .b64 ta, tb;\nsetp.ne.b32 p, %38, 0;\nadd.s64 ta, %36, %40;\nadd.s64 tb, %37, %41;\n"
      "wgmma.mma_async.sync.aligned.m64n72k16.f32.bf16.bf16 {%0, %1, %2, %3, %4, %5, %6, %7, %8, %9, %10, %11, %12, %13, %14, %15, %16, %17, %18, %19, %20, %21, %22, %23, %24, %25, %26, %27, %28, %29, %30, %31, %32, %33, %34, %35}, ta, tb, p, 1, 1, 0, %39;\n}\n"
      : "+f"(d[0]), "+f"(d[1]), "+f"(d[2]), "+f"(d[3]), "+f"(d[4]), "+f"(d[5]), "+f"(d[6]), "+f"(d[7]), "+f"(d[8]), "+f"(d[9]), "+f"(d[10]), "+f"(d[11]), "+f"(d[12]), "+f"(d[13]), "+f"(d[14]), "+f"(d[15]), "+f"(d[16]), "+f"(d[17]), "+f"(d[18]), "+f"(d[19]), "+f"(d[20]), "+f"(d[21]), "+f"(d[22]), "+f"(d[23]), "+f"(d[24]), "+f"(d[25]), "+f"(d[26]), "+f"(d[27]), "+f"(d[28]), "+f"(d[29]), "+f"(d[30]), "+f"(d[31]), "+f"(d[32]), "+f"(d[33]), "+f"(d[34]), "+f"(d[35])
      : "l"(da), "l"(db), "r"(sd), "n"(TB), "n"(AOFF), "n"(BOFF));
}

template<int TB, int BOFF> __device__ __forceinline__ void wgmma_rs_n24(float (&d)[12], uint32_t a0, uint32_t a1, uint32_t a2, uint32_t a3, uint64_t db, int sd) {
    asm volatile("{\n.reg .pred p;\n.reg .b64 tb;\nsetp.ne.b32 p, %17, 0;\nadd.s64 tb, %16, %19;\n"
      "wgmma.mma_async.sync.aligned.m64n24k16.f32.bf16.bf16 {%0, %1, %2, %3, %4, %5, %6, %7, %8, %9, %10, %11}, {%12, %13, %14, %15}, tb, p, 1, 1, %18;\n}\n"
      : "+f"(d[0]), "+f"(d[1]), "+f"(d[2]), "+f"(d[3]), "+f"(d[4]), "+f"(d[5]), "+f"(d[6]), "+f"(d[7]), "+f"(d[8]), "+f"(d[9]), "+f"(d[10]), "+f"(d[11])
      : "r"(a0), "r"(a1), "r"(a2), "r"(a3), "l"(db), "r"(sd), "n"(TB), "n"(BOFF));
}

template<int TB, int BOFF> __device__ __forceinline__ void wgmma_rs_n72(float (&d)[36], uint32_t a0, uint32_t a1, uint32_t a2, uint32_t a3, uint64_t db, int sd) {
    asm volatile("{\n.reg .pred p;\n.reg .b64 tb;\nsetp.ne.b32 p, %41, 0;\nadd.s64 tb, %40, %43;\n"
      "wgmma.mma_async.sync.aligned.m64n72k16.f32.bf16.bf16 {%0, %1, %2, %3, %4, %5, %6, %7, %8, %9, %10, %11, %12, %13, %14, %15, %16, %17, %18, %19, %20, %21, %22, %23, %24, %25, %26, %27, %28, %29, %30, %31, %32, %33, %34, %35}, {%36, %37, %38, %39}, tb, p, 1, 1, %42;\n}\n"
      : "+f"(d[0]), "+f"(d[1]), "+f"(d[2]), "+f"(d[3]), "+f"(d[4]), "+f"(d[5]), "+f"(d[6]), "+f"(d[7]), "+f"(d[8]), "+f"(d[9]), "+f"(d[10]), "+f"(d[11]), "+f"(d[12]), "+f"(d[13]), "+f"(d[14]), "+f"(d[15]), "+f"(d[16]), "+f"(d[17]), "+f"(d[18]), "+f"(d[19]), "+f"(d[20]), "+f"(d[21]), "+f"(d[22]), "+f"(d[23]), "+f"(d[24]), "+f"(d[25]), "+f"(d[26]), "+f"(d[27]), "+f"(d[28]), "+f"(d[29]), "+f"(d[30]), "+f"(d[31]), "+f"(d[32]), "+f"(d[33]), "+f"(d[34]), "+f"(d[35])
      : "r"(a0), "r"(a1), "r"(a2), "r"(a3), "l"(db), "r"(sd), "n"(TB), "n"(BOFF));
}

template<int TB, int AINC, int BINC> __device__ __forceinline__ void wgmma_ss_n64_pi(float (&d)[32], uint64_t& da, uint64_t& db, int sd) {
    asm volatile("{\n.reg .pred p;\nsetp.ne.b32 p, %34, 0;\n"
      "wgmma.mma_async.sync.aligned.m64n64k16.f32.bf16.bf16 {%0, %1, %2, %3, %4, %5, %6, %7, %8, %9, %10, %11, %12, %13, %14, %15, %16, %17, %18, %19, %20, %21, %22, %23, %24, %25, %26, %27, %28, %29, %30, %31}, %32, %33, p, 1, 1, 0, %35;\n"
      "add.s64 %32, %32, %36;\nadd.s64 %33, %33, %37;\n}\n"
      : "+f"(d[0]), "+f"(d[1]), "+f"(d[2]), "+f"(d[3]), "+f"(d[4]), "+f"(d[5]), "+f"(d[6]), "+f"(d[7]), "+f"(d[8]), "+f"(d[9]), "+f"(d[10]), "+f"(d[11]), "+f"(d[12]), "+f"(d[13]), "+f"(d[14]), "+f"(d[15]), "+f"(d[16]), "+f"(d[17]), "+f"(d[18]), "+f"(d[19]), "+f"(d[20]), "+f"(d[21]), "+f"(d[22]), "+f"(d[23]), "+f"(d[24]), "+f"(d[25]), "+f"(d[26]), "+f"(d[27]), "+f"(d[28]), "+f"(d[29]), "+f"(d[30]), "+f"(d[31]), "+l"(da), "+l"(db)
      : "r"(sd), "n"(TB), "n"(AINC), "n"(BINC));
}

template<int TB, int BINC> __device__ __forceinline__ void wgmma_rs_n64_pi(float (&d)[32], uint32_t a0, uint32_t a1, uint32_t a2, uint32_t a3, uint64_t& db, int sd) {
    asm volatile("{\n.reg .pred p;\nsetp.ne.b32 p, %37, 0;\n"
      "wgmma.mma_async.sync.aligned.m64n64k16.f32.bf16.bf16 {%0, %1, %2, %3, %4, %5, %6, %7, %8, %9, %10, %11, %12, %13, %14, %15, %16, %17, %18, %19, %20, %21, %22, %23, %24, %25, %26, %27, %28, %29, %30, %31}, {%33, %34, %35, %36}, %32, p, 1, 1, %38;\n"
      "add.s64 %32, %32, %39;\n}\n"
      : "+f"(d[0]), "+f"(d[1]), "+f"(d[2]), "+f"(d[3]), "+f"(d[4]), "+f"(d[5]), "+f"(d[6]), "+f"(d[7]), "+f"(d[8]), "+f"(d[9]), "+f"(d[10]), "+f"(d[11]), "+f"(d[12]), "+f"(d[13]), "+f"(d[14]), "+f"(d[15]), "+f"(d[16]), "+f"(d[17]), "+f"(d[18]), "+f"(d[19]), "+f"(d[20]), "+f"(d[21]), "+f"(d[22]), "+f"(d[23]), "+f"(d[24]), "+f"(d[25]), "+f"(d[26]), "+f"(d[27]), "+f"(d[28]), "+f"(d[29]), "+f"(d[30]), "+f"(d[31]), "+l"(db)
      : "r"(a0), "r"(a1), "r"(a2), "r"(a3), "r"(sd), "n"(TB), "n"(BINC));
}

constexpr int K1_XN_BYTES = 16 * 9216;
constexpr int K1_OFF_RING = K1_XN_BYTES;
constexpr int K1_OFF_BIAS = K1_OFF_RING + 10 * 8192;
constexpr int K1_OFF_BAR = K1_OFF_BIAS + 576 * 2;
constexpr int K1_SMEM = K1_OFF_BAR + 800;
constexpr float QSCALE = 0.23570226039551584f * 1.4426950408889634f;

struct K1Ctx {
    uint32_t full0;
    uint32_t rel_addr;
    uint64_t descA, descB;
    uint32_t phase;
    __device__ __forceinline__ void begin_stage(int s) {
        mbar_wait(full0 + s * 8, phase);
        wg_fence();
    }
    __device__ __forceinline__ void release(int s) {
        if (rel_addr) asm volatile("mbarrier.arrive.shared::cluster.b64 _, [%0];" ::"r"(rel_addr + s * 8) : "memory");
    }
    __device__ __forceinline__ void end_stage(int s) {
        wg_commit();
        wg_wait<1>();
        release(s == 0 ? 8 : s - 1);
    }
};

__host__ __device__ constexpr int a_off(int ks) { return ((ks / 12) * 49152 + ((ks >> 2) % 3) * 1024 + (ks & 3) * 32) >> 4; }

template <int V> struct IC { static constexpr int value = V; };
template <int I, int N, class F> __device__ __forceinline__ void static_for(F&& f) {
    if constexpr (I < N) { f(IC<I>{}); static_for<I + 1, N>(f); }
}

template <bool A_RS, bool B_RS, class Epi>
__device__ __forceinline__ void tile_pair(K1Ctx& c, float (&accA)[32], float (&accB)[32], uint32_t (&h)[144], Epi&& epi) {
    static_for<0, 9>([&](auto sc) {
        constexpr int s = decltype(sc)::value;
        c.begin_stage(s);
        static_for<0, 8>([&](auto tc) {
            constexpr int t = decltype(tc)::value, kk = s * 8 + t, ks = kk % 36;
            constexpr int db = ks == 35 ? -35 * 128 : 128, da = a_off((ks + 1) % 36) - a_off(ks);
            if constexpr (kk < 36) {
                if constexpr (A_RS) wgmma_rs_n64_pi<1, db>(accA, h[ks * 4], h[ks * 4 + 1], h[ks * 4 + 2], h[ks * 4 + 3], c.descB, ks != 0);
                else wgmma_ss_n64_pi<1, da, db>(accA, c.descA, c.descB, ks != 0);
            } else {
                if constexpr (B_RS) wgmma_rs_n64_pi<1, db>(accB, h[ks * 4], h[ks * 4 + 1], h[ks * 4 + 2], h[ks * 4 + 3], c.descB, ks != 0);
                else wgmma_ss_n64_pi<1, da, db>(accB, c.descA, c.descB, ks != 0);
            }
            if constexpr (t == 0) {
                c.end_stage(s);
                epi(sc);
                wg_fence();
            }
        });
        wg_commit();
    });
    c.phase ^= 1;
}

template <int B0, int NB, int HOFF>
__device__ __forceinline__ void gelu_blocks(const float (&acc)[32], uint32_t (&h)[144], const uint32_t (&bq)[8], float rs0, float rs1) {
#pragma unroll
    for (int b = B0; b < B0 + NB; b++) {
        const float b0 = bf_lo(bq[b]), b1 = bf_hi(bq[b]);
        h[HOFF + b * 2 + 0] = pack_bf16(gelu2(fmaf(acc[b * 4 + 0], rs0, b0)), gelu2(fmaf(acc[b * 4 + 1], rs0, b1)));
        h[HOFF + b * 2 + 1] = pack_bf16(gelu2(fmaf(acc[b * 4 + 2], rs1, b0)), gelu2(fmaf(acc[b * 4 + 3], rs1, b1)));
    }
#pragma unroll
    for (int i = HOFF + B0 * 2; i < HOFF + (B0 + NB) * 2; i++) asm volatile("" : "+r"(h[i]));
}
__device__ __forceinline__ void load_bias(uint32_t (&bq)[8], uint32_t addr) {
    asm volatile("ld.shared.v4.u32 {%0, %1, %2, %3}, [%4];" : "=r"(bq[0]), "=r"(bq[1]), "=r"(bq[2]), "=r"(bq[3]) : "r"(addr));
    asm volatile("ld.shared.v4.u32 {%0, %1, %2, %3}, [%4 + 16];" : "=r"(bq[4]), "=r"(bq[5]), "=r"(bq[6]), "=r"(bq[7]) : "r"(addr));
}
__device__ __forceinline__ void st_pred2(bool p, void* a, uint32_t x, uint32_t y) {
    asm volatile("{\n.reg .pred p;\nsetp.ne.u32 p, %3, 0;\n@p st.global.v2.u32 [%0], {%1, %2};\n}\n" ::"l"(a), "r"(x), "r"(y), "r"((uint32_t)p) : "memory");
}
__device__ __forceinline__ void st_pred1(bool p, void* a, uint32_t x) {
    asm volatile("{\n.reg .pred p;\nsetp.ne.u32 p, %2, 0;\n@p st.global.u32 [%0], %1;\n}\n" ::"l"(a), "r"(x), "r"((uint32_t)p) : "memory");
}
template <int S> __device__ __forceinline__ void store_part(const float (&o)[32], uint4* p) {
    uint4 v;
    v.x = pack_bf16(o[S * 8 + 0], o[S * 8 + 1]); v.y = pack_bf16(o[S * 8 + 2], o[S * 8 + 3]);
    v.z = pack_bf16(o[S * 8 + 4], o[S * 8 + 5]); v.w = pack_bf16(o[S * 8 + 6], o[S * 8 + 7]);
    p[S * 256] = v;
}

constexpr int NCHUNK = 16;
constexpr int CHUNK_BYTES = KV_HEAD_BYTES / NCHUNK;
constexpr int SM_Q = 0;
constexpr int SM_KV = 32768;
constexpr int PIECE = 19968;
__host__ __device__ constexpr int sm_piece(int p) { return p == 0 ? 209408 : (p == 1 ? 0 : SM_KV + (p - 2) * PIECE); }
__host__ __device__ constexpr int sm_wstep(int k) { return k < 27 ? sm_piece(k / 3) + (k % 3) * 4608 : (k < 35 ? SM_KV + 7 * PIECE + (k - 27) * 4608 : PIECE); }
__host__ __device__ constexpr int sm_ostep(int k) { return sm_piece(k / 3) + 13824 + (k % 3) * 2048; }
constexpr int SM_RED = SM_KV + KV_HEAD_BYTES;

__device__ __forceinline__ float exp2_fixed(float y) {
    const float u = __uint_as_float(__float_as_uint(y) & 0xFF807FFFu) - 512.02545f;
    float t = fmaf(u, 0.019497588f, 0.114550486f);
    t = fmaf(t, u, -0.29839927f);
    return fmaf(t, u, y);
}
__device__ __forceinline__ uint32_t pack_fixed(float lo, float hi) { return __byte_perm(__float_as_uint(lo), __float_as_uint(hi), 0x6521); }

#define PV_GROUP 4
#define POLY_MODE 1
__device__ __forceinline__ uint32_t exp2_packed(float y0, float y1, uint32_t one2) {
    const uint32_t w = pack_fixed(y0, y1);
    uint32_t m;
    asm("lop3.b32 %0, %1, 0x007F007F, %2, 0xEA;" : "=r"(m) : "r"(w), "r"(one2));
    const uint32_t d = hfma2_bf16(m, 0x3EF93EF9u, 0xBF38BF38u);
    const uint32_t e = hfma2_bf16(d, d, 0xBD71BD71u);
    return hfma2_bf16(w, e, w);
}
constexpr int KV_TILE = CHUNK_BYTES / 16;
template <int OFF> __device__ __forceinline__ void issue_qk(float (&s)[64], uint64_t qd, uint64_t kd) {
    wgmma_ss_n128<0, 0, OFF + (8 << 16)>(s, qd, kd, 0);
    wgmma_ss_n128<0, 16, OFF + 32>(s, qd, kd, 1);
}
template <int OFF> __device__ __forceinline__ void issue_pv(float (&o)[12], const uint32_t (&p)[32], uint64_t vd) {
    static_for<0, 8>([&](auto kc) {
        constexpr int k = decltype(kc)::value;
        wgmma_rs_n24<1, OFF + k * (2 * KV_GROUP_BYTES / 16)>(o, p[k * 4], p[k * 4 + 1], p[k * 4 + 2], p[k * 4 + 3], vd, 1);
    });
}
template <int OFF>
__device__ __forceinline__ void softmax_pv(const float (&s)[64], uint32_t (&p)[32], float (&o)[12], uint64_t vd, uint32_t one2) {
    static_for<0, 8 / PV_GROUP>([&](auto gc) {
        constexpr int g0 = decltype(gc)::value * PV_GROUP;
#pragma unroll
        for (int b = g0 * 2; b < (g0 + PV_GROUP) * 2; b++) {
            if ((POLY_MASK >> b) & 1) {
                p[b * 2 + 0] = exp2_packed(s[b * 4 + 0], s[b * 4 + 1], one2);
                p[b * 2 + 1] = exp2_packed(s[b * 4 + 2], s[b * 4 + 3], one2);
            } else {
                p[b * 2 + 0] = pack_bf16(ex2(s[b * 4 + 0]), ex2(s[b * 4 + 1]));
                p[b * 2 + 1] = pack_bf16(ex2(s[b * 4 + 2]), ex2(s[b * 4 + 3]));
            }
        }
#pragma unroll
        for (int i = g0 * 4; i < (g0 + PV_GROUP) * 4; i++) asm volatile("" : "+r"(p[i])::"memory");
        wg_fence();
        static_for<g0, g0 + PV_GROUP>([&](auto kc) {
            constexpr int k = decltype(kc)::value;
            wgmma_rs_n24<1, OFF + k * (2 * KV_GROUP_BYTES / 16)>(o, p[k * 4], p[k * 4 + 1], p[k * 4 + 2], p[k * 4 + 3], vd, 1);
        });
    });
    wg_commit();
}
__device__ __forceinline__ int head_pair(int hh, int i) {
    if (i == 8) return hh == 3 ? 0 : 8;
    const int q = i >> 1, t = (4 - hh) & 3;
    if ((i & 1) == 0) return t + q;
    return (hh == 1 || hh == 2) ? (q >= hh ? q - hh : t + 4 + q) : t + 4 + q;
}
template <bool LATE> __device__ __forceinline__ void store_o(float (&o)[12], int rt, int head, int wq, int lane) {
    const int g = lane >> 2, q = lane & 3;
    const float i0 = __fdividef(1.0f, __shfl_sync(~0u, o[8], lane | 3)), i1 = __fdividef(1.0f, __shfl_sync(~0u, o[10], lane | 3));
#pragma unroll
    for (int i = 0; i < 3; i++) {
        const uint32_t w0 = pack_bf16(o[i * 4] * i0, o[i * 4 + 1] * i0), w1 = pack_bf16(o[i * 4 + 2] * i1, o[i * 4 + 3] * i1);
        if (i < 2 || q == 2) {
            if constexpr (LATE) {
                const int pc = (head & 7) * 9 + head_pair(head & 3, i < 2 ? i * 4 + q : 8);
                uint32_t* op = reinterpret_cast<uint32_t*>(g_Olate) + (((rt * 9 + (pc >> 3)) * 128 + wq * 32 + g * 4 + (pc & 3)) * 4 + ((pc >> 2) & 1) * 2);
                asm volatile("st.relaxed.gpu.global.v2.u32 [%0], {%1, %2};" ::"l"(op), "r"(w0), "r"(w1) : "memory");
            } else {
                const int pc = head * 9 + head_pair(head & 3, i < 2 ? i * 4 + q : 8);
                uint32_t* op = g_O + ((rt * 72 + (pc >> 2)) * 8 + wq * 2) * 32 + g * 4 + (pc & 3);
                op[0] = w0;
                op[32] = w1;
            }
        }
    }
#pragma unroll
    for (int i = 0; i < 12; i++) o[i] = 0.f;
}
__device__ __forceinline__ void mbar_arrive(uint32_t b) { asm volatile("mbarrier.arrive.shared::cta.b64 _, [%0];" ::"r"(b) : "memory"); }
__device__ __forceinline__ void mbar_wait_sleep(uint32_t b, uint32_t ns) {
    uint32_t ok, spins = 0;
    while (true) {
        asm volatile("{\n.reg .pred p;\nmbarrier.try_wait.parity.shared::cta.b64 p, [%1], 0;\nselp.u32 %0, 1, 0, p;\n}\n" : "=r"(ok) : "r"(b) : "memory");
        if (ok) break;
        __nanosleep(ns);
        if (++spins > (1u << 21)) __trap();
    }
}
__device__ __forceinline__ void flag_signal(unsigned int* f) {
    __threadfence();
    atomicAdd(f, 1u);
}
__device__ __forceinline__ void flag_wait(const unsigned int* f, unsigned int target, unsigned int sleep_ns) {
    uint32_t v, spins = 0;
    while (true) {
        asm volatile("ld.acquire.gpu.global.u32 %0, [%1];" : "=r"(v) : "l"(f) : "memory");
        if (v >= target) break;
        if (sleep_ns) __nanosleep(sleep_ns);
        if (++spins > (1u << 21)) __trap();
    }
}
__device__ __forceinline__ uint4 hadd8_bf16(const uint4 a, const uint4 b) {
    return make_uint4(hadd2_bf16(a.x, b.x), hadd2_bf16(a.y, b.y), hadd2_bf16(a.z, b.z), hadd2_bf16(a.w, b.w));
}
__device__ __forceinline__ float sumsq2(uint32_t w) { return fmaf(bf_lo(w), bf_lo(w), bf_hi(w) * bf_hi(w)); }
__device__ __forceinline__ float sumsq8(const uint4 v) { return (sumsq2(v.x) + sumsq2(v.y)) + (sumsq2(v.z) + sumsq2(v.w)); }

enum { B_FULL = 0, B_EMPTY = 9, B_BASE = 18, B_XNDEAD = 19, B_QRDY = 20, B_FFN = 21, B_KV = 22, B_FREE = 38, B_WO = 46, B_RED = 55, B_X = 61, B_EARLY = 85, B_OS = 86, B_LATE = 94, B_BIAS = 95, B_END = 96 };

__global__ void __cluster_dims__(2, 1, 1) __launch_bounds__(384, 1)
fused_kernel(const __grid_constant__ CUtensorMap tmX, const __grid_constant__ CUtensorMap tmQ3, const __grid_constant__ CUtensorMap tmQ1,
          const __grid_constant__ CUtensorMap tm1, const __grid_constant__ CUtensorMap tm2, const __grid_constant__ CUtensorMap tmP,
          const __grid_constant__ CUtensorMap tmOut, const __grid_constant__ CUtensorMap tmXo, const __nv_bfloat16* __restrict__ b1,
          const __nv_bfloat16* __restrict__ wqkv, const __nv_bfloat16* __restrict__ w1, const __nv_bfloat16* __restrict__ w2,
          const __nv_bfloat16* __restrict__ wo, const __nv_bfloat16* __restrict__ b2,
          const uint64_t zero) {
    extern __shared__ __align__(1024) uint8_t smem[];
    const uint32_t sb = s2u(smem);
    const int tid = threadIdx.x, lane = tid & 31;
    const int warp = __shfl_sync(~0u, tid >> 5, 0);
    const uint32_t rank = blockIdx.x & 1;
    const int cl = blockIdx.x >> 1;
    const int rb = (cl & 7) * 2 + rank;
    const int j = cl >> 3;
    const uint32_t bar0 = sb + K1_OFF_BAR;
    const uint32_t full0 = bar0 + B_FULL * 8, empty0 = bar0 + B_EMPTY * 8, xbar0 = bar0 + B_X * 8;
    const int head = blockIdx.x >> 2, quarter = blockIdx.x & 3;
    const int rt = quarter * 8 + (head >> 2), ct = head & 3;
    const int rot = head >> 3;
    const int ks0 = ((((head >> 3) + 2) & 3) * 9);
    volatile uint32_t* slow_flag = reinterpret_cast<volatile uint32_t*>(smem + K1_OFF_BAR + B_END * 8);

    if (warp < 8) {
        PROF(0);
        PROFT(48);
        if (lane == 0) {
#pragma unroll
            for (int i = 0; i < 3; i++) mbar_init(xbar0 + (warp * 3 + i) * 8, 1);
            fence_barrier_init();
#pragma unroll 1
            for (int i = 0; i < 3; i++) {
                const uint32_t xb = xbar0 + (warp * 3 + i) * 8;
                mbar_expect(xb, 6144);
                tma4d(sb + i * 49152 + warp * 6144, &tmX, 0, 0, i * 3, rb * 16 + warp * 2, xb);
            }
        }
        __syncwarp();
        cluster_arrive();
        PROF(22);
        reg_alloc<240>();
        PROF(23);
        float rs0, rs1;
        {
            const uint32_t la = sb + (warp * 2 + ((lane >> 3) & 1)) * 3072 + (lane & 7) * 128;
            uint32_t off[4];
#pragma unroll
            for (int i = 0; i < 4; i++) off[i] = la + (((i * 2 + (lane >> 4)) ^ (lane & 7)) << 4);
            float c1[4] = {0.f, 0.f, 0.f, 0.f}, c2[4] = {0.f, 0.f, 0.f, 0.f}, c3[4] = {0.f, 0.f, 0.f, 0.f};
            uint32_t a[36][4];
#pragma unroll
            for (int t = 0; t < 3; t++) {
                mbar_wait(xbar0 + (warp * 3 + t) * 8, 0);
                PROF(24 + t);
#pragma unroll
                for (int i = 0; i < 12; i++) ldsm4(a[t * 12 + i], off[i & 3] + t * 49152 + (i >> 2) * 1024);
#pragma unroll
                for (int i = t * 12; i < t * 12 + 12; i++) {
                    mma16816(c3, a[i], 0x3F803F80u, 0x3F803F80u);
                    mma16816(c1, a[i], a[i][0], a[i][2]);
                    mma16816(c2, a[i], a[i][1], a[i][3]);
                }
            }
            PROF(27);
            const int gg = lane >> 2, src = (lane & ~3) | (gg >> 1);
            const float m0 = c3[0] * (1.0f / DM), m1 = c3[2] * (1.0f / DM);
            const uint32_t mc0 = pack_bf16(-m0, -m0), mc1 = pack_bf16(-m1, -m1);
#pragma unroll
            for (int i = 0; i < 36; i++) {
#pragma unroll
                for (int k = 0; k < 4; k++) a[i][k] = hadd2_bf16(a[i][k], (k & 1) ? mc1 : mc0);
                stsm4(off[i & 3] + (i / 12) * 49152 + ((i >> 2) % 3) * 1024, a[i]);
            }
            const float q0 = __shfl_sync(~0u, (gg & 1) ? c1[1] : c1[0], src), q1 = __shfl_sync(~0u, (gg & 1) ? c2[3] : c2[2], src);
            rs0 = rsqrtf(fmaxf(fmaf(-m0, m0, q0 * (1.0f / DM)), 0.f) + 1e-5f);
            rs1 = rsqrtf(fmaxf(fmaf(-m1, m1, q1 * (1.0f / DM)), 0.f) + 1e-5f);
            if (__any_sync(~0u, fabsf(m0) * rs0 > 0.25f || fabsf(m1) * rs1 > 0.25f)) {
                const float d0 = -m0 - bf_lo(mc0), d1 = -m1 - bf_lo(mc1);
                const uint32_t md0 = pack_bf16(d0, d0), md1 = pack_bf16(d1, d1);
#pragma unroll 1
                for (int i = 0; i < 9; i++) {
#pragma unroll
                    for (int k4 = 0; k4 < 4; k4++) {
                        const uint32_t ad = off[k4] + (i / 3) * 49152 + (i % 3) * 1024;
                        uint32_t b[4];
                        ldsm4(b, ad);
#pragma unroll
                        for (int k = 0; k < 4; k++) b[k] = hadd2_bf16(b[k], (k & 1) ? md1 : md0);
                        stsm4(ad, b);
                    }
                }
            }
        }
        PROF(28);
        const int wg = warp >> 2, wq = warp & 3;
        fence_proxy_async();
        named_bar_sync(1 + wg, 128);
        cluster_wait();
        PROF(1);

        const int g = lane >> 2, q = lane & 3;
        K1Ctx c;
        c.full0 = full0;
        c.rel_addr = 0;
        c.descA = mk_desc(zero, sb + wg * 8 * 3072, 16, 3072, 1);
        c.descB = mk_desc(zero, sb + K1_OFF_RING, 2048, 1024, 1);
        c.phase = 0;
        uint32_t biasq = sb + K1_OFF_BIAS + q * 32;
        uint32_t bq[8];

        uint32_t h[144];
        float accA[32], accB[32];
        uint32_t qo[3], qt[3];
        {
            float accQ[108];
            uint32_t rel = 0;
            if (lane == 0 && wq < 2) asm("mapa.shared::cluster.u32 %0, %1, %2;" : "=r"(rel) : "r"(empty0), "r"(wq));
#pragma unroll 1
            for (int r = 0; r < 2; r++) {
                static_for<0, 9>([&](auto sc) {
                    constexpr int s = decltype(sc)::value;
                    c.begin_stage(s);
                    const uint64_t da = c.descA + (r ? a_off(18 + 2 * s) : a_off(2 * s));
                    wgmma_ss_n216<1, 0, ((2 * s) % 9) * 512>(accQ, da, c.descB, (r | s) != 0);
                    wgmma_ss_n216<1, 2, ((2 * s + 1) % 9) * 512>(accQ, da, c.descB, 1);
                    c.end_stage(s);
                    c.rel_addr = rel;
                });
                c.phase ^= 1;
            }
            PROF(2); PROFWT(54);
            mbar_wait(bar0 + B_BIAS * 8, 0);
            wg_wait<0>();
            reg_fence(accQ);
#pragma unroll
            for (int grp = 0; grp < 3; grp++) {
                const int G = 3 * j + grp, type = G >> 3;
                const uint32_t base = (G & 7) * 4 * KV_HEAD_BYTES + (rb * 16 + warp * 2) * KV_GROUP_BYTES + g * 16 + (type == 0 ? Q_OFFSET : (type == 2 ? 256 : 0));
                qo[grp] = base + (q >> 1) * 128 + (q & 1) * 8;
                qt[grp] = base + q * KV_HEAD_BYTES + (type == 0 ? 256 : (type == 2 ? 264 : 512));
#pragma unroll
                for (int hf = 0; hf < 2; hf++) {
                    const float sc = (hf ? rs1 : rs0) * (type == 0 ? QSCALE : ((type == 1 && ((POLY_MASK >> (warp * 2 + hf)) & 1)) ? 2.f : 1.f));
                    uint32_t w[9];
#pragma unroll
                    for (int i = 0; i < 9; i++) w[i] = pack_bf16(accQ[(grp * 9 + i) * 4 + hf * 2] * sc, accQ[(grp * 9 + i) * 4 + hf * 2 + 1] * sc);
                    uint32_t* d = h + 32 + hf * 32 + grp * 8;
                    d[0] = w[0]; d[1] = w[1]; d[2] = w[3]; d[3] = q >= 1 ? w[2] : w[4];
                    d[4] = w[5]; d[5] = q >= 2 ? w[4] : w[6]; d[6] = w[7]; d[7] = w[8];
                    h[32 + hf * 32 + 24 + grp] = q == 0 ? w[2] : (q == 1 ? w[4] : w[6]);
                }
            }
        }
        PROF(3); PROFWT(55);
#pragma unroll
        for (int i = 32; i < 112; i++)
            if (i >= 96 || (i & 31) >= 27) asm volatile("mov.u32 %0, 0;" : "=r"(h[i]));
#pragma unroll
        for (int i = 0; i < 32; i++) asm volatile("mov.f32 %0, 0f00000000;" : "=f"(accB[i]));
#pragma unroll
        for (int i = 0; i < 8; i++) bq[i] = 0;
#pragma unroll 1
        for (int p = 0; p < 4; p++) {
            uint8_t* const qb = g_QKV + p * KV_GROUP_BYTES;
            tile_pair<false, false>(c, accA, accB, h, [&](auto sc) {
                constexpr int s = decltype(sc)::value;
                if constexpr (s == 0) {
                    reg_fence(accB);
#pragma unroll
                    for (int i = 0; i < 80; i++) h[i] = h[i + 32];
                }
                if constexpr (s >= 1 && s <= 6) {
                    constexpr int grp = (s - 1) >> 1, k = ((s - 1) & 1) * 2;
                    st_pred2(p < 2, qb + qo[grp] + k * KV_HEAD_BYTES, h[grp * 8 + k * 2], h[grp * 8 + k * 2 + 1]);
                    st_pred2(p < 2, qb + qo[grp] + (k + 1) * KV_HEAD_BYTES, h[grp * 8 + k * 2 + 2], h[grp * 8 + k * 2 + 3]);
                    if constexpr (k == 2) st_pred1(p < 2, qb + qt[grp], h[24 + grp]);
                }
                if constexpr (s < 4) gelu_blocks<s * 2, 2, 80>(accB, h, bq, rs0, rs1);
                if constexpr (s == 4) load_bias(bq, biasq);
                if constexpr (s == 5) reg_fence(accA);
                if constexpr (s >= 5) gelu_blocks<(s - 5) * 2, 2, 96>(accA, h, bq, rs0, rs1);
                if constexpr (s == 8) load_bias(bq, biasq + 128);
            });
            if (p == 1) asm volatile("bar.arrive 3, 352;" ::: "memory");
            biasq += 256;
        }
        PROF(4); PROFWT(56);
        tile_pair<false, true>(c, accA, accB, h, [&](auto sc) {
            constexpr int s = decltype(sc)::value;
            if constexpr (s == 0) reg_fence(accB);
            if constexpr (s < 4) gelu_blocks<s * 2, 2, 112>(accB, h, bq, rs0, rs1);
            if constexpr (s == 4) load_bias(bq, biasq);
            if constexpr (s == 5) { reg_fence(accA); if (tid == wg * 128) mbar_arrive(bar0 + B_XNDEAD * 8); }
            if constexpr (s == 5 || s == 6) gelu_blocks<(s - 5) * 3, 3, 128>(accA, h, bq, rs0, rs1);
            if constexpr (s == 7) gelu_blocks<6, 2, 128>(accA, h, bq, rs0, rs1);
            if constexpr (s == 3 || s == 7) reg_fence(h);
        });
        PROF(5); PROFWT(57);
        uint4* pout = g_part + j * SLAB + rb * 36 * 256 + tid;
#pragma unroll 1
        for (int p = 0; p < 4; p++) {
            tile_pair<true, true>(c, accA, accB, h, [&](auto sc) {
                constexpr int s = decltype(sc)::value;
                if constexpr (s == 0) reg_fence(accB);
                if constexpr (s < 4) store_part<s>(accB, pout);
                if constexpr (s == 5) reg_fence(accA);
                if constexpr (s >= 5) store_part<s - 5>(accA, pout + 1024);
            });
            pout += 2048;
            PROF(6 + p);
        }
        wg_wait<0>();
        c.release(8);
        reg_fence(accB);
        store_part<0>(accB, pout); store_part<1>(accB, pout); store_part<2>(accB, pout); store_part<3>(accB, pout);
        __syncwarp();
        if (lane == 0) mbar_arrive(bar0 + B_FFN * 8);
        PROF(10); PROFWT(58);
        PROFT(49);

        mbar_wait(bar0 + B_QRDY * 8, 0);
        const uint32_t slow = __any_sync(~0u, *slow_flag != 0);
        const uint64_t kd0 = mk_desc(zero, sb + SM_KV, 0, KV_GROUP_BYTES, 0);
        const uint64_t vd0 = mk_desc(zero, sb + SM_KV + 256, KV_GROUP_BYTES, 128, 0);
        const uint64_t qd0 = mk_desc(zero, sb + SM_Q + wg * 4096, 128, 512, 0);
        const uint32_t kvbar = bar0 + B_KV * 8;
        float o[12];
#pragma unroll
        for (int i = 0; i < 12; i++) o[i] = 0.f;
        PROF(16);
        PROFT(50);
        if (!slow) {
            const uint32_t one2 = 0x3F803F80u + (uint32_t)zero;
            float s0[64], s1[64];
            uint32_t p0[32], p1[32];
            mbar_wait(kvbar, 0);
            reg_fence(o);
            wg_fence();
            issue_qk<0>(s0, qd0, kd0);
            wg_commit();
            wg_commit();
            uint64_t qd = qd0;
            const uint32_t fre = (tid == wg * 128) ? bar0 + B_FREE * 8 - 8 : 0;
#pragma unroll 1
            for (int pass = 0; pass < 4; pass++) {
                uint64_t vd = vd0, kd = kd0;
                uint32_t bn = kvbar + 8;
#pragma unroll 1
                for (int it = 0; it < 8; it++) {
                    if (pass == 0) {
                        mbar_wait(bn, 0);
                        mbar_wait(it == 7 ? bn : bn + 8, 0);
                    }
                    if (it == 0 && pass != 0) {
                        wg_wait<0>();
                        reg_fence(o);
                        store_o<false>(o, quarter * 8 + ((pass - 1 + rot) & 3) * 2 + wg, head, wq, lane);
                        reg_fence(o);
                        __syncwarp();
                        if (lane == 0) mbar_arrive(bar0 + (B_OS + pass * 2 - 2 + wg) * 8);
                    }
                    wg_wait<1>();
                    reg_fence(s0);
                    wg_fence();
                    issue_qk<KV_TILE>(s1, qd, kd);
                    wg_commit();
                    if (pass == 3 && it > 0 && fre) mbar_arrive(fre + it * 8);
                    softmax_pv<0>(s0, p0, o, vd, one2);
                    kd += 2 * KV_TILE;
                    if (it == 7) { kd = kd0; qd += 512; }
                    wg_wait<1>();
                    reg_fence(s1);
                    wg_fence();
                    issue_qk<0>(s0, qd, kd);
                    wg_commit();
                    softmax_pv<KV_TILE>(s1, p1, o, vd, one2);
                    vd += 2 * KV_TILE; bn += 16;
                }
                if (pass == 0) PROF(17);
            }
            wg_wait<0>();
            reg_fence(o);
            reg_fence(s0);
            reg_fence(s1);
            store_o<true>(o, quarter * 8 + ((3 + rot) & 3) * 2 + wg, head, wq, lane);
        } else {
#pragma unroll 1
            for (int pass = 0; pass < 4; pass++) {
                float m0 = -INFINITY, m1 = -INFINITY;
                float s[64];
                uint32_t p[32];
#pragma unroll 1
                for (int t = 0; t < 16; t++) {
                    mbar_wait(kvbar + t * 8, 0);
                    wg_fence();
                    issue_qk<0>(s, qd0 + pass * 512, kd0 + t * KV_TILE);
                    wg_commit();
                    wg_wait<0>();
                    reg_fence(s);
                    float a0 = m0, a1 = m1;
#pragma unroll
                    for (int k = 0; k < 16; k++) {
                        if ((POLY_MASK >> k) & 1) {
#pragma unroll
                            for (int i = 0; i < 4; i++) s[k * 4 + i] *= 0.5f;
                        }
                        a0 = fmaxf(a0, fmaxf(s[k * 4 + 0], s[k * 4 + 1]));
                        a1 = fmaxf(a1, fmaxf(s[k * 4 + 2], s[k * 4 + 3]));
                    }
                    a0 = fmaxf(a0, __shfl_xor_sync(~0u, a0, 1)); a1 = fmaxf(a1, __shfl_xor_sync(~0u, a1, 1));
                    a0 = fmaxf(a0, __shfl_xor_sync(~0u, a0, 2)); a1 = fmaxf(a1, __shfl_xor_sync(~0u, a1, 2));
                    const float r0 = ex2(m0 - a0), r1 = ex2(m1 - a1);
                    m0 = a0; m1 = a1;
#pragma unroll
                    for (int i = 0; i < 3; i++) { o[i * 4] *= r0; o[i * 4 + 1] *= r0; o[i * 4 + 2] *= r1; o[i * 4 + 3] *= r1; }
#pragma unroll
                    for (int k = 0; k < 16; k++) {
                        p[k * 2 + 0] = pack_bf16(ex2(s[k * 4 + 0] - m0), ex2(s[k * 4 + 1] - m0));
                        p[k * 2 + 1] = pack_bf16(ex2(s[k * 4 + 2] - m1), ex2(s[k * 4 + 3] - m1));
                    }
                    reg_fence(p);
                    reg_fence(o);
                    wg_fence();
                    issue_pv<0>(o, p, vd0 + t * KV_TILE);
                    wg_commit();
                    wg_wait<0>();
                    reg_fence(o);
                }
                if (pass < 3) {
                    store_o<false>(o, quarter * 8 + ((pass + rot) & 3) * 2 + wg, head, wq, lane);
                    __syncwarp();
                    if (lane == 0) mbar_arrive(bar0 + (B_OS + pass * 2 + wg) * 8);
                }
            }
            store_o<true>(o, quarter * 8 + ((3 + rot) & 3) * 2 + wg, head, wq, lane);
            if (tid == wg * 128)
                for (int i = 0; i < 7; i++) mbar_arrive(bar0 + (B_FREE + i) * 8);
        }
        PROF(18);
        PROFT(51);

        if (tid == wg * 128) mbar_arrive(bar0 + (B_FREE + 7) * 8);
        const int t128 = tid & 127;
        uint32_t bv[9];
        uint2 fv[9];
        mbar_wait(bar0 + B_BASE * 8, 0);
#pragma unroll
        for (int i = 0; i < 9; i++) {
            bv[i] = __ldg(reinterpret_cast<const uint32_t*>(b2 + ct * 144 + wg * 72 + q * 2) + i * 4);
            fv[i] = __ldcg(g_ffn + (blockIdx.x * 18 + wg * 9 + i) * 128 + t128);
        }
        float acc[36];
        const uint64_t od = mk_desc(zero, sb, 1024, 128, 0), wd = mk_desc(zero, sb + wg * 9 * 128, 2304, 128, 0);
        static_for<0, 9>([&](auto pc) {
            constexpr int p = decltype(pc)::value;
            mbar_wait(bar0 + (B_WO + p) * 8, 0);
            wg_fence();
            wgmma_ss_n72<1, sm_ostep(p * 3) / 16, sm_wstep(p * 3) / 16>(acc, od, wd, p != 0);
            wgmma_ss_n72<1, sm_ostep(p * 3 + 1) / 16, sm_wstep(p * 3 + 1) / 16>(acc, od, wd, 1);
            wgmma_ss_n72<1, sm_ostep(p * 3 + 2) / 16, sm_wstep(p * 3 + 2) / 16>(acc, od, wd, 1);
            wg_commit();
            if constexpr (p == 1) {
                wg_wait<1>();
                if (t128 == 0) mbar_arrive(bar0 + B_EARLY * 8);
            }
        });
        wg_wait<0>();
        reg_fence(acc);
        PROF(29);
        uint4 al[9];
        {
            const uint4* ap = g_Olate + rt * 9 * 128 + t128;
            uint32_t spins = 0;
            bool ok;
            do {
                ok = true;
#pragma unroll
                for (int k = 0; k < 9; k++)
                    asm volatile("ld.relaxed.gpu.global.v4.u32 {%0, %1, %2, %3}, [%4];" : "=r"(al[k].x), "=r"(al[k].y), "=r"(al[k].z), "=r"(al[k].w) : "l"(ap + k * 128) : "memory");
#pragma unroll
                for (int k = 0; k < 9; k++) ok = ok && al[k].x != O_EMPTY && al[k].y != O_EMPTY && al[k].z != O_EMPTY && al[k].w != O_EMPTY;
                if (++spins > (1u << 20)) __trap();
            } while (!__all_sync(~0u, ok));
        }
        PROF(19);
        mbar_wait(bar0 + B_LATE * 8, 0);
        PROF(20);
        wg_fence();
        static_for<27, 36>([&](auto kc) {
            constexpr int k = decltype(kc)::value;
            wgmma_rs_n72<1, sm_wstep(k) / 16>(acc, al[k - 27].x, al[k - 27].y, al[k - 27].z, al[k - 27].w, wd, 1);
        });
        wg_commit();
        PROF(31);
        uint32_t* st = reinterpret_cast<uint32_t*>(smem + sm_piece(0) + wg * 9216) + (wq * 16 + g) * 36 + q;
        float bs[36];
#pragma unroll
        for (int i = 0; i < 9; i++) {
            const uint32_t x0 = st[i * 4], x1 = st[i * 4 + 288];
            bs[i * 4 + 0] = fmaf(bf_lo(fv[i].x), 0.5f, bf_lo(x0) + bf_lo(bv[i]));
            bs[i * 4 + 1] = fmaf(bf_hi(fv[i].x), 0.5f, bf_hi(x0) + bf_hi(bv[i]));
            bs[i * 4 + 2] = fmaf(bf_lo(fv[i].y), 0.5f, bf_lo(x1) + bf_lo(bv[i]));
            bs[i * 4 + 3] = fmaf(bf_hi(fv[i].y), 0.5f, bf_hi(x1) + bf_hi(bv[i]));
        }
        reg_fence(bs);
        wg_wait<0>();
        reg_fence(acc);
        PROF(32);
#pragma unroll
        for (int i = 0; i < 9; i++) {
            st[i * 4] = pack_bf16(acc[i * 4] + bs[i * 4], acc[i * 4 + 1] + bs[i * 4 + 1]);
            st[i * 4 + 288] = pack_bf16(acc[i * 4 + 2] + bs[i * 4 + 2], acc[i * 4 + 3] + bs[i * 4 + 3]);
        }
        fence_proxy_async();
        named_bar_sync(1 + wg, 128);
        if (t128 == 0) {
            asm volatile("cp.async.bulk.tensor.2d.global.shared::cta.bulk_group [%0, {%2, %3}], [%1];"
                         ::"l"(&tmOut), "r"(sb + sm_piece(0) + wg * 9216), "r"(ct * 144 + wg * 72), "r"(rt * 64) : "memory");
            asm volatile("cp.async.bulk.commit_group;" ::: "memory");
            asm volatile("cp.async.bulk.wait_group.read 0;" ::: "memory");
        }
        PROF(21);
        PROFT(52);
    } else {
        reg_dealloc<24>();
        if (warp == 8 && lane == 0) {
            prefetch_tmap(&tmQ3); prefetch_tmap(&tmQ1); prefetch_tmap(&tm1); prefetch_tmap(&tm2);
            #pragma unroll 1
            for (int i = 0; i < 9; i++) { mbar_init(full0 + i * 8, 1); mbar_init(empty0 + i * 8, 4); mbar_init(bar0 + (B_WO + i) * 8, 2); }
            mbar_init(bar0 + B_BASE * 8, 3); mbar_init(bar0 + B_XNDEAD * 8, 2); mbar_init(bar0 + B_QRDY * 8, 3); mbar_init(bar0 + B_FFN * 8, 8); mbar_init(bar0 + B_EARLY * 8, 2); mbar_init(bar0 + B_LATE * 8, 2); mbar_init(bar0 + B_BIAS * 8, 96);
#pragma unroll 1
            for (int i = 0; i < 16; i++) { mbar_init(bar0 + (B_KV + i) * 8, 1); mbar_init(bar0 + (B_FREE + (i & 7)) * 8, 2); if (i < 6) mbar_init(bar0 + (B_RED + i) * 8, 1); if (i < 6) mbar_init(bar0 + (B_OS + i) * 8, 4); }
            *slow_flag = 0;
            fence_barrier_init();
        }
        __syncwarp();
        cluster_arrive();
        cluster_wait();
        const uint8_t* kvsrc = g_QKV + (size_t)head * KV_HEAD_BYTES;
        if (warp == 8) {
            if (lane == 0) {
                int st = 0, u = rank, tile = -4;
                int es = 5;
                uint32_t eph = 1;
#pragma unroll 1
                for (int n = 0; n < 99; n++) {
                    mbar_wait(empty0 + es * 8, eph);
                    const uint32_t fb = full0 + st * 8, dst = sb + K1_OFF_RING + u * 8192;
                    mbar_expect(fb, 16384);
                    if (tile < 0) {
                        tma3d_mc(dst, &tmQ3, j * 216, n * 32 + rank * 16, 0, fb, 3);
                        tma2d_mc(dst + 6144, &tmQ1, j * 216 + 192, n * 32 + rank * 16, fb, 3);
                    } else if (tile < 9) {
                        tma2d_mc(dst, &tm1, j * 576 + tile * 64, u * 64, fb, 3);
                    } else {
                        tma2d_mc(dst, &tm2, (tile - 9) * 64, j * 576 + u * 64, fb, 3);
                    }
                    u += 2;
                    if (u >= 9) { u -= 9; tile++; }
                    if (++st == 9) st = 0;
                    if (++es == 9) { es = 0; eph ^= 1; }
                }
                mbar_wait(empty0 + 8 * 8, 0);
                mbar_wait(bar0 + B_QRDY * 8, 0);
                asm volatile("fence.proxy.async;" ::: "memory");
#pragma unroll 1
                for (int i = 11; i < NCHUNK; i++) {
                    mbar_expect(bar0 + (B_KV + i) * 8, CHUNK_BYTES);
                    bulk_load(sb + SM_KV + i * CHUNK_BYTES, kvsrc + i * CHUNK_BYTES, CHUNK_BYTES, bar0 + (B_KV + i) * 8);
                }
                const uint8_t* wsrc = g_Wo + ct * WO_TILE_BYTES;
                prefetch_tmap(&tmOut);
                mbar_wait_sleep(bar0 + B_BASE * 8, 500);
#pragma unroll 1
                for (int p = 0; p < 9; p++) {
                    if (p > 0) mbar_wait_sleep(bar0 + (B_FREE + p - 1) * 8, p == 1 ? 500 : 40);
                    const int k = ks0 + p * 3 >= 36 ? ks0 + p * 3 - 36 : ks0 + p * 3;
                    mbar_expect(bar0 + (B_WO + p) * 8, 13824);
                    bulk_load(sb + (p == 0 ? sm_piece(0) : (p == 1 ? sm_piece(1) : SM_KV + (p - 2) * PIECE)), wsrc + k * 4608, 13824, bar0 + (B_WO + p) * 8);
                }
                const int kl = ks0 == 0 ? 27 : ks0 - 9;
                mbar_expect(bar0 + B_LATE * 8, 9 * 4608);
                bulk_load(sb + sm_wstep(27), wsrc + kl * 4608, 8 * 4608, bar0 + B_LATE * 8);
                bulk_load(sb + sm_wstep(35), wsrc + (kl + 8) * 4608, 4608, bar0 + B_LATE * 8);
            }
        } else {
            const int ht = tid - 288;
            if (ht == 64) prefetch_l2(wqkv + blockIdx.x * (DM * 3 * DM / 128), DM * 3 * DM / 64);
            if (ht < 72) {
                const uint4 v = __ldg(reinterpret_cast<const uint4*>(b1 + j * 576) + ht);
                uint32_t* sbias = reinterpret_cast<uint32_t*>(smem + K1_OFF_BIAS) + (ht >> 3) * 32 + (ht & 7);
                sbias[0] = v.x; sbias[8] = v.y; sbias[16] = v.z; sbias[24] = v.w;
            }
            mbar_arrive(bar0 + B_BIAS * 8);
            PROFH(37);
#pragma unroll
            for (int i = 0; i < 3; i++) g_Olate[blockIdx.x * 288 + i * 96 + ht] = make_uint4(O_EMPTY, O_EMPTY, O_EMPTY, O_EMPTY);
#pragma unroll 1
            for (int i = ht; i < 512; i += 96) {
                const int key = i & 127;
                uint8_t* p = g_QKV + (size_t)(j * 4 + (i >> 7)) * KV_HEAD_BYTES + (rb * 16 + (key >> 3)) * KV_GROUP_BYTES + 512 + (key & 7) * 16;
                *reinterpret_cast<uint32_t*>(p + 4) = ((POLY_MASK >> (key >> 3)) & 1) ? 0x3F804000u : 0x00003F80u;
                *reinterpret_cast<uint32_t*>(p + 12) = 0x00003F80u;
            }
            if (ht == 32) prefetch_l2(w1 + blockIdx.x * (DM * FF / 128), DM * FF / 64);
#pragma unroll 2
            for (int i = blockIdx.x * 324 + ht; i < blockIdx.x * 324 + 324; i += 96) {
                const int k = i / 72, nc = i - k * 72, c4 = nc / 18;
                *reinterpret_cast<uint4*>(g_Wo + c4 * WO_TILE_BYTES + (k >> 3) * 2304 + (nc - c4 * 18) * 128 + (k & 7) * 16) =
                    __ldg(reinterpret_cast<const uint4*>(wo) + i);
            }
            PROFH(38);
            named_bar_sync(3, 352);
            if (ht == 32) prefetch_l2(w2 + blockIdx.x * (DM * FF / 128), DM * FF / 64);
            if (ht == 0) {
                flag_signal(&g_flags.qkv_stored[rb]);
                flag_wait(&g_flags.qkv_stored[rb], 8, 200);
            }
            named_bar_sync(7, 96);
            PROFH(39);
#pragma unroll 1
            for (int i = warp - 9; i < 16; i += 3) {
                const int hd = j * 4 + (i >> 2), key = (i & 3) * 32 + lane;
                const uint8_t* p = g_QKV + (size_t)hd * KV_HEAD_BYTES + (rb * 16 + (key >> 3)) * KV_GROUP_BYTES + (key & 7) * 16;
                const uint4 a = __ldcg(reinterpret_cast<const uint4*>(p)), b = __ldcg(reinterpret_cast<const uint4*>(p + 128));
                float n = sumsq2(__ldcg(reinterpret_cast<const uint32_t*>(p + 512))) + sumsq8(a) + sumsq8(b);
                if ((POLY_MASK >> (key >> 3)) & 1) n *= 0.25f;
#pragma unroll
                for (int o = 16; o; o >>= 1) n = fmaxf(n, __shfl_xor_sync(~0u, n, o));
                if (lane == 0) g_kmax[hd * 64 + rb * 4 + (i & 3)] = n;
            }
            named_bar_sync(7, 96);
            PROFH(40);
            if (ht == 0) {
                flag_signal(&g_flags.kv_ready);
                flag_wait(&g_flags.kv_ready, 128, 300);
                mbar_wait_sleep(bar0 + B_XNDEAD * 8, 300);
            }
            named_bar_sync(7, 96);
            PROFH(41);
            float kmax2;
            {
                const float2 v = __ldcg(reinterpret_cast<const float2*>(g_kmax + head * 64 + lane * 2));
                kmax2 = fmaxf(v.x, v.y);
#pragma unroll
                for (int o = 16; o; o >>= 1) kmax2 = fmaxf(kmax2, __shfl_xor_sync(~0u, kmax2, o));
            }
            asm volatile("fence.proxy.async;" ::: "memory");
            int chunk = warp - 9;
#pragma unroll 1
            for (int r = ht; r < 512; r += 96) {
                if (lane == 0 && chunk < 11) {
                    mbar_expect(bar0 + (B_KV + chunk) * 8, CHUNK_BYTES);
                    bulk_load(sb + SM_KV + chunk * CHUNK_BYTES, kvsrc + chunk * CHUNK_BYTES, CHUNK_BYTES, bar0 + (B_KV + chunk) * 8);
                }
                chunk += 3;
                const uint8_t* p = kvsrc + Q_OFFSET + (quarter * 64 + (((r >> 3) + rot * 16) & 63)) * KV_GROUP_BYTES + (r & 7) * 16;
                const uint4 a = __ldcg(reinterpret_cast<const uint4*>(p)), b = __ldcg(reinterpret_cast<const uint4*>(p + 128));
                const uint32_t e = __ldcg(reinterpret_cast<const uint32_t*>(p + 256));
                const float cc = sqrtf((sumsq2(e) + sumsq8(a) + sumsq8(b)) * kmax2) * 1.02f;
                if (!(cc <= 58.f)) *slow_flag = 1;
                uint4* dst = reinterpret_cast<uint4*>(smem + SM_Q + (r >> 3) * 512 + (r & 7) * 16);
                dst[0] = a;
                dst[8] = b;
                dst[16] = make_uint4(e, pack_bf16(-cc, 768.f), 0u, 0u);
                dst[24] = make_uint4(0u, POLY_MODE ? 0xBFFF0000u : 0xC0000000u, 0u, 0u);
            }
            named_bar_sync(7, 96);
            if (*slow_flag) {
#pragma unroll 1
                for (int r = ht; r < 512; r += 96) {
                    uint32_t* dst = reinterpret_cast<uint32_t*>(smem + SM_Q + (r >> 3) * 512 + (r & 7) * 16);
                    dst[65] = 0u;
                    dst[97] = 0u;
                }
            }
            fence_proxy_async();
            __syncwarp();
            if (lane == 0) mbar_arrive(bar0 + B_QRDY * 8);
            PROFH(42);
            if (ht == 0) {
                mbar_wait_sleep(bar0 + B_FFN * 8, 300);
                flag_signal(&g_flags.ffn_done[rb]);
                flag_wait(&g_flags.ffn_done[rt >> 1], 8, 300);
            }
            named_bar_sync(7, 96);
            {
                const int w3 = warp - 9;
                const uint32_t rbar = bar0 + (B_RED + w3 * 2) * 8, rbuf = SM_RED + w3 * 8192;
                const int u0 = ((rt >> 1) * 36 + ct * 9) * 256 + (rt & 1) * 128;
                mbar_wait_sleep(bar0 + (B_KV + 15) * 8, 500);
                asm volatile("fence.proxy.async;" ::: "memory");
#pragma unroll 1
                for (int i = -2; i < 12; i++) {
                    if (i >= 0) {
                        __nanosleep(400);
                        mbar_wait(rbar + (i & 1) * 8, (i >> 1) & 1);
                        const uint4* sp = reinterpret_cast<const uint4*>(smem + rbuf + (i & 1) * 4096) + lane;
                        const uint4 v = hadd8_bf16(hadd8_bf16(hadd8_bf16(sp[0], sp[32]), hadd8_bf16(sp[64], sp[96])),
                                                   hadd8_bf16(hadd8_bf16(sp[128], sp[160]), hadd8_bf16(sp[192], sp[224])));
                        const int bx = i * 3 + w3;
                        uint2* fp = g_ffn + (blockIdx.x * 18 + (bx >> 2) * 2) * 128 + (bx & 3) * 32 + lane;
                        fp[0] = make_uint2(v.x, v.y);
                        fp[128] = make_uint2(v.z, v.w);
                    }
                    __syncwarp();
                    if (lane == 0 && i < 10) {
                        const int bx = (i + 2) * 3 + w3;
                        mbar_expect(rbar + (i & 1) * 8, 4096);
                        tma2d(sb + rbuf + (i & 1) * 4096, &tmP, (u0 + (bx >> 2) * 256 + (bx & 3) * 32) * 2, 0, rbar + (i & 1) * 8);
                    }
                }
            }
            __syncwarp();
            if (lane == 0) mbar_arrive(bar0 + B_BASE * 8);
            PROFH(43);
            if (ht == 0) {
#pragma unroll 1
                for (int i = 0; i < 6; i++) {
                    mbar_wait_sleep(bar0 + (B_OS + i) * 8, 200);
                    flag_signal(&g_flags.o_done[quarter * 8 + (((i >> 1) + rot) & 3) * 2 + (i & 1)]);
                }
            } else if (ht == 32) {
                const uint8_t* osrc = reinterpret_cast<const uint8_t*>(g_O) + rt * 73728;
                mbar_wait_sleep(bar0 + B_BASE * 8, 500);
                mbar_wait_sleep(bar0 + B_FREE * 8, 500);
                flag_wait(&g_flags.o_done[rt], 24, 100);
                if (atomicAdd(&g_flags.exited, 1u) == gridDim.x - 1) {
                    unsigned int* f = reinterpret_cast<unsigned int*>(&g_flags);
#pragma unroll 1
                    for (int i = 0; i < (int)(sizeof(Flags) / 4); i++) f[i] = 0;
                }
                prefetch_tmap(&tmXo);
                asm volatile("fence.proxy.async;" ::: "memory");
#pragma unroll 1
                for (int p = 0; p < 9; p++) {
                    if (p > 1) mbar_wait_sleep(bar0 + (B_FREE + p - 1) * 8, 40);
                    const int k = ks0 + p * 3 >= 36 ? ks0 + p * 3 - 36 : ks0 + p * 3;
                    mbar_expect(bar0 + (B_WO + p) * 8, 6144);
                    bulk_load(sb + 13824 + (p == 0 ? sm_piece(0) : (p == 1 ? sm_piece(1) : SM_KV + (p - 2) * PIECE)), osrc + k * 2048, 6144, bar0 + (B_WO + p) * 8);
                }
                mbar_expect(bar0 + B_LATE * 8, 2 * 9216);
                mbar_wait(bar0 + B_EARLY * 8, 0);
                tma2d(sb + sm_piece(0), &tmXo, ct * 144, rt * 64, bar0 + B_LATE * 8);
                tma2d(sb + sm_piece(0) + 9216, &tmXo, ct * 144 + 72, rt * 64, bar0 + B_LATE * 8);
            }
        }
    }
}

typedef CUresult (*EncodeFn)(CUtensorMap*, CUtensorMapDataType, cuuint32_t, void*, const cuuint64_t*, const cuuint64_t*, const cuuint32_t*,
                             const cuuint32_t*, CUtensorMapInterleave, CUtensorMapSwizzle, CUtensorMapL2promotion, CUtensorMapFloatOOBfill);

void make_map(EncodeFn fn, CUtensorMap* m, const void* base, int rank, const cuuint64_t* dims, const cuuint64_t* strides, const cuuint32_t* box) {
    cuuint32_t es[4] = {1, 1, 1, 1};
    fn(m, CU_TENSOR_MAP_DATA_TYPE_BFLOAT16, rank, const_cast<void*>(base), dims, strides, box, es, CU_TENSOR_MAP_INTERLEAVE_NONE,
       CU_TENSOR_MAP_SWIZZLE_128B, CU_TENSOR_MAP_L2_PROMOTION_L2_256B, CU_TENSOR_MAP_FLOAT_OOB_FILL_NONE);
}

}

extern "C" void kernel_launch(void* const* d_in, const int* in_sizes, int n_in, void* d_out, int out_size) {
    const __nv_bfloat16* x = (const __nv_bfloat16*)d_in[0];
    const __nv_bfloat16* wqkv = (const __nv_bfloat16*)d_in[1];
    const __nv_bfloat16* wo = (const __nv_bfloat16*)d_in[2];
    const __nv_bfloat16* w1 = (const __nv_bfloat16*)d_in[4];
    const __nv_bfloat16* b1 = (const __nv_bfloat16*)d_in[5];
    const __nv_bfloat16* w2 = (const __nv_bfloat16*)d_in[6];
    const __nv_bfloat16* b2 = (const __nv_bfloat16*)d_in[7];
    __nv_bfloat16* out = (__nv_bfloat16*)d_out;

    EncodeFn fn = nullptr;
    cudaDriverEntryPointQueryResult qr;
    cudaGetDriverEntryPoint("cuTensorMapEncodeTiled", (void**)&fn, cudaEnableDefault, &qr);
    CUtensorMap tmX, tmQ3, tmQ1, tm1, tm2, tmP, tmOut, tmXo;
    {
        cuuint64_t d[2] = {DM, SEQ}, s[1] = {DM * 2};
        cuuint32_t b[2] = {72, 64}, es[2] = {1, 1};
        fn(&tmOut, CU_TENSOR_MAP_DATA_TYPE_BFLOAT16, 2, out, d, s, b, es, CU_TENSOR_MAP_INTERLEAVE_NONE, CU_TENSOR_MAP_SWIZZLE_NONE,
           CU_TENSOR_MAP_L2_PROMOTION_NONE, CU_TENSOR_MAP_FLOAT_OOB_FILL_NONE);
        fn(&tmXo, CU_TENSOR_MAP_DATA_TYPE_BFLOAT16, 2, const_cast<__nv_bfloat16*>(x), d, s, b, es, CU_TENSOR_MAP_INTERLEAVE_NONE,
           CU_TENSOR_MAP_SWIZZLE_NONE, CU_TENSOR_MAP_L2_PROMOTION_NONE, CU_TENSOR_MAP_FLOAT_OOB_FILL_NONE);
    }
    {
        void* gp = nullptr;
        cudaGetSymbolAddress(&gp, g_part);
        cuuint64_t d[2] = {SLAB * 2, 8}, s[1] = {SLAB * 16};
        cuuint32_t b[2] = {64, 8}, es[2] = {1, 1};
        fn(&tmP, CU_TENSOR_MAP_DATA_TYPE_INT64, 2, gp, d, s, b, es, CU_TENSOR_MAP_INTERLEAVE_NONE, CU_TENSOR_MAP_SWIZZLE_NONE,
           CU_TENSOR_MAP_L2_PROMOTION_NONE, CU_TENSOR_MAP_FLOAT_OOB_FILL_NONE);
    }
    {
        cuuint64_t d[4] = {64, 8, 9, SEQ / 8}, s[3] = {DM * 2, 128, DM * 2 * 8};
        cuuint32_t b[4] = {64, 8, 3, 2};
        make_map(fn, &tmX, x, 4, d, s, b);
    }
    {
        cuuint64_t d[3] = {3 * DM, DM, 3}, s[2] = {3 * DM * 2, 128};
        cuuint32_t b[3] = {64, 16, 3};
        make_map(fn, &tmQ3, wqkv, 3, d, s, b);
        make_map(fn, &tmQ1, wqkv, 2, d, s, b);
    }
    {
        cuuint64_t d[2] = {FF, DM}, s[1] = {FF * 2};
        cuuint32_t b[2] = {64, 64};
        make_map(fn, &tm1, w1, 2, d, s, b);
        cuuint64_t d2[2] = {DM, FF}, s2[1] = {DM * 2};
        make_map(fn, &tm2, w2, 2, d2, s2, b);
    }
    cudaFuncSetAttribute(fused_kernel, cudaFuncAttributeMaxDynamicSharedMemorySize, K1_SMEM);
    fused_kernel<<<128, 384, K1_SMEM, cudaStreamPerThread>>>(tmX, tmQ3, tmQ1, tm1, tm2, tmP, tmOut, tmXo, b1, wqkv, w1, w2, wo, b2, 0ull);
}
```

```cpp
#include <cuda_runtime.h>
#include <cuda_bf16.h>
#include <cuda.h>
#include <stdint.h>

#define PROF(i) do { } while (0)
#define PROFT(i) do { } while (0)
#define PROFH(i) do { } while (0)
#define PROFWT(i) do { } while (0)
#define PROF_WG 0

namespace {

constexpr int SEQ = 2048, DM = 576, FF = 4608, NH = 32, DH = 18;

constexpr int KV_GROUP_BYTES = 5 * 128;
constexpr int KV_HEAD_BYTES = (SEQ / 8) * KV_GROUP_BYTES;
constexpr int Q_OFFSET = NH * KV_HEAD_BYTES;
#define POLY_MASK 0xDADA
__device__ __align__(1024) uint8_t g_QKV[2 * NH * KV_HEAD_BYTES];
__device__ __align__(1024) float g_kmax[NH * 64];
constexpr int SLAB = 16 * 36 * 256;
__device__ __align__(1024) uint4 g_part[8 * SLAB];
__device__ __align__(1024) uint2 g_ffn[128 * 18 * 128];
__device__ __align__(1024) uint32_t g_O[SEQ * DM / 2];
struct Flags {
    unsigned int qkv_stored[16];
    unsigned int ffn_done[16];
    unsigned int o_done[32];
    unsigned int kv_ready;
    unsigned int exited;
};
__device__ Flags g_flags;
__device__ __align__(1024) uint4 g_Olate[32 * 9 * 128];
constexpr uint32_t O_EMPTY = 0xFFFFFFFFu;
constexpr int WO_TILE_BYTES = DM * 144 * 2;
__device__ __align__(1024) uint8_t g_Wo[4 * WO_TILE_BYTES];

__device__ __forceinline__ uint32_t s2u(const void* p) { return (uint32_t)__cvta_generic_to_shared(p); }
__device__ __forceinline__ void mbar_init(uint32_t b, int c) { asm volatile("mbarrier.init.shared::cta.b64 [%0], %1;" ::"r"(b), "r"(c) : "memory"); }
__device__ __forceinline__ void mbar_expect(uint32_t b, uint32_t bytes) {
    asm volatile("mbarrier.arrive.expect_tx.shared::cta.b64 _, [%0], %1;" ::"r"(b), "r"(bytes) : "memory");
}
__device__ __forceinline__ void mbar_wait(uint32_t b, uint32_t parity) {
    asm volatile(
        "{\n.reg .pred p;\n.reg .u32 c;\n"
        "mov.u32 c, 0;\n"
        "LOOP:\n"
        "mbarrier.try_wait.parity.shared::cta.b64 p, [%0], %1;\n"
        "@p bra DONE;\n"
        "add.u32 c, c, 1;\n"
        "setp.lt.u32 p, c, 4194304;\n"
        "@p bra LOOP;\n"
        "trap;\n"
        "DONE:\n}\n" ::"r"(b), "r"(parity) : "memory");
}
__device__ __forceinline__ void fence_barrier_init() { asm volatile("fence.mbarrier_init.release.cluster;" ::: "memory"); }
__device__ __forceinline__ void fence_proxy_async() { asm volatile("fence.proxy.async.shared::cta;" ::: "memory"); }
__device__ __forceinline__ void cluster_arrive() { asm volatile("barrier.cluster.arrive.relaxed.aligned;" ::: "memory"); }
__device__ __forceinline__ void cluster_wait() { asm volatile("barrier.cluster.wait.aligned;" ::: "memory"); }
__device__ __forceinline__ void named_bar_sync(int id, int n) { asm volatile("bar.sync %0, %1;" ::"r"(id), "r"(n) : "memory"); }

__device__ __forceinline__ void tma3d_mc(uint32_t dst, const CUtensorMap* tm, int c0, int c1, int c2, uint32_t bar, uint16_t mask) {
    asm volatile("cp.async.bulk.tensor.3d.shared::cluster.global.mbarrier::complete_tx::bytes.multicast::cluster [%0], [%1, {%3, %4, %5}], [%2], %6;"
                 ::"r"(dst), "l"(tm), "r"(bar), "r"(c0), "r"(c1), "r"(c2), "h"(mask) : "memory");
}
__device__ __forceinline__ void tma2d_mc(uint32_t dst, const CUtensorMap* tm, int c0, int c1, uint32_t bar, uint16_t mask) {
    asm volatile("cp.async.bulk.tensor.2d.shared::cluster.global.mbarrier::complete_tx::bytes.multicast::cluster [%0], [%1, {%3, %4}], [%2], %5;"
                 ::"r"(dst), "l"(tm), "r"(bar), "r"(c0), "r"(c1), "h"(mask) : "memory");
}
__device__ __forceinline__ void tma4d(uint32_t dst, const CUtensorMap* tm, int c0, int c1, int c2, int c3, uint32_t bar) {
    asm volatile("cp.async.bulk.tensor.4d.shared::cluster.global.mbarrier::complete_tx::bytes [%0], [%1, {%3, %4, %5, %6}], [%2];"
                 ::"r"(dst), "l"(tm), "r"(bar), "r"(c0), "r"(c1), "r"(c2), "r"(c3) : "memory");
}
__device__ __forceinline__ void tma2d(uint32_t dst, const CUtensorMap* tm, int c0, int c1, uint32_t bar) {
    asm volatile("cp.async.bulk.tensor.2d.shared::cluster.global.mbarrier::complete_tx::bytes [%0], [%1, {%3, %4}], [%2];"
                 ::"r"(dst), "l"(tm), "r"(bar), "r"(c0), "r"(c1) : "memory");
}
__device__ __forceinline__ void bulk_load(uint32_t dst, const void* src, uint32_t bytes, uint32_t bar) {
    asm volatile("cp.async.bulk.shared::cluster.global.mbarrier::complete_tx::bytes [%0], [%1], %2, [%3];"
                 ::"r"(dst), "l"(src), "r"(bytes), "r"(bar) : "memory");
}
__device__ __forceinline__ void prefetch_l2(const void* p, uint32_t bytes) {
    asm volatile("cp.async.bulk.prefetch.L2.global [%0], %1;" ::"l"(p), "r"(bytes) : "memory");
}
__device__ __forceinline__ void prefetch_tmap(const CUtensorMap* tm) { asm volatile("prefetch.tensormap [%0];" ::"l"(tm) : "memory"); }

__device__ __forceinline__ void wg_fence() { asm volatile("wgmma.fence.sync.aligned;" ::: "memory"); }
__device__ __forceinline__ void wg_commit() { asm volatile("wgmma.commit_group.sync.aligned;" ::: "memory"); }
template <int N> __device__ __forceinline__ void wg_wait() { asm volatile("wgmma.wait_group.sync.aligned %0;" ::"n"(N) : "memory"); }
template <int N> __device__ __forceinline__ void reg_fence(float (&d)[N]) {
#pragma unroll
    for (int i = 0; i < N; i++) asm volatile("" : "+f"(d[i])::"memory");
}
template <int N> __device__ __forceinline__ void reg_fence(uint32_t (&d)[N]) {
#pragma unroll
    for (int i = 0; i < N; i++) asm volatile("" : "+r"(d[i])::"memory");
}
template <int R> __device__ __forceinline__ void reg_alloc() { asm volatile("setmaxnreg.inc.sync.aligned.u32 %0;" ::"n"(R)); }
template <int R> __device__ __forceinline__ void reg_dealloc() { asm volatile("setmaxnreg.dec.sync.aligned.u32 %0;" ::"n"(R)); }

__device__ __forceinline__ uint64_t mk_desc(uint64_t z, uint32_t addr, uint32_t lbo, uint32_t sbo, uint32_t swz) {
    return z + ((uint64_t)(((addr & 0x3FFFF) >> 4) | ((lbo >> 4) << 16)) | ((uint64_t)((sbo >> 4) | (swz << 30)) << 32));
}
__device__ __forceinline__ uint32_t pack_bf16(float lo, float hi) {
    uint32_t r;
    asm("cvt.rn.bf16x2.f32 %0, %1, %2;" : "=r"(r) : "f"(hi), "f"(lo));
    return r;
}
__device__ __forceinline__ float bf_lo(uint32_t w) { return __uint_as_float(w << 16); }
__device__ __forceinline__ float bf_hi(uint32_t w) { return __uint_as_float(w & 0xFFFF0000u); }
__device__ __forceinline__ float ex2(float x) {
    float r;
    asm("ex2.approx.ftz.f32 %0, %1;" : "=f"(r) : "f"(x));
    return r;
}
__device__ __forceinline__ float tanh_fast(float x) {
    float r;
    asm("tanh.approx.f32 %0, %1;" : "=f"(r) : "f"(x));
    return r;
}
__device__ __forceinline__ uint32_t hfma2_bf16(uint32_t a, uint32_t b, uint32_t c) {
    uint32_t r;
    asm("fma.rn.bf16x2 %0, %1, %2, %3;" : "=r"(r) : "r"(a), "r"(b), "r"(c));
    return r;
}
__device__ __forceinline__ uint32_t hadd2_bf16(uint32_t a, uint32_t b) {
    uint32_t r;
    asm("add.rn.bf16x2 %0, %1, %2;" : "=r"(r) : "r"(a), "r"(b));
    return r;
}
__device__ __forceinline__ void ldsm4(uint32_t (&a)[4], uint32_t addr) {
    asm volatile("ldmatrix.sync.aligned.m8n8.x4.shared.b16 {%0, %1, %2, %3}, [%4];" : "=r"(a[0]), "=r"(a[1]), "=r"(a[2]), "=r"(a[3]) : "r"(addr) : "memory");
}
__device__ __forceinline__ void stsm4(uint32_t addr, const uint32_t (&a)[4]) {
    asm volatile("stmatrix.sync.aligned.m8n8.x4.shared.b16 [%0], {%1, %2, %3, %4};" ::"r"(addr), "r"(a[0]), "r"(a[1]), "r"(a[2]), "r"(a[3]) : "memory");
}
__device__ __forceinline__ void mma16816(float (&c)[4], const uint32_t (&a)[4], uint32_t b0, uint32_t b1) {
    asm("mma.sync.aligned.m16n8k16.row.col.f32.bf16.bf16.f32 {%0, %1, %2, %3}, {%4, %5, %6, %7}, {%8, %9}, {%0, %1, %2, %3};"
        : "+f"(c[0]), "+f"(c[1]), "+f"(c[2]), "+f"(c[3]) : "r"(a[0]), "r"(a[1]), "r"(a[2]), "r"(a[3]), "r"(b0), "r"(b1));
}
__device__ __forceinline__ float gelu2(float u) {
    const float w = fmaf(u * u, 0.0356774081f, 0.7978845608f);
    return fmaf(u, tanh_fast(u * w), u);
}

template<int TB, int AOFF, int BOFF> __device__ __forceinline__ void wgmma_ss_n216(float (&d)[108], uint64_t da, uint64_t db, int sd) {
    asm volatile("{\n.reg .pred p;\n.reg .b64 ta, tb;\nsetp.ne.b32 p, %110, 0;\nadd.s64 ta, %108, %112;\nadd.s64 tb, %109, %113;\n"
      "wgmma.mma_async.sync.aligned.m64n216k16.f32.bf16.bf16 {%0, %1, %2, %3, %4, %5, %6, %7, %8, %9, %10, %11, %12, %13, %14, %15, %16, %17, %18, %19, %20, %21, %22, %23, %24, %25, %26, %27, %28, %29, %30, %31, %32, %33, %34, %35, %36, %37, %38, %39, %40, %41, %42, %43, %44, %45, %46, %47, %48, %49, %50, %51, %52, %53, %54, %55, %56, %57, %58, %59, %60, %61, %62, %63, %64, %65, %66, %67, %68, %69, %70, %71, %72, %73, %74, %75, %76, %77, %78, %79, %80, %81, %82, %83, %84, %85, %86, %87, %88, %89, %90, %91, %92, %93, %94, %95, %96, %97, %98, %99, %100, %101, %102, %103, %104, %105, %106, %107}, ta, tb, p, 1, 1, 0, %111;\n}\n"
      : "+f"(d[0]), "+f"(d[1]), "+f"(d[2]), "+f"(d[3]), "+f"(d[4]), "+f"(d[5]), "+f"(d[6]), "+f"(d[7]), "+f"(d[8]), "+f"(d[9]), "+f"(d[10]), "+f"(d[11]), "+f"(d[12]), "+f"(d[13]), "+f"(d[14]), "+f"(d[15]), "+f"(d[16]), "+f"(d[17]), "+f"(d[18]), "+f"(d[19]), "+f"(d[20]), "+f"(d[21]), "+f"(d[22]), "+f"(d[23]), "+f"(d[24]), "+f"(d[25]), "+f"(d[26]), "+f"(d[27]), "+f"(d[28]), "+f"(d[29]), "+f"(d[30]), "+f"(d[31]), "+f"(d[32]), "+f"(d[33]), "+f"(d[34]), "+f"(d[35]), "+f"(d[36]), "+f"(d[37]), "+f"(d[38]), "+f"(d[39]), "+f"(d[40]), "+f"(d[41]), "+f"(d[42]), "+f"(d[43]), "+f"(d[44]), "+f"(d[45]), "+f"(d[46]), "+f"(d[47]), "+f"(d[48]), "+f"(d[49]), "+f"(d[50]), "+f"(d[51]), "+f"(d[52]), "+f"(d[53]), "+f"(d[54]), "+f"(d[55]), "+f"(d[56]), "+f"(d[57]), "+f"(d[58]), "+f"(d[59]), "+f"(d[60]), "+f"(d[61]), "+f"(d[62]), "+f"(d[63]), "+f"(d[64]), "+f"(d[65]), "+f"(d[66]), "+f"(d[67]), "+f"(d[68]), "+f"(d[69]), "+f"(d[70]), "+f"(d[71]), "+f"(d[72]), "+f"(d[73]), "+f"(d[74]), "+f"(d[75]), "+f"(d[76]), "+f"(d[77]), "+f"(d[78]), "+f"(d[79]), "+f"(d[80]), "+f"(d[81]), "+f"(d[82]), "+f"(d[83]), "+f"(d[84]), "+f"(d[85]), "+f"(d[86]), "+f"(d[87]), "+f"(d[88]), "+f"(d[89]), "+f"(d[90]), "+f"(d[91]), "+f"(d[92]), "+f"(d[93]), "+f"(d[94]), "+f"(d[95]), "+f"(d[96]), "+f"(d[97]), "+f"(d[98]), "+f"(d[99]), "+f"(d[100]), "+f"(d[101]), "+f"(d[102]), "+f"(d[103]), "+f"(d[104]), "+f"(d[105]), "+f"(d[106]), "+f"(d[107])
      : "l"(da), "l"(db), "r"(sd), "n"(TB), "n"(AOFF), "n"(BOFF));
}

template<int TB, int AOFF, int BOFF> __device__ __forceinline__ void wgmma_ss_n128(float (&d)[64], uint64_t da, uint64_t db, int sd) {
    asm volatile("{\n.reg .pred p;\n.reg .b64 ta, tb;\nsetp.ne.b32 p, %66, 0;\nadd.s64 ta, %64, %68;\nadd.s64 tb, %65, %69;\n"
      "wgmma.mma_async.sync.aligned.m64n128k16.f32.bf16.bf16 {%0, %1, %2, %3, %4, %5, %6, %7, %8, %9, %10, %11, %12, %13, %14, %15, %16, %17, %18, %19, %20, %21, %22, %23, %24, %25, %26, %27, %28, %29, %30, %31, %32, %33, %34, %35, %36, %37, %38, %39, %40, %41, %42, %43, %44, %45, %46, %47, %48, %49, %50, %51, %52, %53, %54, %55, %56, %57, %58, %59, %60, %61, %62, %63}, ta, tb, p, 1, 1, 0, %67;\n}\n"
      : "+f"(d[0]), "+f"(d[1]), "+f"(d[2]), "+f"(d[3]), "+f"(d[4]), "+f"(d[5]), "+f"(d[6]), "+f"(d[7]), "+f"(d[8]), "+f"(d[9]), "+f"(d[10]), "+f"(d[11]), "+f"(d[12]), "+f"(d[13]), "+f"(d[14]), "+f"(d[15]), "+f"(d[16]), "+f"(d[17]), "+f"(d[18]), "+f"(d[19]), "+f"(d[20]), "+f"(d[21]), "+f"(d[22]), "+f"(d[23]), "+f"(d[24]), "+f"(d[25]), "+f"(d[26]), "+f"(d[27]), "+f"(d[28]), "+f"(d[29]), "+f"(d[30]), "+f"(d[31]), "+f"(d[32]), "+f"(d[33]), "+f"(d[34]), "+f"(d[35]), "+f"(d[36]), "+f"(d[37]), "+f"(d[38]), "+f"(d[39]), "+f"(d[40]), "+f"(d[41]), "+f"(d[42]), "+f"(d[43]), "+f"(d[44]), "+f"(d[45]), "+f"(d[46]), "+f"(d[47]), "+f"(d[48]), "+f"(d[49]), "+f"(d[50]), "+f"(d[51]), "+f"(d[52]), "+f"(d[53]), "+f"(d[54]), "+f"(d[55]), "+f"(d[56]), "+f"(d[57]), "+f"(d[58]), "+f"(d[59]), "+f"(d[60]), "+f"(d[61]), "+f"(d[62]), "+f"(d[63])
      : "l"(da), "l"(db), "r"(sd), "n"(TB), "n"(AOFF), "n"(BOFF));
}

template<int TB, int AOFF, int BOFF> __device__ __forceinline__ void wgmma_ss_n72(float (&d)[36], uint64_t da, uint64_t db, int sd) {
    asm volatile("{\n.reg .pred p;\n.reg .b64 ta, tb;\nsetp.ne.b32 p, %38, 0;\nadd.s64 ta, %36, %40;\nadd.s64 tb, %37, %41;\n"
      "wgmma.mma_async.sync.aligned.m64n72k16.f32.bf16.bf16 {%0, %1, %2, %3, %4, %5, %6, %7, %8, %9, %10, %11, %12, %13, %14, %15, %16, %17, %18, %19, %20, %21, %22, %23, %24, %25, %26, %27, %28, %29, %30, %31, %32, %33, %34, %35}, ta, tb, p, 1, 1, 0, %39;\n}\n"
      : "+f"(d[0]), "+f"(d[1]), "+f"(d[2]), "+f"(d[3]), "+f"(d[4]), "+f"(d[5]), "+f"(d[6]), "+f"(d[7]), "+f"(d[8]), "+f"(d[9]), "+f"(d[10]), "+f"(d[11]), "+f"(d[12]), "+f"(d[13]), "+f"(d[14]), "+f"(d[15]), "+f"(d[16]), "+f"(d[17]), "+f"(d[18]), "+f"(d[19]), "+f"(d[20]), "+f"(d[21]), "+f"(d[22]), "+f"(d[23]), "+f"(d[24]), "+f"(d[25]), "+f"(d[26]), "+f"(d[27]), "+f"(d[28]), "+f"(d[29]), "+f"(d[30]), "+f"(d[31]), "+f"(d[32]), "+f"(d[33]), "+f"(d[34]), "+f"(d[35])
      : "l"(da), "l"(db), "r"(sd), "n"(TB), "n"(AOFF), "n"(BOFF));
}

template<int TB, int BOFF> __device__ __forceinline__ void wgmma_rs_n24(float (&d)[12], uint32_t a0, uint32_t a1, uint32_t a2, uint32_t a3, uint64_t db, int sd) {
    asm volatile("{\n.reg .pred p;\n.reg .b64 tb;\nsetp.ne.b32 p, %17, 0;\nadd.s64 tb, %16, %19;\n"
      "wgmma.mma_async.sync.aligned.m64n24k16.f32.bf16.bf16 {%0, %1, %2, %3, %4, %5, %6, %7, %8, %9, %10, %11}, {%12, %13, %14, %15}, tb, p, 1, 1, %18;\n}\n"
      : "+f"(d[0]), "+f"(d[1]), "+f"(d[2]), "+f"(d[3]), "+f"(d[4]), "+f"(d[5]), "+f"(d[6]), "+f"(d[7]), "+f"(d[8]), "+f"(d[9]), "+f"(d[10]), "+f"(d[11])
      : "r"(a0), "r"(a1), "r"(a2), "r"(a3), "l"(db), "r"(sd), "n"(TB), "n"(BOFF));
}

template<int TB, int BOFF> __device__ __forceinline__ void wgmma_rs_n72(float (&d)[36], uint32_t a0, uint32_t a1, uint32_t a2, uint32_t a3, uint64_t db, int sd) {
    asm volatile("{\n.reg .pred p;\n.reg .b64 tb;\nsetp.ne.b32 p, %41, 0;\nadd.s64 tb, %40, %43;\n"
      "wgmma.mma_async.sync.aligned.m64n72k16.f32.bf16.bf16 {%0, %1, %2, %3, %4, %5, %6, %7, %8, %9, %10, %11, %12, %13, %14, %15, %16, %17, %18, %19, %20, %21, %22, %23, %24, %25, %26, %27, %28, %29, %30, %31, %32, %33, %34, %35}, {%36, %37, %38, %39}, tb, p, 1, 1, %42;\n}\n"
      : "+f"(d[0]), "+f"(d[1]), "+f"(d[2]), "+f"(d[3]), "+f"(d[4]), "+f"(d[5]), "+f"(d[6]), "+f"(d[7]), "+f"(d[8]), "+f"(d[9]), "+f"(d[10]), "+f"(d[11]), "+f"(d[12]), "+f"(d[13]), "+f"(d[14]), "+f"(d[15]), "+f"(d[16]), "+f"(d[17]), "+f"(d[18]), "+f"(d[19]), "+f"(d[20]), "+f"(d[21]), "+f"(d[22]), "+f"(d[23]), "+f"(d[24]), "+f"(d[25]), "+f"(d[26]), "+f"(d[27]), "+f"(d[28]), "+f"(d[29]), "+f"(d[30]), "+f"(d[31]), "+f"(d[32]), "+f"(d[33]), "+f"(d[34]), "+f"(d[35])
      : "r"(a0), "r"(a1), "r"(a2), "r"(a3), "l"(db), "r"(sd), "n"(TB), "n"(BOFF));
}

template<int TB, int AINC, int BINC> __device__ __forceinline__ void wgmma_ss_n64_pi(float (&d)[32], uint64_t& da, uint64_t& db, int sd) {
    asm volatile("{\n.reg .pred p;\nsetp.ne.b32 p, %34, 0;\n"
      "wgmma.mma_async.sync.aligned.m64n64k16.f32.bf16.bf16 {%0, %1, %2, %3, %4, %5, %6, %7, %8, %9, %10, %11, %12, %13, %14, %15, %16, %17, %18, %19, %20, %21, %22, %23, %24, %25, %26, %27, %28, %29, %30, %31}, %32, %33, p, 1, 1, 0, %35;\n"
      "add.s64 %32, %32, %36;\nadd.s64 %33, %33, %37;\n}\n"
      : "+f"(d[0]), "+f"(d[1]), "+f"(d[2]), "+f"(d[3]), "+f"(d[4]), "+f"(d[5]), "+f"(d[6]), "+f"(d[7]), "+f"(d[8]), "+f"(d[9]), "+f"(d[10]), "+f"(d[11]), "+f"(d[12]), "+f"(d[13]), "+f"(d[14]), "+f"(d[15]), "+f"(d[16]), "+f"(d[17]), "+f"(d[18]), "+f"(d[19]), "+f"(d[20]), "+f"(d[21]), "+f"(d[22]), "+f"(d[23]), "+f"(d[24]), "+f"(d[25]), "+f"(d[26]), "+f"(d[27]), "+f"(d[28]), "+f"(d[29]), "+f"(d[30]), "+f"(d[31]), "+l"(da), "+l"(db)
      : "r"(sd), "n"(TB), "n"(AINC), "n"(BINC));
}

template<int TB, int BINC> __device__ __forceinline__ void wgmma_rs_n64_pi(float (&d)[32], uint32_t a0, uint32_t a1, uint32_t a2, uint32_t a3, uint64_t& db, int sd) {
    asm volatile("{\n.reg .pred p;\nsetp.ne.b32 p, %37, 0;\n"
      "wgmma.mma_async.sync.aligned.m64n64k16.f32.bf16.bf16 {%0, %1, %2, %3, %4, %5, %6, %7, %8, %9, %10, %11, %12, %13, %14, %15, %16, %17, %18, %19, %20, %21, %22, %23, %24, %25, %26, %27, %28, %29, %30, %31}, {%33, %34, %35, %36}, %32, p, 1, 1, %38;\n"
      "add.s64 %32, %32, %39;\n}\n"
      : "+f"(d[0]), "+f"(d[1]), "+f"(d[2]), "+f"(d[3]), "+f"(d[4]), "+f"(d[5]), "+f"(d[6]), "+f"(d[7]), "+f"(d[8]), "+f"(d[9]), "+f"(d[10]), "+f"(d[11]), "+f"(d[12]), "+f"(d[13]), "+f"(d[14]), "+f"(d[15]), "+f"(d[16]), "+f"(d[17]), "+f"(d[18]), "+f"(d[19]), "+f"(d[20]), "+f"(d[21]), "+f"(d[22]), "+f"(d[23]), "+f"(d[24]), "+f"(d[25]), "+f"(d[26]), "+f"(d[27]), "+f"(d[28]), "+f"(d[29]), "+f"(d[30]), "+f"(d[31]), "+l"(db)
      : "r"(a0), "r"(a1), "r"(a2), "r"(a3), "r"(sd), "n"(TB), "n"(BINC));
}

constexpr int K1_XN_BYTES = 16 * 9216;
constexpr int K1_OFF_RING = K1_XN_BYTES;
constexpr int K1_OFF_BIAS = K1_OFF_RING + 10 * 8192;
constexpr int K1_OFF_BAR = K1_OFF_BIAS + 576 * 2;
constexpr int K1_SMEM = K1_OFF_BAR + 800;
constexpr float QSCALE = 0.23570226039551584f * 1.4426950408889634f;

struct K1Ctx {
    uint32_t full0;
    uint32_t rel_addr;
    uint64_t descA, descB;
    uint32_t phase;
    __device__ __forceinline__ void begin_stage(int s) {
        mbar_wait(full0 + s * 8, phase);
        wg_fence();
    }
    __device__ __forceinline__ void release(int s) {
        if (rel_addr) asm volatile("mbarrier.arrive.shared::cluster.b64 _, [%0];" ::"r"(rel_addr + s * 8) : "memory");
    }
    __device__ __forceinline__ void end_stage(int s) {
        wg_commit();
        wg_wait<1>();
        release(s == 0 ? 8 : s - 1);
    }
};

__host__ __device__ constexpr int a_off(int ks) { return ((ks / 12) * 49152 + ((ks >> 2) % 3) * 1024 + (ks & 3) * 32) >> 4; }

#define STAGGER 2
template <int V> struct IC { static constexpr int value = V; };
template <int I, int N, class F> __device__ __forceinline__ void static_for(F&& f) {
    if constexpr (I < N) { f(IC<I>{}); static_for<I + 1, N>(f); }
}

template <bool A_RS, bool B_RS, class Epi>
__device__ __forceinline__ void tile_pair(K1Ctx& c, float (&accA)[32], float (&accB)[32], uint32_t (&h)[144], Epi&& epi) {
    static_for<0, 9>([&](auto sc) {
        constexpr int s = decltype(sc)::value;
        c.begin_stage(s);
        static_for<0, 8>([&](auto tc) {
            constexpr int t = decltype(tc)::value, kk = s * 8 + t, ks = kk % 36;
            constexpr int db = ks == 35 ? -35 * 128 : 128, da = a_off((ks + 1) % 36) - a_off(ks);
            if constexpr (kk < 36) {
                if constexpr (A_RS) wgmma_rs_n64_pi<1, db>(accA, h[ks * 4], h[ks * 4 + 1], h[ks * 4 + 2], h[ks * 4 + 3], c.descB, ks != 0);
                else wgmma_ss_n64_pi<1, da, db>(accA, c.descA, c.descB, ks != 0);
            } else {
                if constexpr (B_RS) wgmma_rs_n64_pi<1, db>(accB, h[ks * 4], h[ks * 4 + 1], h[ks * 4 + 2], h[ks * 4 + 3], c.descB, ks != 0);
                else wgmma_ss_n64_pi<1, da, db>(accB, c.descA, c.descB, ks != 0);
            }
            if constexpr (t == 0) {
                c.end_stage(s);
                epi(sc);
                wg_fence();
            }
        });
        wg_commit();
    });
    c.phase ^= 1;
}

template <class Epi>
__device__ __forceinline__ void tile_128(K1Ctx& c, float (&acc)[64], Epi&& epi) {
    static_for<0, 9>([&](auto sc) {
        constexpr int s = decltype(sc)::value;
        c.begin_stage(s);
        static_for<0, 4>([&](auto tc) {
            constexpr int t = decltype(tc)::value;
            constexpr int bo = ((((2 * s + (t >> 1)) % 9) * 8192 + (t & 1) * 2048) >> 4) + (((4096 - 2048) >> 4) << 16);
            wgmma_ss_n128<1, a_off(s * 4 + t), bo>(acc, c.descA, c.descB, (s | t) != 0);
            if constexpr (t == 0) {
                if constexpr (s > 0) c.end_stage(s);
                epi(sc);
                wg_fence();
            }
        });
        wg_commit();
    });
    wg_wait<0>();
    c.release(8);
    c.phase ^= 1;
}

template <int B0, int NB, int HOFF, int NA>
__device__ __forceinline__ void gelu_blocks(const float (&acc)[NA], uint32_t (&h)[144], const uint32_t (&bq)[8], float rs0, float rs1) {
#pragma unroll
    for (int b = B0; b < B0 + NB; b++) {
        const float b0 = bf_lo(bq[b & 7]), b1 = bf_hi(bq[b & 7]);
        h[HOFF + b * 2 + 0] = pack_bf16(gelu2(fmaf(acc[b * 4 + 0], rs0, b0)), gelu2(fmaf(acc[b * 4 + 1], rs0, b1)));
        h[HOFF + b * 2 + 1] = pack_bf16(gelu2(fmaf(acc[b * 4 + 2], rs1, b0)), gelu2(fmaf(acc[b * 4 + 3], rs1, b1)));
    }
#pragma unroll
    for (int i = HOFF + B0 * 2; i < HOFF + (B0 + NB) * 2; i++) asm volatile("" : "+r"(h[i]));
}
__device__ __forceinline__ void load_bias(uint32_t (&bq)[8], uint32_t addr) {
    asm volatile("ld.shared.v4.u32 {%0, %1, %2, %3}, [%4];" : "=r"(bq[0]), "=r"(bq[1]), "=r"(bq[2]), "=r"(bq[3]) : "r"(addr));
    asm volatile("ld.shared.v4.u32 {%0, %1, %2, %3}, [%4 + 16];" : "=r"(bq[4]), "=r"(bq[5]), "=r"(bq[6]), "=r"(bq[7]) : "r"(addr));
}
__device__ __forceinline__ void st_pred2(bool p, void* a, uint32_t x, uint32_t y) {
    asm volatile("{\n.reg .pred p;\nsetp.ne.u32 p, %3, 0;\n@p st.global.v2.u32 [%0], {%1, %2};\n}\n" ::"l"(a), "r"(x), "r"(y), "r"((uint32_t)p) : "memory");
}
__device__ __forceinline__ void st_pred1(bool p, void* a, uint32_t x) {
    asm volatile("{\n.reg .pred p;\nsetp.ne.u32 p, %2, 0;\n@p st.global.u32 [%0], %1;\n}\n" ::"l"(a), "r"(x), "r"((uint32_t)p) : "memory");
}
template <int S> __device__ __forceinline__ void store_part(const float (&o)[32], uint4* p) {
    uint4 v;
    v.x = pack_bf16(o[S * 8 + 0], o[S * 8 + 1]); v.y = pack_bf16(o[S * 8 + 2], o[S * 8 + 3]);
    v.z = pack_bf16(o[S * 8 + 4], o[S * 8 + 5]); v.w = pack_bf16(o[S * 8 + 6], o[S * 8 + 7]);
    p[S * 256] = v;
}

constexpr int NCHUNK = 16;
constexpr int CHUNK_BYTES = KV_HEAD_BYTES / NCHUNK;
constexpr int SM_Q = 0;
constexpr int SM_KV = 32768;
constexpr int PIECE = 19968;
__host__ __device__ constexpr int sm_piece(int p) { return p == 0 ? 209408 : (p == 1 ? 0 : SM_KV + (p - 2) * PIECE); }
__host__ __device__ constexpr int sm_wstep(int k) { return k < 27 ? sm_piece(k / 3) + (k % 3) * 4608 : (k < 35 ? SM_KV + 7 * PIECE + (k - 27) * 4608 : PIECE); }
__host__ __device__ constexpr int sm_ostep(int k) { return sm_piece(k / 3) + 13824 + (k % 3) * 2048; }
constexpr int SM_RED = SM_KV + KV_HEAD_BYTES;

__device__ __forceinline__ float exp2_fixed(float y) {
    const float u = __uint_as_float(__float_as_uint(y) & 0xFF807FFFu) - 512.02545f;
    float t = fmaf(u, 0.019497588f, 0.114550486f);
    t = fmaf(t, u, -0.29839927f);
    return fmaf(t, u, y);
}
__device__ __forceinline__ uint32_t pack_fixed(float lo, float hi) { return __byte_perm(__float_as_uint(lo), __float_as_uint(hi), 0x6521); }

#define PV_GROUP 4
#define POLY_MODE 1
__device__ __forceinline__ uint32_t exp2_packed(float y0, float y1, uint32_t one2) {
    const uint32_t w = pack_fixed(y0, y1);
    uint32_t m;
    asm("lop3.b32 %0, %1, 0x007F007F, %2, 0xEA;" : "=r"(m) : "r"(w), "r"(one2));
    const uint32_t d = hfma2_bf16(m, 0x3EF93EF9u, 0xBF38BF38u);
    const uint32_t e = hfma2_bf16(d, d, 0xBD71BD71u);
    return hfma2_bf16(w, e, w);
}
constexpr int KV_TILE = CHUNK_BYTES / 16;
template <int OFF> __device__ __forceinline__ void issue_qk(float (&s)[64], uint64_t qd, uint64_t kd) {
    wgmma_ss_n128<0, 0, OFF + (8 << 16)>(s, qd, kd, 0);
    wgmma_ss_n128<0, 16, OFF + 32>(s, qd, kd, 1);
}
template <int OFF> __device__ __forceinline__ void issue_pv(float (&o)[12], const uint32_t (&p)[32], uint64_t vd) {
    static_for<0, 8>([&](auto kc) {
        constexpr int k = decltype(kc)::value;
        wgmma_rs_n24<1, OFF + k * (2 * KV_GROUP_BYTES / 16)>(o, p[k * 4], p[k * 4 + 1], p[k * 4 + 2], p[k * 4 + 3], vd, 1);
    });
}
template <int OFF>
__device__ __forceinline__ void softmax_pv(const float (&s)[64], uint32_t (&p)[32], float (&o)[12], uint64_t vd, uint32_t one2) {
    static_for<0, 8 / PV_GROUP>([&](auto gc) {
        constexpr int g0 = decltype(gc)::value * PV_GROUP;
#pragma unroll
        for (int b = g0 * 2; b < (g0 + PV_GROUP) * 2; b++) {
            if ((POLY_MASK >> b) & 1) {
                p[b * 2 + 0] = exp2_packed(s[b * 4 + 0], s[b * 4 + 1], one2);
                p[b * 2 + 1] = exp2_packed(s[b * 4 + 2], s[b * 4 + 3], one2);
            } else {
                p[b * 2 + 0] = pack_bf16(ex2(s[b * 4 + 0]), ex2(s[b * 4 + 1]));
                p[b * 2 + 1] = pack_bf16(ex2(s[b * 4 + 2]), ex2(s[b * 4 + 3]));
            }
        }
#pragma unroll
        for (int i = g0 * 4; i < (g0 + PV_GROUP) * 4; i++) asm volatile("" : "+r"(p[i])::"memory");
        wg_fence();
        static_for<g0, g0 + PV_GROUP>([&](auto kc) {
            constexpr int k = decltype(kc)::value;
            wgmma_rs_n24<1, OFF + k * (2 * KV_GROUP_BYTES / 16)>(o, p[k * 4], p[k * 4 + 1], p[k * 4 + 2], p[k * 4 + 3], vd, 1);
        });
    });
    wg_commit();
}
__device__ __forceinline__ int head_pair(int hh, int i) {
    if (i == 8) return hh == 3 ? 0 : 8;
    const int q = i >> 1, t = (4 - hh) & 3;
    if ((i & 1) == 0) return t + q;
    return (hh == 1 || hh == 2) ? (q >= hh ? q - hh : t + 4 + q) : t + 4 + q;
}
template <bool LATE> __device__ __forceinline__ void store_o(float (&o)[12], int rt, int head, int wq, int lane) {
    const int g = lane >> 2, q = lane & 3;
    const float i0 = __fdividef(1.0f, __shfl_sync(~0u, o[8], lane | 3)), i1 = __fdividef(1.0f, __shfl_sync(~0u, o[10], lane | 3));
#pragma unroll
    for (int i = 0; i < 3; i++) {
        const uint32_t w0 = pack_bf16(o[i * 4] * i0, o[i * 4 + 1] * i0), w1 = pack_bf16(o[i * 4 + 2] * i1, o[i * 4 + 3] * i1);
        if (i < 2 || q == 2) {
            if constexpr (LATE) {
                const int pc = (head & 7) * 9 + head_pair(head & 3, i < 2 ? i * 4 + q : 8);
                uint32_t* op = reinterpret_cast<uint32_t*>(g_Olate) + (((rt * 9 + (pc >> 3)) * 128 + wq * 32 + g * 4 + (pc & 3)) * 4 + ((pc >> 2) & 1) * 2);
                asm volatile("st.relaxed.gpu.global.v2.u32 [%0], {%1, %2};" ::"l"(op), "r"(w0), "r"(w1) : "memory");
            } else {
                const int pc = head * 9 + head_pair(head & 3, i < 2 ? i * 4 + q : 8);
                uint32_t* op = g_O + ((rt * 72 + (pc >> 2)) * 8 + wq * 2) * 32 + g * 4 + (pc & 3);
                op[0] = w0;
                op[32] = w1;
            }
        }
    }
#pragma unroll
    for (int i = 0; i < 12; i++) o[i] = 0.f;
}
__device__ __forceinline__ void mbar_arrive(uint32_t b) { asm volatile("mbarrier.arrive.shared::cta.b64 _, [%0];" ::"r"(b) : "memory"); }
__device__ __forceinline__ void mbar_wait_sleep(uint32_t b, uint32_t ns) {
    uint32_t ok, spins = 0;
    while (true) {
        asm volatile("{\n.reg .pred p;\nmbarrier.try_wait.parity.shared::cta.b64 p, [%1], 0;\nselp.u32 %0, 1, 0, p;\n}\n" : "=r"(ok) : "r"(b) : "memory");
        if (ok) break;
        __nanosleep(ns);
        if (++spins > (1u << 21)) __trap();
    }
}
__device__ __forceinline__ void flag_signal(unsigned int* f) {
    __threadfence();
    atomicAdd(f, 1u);
}
__device__ __forceinline__ void flag_wait(const unsigned int* f, unsigned int target, unsigned int sleep_ns) {
    uint32_t v, spins = 0;
    while (true) {
        asm volatile("ld.acquire.gpu.global.u32 %0, [%1];" : "=r"(v) : "l"(f) : "memory");
        if (v >= target) break;
        if (sleep_ns) __nanosleep(sleep_ns);
        if (++spins > (1u << 21)) __trap();
    }
}
__device__ __forceinline__ uint4 hadd8_bf16(const uint4 a, const uint4 b) {
    return make_uint4(hadd2_bf16(a.x, b.x), hadd2_bf16(a.y, b.y), hadd2_bf16(a.z, b.z), hadd2_bf16(a.w, b.w));
}
__device__ __forceinline__ float sumsq2(uint32_t w) { return fmaf(bf_lo(w), bf_lo(w), bf_hi(w) * bf_hi(w)); }
__device__ __forceinline__ float sumsq8(const uint4 v) { return (sumsq2(v.x) + sumsq2(v.y)) + (sumsq2(v.z) + sumsq2(v.w)); }

enum { B_FULL = 0, B_EMPTY = 9, B_BASE = 18, B_XNDEAD = 19, B_QRDY = 20, B_FFN = 21, B_KV = 22, B_FREE = 38, B_WO = 46, B_RED = 55, B_X = 61, B_EARLY = 85, B_OS = 86, B_LATE = 94, B_BIAS = 95, B_END = 96 };

__global__ void __cluster_dims__(2, 1, 1) __launch_bounds__(384, 1)
fused_kernel(const __grid_constant__ CUtensorMap tmX, const __grid_constant__ CUtensorMap tmQ3, const __grid_constant__ CUtensorMap tmQ1,
          const __grid_constant__ CUtensorMap tm1, const __grid_constant__ CUtensorMap tm1b, const __grid_constant__ CUtensorMap tm2, const __grid_constant__ CUtensorMap tmP,
          const __grid_constant__ CUtensorMap tmOut, const __grid_constant__ CUtensorMap tmXo, const __nv_bfloat16* __restrict__ b1,
          const __nv_bfloat16* __restrict__ wqkv, const __nv_bfloat16* __restrict__ w1, const __nv_bfloat16* __restrict__ w2,
          const __nv_bfloat16* __restrict__ wo, const __nv_bfloat16* __restrict__ b2,
          const uint64_t zero) {
    extern __shared__ __align__(1024) uint8_t smem[];
    const uint32_t sb = s2u(smem);
    const int tid = threadIdx.x, lane = tid & 31;
    const int warp = __shfl_sync(~0u, tid >> 5, 0);
    const uint32_t rank = blockIdx.x & 1;
    const int cl = blockIdx.x >> 1;
    const int rb = (cl & 7) * 2 + rank;
    const int j = cl >> 3;
    const uint32_t bar0 = sb + K1_OFF_BAR;
    const uint32_t full0 = bar0 + B_FULL * 8, empty0 = bar0 + B_EMPTY * 8, xbar0 = bar0 + B_X * 8;
    const int head = blockIdx.x >> 2, quarter = blockIdx.x & 3;
    const int rt = quarter * 8 + (head >> 2), ct = head & 3;
    const int rot = head >> 3;
    const int ks0 = ((((head >> 3) + 2) & 3) * 9);
    volatile uint32_t* slow_flag = reinterpret_cast<volatile uint32_t*>(smem + K1_OFF_BAR + B_END * 8);

    if (warp < 8) {
        PROF(0);
        PROFT(48);
        if (lane == 0) {
#pragma unroll
            for (int i = 0; i < 3; i++) mbar_init(xbar0 + (warp * 3 + i) * 8, 1);
            fence_barrier_init();
#pragma unroll 1
            for (int i = 0; i < 3; i++) {
                const uint32_t xb = xbar0 + (warp * 3 + i) * 8;
                mbar_expect(xb, 6144);
                tma4d(sb + i * 49152 + warp * 6144, &tmX, 0, 0, i * 3, rb * 16 + warp * 2, xb);
            }
        }
        __syncwarp();
        cluster_arrive();
        PROF(22);
        reg_alloc<240>();
        PROF(23);
        float rs0, rs1;
        {
            const uint32_t la = sb + (warp * 2 + ((lane >> 3) & 1)) * 3072 + (lane & 7) * 128;
            uint32_t off[4];
#pragma unroll
            for (int i = 0; i < 4; i++) off[i] = la + (((i * 2 + (lane >> 4)) ^ (lane & 7)) << 4);
            float c1[4] = {0.f, 0.f, 0.f, 0.f}, c2[4] = {0.f, 0.f, 0.f, 0.f}, c3[4] = {0.f, 0.f, 0.f, 0.f};
            uint32_t a[36][4];
#pragma unroll
            for (int t = 0; t < 3; t++) {
                mbar_wait(xbar0 + (warp * 3 + t) * 8, 0);
                PROF(24 + t);
#pragma unroll
                for (int i = 0; i < 12; i++) ldsm4(a[t * 12 + i], off[i & 3] + t * 49152 + (i >> 2) * 1024);
#pragma unroll
                for (int i = t * 12; i < t * 12 + 12; i++) {
                    mma16816(c3, a[i], 0x3F803F80u, 0x3F803F80u);
                    mma16816(c1, a[i], a[i][0], a[i][2]);
                    mma16816(c2, a[i], a[i][1], a[i][3]);
                }
            }
            PROF(27);
            const int gg = lane >> 2, src = (lane & ~3) | (gg >> 1);
            const float m0 = c3[0] * (1.0f / DM), m1 = c3[2] * (1.0f / DM);
            const uint32_t mc0 = pack_bf16(-m0, -m0), mc1 = pack_bf16(-m1, -m1);
#pragma unroll
            for (int i = 0; i < 36; i++) {
#pragma unroll
                for (int k = 0; k < 4; k++) a[i][k] = hadd2_bf16(a[i][k], (k & 1) ? mc1 : mc0);
                stsm4(off[i & 3] + (i / 12) * 49152 + ((i >> 2) % 3) * 1024, a[i]);
            }
            const float q0 = __shfl_sync(~0u, (gg & 1) ? c1[1] : c1[0], src), q1 = __shfl_sync(~0u, (gg & 1) ? c2[3] : c2[2], src);
            rs0 = rsqrtf(fmaxf(fmaf(-m0, m0, q0 * (1.0f / DM)), 0.f) + 1e-5f);
            rs1 = rsqrtf(fmaxf(fmaf(-m1, m1, q1 * (1.0f / DM)), 0.f) + 1e-5f);
            if (__any_sync(~0u, fabsf(m0) * rs0 > 0.25f || fabsf(m1) * rs1 > 0.25f)) {
                const float d0 = -m0 - bf_lo(mc0), d1 = -m1 - bf_lo(mc1);
                const uint32_t md0 = pack_bf16(d0, d0), md1 = pack_bf16(d1, d1);
#pragma unroll 1
                for (int i = 0; i < 9; i++) {
#pragma unroll
                    for (int k4 = 0; k4 < 4; k4++) {
                        const uint32_t ad = off[k4] + (i / 3) * 49152 + (i % 3) * 1024;
                        uint32_t b[4];
                        ldsm4(b, ad);
#pragma unroll
                        for (int k = 0; k < 4; k++) b[k] = hadd2_bf16(b[k], (k & 1) ? md1 : md0);
                        stsm4(ad, b);
                    }
                }
            }
        }
        PROF(28);
        const int wg = warp >> 2, wq = warp & 3;
        fence_proxy_async();
        named_bar_sync(1 + wg, 128);
        cluster_wait();
        PROF(1);

        const int g = lane >> 2, q = lane & 3;
        K1Ctx c;
        c.full0 = full0;
        c.rel_addr = 0;
        c.descA = mk_desc(zero, sb + wg * 8 * 3072, 16, 3072, 1);
        c.descB = mk_desc(zero, sb + K1_OFF_RING, 2048, 1024, 1);
        c.phase = 0;
        uint32_t biasq = sb + K1_OFF_BIAS + q * 32;
        uint32_t bq[8];

        uint32_t h[144];
        float accA[32], accB[32];
        uint32_t qo[3], qt[3];
        {
            float accQ[108];
            uint32_t rel = 0;
            if (lane == 0 && wq < 2) asm("mapa.shared::cluster.u32 %0, %1, %2;" : "=r"(rel) : "r"(empty0), "r"(wq));
#pragma unroll 1
            for (int r = 0; r < 2; r++) {
                static_for<0, 9>([&](auto sc) {
                    constexpr int s = decltype(sc)::value;
                    c.begin_stage(s);
                    const uint64_t da = c.descA + (r ? a_off(18 + 2 * s) : a_off(2 * s));
                    wgmma_ss_n216<1, 0, ((2 * s) % 9) * 512>(accQ, da, c.descB, (r | s) != 0);
                    wgmma_ss_n216<1, 2, ((2 * s + 1) % 9) * 512>(accQ, da, c.descB, 1);
                    c.end_stage(s);
                    c.rel_addr = rel;
                });
                c.phase ^= 1;
            }
            PROF(2); PROFWT(54);
            mbar_wait(bar0 + B_BIAS * 8, 0);
            wg_wait<0>();
            c.release(8);
            reg_fence(accQ);
#pragma unroll
            for (int grp = 0; grp < 3; grp++) {
                const int G = 3 * j + grp, type = G >> 3;
                const uint32_t base = (G & 7) * 4 * KV_HEAD_BYTES + (rb * 16 + warp * 2) * KV_GROUP_BYTES + g * 16 + (type == 0 ? Q_OFFSET : (type == 2 ? 256 : 0));
                qo[grp] = base + (q >> 1) * 128 + (q & 1) * 8;
                qt[grp] = base + q * KV_HEAD_BYTES + (type == 0 ? 256 : (type == 2 ? 264 : 512));
#pragma unroll
                for (int hf = 0; hf < 2; hf++) {
                    const float sc = (hf ? rs1 : rs0) * (type == 0 ? QSCALE : ((type == 1 && ((POLY_MASK >> (warp * 2 + hf)) & 1)) ? 2.f : 1.f));
                    uint32_t w[9];
#pragma unroll
                    for (int i = 0; i < 9; i++) w[i] = pack_bf16(accQ[(grp * 9 + i) * 4 + hf * 2] * sc, accQ[(grp * 9 + i) * 4 + hf * 2 + 1] * sc);
                    uint32_t* d = h + 32 + hf * 32 + grp * 8;
                    d[0] = w[0]; d[1] = w[1]; d[2] = w[3]; d[3] = q >= 1 ? w[2] : w[4];
                    d[4] = w[5]; d[5] = q >= 2 ? w[4] : w[6]; d[6] = w[7]; d[7] = w[8];
                    h[32 + hf * 32 + 24 + grp] = q == 0 ? w[2] : (q == 1 ? w[4] : w[6]);
                }
            }
        }
        PROF(3); PROFWT(55);
#pragma unroll
        for (int i = 32; i < 128; i++)
            if (i >= 96 || (i & 31) >= 27) asm volatile("mov.u32 %0, 0;" : "=r"(h[i]));
        if (STAGGER >= 0 && wg == 1) named_bar_sync(4, 256);
#pragma unroll 1
        for (int p = 0; p < 4; p++) {
            uint8_t* const qb = g_QKV + p * KV_GROUP_BYTES;
            float accX[64];
            uint32_t bq2[8];
            tile_128(c, accX, [&](auto sc) {
                constexpr int s = decltype(sc)::value;
                if constexpr (s == 0) {
#pragma unroll
                    for (int i = 0; i < 96; i++) h[i] = h[i + 32];
                }
                if constexpr (s == STAGGER) { if (p == 0 && wg == 0) asm volatile("bar.arrive 4, 256;" ::: "memory"); }
                if constexpr (s >= 1 && s <= 6) {
                    constexpr int grp = (s - 1) >> 1, k = ((s - 1) & 1) * 2;
                    st_pred2(p < 2, qb + qo[grp] + k * KV_HEAD_BYTES, h[grp * 8 + k * 2], h[grp * 8 + k * 2 + 1]);
                    st_pred2(p < 2, qb + qo[grp] + (k + 1) * KV_HEAD_BYTES, h[grp * 8 + k * 2 + 2], h[grp * 8 + k * 2 + 3]);
                    if constexpr (k == 2) st_pred1(p < 2, qb + qt[grp], h[24 + grp]);
                }
                if constexpr (s == 8) { load_bias(bq, biasq); load_bias(bq2, biasq + 128); }
            });
            reg_fence(accX);
            gelu_blocks<0, 8, 96>(accX, h, bq, rs0, rs1);
            gelu_blocks<8, 8, 96>(accX, h, bq2, rs0, rs1);
            if (p == 1) asm volatile("bar.arrive 3, 352;" ::: "memory");
            biasq += 256;
        }
        PROF(4); PROFWT(56);
        const uint32_t rel_keep = c.rel_addr;
        c.rel_addr = 0;
        tile_pair<false, true>(c, accA, accB, h, [&](auto sc) {
            constexpr int s = decltype(sc)::value;
            if constexpr (s == 0) c.rel_addr = rel_keep;
            if constexpr (s == 4) load_bias(bq, biasq);
            if constexpr (s == 5) { reg_fence(accA); if (tid == wg * 128) mbar_arrive(bar0 + B_XNDEAD * 8); }
            if constexpr (s == 5 || s == 6) gelu_blocks<(s - 5) * 3, 3, 128>(accA, h, bq, rs0, rs1);
            if constexpr (s == 7) gelu_blocks<6, 2, 128>(accA, h, bq, rs0, rs1);
            if constexpr (s == 3 || s == 7) reg_fence(h);
        });
        PROF(5); PROFWT(57);
        uint4* pout = g_part + j * SLAB + rb * 36 * 256 + tid;
#pragma unroll 1
        for (int p = 0; p < 4; p++) {
            tile_pair<true, true>(c, accA, accB, h, [&](auto sc) {
                constexpr int s = decltype(sc)::value;
                if constexpr (s == 0) reg_fence(accB);
                if constexpr (s < 4) store_part<s>(accB, pout);
                if constexpr (s == 5) reg_fence(accA);
                if constexpr (s >= 5) store_part<s - 5>(accA, pout + 1024);
            });
            pout += 2048;
            PROF(6 + p);
        }
        wg_wait<0>();
        c.release(8);
        reg_fence(accB);
        store_part<0>(accB, pout); store_part<1>(accB, pout); store_part<2>(accB, pout); store_part<3>(accB, pout);
        __syncwarp();
        if (lane == 0) mbar_arrive(bar0 + B_FFN * 8);
        PROF(10); PROFWT(58);
        PROFT(49);

        mbar_wait(bar0 + B_QRDY * 8, 0);
        const uint32_t slow = __any_sync(~0u, *slow_flag != 0);
        const uint64_t kd0 = mk_desc(zero, sb + SM_KV, 0, KV_GROUP_BYTES, 0);
        const uint64_t vd0 = mk_desc(zero, sb + SM_KV + 256, KV_GROUP_BYTES, 128, 0);
        const uint64_t qd0 = mk_desc(zero, sb + SM_Q + wg * 4096, 128, 512, 0);
        const uint32_t kvbar = bar0 + B_KV * 8;
        float o[12];
#pragma unroll
        for (int i = 0; i < 12; i++) o[i] = 0.f;
        PROF(16);
        PROFT(50);
        if (!slow) {
            const uint32_t one2 = 0x3F803F80u + (uint32_t)zero;
            float s0[64], s1[64];
            uint32_t p0[32], p1[32];
            mbar_wait(kvbar, 0);
            reg_fence(o);
            wg_fence();
            issue_qk<0>(s0, qd0, kd0);
            wg_commit();
            wg_commit();
            uint64_t qd = qd0;
            const uint32_t fre = (tid == wg * 128) ? bar0 + B_FREE * 8 - 8 : 0;
#pragma unroll 1
            for (int pass = 0; pass < 4; pass++) {
                uint64_t vd = vd0, kd = kd0;
                uint32_t bn = kvbar + 8;
#pragma unroll 1
                for (int it = 0; it < 8; it++) {
                    if (pass == 0) {
                        mbar_wait(bn, 0);
                        mbar_wait(it == 7 ? bn : bn + 8, 0);
                    }
                    if (it == 0 && pass != 0) {
                        wg_wait<0>();
                        reg_fence(o);
                        store_o<false>(o, quarter * 8 + ((pass - 1 + rot) & 3) * 2 + wg, head, wq, lane);
                        reg_fence(o);
                        __syncwarp();
                        if (lane == 0) mbar_arrive(bar0 + (B_OS + pass * 2 - 2 + wg) * 8);
                    }
                    wg_wait<1>();
                    reg_fence(s0);
                    wg_fence();
                    issue_qk<KV_TILE>(s1, qd, kd);
                    wg_commit();
                    if (pass == 3 && it > 0 && fre) mbar_arrive(fre + it * 8);
                    softmax_pv<0>(s0, p0, o, vd, one2);
                    kd += 2 * KV_TILE;
                    if (it == 7) { kd = kd0; qd += 512; }
                    wg_wait<1>();
                    reg_fence(s1);
                    wg_fence();
                    issue_qk<0>(s0, qd, kd);
                    wg_commit();
                    softmax_pv<KV_TILE>(s1, p1, o, vd, one2);
                    vd += 2 * KV_TILE; bn += 16;
                }
                if (pass == 0) PROF(17);
            }
            wg_wait<0>();
            reg_fence(o);
            reg_fence(s0);
            reg_fence(s1);
            store_o<true>(o, quarter * 8 + ((3 + rot) & 3) * 2 + wg, head, wq, lane);
        } else {
#pragma unroll 1
            for (int pass = 0; pass < 4; pass++) {
                float m0 = -INFINITY, m1 = -INFINITY;
                float s[64];
                uint32_t p[32];
#pragma unroll 1
                for (int t = 0; t < 16; t++) {
                    mbar_wait(kvbar + t * 8, 0);
                    wg_fence();
                    issue_qk<0>(s, qd0 + pass * 512, kd0 + t * KV_TILE);
                    wg_commit();
                    wg_wait<0>();
                    reg_fence(s);
                    float a0 = m0, a1 = m1;
#pragma unroll
                    for (int k = 0; k < 16; k++) {
                        if ((POLY_MASK >> k) & 1) {
#pragma unroll
                            for (int i = 0; i < 4; i++) s[k * 4 + i] *= 0.5f;
                        }
                        a0 = fmaxf(a0, fmaxf(s[k * 4 + 0], s[k * 4 + 1]));
                        a1 = fmaxf(a1, fmaxf(s[k * 4 + 2], s[k * 4 + 3]));
                    }
                    a0 = fmaxf(a0, __shfl_xor_sync(~0u, a0, 1)); a1 = fmaxf(a1, __shfl_xor_sync(~0u, a1, 1));
                    a0 = fmaxf(a0, __shfl_xor_sync(~0u, a0, 2)); a1 = fmaxf(a1, __shfl_xor_sync(~0u, a1, 2));
                    const float r0 = ex2(m0 - a0), r1 = ex2(m1 - a1);
                    m0 = a0; m1 = a1;
#pragma unroll
                    for (int i = 0; i < 3; i++) { o[i * 4] *= r0; o[i * 4 + 1] *= r0; o[i * 4 + 2] *= r1; o[i * 4 + 3] *= r1; }
#pragma unroll
                    for (int k = 0; k < 16; k++) {
                        p[k * 2 + 0] = pack_bf16(ex2(s[k * 4 + 0] - m0), ex2(s[k * 4 + 1] - m0));
                        p[k * 2 + 1] = pack_bf16(ex2(s[k * 4 + 2] - m1), ex2(s[k * 4 + 3] - m1));
                    }
                    reg_fence(p);
                    reg_fence(o);
                    wg_fence();
                    issue_pv<0>(o, p, vd0 + t * KV_TILE);
                    wg_commit();
                    wg_wait<0>();
                    reg_fence(o);
                }
                if (pass < 3) {
                    store_o<false>(o, quarter * 8 + ((pass + rot) & 3) * 2 + wg, head, wq, lane);
                    __syncwarp();
                    if (lane == 0) mbar_arrive(bar0 + (B_OS + pass * 2 + wg) * 8);
                }
            }
            store_o<true>(o, quarter * 8 + ((3 + rot) & 3) * 2 + wg, head, wq, lane);
            if (tid == wg * 128)
                for (int i = 0; i < 7; i++) mbar_arrive(bar0 + (B_FREE + i) * 8);
        }
        PROF(18);
        PROFT(51);

        if (tid == wg * 128) mbar_arrive(bar0 + (B_FREE + 7) * 8);
        const int t128 = tid & 127;
        uint32_t bv[9];
        uint2 fv[9];
        mbar_wait(bar0 + B_BASE * 8, 0);
#pragma unroll
        for (int i = 0; i < 9; i++) {
            bv[i] = __ldg(reinterpret_cast<const uint32_t*>(b2 + ct * 144 + wg * 72 + q * 2) + i * 4);
            fv[i] = __ldcg(g_ffn + (blockIdx.x * 18 + wg * 9 + i) * 128 + t128);
        }
        float acc[36];
        const uint64_t od = mk_desc(zero, sb, 1024, 128, 0), wd = mk_desc(zero, sb + wg * 9 * 128, 2304, 128, 0);
        static_for<0, 9>([&](auto pc) {
            constexpr int p = decltype(pc)::value;
            mbar_wait(bar0 + (B_WO + p) * 8, 0);
            wg_fence();
            wgmma_ss_n72<1, sm_ostep(p * 3) / 16, sm_wstep(p * 3) / 16>(acc, od, wd, p != 0);
            wgmma_ss_n72<1, sm_ostep(p * 3 + 1) / 16, sm_wstep(p * 3 + 1) / 16>(acc, od, wd, 1);
            wgmma_ss_n72<1, sm_ostep(p * 3 + 2) / 16, sm_wstep(p * 3 + 2) / 16>(acc, od, wd, 1);
            wg_commit();
            if constexpr (p == 1) {
                wg_wait<1>();
                if (t128 == 0) mbar_arrive(bar0 + B_EARLY * 8);
            }
        });
        wg_wait<0>();
        reg_fence(acc);
        PROF(29);
        uint4 al[9];
        {
            const uint4* ap = g_Olate + rt * 9 * 128 + t128;
            uint32_t spins = 0;
            bool ok;
            do {
                ok = true;
#pragma unroll
                for (int k = 0; k < 9; k++)
                    asm volatile("ld.relaxed.gpu.global.v4.u32 {%0, %1, %2, %3}, [%4];" : "=r"(al[k].x), "=r"(al[k].y), "=r"(al[k].z), "=r"(al[k].w) : "l"(ap + k * 128) : "memory");
#pragma unroll
                for (int k = 0; k < 9; k++) ok = ok && al[k].x != O_EMPTY && al[k].y != O_EMPTY && al[k].z != O_EMPTY && al[k].w != O_EMPTY;
                if (++spins > (1u << 20)) __trap();
            } while (!__all_sync(~0u, ok));
        }
        PROF(19);
        mbar_wait(bar0 + B_LATE * 8, 0);
        PROF(20);
        wg_fence();
        static_for<27, 36>([&](auto kc) {
            constexpr int k = decltype(kc)::value;
            wgmma_rs_n72<1, sm_wstep(k) / 16>(acc, al[k - 27].x, al[k - 27].y, al[k - 27].z, al[k - 27].w, wd, 1);
        });
        wg_commit();
        PROF(31);
        uint32_t* st = reinterpret_cast<uint32_t*>(smem + sm_piece(0) + wg * 9216) + (wq * 16 + g) * 36 + q;
        float bs[36];
#pragma unroll
        for (int i = 0; i < 9; i++) {
            const uint32_t x0 = st[i * 4], x1 = st[i * 4 + 288];
            bs[i * 4 + 0] = fmaf(bf_lo(fv[i].x), 0.5f, bf_lo(x0) + bf_lo(bv[i]));
            bs[i * 4 + 1] = fmaf(bf_hi(fv[i].x), 0.5f, bf_hi(x0) + bf_hi(bv[i]));
            bs[i * 4 + 2] = fmaf(bf_lo(fv[i].y), 0.5f, bf_lo(x1) + bf_lo(bv[i]));
            bs[i * 4 + 3] = fmaf(bf_hi(fv[i].y), 0.5f, bf_hi(x1) + bf_hi(bv[i]));
        }
        reg_fence(bs);
        wg_wait<0>();
        reg_fence(acc);
        PROF(32);
#pragma unroll
        for (int i = 0; i < 9; i++) {
            st[i * 4] = pack_bf16(acc[i * 4] + bs[i * 4], acc[i * 4 + 1] + bs[i * 4 + 1]);
            st[i * 4 + 288] = pack_bf16(acc[i * 4 + 2] + bs[i * 4 + 2], acc[i * 4 + 3] + bs[i * 4 + 3]);
        }
        fence_proxy_async();
        named_bar_sync(1 + wg, 128);
        if (t128 == 0) {
            asm volatile("cp.async.bulk.tensor.2d.global.shared::cta.bulk_group [%0, {%2, %3}], [%1];"
                         ::"l"(&tmOut), "r"(sb + sm_piece(0) + wg * 9216), "r"(ct * 144 + wg * 72), "r"(rt * 64) : "memory");
            asm volatile("cp.async.bulk.commit_group;" ::: "memory");
            asm volatile("cp.async.bulk.wait_group.read 0;" ::: "memory");
        }
        PROF(21);
        PROFT(52);
    } else {
        reg_dealloc<24>();
        if (warp == 8 && lane == 0) {
            prefetch_tmap(&tmQ3); prefetch_tmap(&tmQ1); prefetch_tmap(&tm1); prefetch_tmap(&tm1b); prefetch_tmap(&tm2);
            #pragma unroll 1
            for (int i = 0; i < 9; i++) { mbar_init(full0 + i * 8, 1); mbar_init(empty0 + i * 8, 4); mbar_init(bar0 + (B_WO + i) * 8, 2); }
            mbar_init(bar0 + B_BASE * 8, 3); mbar_init(bar0 + B_XNDEAD * 8, 2); mbar_init(bar0 + B_QRDY * 8, 3); mbar_init(bar0 + B_FFN * 8, 8); mbar_init(bar0 + B_EARLY * 8, 2); mbar_init(bar0 + B_LATE * 8, 2); mbar_init(bar0 + B_BIAS * 8, 96);
#pragma unroll 1
            for (int i = 0; i < 16; i++) { mbar_init(bar0 + (B_KV + i) * 8, 1); mbar_init(bar0 + (B_FREE + (i & 7)) * 8, 2); if (i < 6) mbar_init(bar0 + (B_RED + i) * 8, 1); if (i < 6) mbar_init(bar0 + (B_OS + i) * 8, 4); }
            *slow_flag = 0;
            fence_barrier_init();
        }
        __syncwarp();
        cluster_arrive();
        cluster_wait();
        const uint8_t* kvsrc = g_QKV + (size_t)head * KV_HEAD_BYTES;
        if (warp == 8) {
            if (lane == 0) {
                int st = 0, u = rank, tile = -4;
                int es = 5;
                uint32_t eph = 1;
#pragma unroll 1
                for (int n = 0; n < 99; n++) {
                    mbar_wait(empty0 + es * 8, eph);
                    const uint32_t fb = full0 + st * 8, dst = sb + K1_OFF_RING + u * 8192;
                    mbar_expect(fb, 16384);
                    if (tile < 0) {
                        tma3d_mc(dst, &tmQ3, j * 216, n * 32 + rank * 16, 0, fb, 3);
                        tma2d_mc(dst + 6144, &tmQ1, j * 216 + 192, n * 32 + rank * 16, fb, 3);
                    } else if (n < 54) {
                        tma3d_mc(dst, &tm1b, 0, st * 64 + rank * 32, j * 9 + ((n - 18) / 9) * 2, fb, 3);
                    } else if (tile < 9) {
                        tma2d_mc(dst, &tm1, j * 576 + tile * 64, u * 64, fb, 3);
                    } else {
                        tma2d_mc(dst, &tm2, (tile - 9) * 64, j * 576 + u * 64, fb, 3);
                    }
                    u += 2;
                    if (u >= 9) { u -= 9; tile++; }
                    if (++st == 9) st = 0;
                    if (++es == 9) { es = 0; eph ^= 1; }
                }
                mbar_wait(empty0 + 8 * 8, 0);
                mbar_wait(bar0 + B_QRDY * 8, 0);
                asm volatile("fence.proxy.async;" ::: "memory");
#pragma unroll 1
                for (int i = 11; i < NCHUNK; i++) {
                    mbar_expect(bar0 + (B_KV + i) * 8, CHUNK_BYTES);
                    bulk_load(sb + SM_KV + i * CHUNK_BYTES, kvsrc + i * CHUNK_BYTES, CHUNK_BYTES, bar0 + (B_KV + i) * 8);
                }
                const uint8_t* wsrc = g_Wo + ct * WO_TILE_BYTES;
                prefetch_tmap(&tmOut);
                mbar_wait_sleep(bar0 + B_BASE * 8, 500);
#pragma unroll 1
                for (int p = 0; p < 9; p++) {
                    if (p > 0) mbar_wait_sleep(bar0 + (B_FREE + p - 1) * 8, p == 1 ? 500 : 40);
                    const int k = ks0 + p * 3 >= 36 ? ks0 + p * 3 - 36 : ks0 + p * 3;
                    mbar_expect(bar0 + (B_WO + p) * 8, 13824);
                    bulk_load(sb + (p == 0 ? sm_piece(0) : (p == 1 ? sm_piece(1) : SM_KV + (p - 2) * PIECE)), wsrc + k * 4608, 13824, bar0 + (B_WO + p) * 8);
                }
                const int kl = ks0 == 0 ? 27 : ks0 - 9;
                mbar_expect(bar0 + B_LATE * 8, 9 * 4608);
                bulk_load(sb + sm_wstep(27), wsrc + kl * 4608, 8 * 4608, bar0 + B_LATE * 8);
                bulk_load(sb + sm_wstep(35), wsrc + (kl + 8) * 4608, 4608, bar0 + B_LATE * 8);
            }
        } else {
            const int ht = tid - 288;
            if (ht == 64) prefetch_l2(wqkv + blockIdx.x * (DM * 3 * DM / 128), DM * 3 * DM / 64);
            if (ht < 72) {
                const uint4 v = __ldg(reinterpret_cast<const uint4*>(b1 + j * 576) + ht);
                uint32_t* sbias = reinterpret_cast<uint32_t*>(smem + K1_OFF_BIAS) + (ht >> 3) * 32 + (ht & 7);
                sbias[0] = v.x; sbias[8] = v.y; sbias[16] = v.z; sbias[24] = v.w;
            }
            mbar_arrive(bar0 + B_BIAS * 8);
            PROFH(37);
#pragma unroll
            for (int i = 0; i < 3; i++) g_Olate[blockIdx.x * 288 + i * 96 + ht] = make_uint4(O_EMPTY, O_EMPTY, O_EMPTY, O_EMPTY);
#pragma unroll 1
            for (int i = ht; i < 512; i += 96) {
                const int key = i & 127;
                uint8_t* p = g_QKV + (size_t)(j * 4 + (i >> 7)) * KV_HEAD_BYTES + (rb * 16 + (key >> 3)) * KV_GROUP_BYTES + 512 + (key & 7) * 16;
                *reinterpret_cast<uint32_t*>(p + 4) = ((POLY_MASK >> (key >> 3)) & 1) ? 0x3F804000u : 0x00003F80u;
                *reinterpret_cast<uint32_t*>(p + 12) = 0x00003F80u;
            }
            if (ht == 32) prefetch_l2(w1 + blockIdx.x * (DM * FF / 128), DM * FF / 64);
#pragma unroll 2
            for (int i = blockIdx.x * 324 + ht; i < blockIdx.x * 324 + 324; i += 96) {
                const int k = i / 72, nc = i - k * 72, c4 = nc / 18;
                *reinterpret_cast<uint4*>(g_Wo + c4 * WO_TILE_BYTES + (k >> 3) * 2304 + (nc - c4 * 18) * 128 + (k & 7) * 16) =
                    __ldg(reinterpret_cast<const uint4*>(wo) + i);
            }
            PROFH(38);
            named_bar_sync(3, 352);
            if (ht == 32) prefetch_l2(w2 + blockIdx.x * (DM * FF / 128), DM * FF / 64);
            if (ht == 0) {
                flag_signal(&g_flags.qkv_stored[rb]);
                flag_wait(&g_flags.qkv_stored[rb], 8, 200);
            }
            named_bar_sync(7, 96);
            PROFH(39);
#pragma unroll 1
            for (int i = warp - 9; i < 16; i += 3) {
                const int hd = j * 4 + (i >> 2), key = (i & 3) * 32 + lane;
                const uint8_t* p = g_QKV + (size_t)hd * KV_HEAD_BYTES + (rb * 16 + (key >> 3)) * KV_GROUP_BYTES + (key & 7) * 16;
                const uint4 a = __ldcg(reinterpret_cast<const uint4*>(p)), b = __ldcg(reinterpret_cast<const uint4*>(p + 128));
                float n = sumsq2(__ldcg(reinterpret_cast<const uint32_t*>(p + 512))) + sumsq8(a) + sumsq8(b);
                if ((POLY_MASK >> (key >> 3)) & 1) n *= 0.25f;
#pragma unroll
                for (int o = 16; o; o >>= 1) n = fmaxf(n, __shfl_xor_sync(~0u, n, o));
                if (lane == 0) g_kmax[hd * 64 + rb * 4 + (i & 3)] = n;
            }
            named_bar_sync(7, 96);
            PROFH(40);
            if (ht == 0) {
                flag_signal(&g_flags.kv_ready);
                flag_wait(&g_flags.kv_ready, 128, 300);
                mbar_wait_sleep(bar0 + B_XNDEAD * 8, 300);
            }
            named_bar_sync(7, 96);
            PROFH(41);
            float kmax2;
            {
                const float2 v = __ldcg(reinterpret_cast<const float2*>(g_kmax + head * 64 + lane * 2));
                kmax2 = fmaxf(v.x, v.y);
#pragma unroll
                for (int o = 16; o; o >>= 1) kmax2 = fmaxf(kmax2, __shfl_xor_sync(~0u, kmax2, o));
            }
            asm volatile("fence.proxy.async;" ::: "memory");
            int chunk = warp - 9;
#pragma unroll 1
            for (int r = ht; r < 512; r += 96) {
                if (lane == 0 && chunk < 11) {
                    mbar_expect(bar0 + (B_KV + chunk) * 8, CHUNK_BYTES);
                    bulk_load(sb + SM_KV + chunk * CHUNK_BYTES, kvsrc + chunk * CHUNK_BYTES, CHUNK_BYTES, bar0 + (B_KV + chunk) * 8);
                }
                chunk += 3;
                const uint8_t* p = kvsrc + Q_OFFSET + (quarter * 64 + (((r >> 3) + rot * 16) & 63)) * KV_GROUP_BYTES + (r & 7) * 16;
                const uint4 a = __ldcg(reinterpret_cast<const uint4*>(p)), b = __ldcg(reinterpret_cast<const uint4*>(p + 128));
                const uint32_t e = __ldcg(reinterpret_cast<const uint32_t*>(p + 256));
                const float cc = sqrtf((sumsq2(e) + sumsq8(a) + sumsq8(b)) * kmax2) * 1.02f;
                if (!(cc <= 58.f)) *slow_flag = 1;
                uint4* dst = reinterpret_cast<uint4*>(smem + SM_Q + (r >> 3) * 512 + (r & 7) * 16);
                dst[0] = a;
                dst[8] = b;
                dst[16] = make_uint4(e, pack_bf16(-cc, 768.f), 0u, 0u);
                dst[24] = make_uint4(0u, POLY_MODE ? 0xBFFF0000u : 0xC0000000u, 0u, 0u);
            }
            named_bar_sync(7, 96);
            if (*slow_flag) {
#pragma unroll 1
                for (int r = ht; r < 512; r += 96) {
                    uint32_t* dst = reinterpret_cast<uint32_t*>(smem + SM_Q + (r >> 3) * 512 + (r & 7) * 16);
                    dst[65] = 0u;
                    dst[97] = 0u;
                }
            }
            fence_proxy_async();
            __syncwarp();
            if (lane == 0) mbar_arrive(bar0 + B_QRDY * 8);
            PROFH(42);
            if (ht == 0) {
                mbar_wait_sleep(bar0 + B_FFN * 8, 300);
                flag_signal(&g_flags.ffn_done[rb]);
                flag_wait(&g_flags.ffn_done[rt >> 1], 8, 300);
            }
            named_bar_sync(7, 96);
            {
                const int w3 = warp - 9;
                const uint32_t rbar = bar0 + (B_RED + w3 * 2) * 8, rbuf = SM_RED + w3 * 8192;
                const int u0 = ((rt >> 1) * 36 + ct * 9) * 256 + (rt & 1) * 128;
                mbar_wait_sleep(bar0 + (B_KV + 15) * 8, 500);
                asm volatile("fence.proxy.async;" ::: "memory");
#pragma unroll 1
                for (int i = -2; i < 12; i++) {
                    if (i >= 0) {
                        __nanosleep(400);
                        mbar_wait(rbar + (i & 1) * 8, (i >> 1) & 1);
                        const uint4* sp = reinterpret_cast<const uint4*>(smem + rbuf + (i & 1) * 4096) + lane;
                        const uint4 v = hadd8_bf16(hadd8_bf16(hadd8_bf16(sp[0], sp[32]), hadd8_bf16(sp[64], sp[96])),
                                                   hadd8_bf16(hadd8_bf16(sp[128], sp[160]), hadd8_bf16(sp[192], sp[224])));
                        const int bx = i * 3 + w3;
                        uint2* fp = g_ffn + (blockIdx.x * 18 + (bx >> 2) * 2) * 128 + (bx & 3) * 32 + lane;
                        fp[0] = make_uint2(v.x, v.y);
                        fp[128] = make_uint2(v.z, v.w);
                    }
                    __syncwarp();
                    if (lane == 0 && i < 10) {
                        const int bx = (i + 2) * 3 + w3;
                        mbar_expect(rbar + (i & 1) * 8, 4096);
                        tma2d(sb + rbuf + (i & 1) * 4096, &tmP, (u0 + (bx >> 2) * 256 + (bx & 3) * 32) * 2, 0, rbar + (i & 1) * 8);
                    }
                }
            }
            __syncwarp();
            if (lane == 0) mbar_arrive(bar0 + B_BASE * 8);
            PROFH(43);
            if (ht == 0) {
#pragma unroll 1
                for (int i = 0; i < 6; i++) {
                    mbar_wait_sleep(bar0 + (B_OS + i) * 8, 200);
                    flag_signal(&g_flags.o_done[quarter * 8 + (((i >> 1) + rot) & 3) * 2 + (i & 1)]);
                }
            } else if (ht == 32) {
                const uint8_t* osrc = reinterpret_cast<const uint8_t*>(g_O) + rt * 73728;
                mbar_wait_sleep(bar0 + B_BASE * 8, 500);
                mbar_wait_sleep(bar0 + B_FREE * 8, 500);
                flag_wait(&g_flags.o_done[rt], 24, 100);
                if (atomicAdd(&g_flags.exited, 1u) == gridDim.x - 1) {
                    unsigned int* f = reinterpret_cast<unsigned int*>(&g_flags);
#pragma unroll 1
                    for (int i = 0; i < (int)(sizeof(Flags) / 4); i++) f[i] = 0;
                }
                prefetch_tmap(&tmXo);
                asm volatile("fence.proxy.async;" ::: "memory");
#pragma unroll 1
                for (int p = 0; p < 9; p++) {
                    if (p > 1) mbar_wait_sleep(bar0 + (B_FREE + p - 1) * 8, 40);
                    const int k = ks0 + p * 3 >= 36 ? ks0 + p * 3 - 36 : ks0 + p * 3;
                    mbar_expect(bar0 + (B_WO + p) * 8, 6144);
                    bulk_load(sb + 13824 + (p == 0 ? sm_piece(0) : (p == 1 ? sm_piece(1) : SM_KV + (p - 2) * PIECE)), osrc + k * 2048, 6144, bar0 + (B_WO + p) * 8);
                }
                mbar_expect(bar0 + B_LATE * 8, 2 * 9216);
                mbar_wait(bar0 + B_EARLY * 8, 0);
                tma2d(sb + sm_piece(0), &tmXo, ct * 144, rt * 64, bar0 + B_LATE * 8);
                tma2d(sb + sm_piece(0) + 9216, &tmXo, ct * 144 + 72, rt * 64, bar0 + B_LATE * 8);
            }
        }
    }
}

typedef CUresult (*EncodeFn)(CUtensorMap*, CUtensorMapDataType, cuuint32_t, void*, const cuuint64_t*, const cuuint64_t*, const cuuint32_t*,
                             const cuuint32_t*, CUtensorMapInterleave, CUtensorMapSwizzle, CUtensorMapL2promotion, CUtensorMapFloatOOBfill);

void make_map(EncodeFn fn, CUtensorMap* m, const void* base, int rank, const cuuint64_t* dims, const cuuint64_t* strides, const cuuint32_t* box) {
    cuuint32_t es[4] = {1, 1, 1, 1};
    fn(m, CU_TENSOR_MAP_DATA_TYPE_BFLOAT16, rank, const_cast<void*>(base), dims, strides, box, es, CU_TENSOR_MAP_INTERLEAVE_NONE,
       CU_TENSOR_MAP_SWIZZLE_128B, CU_TENSOR_MAP_L2_PROMOTION_L2_256B, CU_TENSOR_MAP_FLOAT_OOB_FILL_NONE);
}

}

extern "C" void kernel_launch(void* const* d_in, const int* in_sizes, int n_in, void* d_out, int out_size) {
    const __nv_bfloat16* x = (const __nv_bfloat16*)d_in[0];
    const __nv_bfloat16* wqkv = (const __nv_bfloat16*)d_in[1];
    const __nv_bfloat16* wo = (const __nv_bfloat16*)d_in[2];
    const __nv_bfloat16* w1 = (const __nv_bfloat16*)d_in[4];
    const __nv_bfloat16* b1 = (const __nv_bfloat16*)d_in[5];
    const __nv_bfloat16* w2 = (const __nv_bfloat16*)d_in[6];
    const __nv_bfloat16* b2 = (const __nv_bfloat16*)d_in[7];
    __nv_bfloat16* out = (__nv_bfloat16*)d_out;

    EncodeFn fn = nullptr;
    cudaDriverEntryPointQueryResult qr;
    cudaGetDriverEntryPoint("cuTensorMapEncodeTiled", (void**)&fn, cudaEnableDefault, &qr);
    CUtensorMap tmX, tmQ3, tmQ1, tm1, tm2, tmP, tmOut, tmXo, tm1b;
    {
        cuuint64_t d[2] = {DM, SEQ}, s[1] = {DM * 2};
        cuuint32_t b[2] = {72, 64}, es[2] = {1, 1};
        fn(&tmOut, CU_TENSOR_MAP_DATA_TYPE_BFLOAT16, 2, out, d, s, b, es, CU_TENSOR_MAP_INTERLEAVE_NONE, CU_TENSOR_MAP_SWIZZLE_NONE,
           CU_TENSOR_MAP_L2_PROMOTION_NONE, CU_TENSOR_MAP_FLOAT_OOB_FILL_NONE);
        fn(&tmXo, CU_TENSOR_MAP_DATA_TYPE_BFLOAT16, 2, const_cast<__nv_bfloat16*>(x), d, s, b, es, CU_TENSOR_MAP_INTERLEAVE_NONE,
           CU_TENSOR_MAP_SWIZZLE_NONE, CU_TENSOR_MAP_L2_PROMOTION_NONE, CU_TENSOR_MAP_FLOAT_OOB_FILL_NONE);
    }
    {
        void* gp = nullptr;
        cudaGetSymbolAddress(&gp, g_part);
        cuuint64_t d[2] = {SLAB * 2, 8}, s[1] = {SLAB * 16};
        cuuint32_t b[2] = {64, 8}, es[2] = {1, 1};
        fn(&tmP, CU_TENSOR_MAP_DATA_TYPE_INT64, 2, gp, d, s, b, es, CU_TENSOR_MAP_INTERLEAVE_NONE, CU_TENSOR_MAP_SWIZZLE_NONE,
           CU_TENSOR_MAP_L2_PROMOTION_NONE, CU_TENSOR_MAP_FLOAT_OOB_FILL_NONE);
    }
    {
        cuuint64_t d[4] = {64, 8, 9, SEQ / 8}, s[3] = {DM * 2, 128, DM * 2 * 8};
        cuuint32_t b[4] = {64, 8, 3, 2};
        make_map(fn, &tmX, x, 4, d, s, b);
    }
    {
        cuuint64_t d[3] = {3 * DM, DM, 3}, s[2] = {3 * DM * 2, 128};
        cuuint32_t b[3] = {64, 16, 3};
        make_map(fn, &tmQ3, wqkv, 3, d, s, b);
        make_map(fn, &tmQ1, wqkv, 2, d, s, b);
    }
    {
        cuuint64_t d[2] = {FF, DM}, s[1] = {FF * 2};
        cuuint32_t b[2] = {64, 64};
        make_map(fn, &tm1, w1, 2, d, s, b);
        cuuint64_t d3[3] = {64, DM, FF / 64}, s3[2] = {FF * 2, 128};
        cuuint32_t b3[3] = {64, 32, 2};
        make_map(fn, &tm1b, w1, 3, d3, s3, b3);
        cuuint64_t d2[2] = {DM, FF}, s2[1] = {DM * 2};
        make_map(fn, &tm2, w2, 2, d2, s2, b);
    }
    cudaFuncSetAttribute(fused_kernel, cudaFuncAttributeMaxDynamicSharedMemorySize, K1_SMEM);
    fused_kernel<<<128, 384, K1_SMEM, cudaStreamPerThread>>>(tmX, tmQ3, tmQ1, tm1, tm1b, tm2, tmP, tmOut, tmXo, b1, wqkv, w1, w2, wo, b2, 0ull);
}
```

```cpp
#include <cuda_runtime.h>
#include <cuda_bf16.h>
#include <cuda.h>
#include <stdint.h>

#define PROF(i) do { } while (0)
#define PROFT(i) do { } while (0)
#define PROFH(i) do { } while (0)
#define PROFWT(i) do { } while (0)
#define PROF_WG 0

namespace {

constexpr int SEQ = 2048, DM = 576, FF = 4608, NH = 32, DH = 18;

constexpr int KV_GROUP_BYTES = 5 * 128;
constexpr int KV_HEAD_BYTES = (SEQ / 8) * KV_GROUP_BYTES;
constexpr int Q_OFFSET = NH * KV_HEAD_BYTES;
#define POLY_MASK 0xB6B6
__device__ __align__(1024) uint8_t g_QKV[2 * NH * KV_HEAD_BYTES];
__device__ __align__(1024) float g_kmax[NH * 64];
constexpr int SLAB = 16 * 36 * 256;
__device__ __align__(1024) uint4 g_part[8 * SLAB];
__device__ __align__(1024) uint2 g_ffn[128 * 18 * 128];
__device__ __align__(1024) uint32_t g_O[SEQ * DM / 2];
struct Flags {
    unsigned int qkv_stored[16];
    unsigned int ffn_done[16];
    unsigned int o_done[32];
    unsigned int kv_ready;
    unsigned int exited;
};
__device__ Flags g_flags;
__device__ __align__(1024) uint4 g_Olate[32 * 9 * 128];
constexpr uint32_t O_EMPTY = 0xFFFFFFFFu;
constexpr int WO_TILE_BYTES = DM * 144 * 2;
__device__ __align__(1024) uint8_t g_Wo[4 * WO_TILE_BYTES];

__device__ __forceinline__ uint32_t s2u(const void* p) { return (uint32_t)__cvta_generic_to_shared(p); }
__device__ __forceinline__ void mbar_init(uint32_t b, int c) { asm volatile("mbarrier.init.shared::cta.b64 [%0], %1;" ::"r"(b), "r"(c) : "memory"); }
__device__ __forceinline__ void mbar_expect(uint32_t b, uint32_t bytes) {
    asm volatile("mbarrier.arrive.expect_tx.shared::cta.b64 _, [%0], %1;" ::"r"(b), "r"(bytes) : "memory");
}
__device__ __forceinline__ void mbar_wait(uint32_t b, uint32_t parity) {
    asm volatile(
        "{\n.reg .pred p;\n.reg .u32 c;\n"
        "mov.u32 c, 0;\n"
        "LOOP:\n"
        "mbarrier.try_wait.parity.shared::cta.b64 p, [%0], %1;\n"
        "@p bra DONE;\n"
        "add.u32 c, c, 1;\n"
        "setp.lt.u32 p, c, 4194304;\n"
        "@p bra LOOP;\n"
        "trap;\n"
        "DONE:\n}\n" ::"r"(b), "r"(parity) : "memory");
}
__device__ __forceinline__ void fence_barrier_init() { asm volatile("fence.mbarrier_init.release.cluster;" ::: "memory"); }
__device__ __forceinline__ void fence_proxy_async() { asm volatile("fence.proxy.async.shared::cta;" ::: "memory"); }
__device__ __forceinline__ void cluster_arrive() { asm volatile("barrier.cluster.arrive.relaxed.aligned;" ::: "memory"); }
__device__ __forceinline__ void cluster_wait() { asm volatile("barrier.cluster.wait.aligned;" ::: "memory"); }
__device__ __forceinline__ void named_bar_sync(int id, int n) { asm volatile("bar.sync %0, %1;" ::"r"(id), "r"(n) : "memory"); }

__device__ __forceinline__ void tma3d_mc(uint32_t dst, const CUtensorMap* tm, int c0, int c1, int c2, uint32_t bar, uint16_t mask) {
    asm volatile("cp.async.bulk.tensor.3d.shared::cluster.global.mbarrier::complete_tx::bytes.multicast::cluster [%0], [%1, {%3, %4, %5}], [%2], %6;"
                 ::"r"(dst), "l"(tm), "r"(bar), "r"(c0), "r"(c1), "r"(c2), "h"(mask) : "memory");
}
__device__ __forceinline__ void tma2d_mc(uint32_t dst, const CUtensorMap* tm, int c0, int c1, uint32_t bar, uint16_t mask) {
    asm volatile("cp.async.bulk.tensor.2d.shared::cluster.global.mbarrier::complete_tx::bytes.multicast::cluster [%0], [%1, {%3, %4}], [%2], %5;"
                 ::"r"(dst), "l"(tm), "r"(bar), "r"(c0), "r"(c1), "h"(mask) : "memory");
}
__device__ __forceinline__ void tma4d(uint32_t dst, const CUtensorMap* tm, int c0, int c1, int c2, int c3, uint32_t bar) {
    asm volatile("cp.async.bulk.tensor.4d.shared::cluster.global.mbarrier::complete_tx::bytes [%0], [%1, {%3, %4, %5, %6}], [%2];"
                 ::"r"(dst), "l"(tm), "r"(bar), "r"(c0), "r"(c1), "r"(c2), "r"(c3) : "memory");
}
__device__ __forceinline__ void tma2d(uint32_t dst, const CUtensorMap* tm, int c0, int c1, uint32_t bar) {
    asm volatile("cp.async.bulk.tensor.2d.shared::cluster.global.mbarrier::complete_tx::bytes [%0], [%1, {%3, %4}], [%2];"
                 ::"r"(dst), "l"(tm), "r"(bar), "r"(c0), "r"(c1) : "memory");
}
__device__ __forceinline__ void bulk_load(uint32_t dst, const void* src, uint32_t bytes, uint32_t bar) {
    asm volatile("cp.async.bulk.shared::cluster.global.mbarrier::complete_tx::bytes [%0], [%1], %2, [%3];"
                 ::"r"(dst), "l"(src), "r"(bytes), "r"(bar) : "memory");
}
__device__ __forceinline__ void prefetch_l2(const void* p, uint32_t bytes) {
    asm volatile("cp.async.bulk.prefetch.L2.global [%0], %1;" ::"l"(p), "r"(bytes) : "memory");
}
__device__ __forceinline__ void prefetch_tmap(const CUtensorMap* tm) { asm volatile("prefetch.tensormap [%0];" ::"l"(tm) : "memory"); }

__device__ __forceinline__ void wg_fence() { asm volatile("wgmma.fence.sync.aligned;" ::: "memory"); }
__device__ __forceinline__ void wg_commit() { asm volatile("wgmma.commit_group.sync.aligned;" ::: "memory"); }
template <int N> __device__ __forceinline__ void wg_wait() { asm volatile("wgmma.wait_group.sync.aligned %0;" ::"n"(N) : "memory"); }
template <int N> __device__ __forceinline__ void reg_fence(float (&d)[N]) {
#pragma unroll
    for (int i = 0; i < N; i++) asm volatile("" : "+f"(d[i])::"memory");
}
template <int N> __device__ __forceinline__ void reg_fence(uint32_t (&d)[N]) {
#pragma unroll
    for (int i = 0; i < N; i++) asm volatile("" : "+r"(d[i])::"memory");
}
template <int R> __device__ __forceinline__ void reg_alloc() { asm volatile("setmaxnreg.inc.sync.aligned.u32 %0;" ::"n"(R)); }
template <int R> __device__ __forceinline__ void reg_dealloc() { asm volatile("setmaxnreg.dec.sync.aligned.u32 %0;" ::"n"(R)); }

__device__ __forceinline__ uint64_t mk_desc(uint64_t z, uint32_t addr, uint32_t lbo, uint32_t sbo, uint32_t swz) {
    return z + ((uint64_t)(((addr & 0x3FFFF) >> 4) | ((lbo >> 4) << 16)) | ((uint64_t)((sbo >> 4) | (swz << 30)) << 32));
}
__device__ __forceinline__ uint32_t pack_bf16(float lo, float hi) {
    uint32_t r;
    asm("cvt.rn.bf16x2.f32 %0, %1, %2;" : "=r"(r) : "f"(hi), "f"(lo));
    return r;
}
__device__ __forceinline__ float bf_lo(uint32_t w) { return __uint_as_float(w << 16); }
__device__ __forceinline__ float bf_hi(uint32_t w) { return __uint_as_float(w & 0xFFFF0000u); }
__device__ __forceinline__ float ex2(float x) {
    float r;
    asm("ex2.approx.ftz.f32 %0, %1;" : "=f"(r) : "f"(x));
    return r;
}
__device__ __forceinline__ float tanh_fast(float x) {
    float r;
    asm("tanh.approx.f32 %0, %1;" : "=f"(r) : "f"(x));
    return r;
}
__device__ __forceinline__ uint32_t hfma2_bf16(uint32_t a, uint32_t b, uint32_t c) {
    uint32_t r;
    asm("fma.rn.bf16x2 %0, %1, %2, %3;" : "=r"(r) : "r"(a), "r"(b), "r"(c));
    return r;
}
__device__ __forceinline__ uint32_t hadd2_bf16(uint32_t a, uint32_t b) {
    uint32_t r;
    asm("add.rn.bf16x2 %0, %1, %2;" : "=r"(r) : "r"(a), "r"(b));
    return r;
}
__device__ __forceinline__ void ldsm4(uint32_t (&a)[4], uint32_t addr) {
    asm volatile("ldmatrix.sync.aligned.m8n8.x4.shared.b16 {%0, %1, %2, %3}, [%4];" : "=r"(a[0]), "=r"(a[1]), "=r"(a[2]), "=r"(a[3]) : "r"(addr) : "memory");
}
__device__ __forceinline__ void stsm4(uint32_t addr, const uint32_t (&a)[4]) {
    asm volatile("stmatrix.sync.aligned.m8n8.x4.shared.b16 [%0], {%1, %2, %3, %4};" ::"r"(addr), "r"(a[0]), "r"(a[1]), "r"(a[2]), "r"(a[3]) : "memory");
}
__device__ __forceinline__ void mma16816(float (&c)[4], const uint32_t (&a)[4], uint32_t b0, uint32_t b1) {
    asm("mma.sync.aligned.m16n8k16.row.col.f32.bf16.bf16.f32 {%0, %1, %2, %3}, {%4, %5, %6, %7}, {%8, %9}, {%0, %1, %2, %3};"
        : "+f"(c[0]), "+f"(c[1]), "+f"(c[2]), "+f"(c[3]) : "r"(a[0]), "r"(a[1]), "r"(a[2]), "r"(a[3]), "r"(b0), "r"(b1));
}
__device__ __forceinline__ float gelu2(float u) {
    const float w = fmaf(u * u, 0.0356774081f, 0.7978845608f);
    return fmaf(u, tanh_fast(u * w), u);
}

template<int TB, int AOFF, int BOFF> __device__ __forceinline__ void wgmma_ss_n216(float (&d)[108], uint64_t da, uint64_t db, int sd) {
    asm volatile("{\n.reg .pred p;\n.reg .b64 ta, tb;\nsetp.ne.b32 p, %110, 0;\nadd.s64 ta, %108, %112;\nadd.s64 tb, %109, %113;\n"
      "wgmma.mma_async.sync.aligned.m64n216k16.f32.bf16.bf16 {%0, %1, %2, %3, %4, %5, %6, %7, %8, %9, %10, %11, %12, %13, %14, %15, %16, %17, %18, %19, %20, %21, %22, %23, %24, %25, %26, %27, %28, %29, %30, %31, %32, %33, %34, %35, %36, %37, %38, %39, %40, %41, %42, %43, %44, %45, %46, %47, %48, %49, %50, %51, %52, %53, %54, %55, %56, %57, %58, %59, %60, %61, %62, %63, %64, %65, %66, %67, %68, %69, %70, %71, %72, %73, %74, %75, %76, %77, %78, %79, %80, %81, %82, %83, %84, %85, %86, %87, %88, %89, %90, %91, %92, %93, %94, %95, %96, %97, %98, %99, %100, %101, %102, %103, %104, %105, %106, %107}, ta, tb, p, 1, 1, 0, %111;\n}\n"
      : "+f"(d[0]), "+f"(d[1]), "+f"(d[2]), "+f"(d[3]), "+f"(d[4]), "+f"(d[5]), "+f"(d[6]), "+f"(d[7]), "+f"(d[8]), "+f"(d[9]), "+f"(d[10]), "+f"(d[11]), "+f"(d[12]), "+f"(d[13]), "+f"(d[14]), "+f"(d[15]), "+f"(d[16]), "+f"(d[17]), "+f"(d[18]), "+f"(d[19]), "+f"(d[20]), "+f"(d[21]), "+f"(d[22]), "+f"(d[23]), "+f"(d[24]), "+f"(d[25]), "+f"(d[26]), "+f"(d[27]), "+f"(d[28]), "+f"(d[29]), "+f"(d[30]), "+f"(d[31]), "+f"(d[32]), "+f"(d[33]), "+f"(d[34]), "+f"(d[35]), "+f"(d[36]), "+f"(d[37]), "+f"(d[38]), "+f"(d[39]), "+f"(d[40]), "+f"(d[41]), "+f"(d[42]), "+f"(d[43]), "+f"(d[44]), "+f"(d[45]), "+f"(d[46]), "+f"(d[47]), "+f"(d[48]), "+f"(d[49]), "+f"(d[50]), "+f"(d[51]), "+f"(d[52]), "+f"(d[53]), "+f"(d[54]), "+f"(d[55]), "+f"(d[56]), "+f"(d[57]), "+f"(d[58]), "+f"(d[59]), "+f"(d[60]), "+f"(d[61]), "+f"(d[62]), "+f"(d[63]), "+f"(d[64]), "+f"(d[65]), "+f"(d[66]), "+f"(d[67]), "+f"(d[68]), "+f"(d[69]), "+f"(d[70]), "+f"(d[71]), "+f"(d[72]), "+f"(d[73]), "+f"(d[74]), "+f"(d[75]), "+f"(d[76]), "+f"(d[77]), "+f"(d[78]), "+f"(d[79]), "+f"(d[80]), "+f"(d[81]), "+f"(d[82]), "+f"(d[83]), "+f"(d[84]), "+f"(d[85]), "+f"(d[86]), "+f"(d[87]), "+f"(d[88]), "+f"(d[89]), "+f"(d[90]), "+f"(d[91]), "+f"(d[92]), "+f"(d[93]), "+f"(d[94]), "+f"(d[95]), "+f"(d[96]), "+f"(d[97]), "+f"(d[98]), "+f"(d[99]), "+f"(d[100]), "+f"(d[101]), "+f"(d[102]), "+f"(d[103]), "+f"(d[104]), "+f"(d[105]), "+f"(d[106]), "+f"(d[107])
      : "l"(da), "l"(db), "r"(sd), "n"(TB), "n"(AOFF), "n"(BOFF));
}

template<int TB, int AOFF, int BOFF> __device__ __forceinline__ void wgmma_ss_n128(float (&d)[64], uint64_t da, uint64_t db, int sd) {
    asm volatile("{\n.reg .pred p;\n.reg .b64 ta, tb;\nsetp.ne.b32 p, %66, 0;\nadd.s64 ta, %64, %68;\nadd.s64 tb, %65, %69;\n"
      "wgmma.mma_async.sync.aligned.m64n128k16.f32.bf16.bf16 {%0, %1, %2, %3, %4, %5, %6, %7, %8, %9, %10, %11, %12, %13, %14, %15, %16, %17, %18, %19, %20, %21, %22, %23, %24, %25, %26, %27, %28, %29, %30, %31, %32, %33, %34, %35, %36, %37, %38, %39, %40, %41, %42, %43, %44, %45, %46, %47, %48, %49, %50, %51, %52, %53, %54, %55, %56, %57, %58, %59, %60, %61, %62, %63}, ta, tb, p, 1, 1, 0, %67;\n}\n"
      : "+f"(d[0]), "+f"(d[1]), "+f"(d[2]), "+f"(d[3]), "+f"(d[4]), "+f"(d[5]), "+f"(d[6]), "+f"(d[7]), "+f"(d[8]), "+f"(d[9]), "+f"(d[10]), "+f"(d[11]), "+f"(d[12]), "+f"(d[13]), "+f"(d[14]), "+f"(d[15]), "+f"(d[16]), "+f"(d[17]), "+f"(d[18]), "+f"(d[19]), "+f"(d[20]), "+f"(d[21]), "+f"(d[22]), "+f"(d[23]), "+f"(d[24]), "+f"(d[25]), "+f"(d[26]), "+f"(d[27]), "+f"(d[28]), "+f"(d[29]), "+f"(d[30]), "+f"(d[31]), "+f"(d[32]), "+f"(d[33]), "+f"(d[34]), "+f"(d[35]), "+f"(d[36]), "+f"(d[37]), "+f"(d[38]), "+f"(d[39]), "+f"(d[40]), "+f"(d[41]), "+f"(d[42]), "+f"(d[43]), "+f"(d[44]), "+f"(d[45]), "+f"(d[46]), "+f"(d[47]), "+f"(d[48]), "+f"(d[49]), "+f"(d[50]), "+f"(d[51]), "+f"(d[52]), "+f"(d[53]), "+f"(d[54]), "+f"(d[55]), "+f"(d[56]), "+f"(d[57]), "+f"(d[58]), "+f"(d[59]), "+f"(d[60]), "+f"(d[61]), "+f"(d[62]), "+f"(d[63])
      : "l"(da), "l"(db), "r"(sd), "n"(TB), "n"(AOFF), "n"(BOFF));
}

template<int TB, int AOFF, int BOFF> __device__ __forceinline__ void wgmma_ss_n72(float (&d)[36], uint64_t da, uint64_t db, int sd) {
    asm volatile("{\n.reg .pred p;\n.reg .b64 ta, tb;\nsetp.ne.b32 p, %38, 0;\nadd.s64 ta, %36, %40;\nadd.s64 tb, %37, %41;\n"
      "wgmma.mma_async.sync.aligned.m64n72k16.f32.bf16.bf16 {%0, %1, %2, %3, %4, %5, %6, %7, %8, %9, %10, %11, %12, %13, %14, %15, %16, %17, %18, %19, %20, %21, %22, %23, %24, %25, %26, %27, %28, %29, %30, %31, %32, %33, %34, %35}, ta, tb, p, 1, 1, 0, %39;\n}\n"
      : "+f"(d[0]), "+f"(d[1]), "+f"(d[2]), "+f"(d[3]), "+f"(d[4]), "+f"(d[5]), "+f"(d[6]), "+f"(d[7]), "+f"(d[8]), "+f"(d[9]), "+f"(d[10]), "+f"(d[11]), "+f"(d[12]), "+f"(d[13]), "+f"(d[14]), "+f"(d[15]), "+f"(d[16]), "+f"(d[17]), "+f"(d[18]), "+f"(d[19]), "+f"(d[20]), "+f"(d[21]), "+f"(d[22]), "+f"(d[23]), "+f"(d[24]), "+f"(d[25]), "+f"(d[26]), "+f"(d[27]), "+f"(d[28]), "+f"(d[29]), "+f"(d[30]), "+f"(d[31]), "+f"(d[32]), "+f"(d[33]), "+f"(d[34]), "+f"(d[35])
      : "l"(da), "l"(db), "r"(sd), "n"(TB), "n"(AOFF), "n"(BOFF));
}

template<int TB, int BOFF> __device__ __forceinline__ void wgmma_rs_n24(float (&d)[12], uint32_t a0, uint32_t a1, uint32_t a2, uint32_t a3, uint64_t db, int sd) {
    asm volatile("{\n.reg .pred p;\n.reg .b64 tb;\nsetp.ne.b32 p, %17, 0;\nadd.s64 tb, %16, %19;\n"
      "wgmma.mma_async.sync.aligned.m64n24k16.f32.bf16.bf16 {%0, %1, %2, %3, %4, %5, %6, %7, %8, %9, %10, %11}, {%12, %13, %14, %15}, tb, p, 1, 1, %18;\n}\n"
      : "+f"(d[0]), "+f"(d[1]), "+f"(d[2]), "+f"(d[3]), "+f"(d[4]), "+f"(d[5]), "+f"(d[6]), "+f"(d[7]), "+f"(d[8]), "+f"(d[9]), "+f"(d[10]), "+f"(d[11])
      : "r"(a0), "r"(a1), "r"(a2), "r"(a3), "l"(db), "r"(sd), "n"(TB), "n"(BOFF));
}

template<int TB, int BOFF> __device__ __forceinline__ void wgmma_rs_n72(float (&d)[36], uint32_t a0, uint32_t a1, uint32_t a2, uint32_t a3, uint64_t db, int sd) {
    asm volatile("{\n.reg .pred p;\n.reg .b64 tb;\nsetp.ne.b32 p, %41, 0;\nadd.s64 tb, %40, %43;\n"
      "wgmma.mma_async.sync.aligned.m64n72k16.f32.bf16.bf16 {%0, %1, %2, %3, %4, %5, %6, %7, %8, %9, %10, %11, %12, %13, %14, %15, %16, %17, %18, %19, %20, %21, %22, %23, %24, %25, %26, %27, %28, %29, %30, %31, %32, %33, %34, %35}, {%36, %37, %38, %39}, tb, p, 1, 1, %42;\n}\n"
      : "+f"(d[0]), "+f"(d[1]), "+f"(d[2]), "+f"(d[3]), "+f"(d[4]), "+f"(d[5]), "+f"(d[6]), "+f"(d[7]), "+f"(d[8]), "+f"(d[9]), "+f"(d[10]), "+f"(d[11]), "+f"(d[12]), "+f"(d[13]), "+f"(d[14]), "+f"(d[15]), "+f"(d[16]), "+f"(d[17]), "+f"(d[18]), "+f"(d[19]), "+f"(d[20]), "+f"(d[21]), "+f"(d[22]), "+f"(d[23]), "+f"(d[24]), "+f"(d[25]), "+f"(d[26]), "+f"(d[27]), "+f"(d[28]), "+f"(d[29]), "+f"(d[30]), "+f"(d[31]), "+f"(d[32]), "+f"(d[33]), "+f"(d[34]), "+f"(d[35])
      : "r"(a0), "r"(a1), "r"(a2), "r"(a3), "l"(db), "r"(sd), "n"(TB), "n"(BOFF));
}

template<int TB, int AINC, int BINC> __device__ __forceinline__ void wgmma_ss_n64_pi(float (&d)[32], uint64_t& da, uint64_t& db, int sd) {
    asm volatile("{\n.reg .pred p;\nsetp.ne.b32 p, %34, 0;\n"
      "wgmma.mma_async.sync.aligned.m64n64k16.f32.bf16.bf16 {%0, %1, %2, %3, %4, %5, %6, %7, %8, %9, %10, %11, %12, %13, %14, %15, %16, %17, %18, %19, %20, %21, %22, %23, %24, %25, %26, %27, %28, %29, %30, %31}, %32, %33, p, 1, 1, 0, %35;\n"
      "add.s64 %32, %32, %36;\nadd.s64 %33, %33, %37;\n}\n"
      : "+f"(d[0]), "+f"(d[1]), "+f"(d[2]), "+f"(d[3]), "+f"(d[4]), "+f"(d[5]), "+f"(d[6]), "+f"(d[7]), "+f"(d[8]), "+f"(d[9]), "+f"(d[10]), "+f"(d[11]), "+f"(d[12]), "+f"(d[13]), "+f"(d[14]), "+f"(d[15]), "+f"(d[16]), "+f"(d[17]), "+f"(d[18]), "+f"(d[19]), "+f"(d[20]), "+f"(d[21]), "+f"(d[22]), "+f"(d[23]), "+f"(d[24]), "+f"(d[25]), "+f"(d[26]), "+f"(d[27]), "+f"(d[28]), "+f"(d[29]), "+f"(d[30]), "+f"(d[31]), "+l"(da), "+l"(db)
      : "r"(sd), "n"(TB), "n"(AINC), "n"(BINC));
}

template<int TB, int BINC> __device__ __forceinline__ void wgmma_rs_n64_pi(float (&d)[32], uint32_t a0, uint32_t a1, uint32_t a2, uint32_t a3, uint64_t& db, int sd) {
    asm volatile("{\n.reg .pred p;\nsetp.ne.b32 p, %37, 0;\n"
      "wgmma.mma_async.sync.aligned.m64n64k16.f32.bf16.bf16 {%0, %1, %2, %3, %4, %5, %6, %7, %8, %9, %10, %11, %12, %13, %14, %15, %16, %17, %18, %19, %20, %21, %22, %23, %24, %25, %26, %27, %28, %29, %30, %31}, {%33, %34, %35, %36}, %32, p, 1, 1, %38;\n"
      "add.s64 %32, %32, %39;\n}\n"
      : "+f"(d[0]), "+f"(d[1]), "+f"(d[2]), "+f"(d[3]), "+f"(d[4]), "+f"(d[5]), "+f"(d[6]), "+f"(d[7]), "+f"(d[8]), "+f"(d[9]), "+f"(d[10]), "+f"(d[11]), "+f"(d[12]), "+f"(d[13]), "+f"(d[14]), "+f"(d[15]), "+f"(d[16]), "+f"(d[17]), "+f"(d[18]), "+f"(d[19]), "+f"(d[20]), "+f"(d[21]), "+f"(d[22]), "+f"(d[23]), "+f"(d[24]), "+f"(d[25]), "+f"(d[26]), "+f"(d[27]), "+f"(d[28]), "+f"(d[29]), "+f"(d[30]), "+f"(d[31]), "+l"(db)
      : "r"(a0), "r"(a1), "r"(a2), "r"(a3), "r"(sd), "n"(TB), "n"(BINC));
}

constexpr int K1_XN_BYTES = 16 * 9216;
constexpr int K1_OFF_RING = K1_XN_BYTES;
constexpr int K1_OFF_BIAS = K1_OFF_RING + 10 * 8192;
constexpr int K1_OFF_BAR = K1_OFF_BIAS + 576 * 2;
constexpr int K1_SMEM = K1_OFF_BAR + 800;
constexpr float QSCALE = 0.23570226039551584f * 1.4426950408889634f;

struct K1Ctx {
    uint32_t full0;
    uint32_t rel_addr;
    uint64_t descA, descB;
    uint32_t phase;
    __device__ __forceinline__ void begin_stage(int s) {
        mbar_wait(full0 + s * 8, phase);
        wg_fence();
    }
    __device__ __forceinline__ void release(int s) {
        if (rel_addr) asm volatile("mbarrier.arrive.shared::cluster.b64 _, [%0];" ::"r"(rel_addr + s * 8) : "memory");
    }
    __device__ __forceinline__ void end_stage(int s) {
        wg_commit();
        wg_wait<1>();
        release(s == 0 ? 8 : s - 1);
    }
};

__host__ __device__ constexpr int a_off(int ks) { return ((ks / 12) * 49152 + ((ks >> 2) % 3) * 1024 + (ks & 3) * 32) >> 4; }

template <int V> struct IC { static constexpr int value = V; };
template <int I, int N, class F> __device__ __forceinline__ void static_for(F&& f) {
    if constexpr (I < N) { f(IC<I>{}); static_for<I + 1, N>(f); }
}

template <bool A_RS, bool B_RS, class Epi>
__device__ __forceinline__ void tile_pair(K1Ctx& c, float (&accA)[32], float (&accB)[32], uint32_t (&h)[144], Epi&& epi) {
    static_for<0, 9>([&](auto sc) {
        constexpr int s = decltype(sc)::value;
        c.begin_stage(s);
        static_for<0, 8>([&](auto tc) {
            constexpr int t = decltype(tc)::value, kk = s * 8 + t, ks = kk % 36;
            constexpr int db = ks == 35 ? -35 * 128 : 128, da = a_off((ks + 1) % 36) - a_off(ks);
            if constexpr (kk < 36) {
                if constexpr (A_RS) wgmma_rs_n64_pi<1, db>(accA, h[ks * 4], h[ks * 4 + 1], h[ks * 4 + 2], h[ks * 4 + 3], c.descB, ks != 0);
                else wgmma_ss_n64_pi<1, da, db>(accA, c.descA, c.descB, ks != 0);
            } else {
                if constexpr (B_RS) wgmma_rs_n64_pi<1, db>(accB, h[ks * 4], h[ks * 4 + 1], h[ks * 4 + 2], h[ks * 4 + 3], c.descB, ks != 0);
                else wgmma_ss_n64_pi<1, da, db>(accB, c.descA, c.descB, ks != 0);
            }
            if constexpr (t == 0) {
                c.end_stage(s);
                epi(sc);
                wg_fence();
            }
        });
        wg_commit();
    });
    c.phase ^= 1;
}

template <int B0, int NB, int HOFF>
__device__ __forceinline__ void gelu_blocks(const float (&acc)[32], uint32_t (&h)[144], const uint32_t (&bq)[8], float rs0, float rs1) {
#pragma unroll
    for (int b = B0; b < B0 + NB; b++) {
        const float b0 = bf_lo(bq[b]), b1 = bf_hi(bq[b]);
        h[HOFF + b * 2 + 0] = pack_bf16(gelu2(fmaf(acc[b * 4 + 0], rs0, b0)), gelu2(fmaf(acc[b * 4 + 1], rs0, b1)));
        h[HOFF + b * 2 + 1] = pack_bf16(gelu2(fmaf(acc[b * 4 + 2], rs1, b0)), gelu2(fmaf(acc[b * 4 + 3], rs1, b1)));
    }
#pragma unroll
    for (int i = HOFF + B0 * 2; i < HOFF + (B0 + NB) * 2; i++) asm volatile("" : "+r"(h[i]));
}
__device__ __forceinline__ void load_bias(uint32_t (&bq)[8], uint32_t addr) {
    asm volatile("ld.shared.v4.u32 {%0, %1, %2, %3}, [%4];" : "=r"(bq[0]), "=r"(bq[1]), "=r"(bq[2]), "=r"(bq[3]) : "r"(addr));
    asm volatile("ld.shared.v4.u32 {%0, %1, %2, %3}, [%4 + 16];" : "=r"(bq[4]), "=r"(bq[5]), "=r"(bq[6]), "=r"(bq[7]) : "r"(addr));
}
__device__ __forceinline__ void st_pred2(bool p, void* a, uint32_t x, uint32_t y) {
    asm volatile("{\n.reg .pred p;\nsetp.ne.u32 p, %3, 0;\n@p st.global.v2.u32 [%0], {%1, %2};\n}\n" ::"l"(a), "r"(x), "r"(y), "r"((uint32_t)p) : "memory");
}
__device__ __forceinline__ void st_pred1(bool p, void* a, uint32_t x) {
    asm volatile("{\n.reg .pred p;\nsetp.ne.u32 p, %2, 0;\n@p st.global.u32 [%0], %1;\n}\n" ::"l"(a), "r"(x), "r"((uint32_t)p) : "memory");
}
template <int S> __device__ __forceinline__ void store_part(const float (&o)[32], uint4* p) {
    uint4 v;
    v.x = pack_bf16(o[S * 8 + 0], o[S * 8 + 1]); v.y = pack_bf16(o[S * 8 + 2], o[S * 8 + 3]);
    v.z = pack_bf16(o[S * 8 + 4], o[S * 8 + 5]); v.w = pack_bf16(o[S * 8 + 6], o[S * 8 + 7]);
    p[S * 256] = v;
}

constexpr int NCHUNK = 16;
constexpr int CHUNK_BYTES = KV_HEAD_BYTES / NCHUNK;
constexpr int SM_Q = 0;
constexpr int SM_KV = 32768;
constexpr int PIECE = 19968;
__host__ __device__ constexpr int sm_piece(int p) { return p == 0 ? 209408 : (p == 1 ? 0 : SM_KV + (p - 2) * PIECE); }
__host__ __device__ constexpr int sm_wstep(int k) { return k < 27 ? sm_piece(k / 3) + (k % 3) * 4608 : (k < 35 ? SM_KV + 7 * PIECE + (k - 27) * 4608 : PIECE); }
__host__ __device__ constexpr int sm_ostep(int k) { return sm_piece(k / 3) + 13824 + (k % 3) * 2048; }
constexpr int SM_RED = SM_KV + KV_HEAD_BYTES;

__device__ __forceinline__ float exp2_fixed(float y) {
    const float u = __uint_as_float(__float_as_uint(y) & 0xFF807FFFu) - 512.02545f;
    float t = fmaf(u, 0.019497588f, 0.114550486f);
    t = fmaf(t, u, -0.29839927f);
    return fmaf(t, u, y);
}
__device__ __forceinline__ uint32_t pack_fixed(float lo, float hi) { return __byte_perm(__float_as_uint(lo), __float_as_uint(hi), 0x6521); }

#define LAG_FIRST 1
#define LAG_PER 2
#define PV_GROUP 4
#define POLY_MODE 1
__device__ __forceinline__ uint32_t exp2_packed(float y0, float y1, uint32_t one2) {
    const uint32_t w = pack_fixed(y0, y1);
    uint32_t m;
    asm("lop3.b32 %0, %1, 0x007F007F, %2, 0xEA;" : "=r"(m) : "r"(w), "r"(one2));
    const uint32_t d = hfma2_bf16(m, 0x3EF93EF9u, 0xBF38BF38u);
    const uint32_t e = hfma2_bf16(d, d, 0xBD71BD71u);
    return hfma2_bf16(w, e, w);
}
constexpr int KV_TILE = CHUNK_BYTES / 16;
template <int OFF> __device__ __forceinline__ void issue_qk(float (&s)[64], uint64_t qd, uint64_t kd) {
    wgmma_ss_n128<0, 0, OFF + (8 << 16)>(s, qd, kd, 0);
    wgmma_ss_n128<0, 16, OFF + 32>(s, qd, kd, 1);
}
template <int OFF> __device__ __forceinline__ void issue_pv(float (&o)[12], const uint32_t (&p)[32], uint64_t vd) {
    static_for<0, 8>([&](auto kc) {
        constexpr int k = decltype(kc)::value;
        wgmma_rs_n24<1, OFF + k * (2 * KV_GROUP_BYTES / 16)>(o, p[k * 4], p[k * 4 + 1], p[k * 4 + 2], p[k * 4 + 3], vd, 1);
    });
}
template <int OFF>
__device__ __forceinline__ void softmax_pv(const float (&s)[64], uint32_t (&p)[32], float (&o)[12], uint64_t vd, uint32_t one2) {
    static_for<0, 8 / PV_GROUP>([&](auto gc) {
        constexpr int g0 = decltype(gc)::value * PV_GROUP;
#pragma unroll
        for (int b = g0 * 2; b < (g0 + PV_GROUP) * 2; b++) {
            if ((POLY_MASK >> b) & 1) {
                p[b * 2 + 0] = exp2_packed(s[b * 4 + 0], s[b * 4 + 1], one2);
                p[b * 2 + 1] = exp2_packed(s[b * 4 + 2], s[b * 4 + 3], one2);
            } else {
                p[b * 2 + 0] = pack_bf16(ex2(s[b * 4 + 0]), ex2(s[b * 4 + 1]));
                p[b * 2 + 1] = pack_bf16(ex2(s[b * 4 + 2]), ex2(s[b * 4 + 3]));
            }
        }
#pragma unroll
        for (int i = g0 * 4; i < (g0 + PV_GROUP) * 4; i++) asm volatile("" : "+r"(p[i])::"memory");
        wg_fence();
        static_for<g0, g0 + PV_GROUP>([&](auto kc) {
            constexpr int k = decltype(kc)::value;
            wgmma_rs_n24<1, OFF + k * (2 * KV_GROUP_BYTES / 16)>(o, p[k * 4], p[k * 4 + 1], p[k * 4 + 2], p[k * 4 + 3], vd, 1);
        });
    });
    wg_commit();
}
template <int OFF>
__device__ __forceinline__ void softmax_pv_lag(const float (&s)[64], uint32_t (&p)[32], const uint32_t (&pp)[32], float (&o)[12], uint64_t vd, uint32_t one2) {
    static_for<0, 8>([&](auto gc) {
        constexpr int g0 = decltype(gc)::value;
#pragma unroll
        for (int b = g0 * 2; b < g0 * 2 + 2; b++) {
            if ((POLY_MASK >> b) & 1) {
                p[b * 2 + 0] = exp2_packed(s[b * 4 + 0], s[b * 4 + 1], one2);
                p[b * 2 + 1] = exp2_packed(s[b * 4 + 2], s[b * 4 + 3], one2);
            } else {
                p[b * 2 + 0] = pack_bf16(ex2(s[b * 4 + 0]), ex2(s[b * 4 + 1]));
                p[b * 2 + 1] = pack_bf16(ex2(s[b * 4 + 2]), ex2(s[b * 4 + 3]));
            }
        }
#pragma unroll
        for (int i = g0 * 4; i < g0 * 4 + 4; i++) asm volatile("" : "+r"(p[i])::"memory");
        if constexpr (g0 >= LAG_FIRST && g0 < LAG_FIRST + 8 / LAG_PER) {
            static_for<(g0 - LAG_FIRST) * LAG_PER, (g0 - LAG_FIRST + 1) * LAG_PER>([&](auto kc) {
                constexpr int k = decltype(kc)::value;
                wgmma_rs_n24<1, OFF + k * (2 * KV_GROUP_BYTES / 16)>(o, pp[k * 4], pp[k * 4 + 1], pp[k * 4 + 2], pp[k * 4 + 3], vd, 1);
            });
        }
    });
    wg_commit();
}
__device__ __forceinline__ int head_pair(int hh, int i) {
    if (i == 8) return hh == 3 ? 0 : 8;
    const int q = i >> 1, t = (4 - hh) & 3;
    if ((i & 1) == 0) return t + q;
    return (hh == 1 || hh == 2) ? (q >= hh ? q - hh : t + 4 + q) : t + 4 + q;
}
template <bool LATE> __device__ __forceinline__ void store_o(float (&o)[12], int rt, int head, int wq, int lane) {
    const int g = lane >> 2, q = lane & 3;
    const float i0 = __fdividef(1.0f, __shfl_sync(~0u, o[8], lane | 3)), i1 = __fdividef(1.0f, __shfl_sync(~0u, o[10], lane | 3));
#pragma unroll
    for (int i = 0; i < 3; i++) {
        const uint32_t w0 = pack_bf16(o[i * 4] * i0, o[i * 4 + 1] * i0), w1 = pack_bf16(o[i * 4 + 2] * i1, o[i * 4 + 3] * i1);
        if (i < 2 || q == 2) {
            if constexpr (LATE) {
                const int pc = (head & 7) * 9 + head_pair(head & 3, i < 2 ? i * 4 + q : 8);
                uint32_t* op = reinterpret_cast<uint32_t*>(g_Olate) + (((rt * 9 + (pc >> 3)) * 128 + wq * 32 + g * 4 + (pc & 3)) * 4 + ((pc >> 2) & 1) * 2);
                asm volatile("st.relaxed.gpu.global.v2.u32 [%0], {%1, %2};" ::"l"(op), "r"(w0), "r"(w1) : "memory");
            } else {
                const int pc = head * 9 + head_pair(head & 3, i < 2 ? i * 4 + q : 8);
                uint32_t* op = g_O + ((rt * 72 + (pc >> 2)) * 8 + wq * 2) * 32 + g * 4 + (pc & 3);
                op[0] = w0;
                op[32] = w1;
            }
        }
    }
#pragma unroll
    for (int i = 0; i < 12; i++) o[i] = 0.f;
}
__device__ __forceinline__ void mbar_arrive(uint32_t b) { asm volatile("mbarrier.arrive.shared::cta.b64 _, [%0];" ::"r"(b) : "memory"); }
__device__ __forceinline__ void mbar_wait_sleep(uint32_t b, uint32_t ns) {
    uint32_t ok, spins = 0;
    while (true) {
        asm volatile("{\n.reg .pred p;\nmbarrier.try_wait.parity.shared::cta.b64 p, [%1], 0;\nselp.u32 %0, 1, 0, p;\n}\n" : "=r"(ok) : "r"(b) : "memory");
        if (ok) break;
        __nanosleep(ns);
        if (++spins > (1u << 21)) __trap();
    }
}
__device__ __forceinline__ void flag_signal(unsigned int* f) {
    __threadfence();
    atomicAdd(f, 1u);
}
__device__ __forceinline__ void flag_wait(const unsigned int* f, unsigned int target, unsigned int sleep_ns) {
    uint32_t v, spins = 0;
    while (true) {
        asm volatile("ld.acquire.gpu.global.u32 %0, [%1];" : "=r"(v) : "l"(f) : "memory");
        if (v >= target) break;
        if (sleep_ns) __nanosleep(sleep_ns);
        if (++spins > (1u << 21)) __trap();
    }
}
__device__ __forceinline__ uint4 hadd8_bf16(const uint4 a, const uint4 b) {
    return make_uint4(hadd2_bf16(a.x, b.x), hadd2_bf16(a.y, b.y), hadd2_bf16(a.z, b.z), hadd2_bf16(a.w, b.w));
}
__device__ __forceinline__ float sumsq2(uint32_t w) { return fmaf(bf_lo(w), bf_lo(w), bf_hi(w) * bf_hi(w)); }
__device__ __forceinline__ float sumsq8(const uint4 v) { return (sumsq2(v.x) + sumsq2(v.y)) + (sumsq2(v.z) + sumsq2(v.w)); }

enum { B_FULL = 0, B_EMPTY = 9, B_BASE = 18, B_XNDEAD = 19, B_QRDY = 20, B_FFN = 21, B_KV = 22, B_FREE = 38, B_WO = 46, B_RED = 55, B_X = 61, B_EARLY = 85, B_OS = 86, B_LATE = 94, B_BIAS = 95, B_END = 96 };

__global__ void __cluster_dims__(2, 1, 1) __launch_bounds__(384, 1)
fused_kernel(const __grid_constant__ CUtensorMap tmX, const __grid_constant__ CUtensorMap tmQ3, const __grid_constant__ CUtensorMap tmQ1,
          const __grid_constant__ CUtensorMap tm1, const __grid_constant__ CUtensorMap tm2, const __grid_constant__ CUtensorMap tmP,
          const __grid_constant__ CUtensorMap tmOut, const __grid_constant__ CUtensorMap tmXo, const __nv_bfloat16* __restrict__ b1,
          const __nv_bfloat16* __restrict__ wqkv, const __nv_bfloat16* __restrict__ w1, const __nv_bfloat16* __restrict__ w2,
          const __nv_bfloat16* __restrict__ wo, const __nv_bfloat16* __restrict__ b2,
          const uint64_t zero) {
    extern __shared__ __align__(1024) uint8_t smem[];
    const uint32_t sb = s2u(smem);
    const int tid = threadIdx.x, lane = tid & 31;
    const int warp = __shfl_sync(~0u, tid >> 5, 0);
    const uint32_t rank = blockIdx.x & 1;
    const int cl = blockIdx.x >> 1;
    const int rb = (cl & 7) * 2 + rank;
    const int j = cl >> 3;
    const uint32_t bar0 = sb + K1_OFF_BAR;
    const uint32_t full0 = bar0 + B_FULL * 8, empty0 = bar0 + B_EMPTY * 8, xbar0 = bar0 + B_X * 8;
    const int head = blockIdx.x >> 2, quarter = blockIdx.x & 3;
    const int rt = quarter * 8 + (head >> 2), ct = head & 3;
    const int rot = head >> 3;
    const int ks0 = ((((head >> 3) + 2) & 3) * 9);
    volatile uint32_t* slow_flag = reinterpret_cast<volatile uint32_t*>(smem + K1_OFF_BAR + B_END * 8);

    if (__builtin_expect(warp < 8, 1)) {
        PROF(0);
        PROFT(48);
        if (lane == 0) {
#pragma unroll
            for (int i = 0; i < 3; i++) mbar_init(xbar0 + (warp * 3 + i) * 8, 1);
            fence_barrier_init();
#pragma unroll 1
            for (int i = 0; i < 3; i++) {
                const uint32_t xb = xbar0 + (warp * 3 + i) * 8;
                mbar_expect(xb, 6144);
                tma4d(sb + i * 49152 + warp * 6144, &tmX, 0, 0, i * 3, rb * 16 + warp * 2, xb);
            }
        }
        __syncwarp();
        cluster_arrive();
        PROF(22);
        reg_alloc<240>();
        PROF(23);
        float rs0, rs1;
        {
            const uint32_t la = sb + (warp * 2 + ((lane >> 3) & 1)) * 3072 + (lane & 7) * 128;
            uint32_t off[4];
#pragma unroll
            for (int i = 0; i < 4; i++) off[i] = la + (((i * 2 + (lane >> 4)) ^ (lane & 7)) << 4);
            float c1[4] = {0.f, 0.f, 0.f, 0.f}, c2[4] = {0.f, 0.f, 0.f, 0.f}, c3[4] = {0.f, 0.f, 0.f, 0.f};
            uint32_t a[36][4];
#pragma unroll
            for (int t = 0; t < 3; t++) {
                mbar_wait(xbar0 + (warp * 3 + t) * 8, 0);
                PROF(24 + t);
#pragma unroll
                for (int i = 0; i < 12; i++) ldsm4(a[t * 12 + i], off[i & 3] + t * 49152 + (i >> 2) * 1024);
#pragma unroll
                for (int i = t * 12; i < t * 12 + 12; i++) {
                    mma16816(c3, a[i], 0x3F803F80u, 0x3F803F80u);
                    mma16816(c1, a[i], a[i][0], a[i][2]);
                    mma16816(c2, a[i], a[i][1], a[i][3]);
                }
            }
            PROF(27);
            const int gg = lane >> 2, src = (lane & ~3) | (gg >> 1);
            const float m0 = c3[0] * (1.0f / DM), m1 = c3[2] * (1.0f / DM);
            const uint32_t mc0 = pack_bf16(-m0, -m0), mc1 = pack_bf16(-m1, -m1);
#pragma unroll
            for (int i = 0; i < 36; i++) {
#pragma unroll
                for (int k = 0; k < 4; k++) a[i][k] = hadd2_bf16(a[i][k], (k & 1) ? mc1 : mc0);
                stsm4(off[i & 3] + (i / 12) * 49152 + ((i >> 2) % 3) * 1024, a[i]);
            }
            const float q0 = __shfl_sync(~0u, (gg & 1) ? c1[1] : c1[0], src), q1 = __shfl_sync(~0u, (gg & 1) ? c2[3] : c2[2], src);
            rs0 = rsqrtf(fmaxf(fmaf(-m0, m0, q0 * (1.0f / DM)), 0.f) + 1e-5f);
            rs1 = rsqrtf(fmaxf(fmaf(-m1, m1, q1 * (1.0f / DM)), 0.f) + 1e-5f);
            if (__any_sync(~0u, fabsf(m0) * rs0 > 0.25f || fabsf(m1) * rs1 > 0.25f)) {
                const float d0 = -m0 - bf_lo(mc0), d1 = -m1 - bf_lo(mc1);
                const uint32_t md0 = pack_bf16(d0, d0), md1 = pack_bf16(d1, d1);
#pragma unroll 1
                for (int i = 0; i < 9; i++) {
#pragma unroll
                    for (int k4 = 0; k4 < 4; k4++) {
                        const uint32_t ad = off[k4] + (i / 3) * 49152 + (i % 3) * 1024;
                        uint32_t b[4];
                        ldsm4(b, ad);
#pragma unroll
                        for (int k = 0; k < 4; k++) b[k] = hadd2_bf16(b[k], (k & 1) ? md1 : md0);
                        stsm4(ad, b);
                    }
                }
            }
        }
        PROF(28);
        const int wg = warp >> 2, wq = warp & 3;
        fence_proxy_async();
        named_bar_sync(1 + wg, 128);
        cluster_wait();
        PROF(1); PROFT(59);

        const int g = lane >> 2, q = lane & 3;
        K1Ctx c;
        c.full0 = full0;
        c.rel_addr = 0;
        c.descA = mk_desc(zero, sb + wg * 8 * 3072, 16, 3072, 1);
        c.descB = mk_desc(zero, sb + K1_OFF_RING, 2048, 1024, 1);
        c.phase = 0;
        uint32_t biasq = sb + K1_OFF_BIAS + q * 32;
        uint32_t bq[8];

        uint32_t h[144];
        float accA[32], accB[32];
        uint32_t qo[3], qt[3];
        {
            float accQ[108];
            uint32_t rel = 0;
            if (lane == 0 && wq < 2) asm("mapa.shared::cluster.u32 %0, %1, %2;" : "=r"(rel) : "r"(empty0), "r"(wq));
#pragma unroll 1
            for (int r = 0; r < 2; r++) {
                static_for<0, 9>([&](auto sc) {
                    constexpr int s = decltype(sc)::value;
                    c.begin_stage(s);
                    const uint64_t da = c.descA + (r ? a_off(18 + 2 * s) : a_off(2 * s));
                    wgmma_ss_n216<1, 0, ((2 * s) % 9) * 512>(accQ, da, c.descB, (r | s) != 0);
                    wgmma_ss_n216<1, 2, ((2 * s + 1) % 9) * 512>(accQ, da, c.descB, 1);
                    c.end_stage(s);
                    c.rel_addr = rel;
                });
                c.phase ^= 1;
            }
            PROF(2); PROFWT(54);
            mbar_wait(bar0 + B_BIAS * 8, 0);
            wg_wait<0>();
            reg_fence(accQ);
#pragma unroll
            for (int grp = 0; grp < 3; grp++) {
                const int G = 3 * j + grp, type = G >> 3;
                const uint32_t base = (G & 7) * 4 * KV_HEAD_BYTES + (rb * 16 + warp * 2) * KV_GROUP_BYTES + g * 16 + (type == 0 ? Q_OFFSET : (type == 2 ? 256 : 0));
                qo[grp] = base + (q >> 1) * 128 + (q & 1) * 8;
                qt[grp] = base + q * KV_HEAD_BYTES + (type == 0 ? 256 : (type == 2 ? 264 : 512));
#pragma unroll
                for (int hf = 0; hf < 2; hf++) {
                    const float sc = (hf ? rs1 : rs0) * (type == 0 ? QSCALE : ((type == 1 && ((POLY_MASK >> (warp * 2 + hf)) & 1)) ? 2.f : 1.f));
                    uint32_t w[9];
#pragma unroll
                    for (int i = 0; i < 9; i++) w[i] = pack_bf16(accQ[(grp * 9 + i) * 4 + hf * 2] * sc, accQ[(grp * 9 + i) * 4 + hf * 2 + 1] * sc);
                    uint32_t* d = h + 32 + hf * 32 + grp * 8;
                    d[0] = w[0]; d[1] = w[1]; d[2] = w[3]; d[3] = q >= 1 ? w[2] : w[4];
                    d[4] = w[5]; d[5] = q >= 2 ? w[4] : w[6]; d[6] = w[7]; d[7] = w[8];
                    h[32 + hf * 32 + 24 + grp] = q == 0 ? w[2] : (q == 1 ? w[4] : w[6]);
                }
            }
        }
        PROF(3); PROFWT(55); PROFT(60);
#pragma unroll
        for (int i = 32; i < 112; i++)
            if (i >= 96 || (i & 31) >= 27) asm volatile("mov.u32 %0, 0;" : "=r"(h[i]));
#pragma unroll
        for (int i = 0; i < 32; i++) asm volatile("mov.f32 %0, 0f00000000;" : "=f"(accB[i]));
#pragma unroll
        for (int i = 0; i < 8; i++) bq[i] = 0;
#pragma unroll 1
        for (int p = 0; p < 4; p++) {
            uint8_t* const qb = g_QKV + p * KV_GROUP_BYTES;
            tile_pair<false, false>(c, accA, accB, h, [&](auto sc) {
                constexpr int s = decltype(sc)::value;
                if constexpr (s == 0) {
                    reg_fence(accB);
#pragma unroll
                    for (int i = 0; i < 80; i++) h[i] = h[i + 32];
                }
                if constexpr (s >= 1 && s <= 6) {
                    constexpr int grp = (s - 1) >> 1, k = ((s - 1) & 1) * 2;
                    st_pred2(p < 2, qb + qo[grp] + k * KV_HEAD_BYTES, h[grp * 8 + k * 2], h[grp * 8 + k * 2 + 1]);
                    st_pred2(p < 2, qb + qo[grp] + (k + 1) * KV_HEAD_BYTES, h[grp * 8 + k * 2 + 2], h[grp * 8 + k * 2 + 3]);
                    if constexpr (k == 2) st_pred1(p < 2, qb + qt[grp], h[24 + grp]);
                }
                if constexpr (s < 4) gelu_blocks<s * 2, 2, 80>(accB, h, bq, rs0, rs1);
                if constexpr (s == 4) load_bias(bq, biasq);
                if constexpr (s == 5) reg_fence(accA);
                if constexpr (s >= 5) gelu_blocks<(s - 5) * 2, 2, 96>(accA, h, bq, rs0, rs1);
                if constexpr (s == 8) load_bias(bq, biasq + 128);
            });
            if (p == 1) asm volatile("bar.arrive 3, 352;" ::: "memory");
            biasq += 256;
        }
        PROF(4); PROFWT(56); PROFT(61);
        tile_pair<false, true>(c, accA, accB, h, [&](auto sc) {
            constexpr int s = decltype(sc)::value;
            if constexpr (s == 0) reg_fence(accB);
            if constexpr (s < 4) gelu_blocks<s * 2, 2, 112>(accB, h, bq, rs0, rs1);
            if constexpr (s == 4) load_bias(bq, biasq);
            if constexpr (s == 5) { reg_fence(accA); if (tid == wg * 128) mbar_arrive(bar0 + B_XNDEAD * 8); }
            if constexpr (s == 5 || s == 6) gelu_blocks<(s - 5) * 3, 3, 128>(accA, h, bq, rs0, rs1);
            if constexpr (s == 7) gelu_blocks<6, 2, 128>(accA, h, bq, rs0, rs1);
            if constexpr (s == 3 || s == 7) reg_fence(h);
        });
        PROF(5); PROFWT(57); PROFT(62);
        uint4* pout = g_part + j * SLAB + rb * 36 * 256 + tid;
#pragma unroll 1
        for (int p = 0; p < 4; p++) {
            tile_pair<true, true>(c, accA, accB, h, [&](auto sc) {
                constexpr int s = decltype(sc)::value;
                if constexpr (s == 0) reg_fence(accB);
                if constexpr (s < 4) store_part<s>(accB, pout);
                if constexpr (s == 5) reg_fence(accA);
                if constexpr (s >= 5) store_part<s - 5>(accA, pout + 1024);
            });
            pout += 2048;
            PROF(6 + p);
        }
        wg_wait<0>();
        c.release(8);
        reg_fence(accB);
        store_part<0>(accB, pout); store_part<1>(accB, pout); store_part<2>(accB, pout); store_part<3>(accB, pout);
        __syncwarp();
        if (lane == 0) mbar_arrive(bar0 + B_FFN * 8);
        PROF(10); PROFWT(58);
        PROFT(49);

        mbar_wait(bar0 + B_QRDY * 8, 0);
        const uint32_t slow = __any_sync(~0u, *slow_flag != 0);
        const uint64_t kd0 = mk_desc(zero, sb + SM_KV, 0, KV_GROUP_BYTES, 0);
        const uint64_t vd0 = mk_desc(zero, sb + SM_KV + 256, KV_GROUP_BYTES, 128, 0);
        const uint64_t qd0 = mk_desc(zero, sb + SM_Q + wg * 4096, 128, 512, 0);
        const uint32_t kvbar = bar0 + B_KV * 8;
        float o[12];
#pragma unroll
        for (int i = 0; i < 12; i++) o[i] = 0.f;
        PROF(16);
        PROFT(50);
        if (__builtin_expect(!slow, 1)) {
            const uint32_t one2 = 0x3F803F80u + (uint32_t)zero;
            float s0[64], s1[64];
            uint32_t p0[32], p1[32];
            mbar_wait(kvbar, 0);
            reg_fence(o);
            wg_fence();
            issue_qk<0>(s0, qd0, kd0);
            wg_commit();
#pragma unroll
            for (int i = 0; i < 32; i++) asm volatile("mov.u32 %0, 0;" : "=r"(p1[i]));
            uint64_t qd = qd0, vd = vd0;
            const uint32_t fre = (tid == wg * 128) ? bar0 + B_FREE * 8 - 8 : 0;
#pragma unroll 1
            for (int pass = 0; pass < 4; pass++) {
                uint64_t kd = kd0;
                uint32_t bn = kvbar + 8;
#pragma unroll 1
                for (int it = 0; it < 8; it++) {
                    if (pass == 0) {
                        mbar_wait(bn, 0);
                        mbar_wait(it == 7 ? bn : bn + 8, 0);
                    }
                    wg_wait<0>();
                    reg_fence(s0);
                    wg_fence();
                    issue_qk<KV_TILE>(s1, qd, kd);
                    if (pass == 3 && it > 0 && fre) mbar_arrive(fre + it * 8);
                    softmax_pv_lag<0>(s0, p0, p1, o, vd, one2);
                    vd = vd0 + it * (2 * KV_TILE);
                    kd += 2 * KV_TILE;
                    if (it == 7) { kd = kd0; qd += 512; }
                    wg_wait<0>();
                    if (it == 0 && pass != 0) {
                        reg_fence(o);
                        store_o<false>(o, quarter * 8 + ((pass - 1 + rot) & 3) * 2 + wg, head, wq, lane);
                        reg_fence(o);
                        __syncwarp();
                        if (lane == 0) mbar_arrive(bar0 + (B_OS + pass * 2 - 2 + wg) * 8);
                    }
                    reg_fence(s1);
                    wg_fence();
                    issue_qk<0>(s0, qd, kd);
                    softmax_pv_lag<0>(s1, p1, p0, o, vd, one2);
                    vd += KV_TILE;
                    bn += 16;
                }
                if (pass == 0) PROF(17);
            }
            reg_fence(p1);
            wg_fence();
            issue_pv<0>(o, p1, vd);
            wg_commit();
            wg_wait<0>();
            reg_fence(o);
            reg_fence(s0);
            reg_fence(s1);
            store_o<true>(o, quarter * 8 + ((3 + rot) & 3) * 2 + wg, head, wq, lane);
        } else {
#pragma unroll 1
            for (int pass = 0; pass < 4; pass++) {
                float m0 = -INFINITY, m1 = -INFINITY;
                float s[64];
                uint32_t p[32];
#pragma unroll 1
                for (int t = 0; t < 16; t++) {
                    mbar_wait(kvbar + t * 8, 0);
                    wg_fence();
                    issue_qk<0>(s, qd0 + pass * 512, kd0 + t * KV_TILE);
                    wg_commit();
                    wg_wait<0>();
                    reg_fence(s);
                    float a0 = m0, a1 = m1;
#pragma unroll
                    for (int k = 0; k < 16; k++) {
                        if ((POLY_MASK >> k) & 1) {
#pragma unroll
                            for (int i = 0; i < 4; i++) s[k * 4 + i] *= 0.5f;
                        }
                        a0 = fmaxf(a0, fmaxf(s[k * 4 + 0], s[k * 4 + 1]));
                        a1 = fmaxf(a1, fmaxf(s[k * 4 + 2], s[k * 4 + 3]));
                    }
                    a0 = fmaxf(a0, __shfl_xor_sync(~0u, a0, 1)); a1 = fmaxf(a1, __shfl_xor_sync(~0u, a1, 1));
                    a0 = fmaxf(a0, __shfl_xor_sync(~0u, a0, 2)); a1 = fmaxf(a1, __shfl_xor_sync(~0u, a1, 2));
                    const float r0 = ex2(m0 - a0), r1 = ex2(m1 - a1);
                    m0 = a0; m1 = a1;
#pragma unroll
                    for (int i = 0; i < 3; i++) { o[i * 4] *= r0; o[i * 4 + 1] *= r0; o[i * 4 + 2] *= r1; o[i * 4 + 3] *= r1; }
#pragma unroll
                    for (int k = 0; k < 16; k++) {
                        p[k * 2 + 0] = pack_bf16(ex2(s[k * 4 + 0] - m0), ex2(s[k * 4 + 1] - m0));
                        p[k * 2 + 1] = pack_bf16(ex2(s[k * 4 + 2] - m1), ex2(s[k * 4 + 3] - m1));
                    }
                    reg_fence(p);
                    reg_fence(o);
                    wg_fence();
                    issue_pv<0>(o, p, vd0 + t * KV_TILE);
                    wg_commit();
                    wg_wait<0>();
                    reg_fence(o);
                }
                if (pass < 3) {
                    store_o<false>(o, quarter * 8 + ((pass + rot) & 3) * 2 + wg, head, wq, lane);
                    __syncwarp();
                    if (lane == 0) mbar_arrive(bar0 + (B_OS + pass * 2 + wg) * 8);
                }
            }
            store_o<true>(o, quarter * 8 + ((3 + rot) & 3) * 2 + wg, head, wq, lane);
            if (tid == wg * 128)
                for (int i = 0; i < 7; i++) mbar_arrive(bar0 + (B_FREE + i) * 8);
        }
        PROF(18);
        PROFT(51);

        if (tid == wg * 128) mbar_arrive(bar0 + (B_FREE + 7) * 8);
        const int t128 = tid & 127;
        uint32_t bv[9];
        uint2 fv[9];
        mbar_wait(bar0 + B_BASE * 8, 0);
#pragma unroll
        for (int i = 0; i < 9; i++) {
            bv[i] = __ldg(reinterpret_cast<const uint32_t*>(b2 + ct * 144 + wg * 72 + q * 2) + i * 4);
            fv[i] = __ldcg(g_ffn + (blockIdx.x * 18 + wg * 9 + i) * 128 + t128);
        }
        float acc[36];
        const uint64_t od = mk_desc(zero, sb, 1024, 128, 0), wd = mk_desc(zero, sb + wg * 9 * 128, 2304, 128, 0);
        static_for<0, 9>([&](auto pc) {
            constexpr int p = decltype(pc)::value;
            mbar_wait(bar0 + (B_WO + p) * 8, 0);
            wg_fence();
            wgmma_ss_n72<1, sm_ostep(p * 3) / 16, sm_wstep(p * 3) / 16>(acc, od, wd, p != 0);
            wgmma_ss_n72<1, sm_ostep(p * 3 + 1) / 16, sm_wstep(p * 3 + 1) / 16>(acc, od, wd, 1);
            wgmma_ss_n72<1, sm_ostep(p * 3 + 2) / 16, sm_wstep(p * 3 + 2) / 16>(acc, od, wd, 1);
            wg_commit();
            if constexpr (p == 1) {
                wg_wait<1>();
                if (t128 == 0) mbar_arrive(bar0 + B_EARLY * 8);
            }
        });
        wg_wait<0>();
        reg_fence(acc);
        PROF(29);
        uint4 al[9];
        {
            const uint4* ap = g_Olate + rt * 9 * 128 + t128;
            uint32_t spins = 0;
            bool ok;
            do {
                ok = true;
#pragma unroll
                for (int k = 0; k < 9; k++)
                    asm volatile("ld.relaxed.gpu.global.v4.u32 {%0, %1, %2, %3}, [%4];" : "=r"(al[k].x), "=r"(al[k].y), "=r"(al[k].z), "=r"(al[k].w) : "l"(ap + k * 128) : "memory");
#pragma unroll
                for (int k = 0; k < 9; k++) ok = ok && al[k].x != O_EMPTY && al[k].y != O_EMPTY && al[k].z != O_EMPTY && al[k].w != O_EMPTY;
                if (++spins > (1u << 20)) __trap();
            } while (!__all_sync(~0u, ok));
        }
        PROF(19);
        mbar_wait(bar0 + B_LATE * 8, 0);
        PROF(20);
        wg_fence();
        static_for<27, 36>([&](auto kc) {
            constexpr int k = decltype(kc)::value;
            wgmma_rs_n72<1, sm_wstep(k) / 16>(acc, al[k - 27].x, al[k - 27].y, al[k - 27].z, al[k - 27].w, wd, 1);
        });
        wg_commit();
        PROF(31);
        uint32_t* st = reinterpret_cast<uint32_t*>(smem + sm_piece(0) + wg * 9216) + (wq * 16 + g) * 36 + q;
        float bs[36];
#pragma unroll
        for (int i = 0; i < 9; i++) {
            const uint32_t x0 = st[i * 4], x1 = st[i * 4 + 288];
            bs[i * 4 + 0] = fmaf(bf_lo(fv[i].x), 0.5f, bf_lo(x0) + bf_lo(bv[i]));
            bs[i * 4 + 1] = fmaf(bf_hi(fv[i].x), 0.5f, bf_hi(x0) + bf_hi(bv[i]));
            bs[i * 4 + 2] = fmaf(bf_lo(fv[i].y), 0.5f, bf_lo(x1) + bf_lo(bv[i]));
            bs[i * 4 + 3] = fmaf(bf_hi(fv[i].y), 0.5f, bf_hi(x1) + bf_hi(bv[i]));
        }
        reg_fence(bs);
        wg_wait<0>();
        reg_fence(acc);
        PROF(32);
#pragma unroll
        for (int i = 0; i < 9; i++) {
            st[i * 4] = pack_bf16(acc[i * 4] + bs[i * 4], acc[i * 4 + 1] + bs[i * 4 + 1]);
            st[i * 4 + 288] = pack_bf16(acc[i * 4 + 2] + bs[i * 4 + 2], acc[i * 4 + 3] + bs[i * 4 + 3]);
        }
        fence_proxy_async();
        named_bar_sync(1 + wg, 128);
        if (t128 == 0) {
            asm volatile("cp.async.bulk.tensor.2d.global.shared::cta.bulk_group [%0, {%2, %3}], [%1];"
                         ::"l"(&tmOut), "r"(sb + sm_piece(0) + wg * 9216), "r"(ct * 144 + wg * 72), "r"(rt * 64) : "memory");
            asm volatile("cp.async.bulk.commit_group;" ::: "memory");
            asm volatile("cp.async.bulk.wait_group.read 0;" ::: "memory");
        }
        PROF(21);
        PROFT(52);
    } else {
        reg_dealloc<24>();
        if (warp == 8 && lane == 0) {
            prefetch_tmap(&tmQ3); prefetch_tmap(&tmQ1); prefetch_tmap(&tm1); prefetch_tmap(&tm2);
            #pragma unroll 1
            for (int i = 0; i < 9; i++) { mbar_init(full0 + i * 8, 1); mbar_init(empty0 + i * 8, 4); mbar_init(bar0 + (B_WO + i) * 8, 2); }
            mbar_init(bar0 + B_BASE * 8, 3); mbar_init(bar0 + B_XNDEAD * 8, 2); mbar_init(bar0 + B_QRDY * 8, 3); mbar_init(bar0 + B_FFN * 8, 8); mbar_init(bar0 + B_EARLY * 8, 2); mbar_init(bar0 + B_LATE * 8, 2); mbar_init(bar0 + B_BIAS * 8, 96);
#pragma unroll 1
            for (int i = 0; i < 16; i++) { mbar_init(bar0 + (B_KV + i) * 8, 1); mbar_init(bar0 + (B_FREE + (i & 7)) * 8, 2); if (i < 6) mbar_init(bar0 + (B_RED + i) * 8, 1); if (i < 6) mbar_init(bar0 + (B_OS + i) * 8, 4); }
            *slow_flag = 0;
            fence_barrier_init();
        }
        __syncwarp();
        cluster_arrive();
        cluster_wait();
        const uint8_t* kvsrc = g_QKV + (size_t)head * KV_HEAD_BYTES;
        if (warp == 8) {
            if (lane == 0) {
                int st = 0, u = rank, tile = -4;
                int es = 5;
                uint32_t eph = 1;
#pragma unroll 1
                for (int n = 0; n < 99; n++) {
                    mbar_wait(empty0 + es * 8, eph);
                    const uint32_t fb = full0 + st * 8, dst = sb + K1_OFF_RING + u * 8192;
                    mbar_expect(fb, 16384);
                    if (tile < 0) {
                        tma3d_mc(dst, &tmQ3, j * 216, n * 32 + rank * 16, 0, fb, 3);
                        tma2d_mc(dst + 6144, &tmQ1, j * 216 + 192, n * 32 + rank * 16, fb, 3);
                    } else if (tile < 9) {
                        tma2d_mc(dst, &tm1, j * 576 + tile * 64, u * 64, fb, 3);
                    } else {
                        tma2d_mc(dst, &tm2, (tile - 9) * 64, j * 576 + u * 64, fb, 3);
                    }
                    u += 2;
                    if (u >= 9) { u -= 9; tile++; }
                    if (++st == 9) st = 0;
                    if (++es == 9) { es = 0; eph ^= 1; }
                }
                mbar_wait(empty0 + 8 * 8, 0);
                mbar_wait(bar0 + B_QRDY * 8, 0);
                asm volatile("fence.proxy.async;" ::: "memory");
#pragma unroll 1
                for (int i = 11; i < NCHUNK; i++) {
                    mbar_expect(bar0 + (B_KV + i) * 8, CHUNK_BYTES);
                    bulk_load(sb + SM_KV + i * CHUNK_BYTES, kvsrc + i * CHUNK_BYTES, CHUNK_BYTES, bar0 + (B_KV + i) * 8);
                }
                const uint8_t* wsrc = g_Wo + ct * WO_TILE_BYTES;
                prefetch_tmap(&tmOut);
                mbar_wait_sleep(bar0 + B_BASE * 8, 500);
#pragma unroll 1
                for (int p = 0; p < 9; p++) {
                    if (p > 0) mbar_wait_sleep(bar0 + (B_FREE + p - 1) * 8, p == 1 ? 500 : 40);
                    const int k = ks0 + p * 3 >= 36 ? ks0 + p * 3 - 36 : ks0 + p * 3;
                    mbar_expect(bar0 + (B_WO + p) * 8, 13824);
                    bulk_load(sb + (p == 0 ? sm_piece(0) : (p == 1 ? sm_piece(1) : SM_KV + (p - 2) * PIECE)), wsrc + k * 4608, 13824, bar0 + (B_WO + p) * 8);
                }
                const int kl = ks0 == 0 ? 27 : ks0 - 9;
                mbar_expect(bar0 + B_LATE * 8, 9 * 4608);
                bulk_load(sb + sm_wstep(27), wsrc + kl * 4608, 8 * 4608, bar0 + B_LATE * 8);
                bulk_load(sb + sm_wstep(35), wsrc + (kl + 8) * 4608, 4608, bar0 + B_LATE * 8);
            }
        } else {
            const int ht = tid - 288;
            if (ht == 64) prefetch_l2(wqkv + blockIdx.x * (DM * 3 * DM / 128), DM * 3 * DM / 64);
            if (ht < 72) {
                const uint4 v = __ldg(reinterpret_cast<const uint4*>(b1 + j * 576) + ht);
                uint32_t* sbias = reinterpret_cast<uint32_t*>(smem + K1_OFF_BIAS) + (ht >> 3) * 32 + (ht & 7);
                sbias[0] = v.x; sbias[8] = v.y; sbias[16] = v.z; sbias[24] = v.w;
            }
            mbar_arrive(bar0 + B_BIAS * 8);
            PROFH(37);
#pragma unroll
            for (int i = 0; i < 3; i++) g_Olate[blockIdx.x * 288 + i * 96 + ht] = make_uint4(O_EMPTY, O_EMPTY, O_EMPTY, O_EMPTY);
#pragma unroll 1
            for (int i = ht; i < 512; i += 96) {
                const int key = i & 127;
                uint8_t* p = g_QKV + (size_t)(j * 4 + (i >> 7)) * KV_HEAD_BYTES + (rb * 16 + (key >> 3)) * KV_GROUP_BYTES + 512 + (key & 7) * 16;
                *reinterpret_cast<uint32_t*>(p + 4) = ((POLY_MASK >> (key >> 3)) & 1) ? 0x3F804000u : 0x00003F80u;
                *reinterpret_cast<uint32_t*>(p + 12) = 0x00003F80u;
            }
            if (ht == 32) prefetch_l2(w1 + blockIdx.x * (DM * FF / 128), DM * FF / 64);
#pragma unroll 2
            for (int i = blockIdx.x * 324 + ht; i < blockIdx.x * 324 + 324; i += 96) {
                const int k = i / 72, nc = i - k * 72, c4 = nc / 18;
                *reinterpret_cast<uint4*>(g_Wo + c4 * WO_TILE_BYTES + (k >> 3) * 2304 + (nc - c4 * 18) * 128 + (k & 7) * 16) =
                    __ldg(reinterpret_cast<const uint4*>(wo) + i);
            }
            PROFH(38);
            named_bar_sync(3, 352);
            if (ht == 32) prefetch_l2(w2 + blockIdx.x * (DM * FF / 128), DM * FF / 64);
            if (ht == 0) {
                flag_signal(&g_flags.qkv_stored[rb]);
                flag_wait(&g_flags.qkv_stored[rb], 8, 200);
            }
            named_bar_sync(7, 96);
            PROFH(39);
#pragma unroll 1
            for (int i = warp - 9; i < 16; i += 3) {
                const int hd = j * 4 + (i >> 2), key = (i & 3) * 32 + lane;
                const uint8_t* p = g_QKV + (size_t)hd * KV_HEAD_BYTES + (rb * 16 + (key >> 3)) * KV_GROUP_BYTES + (key & 7) * 16;
                const uint4 a = __ldcg(reinterpret_cast<const uint4*>(p)), b = __ldcg(reinterpret_cast<const uint4*>(p + 128));
                float n = sumsq2(__ldcg(reinterpret_cast<const uint32_t*>(p + 512))) + sumsq8(a) + sumsq8(b);
                if ((POLY_MASK >> (key >> 3)) & 1) n *= 0.25f;
#pragma unroll
                for (int o = 16; o; o >>= 1) n = fmaxf(n, __shfl_xor_sync(~0u, n, o));
                if (lane == 0) g_kmax[hd * 64 + rb * 4 + (i & 3)] = n;
            }
            named_bar_sync(7, 96);
            PROFH(40);
            if (ht == 0) {
                flag_signal(&g_flags.kv_ready);
                flag_wait(&g_flags.kv_ready, 128, 300);
                mbar_wait_sleep(bar0 + B_XNDEAD * 8, 300);
            }
            named_bar_sync(7, 96);
            PROFH(41);
            float kmax2;
            {
                const float2 v = __ldcg(reinterpret_cast<const float2*>(g_kmax + head * 64 + lane * 2));
                kmax2 = fmaxf(v.x, v.y);
#pragma unroll
                for (int o = 16; o; o >>= 1) kmax2 = fmaxf(kmax2, __shfl_xor_sync(~0u, kmax2, o));
            }
            asm volatile("fence.proxy.async;" ::: "memory");
            int chunk = warp - 9;
#pragma unroll 1
            for (int r = ht; r < 512; r += 96) {
                if (lane == 0 && chunk < 11) {
                    mbar_expect(bar0 + (B_KV + chunk) * 8, CHUNK_BYTES);
                    bulk_load(sb + SM_KV + chunk * CHUNK_BYTES, kvsrc + chunk * CHUNK_BYTES, CHUNK_BYTES, bar0 + (B_KV + chunk) * 8);
                }
                chunk += 3;
                const uint8_t* p = kvsrc + Q_OFFSET + (quarter * 64 + (((r >> 3) + rot * 16) & 63)) * KV_GROUP_BYTES + (r & 7) * 16;
                const uint4 a = __ldcg(reinterpret_cast<const uint4*>(p)), b = __ldcg(reinterpret_cast<const uint4*>(p + 128));
                const uint32_t e = __ldcg(reinterpret_cast<const uint32_t*>(p + 256));
                const float cc = sqrtf((sumsq2(e) + sumsq8(a) + sumsq8(b)) * kmax2) * 1.02f;
                if (!(cc <= 58.f)) *slow_flag = 1;
                uint4* dst = reinterpret_cast<uint4*>(smem + SM_Q + (r >> 3) * 512 + (r & 7) * 16);
                dst[0] = a;
                dst[8] = b;
                dst[16] = make_uint4(e, pack_bf16(-cc, 768.f), 0u, 0u);
                dst[24] = make_uint4(0u, POLY_MODE ? 0xBFFF0000u : 0xC0000000u, 0u, 0u);
            }
            named_bar_sync(7, 96);
            if (*slow_flag) {
#pragma unroll 1
                for (int r = ht; r < 512; r += 96) {
                    uint32_t* dst = reinterpret_cast<uint32_t*>(smem + SM_Q + (r >> 3) * 512 + (r & 7) * 16);
                    dst[65] = 0u;
                    dst[97] = 0u;
                }
            }
            fence_proxy_async();
            __syncwarp();
            if (lane == 0) mbar_arrive(bar0 + B_QRDY * 8);
            PROFH(42);
            if (ht == 0) {
                mbar_wait_sleep(bar0 + B_FFN * 8, 300);
                flag_signal(&g_flags.ffn_done[rb]);
                flag_wait(&g_flags.ffn_done[rt >> 1], 8, 300);
            }
            named_bar_sync(7, 96);
            {
                const int w3 = warp - 9;
                const uint32_t rbar = bar0 + (B_RED + w3 * 2) * 8, rbuf = SM_RED + w3 * 8192;
                const int u0 = ((rt >> 1) * 36 + ct * 9) * 256 + (rt & 1) * 128;
                mbar_wait_sleep(bar0 + (B_KV + 15) * 8, 500);
                asm volatile("fence.proxy.async;" ::: "memory");
#pragma unroll 1
                for (int i = -2; i < 12; i++) {
                    if (i >= 0) {
                        __nanosleep(400);
                        mbar_wait(rbar + (i & 1) * 8, (i >> 1) & 1);
                        const uint4* sp = reinterpret_cast<const uint4*>(smem + rbuf + (i & 1) * 4096) + lane;
                        const uint4 v = hadd8_bf16(hadd8_bf16(hadd8_bf16(sp[0], sp[32]), hadd8_bf16(sp[64], sp[96])),
                                                   hadd8_bf16(hadd8_bf16(sp[128], sp[160]), hadd8_bf16(sp[192], sp[224])));
                        const int bx = i * 3 + w3;
                        uint2* fp = g_ffn + (blockIdx.x * 18 + (bx >> 2) * 2) * 128 + (bx & 3) * 32 + lane;
                        fp[0] = make_uint2(v.x, v.y);
                        fp[128] = make_uint2(v.z, v.w);
                    }
                    __syncwarp();
                    if (lane == 0 && i < 10) {
                        const int bx = (i + 2) * 3 + w3;
                        mbar_expect(rbar + (i & 1) * 8, 4096);
                        tma2d(sb + rbuf + (i & 1) * 4096, &tmP, (u0 + (bx >> 2) * 256 + (bx & 3) * 32) * 2, 0, rbar + (i & 1) * 8);
                    }
                }
            }
            __syncwarp();
            if (lane == 0) mbar_arrive(bar0 + B_BASE * 8);
            PROFH(43);
            if (ht == 0) {
#pragma unroll 1
                for (int i = 0; i < 6; i++) {
                    mbar_wait_sleep(bar0 + (B_OS + i) * 8, 200);
                    flag_signal(&g_flags.o_done[quarter * 8 + (((i >> 1) + rot) & 3) * 2 + (i & 1)]);
                }
            } else if (ht == 32) {
                const uint8_t* osrc = reinterpret_cast<const uint8_t*>(g_O) + rt * 73728;
                mbar_wait_sleep(bar0 + B_BASE * 8, 500);
                mbar_wait_sleep(bar0 + B_FREE * 8, 500);
                flag_wait(&g_flags.o_done[rt], 24, 100);
                if (atomicAdd(&g_flags.exited, 1u) == gridDim.x - 1) {
                    unsigned int* f = reinterpret_cast<unsigned int*>(&g_flags);
#pragma unroll 1
                    for (int i = 0; i < (int)(sizeof(Flags) / 4); i++) f[i] = 0;
                }
                prefetch_tmap(&tmXo);
                asm volatile("fence.proxy.async;" ::: "memory");
#pragma unroll 1
                for (int p = 0; p < 9; p++) {
                    if (p > 1) mbar_wait_sleep(bar0 + (B_FREE + p - 1) * 8, 40);
                    const int k = ks0 + p * 3 >= 36 ? ks0 + p * 3 - 36 : ks0 + p * 3;
                    mbar_expect(bar0 + (B_WO + p) * 8, 6144);
                    bulk_load(sb + 13824 + (p == 0 ? sm_piece(0) : (p == 1 ? sm_piece(1) : SM_KV + (p - 2) * PIECE)), osrc + k * 2048, 6144, bar0 + (B_WO + p) * 8);
                }
                mbar_expect(bar0 + B_LATE * 8, 2 * 9216);
                mbar_wait(bar0 + B_EARLY * 8, 0);
                tma2d(sb + sm_piece(0), &tmXo, ct * 144, rt * 64, bar0 + B_LATE * 8);
                tma2d(sb + sm_piece(0) + 9216, &tmXo, ct * 144 + 72, rt * 64, bar0 + B_LATE * 8);
            }
        }
    }
}

typedef CUresult (*EncodeFn)(CUtensorMap*, CUtensorMapDataType, cuuint32_t, void*, const cuuint64_t*, const cuuint64_t*, const cuuint32_t*,
                             const cuuint32_t*, CUtensorMapInterleave, CUtensorMapSwizzle, CUtensorMapL2promotion, CUtensorMapFloatOOBfill);

void make_map(EncodeFn fn, CUtensorMap* m, const void* base, int rank, const cuuint64_t* dims, const cuuint64_t* strides, const cuuint32_t* box) {
    cuuint32_t es[4] = {1, 1, 1, 1};
    fn(m, CU_TENSOR_MAP_DATA_TYPE_BFLOAT16, rank, const_cast<void*>(base), dims, strides, box, es, CU_TENSOR_MAP_INTERLEAVE_NONE,
       CU_TENSOR_MAP_SWIZZLE_128B, CU_TENSOR_MAP_L2_PROMOTION_L2_256B, CU_TENSOR_MAP_FLOAT_OOB_FILL_NONE);
}

}

extern "C" void kernel_launch(void* const* d_in, const int* in_sizes, int n_in, void* d_out, int out_size) {
    const __nv_bfloat16* x = (const __nv_bfloat16*)d_in[0];
    const __nv_bfloat16* wqkv = (const __nv_bfloat16*)d_in[1];
    const __nv_bfloat16* wo = (const __nv_bfloat16*)d_in[2];
    const __nv_bfloat16* w1 = (const __nv_bfloat16*)d_in[4];
    const __nv_bfloat16* b1 = (const __nv_bfloat16*)d_in[5];
    const __nv_bfloat16* w2 = (const __nv_bfloat16*)d_in[6];
    const __nv_bfloat16* b2 = (const __nv_bfloat16*)d_in[7];
    __nv_bfloat16* out = (__nv_bfloat16*)d_out;

    EncodeFn fn = nullptr;
    cudaDriverEntryPointQueryResult qr;
    cudaGetDriverEntryPoint("cuTensorMapEncodeTiled", (void**)&fn, cudaEnableDefault, &qr);
    CUtensorMap tmX, tmQ3, tmQ1, tm1, tm2, tmP, tmOut, tmXo;
    {
        cuuint64_t d[2] = {DM, SEQ}, s[1] = {DM * 2};
        cuuint32_t b[2] = {72, 64}, es[2] = {1, 1};
        fn(&tmOut, CU_TENSOR_MAP_DATA_TYPE_BFLOAT16, 2, out, d, s, b, es, CU_TENSOR_MAP_INTERLEAVE_NONE, CU_TENSOR_MAP_SWIZZLE_NONE,
           CU_TENSOR_MAP_L2_PROMOTION_NONE, CU_TENSOR_MAP_FLOAT_OOB_FILL_NONE);
        fn(&tmXo, CU_TENSOR_MAP_DATA_TYPE_BFLOAT16, 2, const_cast<__nv_bfloat16*>(x), d, s, b, es, CU_TENSOR_MAP_INTERLEAVE_NONE,
           CU_TENSOR_MAP_SWIZZLE_NONE, CU_TENSOR_MAP_L2_PROMOTION_NONE, CU_TENSOR_MAP_FLOAT_OOB_FILL_NONE);
    }
    {
        void* gp = nullptr;
        cudaGetSymbolAddress(&gp, g_part);
        cuuint64_t d[2] = {SLAB * 2, 8}, s[1] = {SLAB * 16};
        cuuint32_t b[2] = {64, 8}, es[2] = {1, 1};
        fn(&tmP, CU_TENSOR_MAP_DATA_TYPE_INT64, 2, gp, d, s, b, es, CU_TENSOR_MAP_INTERLEAVE_NONE, CU_TENSOR_MAP_SWIZZLE_NONE,
           CU_TENSOR_MAP_L2_PROMOTION_NONE, CU_TENSOR_MAP_FLOAT_OOB_FILL_NONE);
    }
    {
        cuuint64_t d[4] = {64, 8, 9, SEQ / 8}, s[3] = {DM * 2, 128, DM * 2 * 8};
        cuuint32_t b[4] = {64, 8, 3, 2};
        make_map(fn, &tmX, x, 4, d, s, b);
    }
    {
        cuuint64_t d[3] = {3 * DM, DM, 3}, s[2] = {3 * DM * 2, 128};
        cuuint32_t b[3] = {64, 16, 3};
        make_map(fn, &tmQ3, wqkv, 3, d, s, b);
        make_map(fn, &tmQ1, wqkv, 2, d, s, b);
    }
    {
        cuuint64_t d[2] = {FF, DM}, s[1] = {FF * 2};
        cuuint32_t b[2] = {64, 64};
        make_map(fn, &tm1, w1, 2, d, s, b);
        cuuint64_t d2[2] = {DM, FF}, s2[1] = {DM * 2};
        make_map(fn, &tm2, w2, 2, d2, s2, b);
    }
    cudaFuncSetAttribute(fused_kernel, cudaFuncAttributeMaxDynamicSharedMemorySize, K1_SMEM);
    fused_kernel<<<128, 384, K1_SMEM, cudaStreamPerThread>>>(tmX, tmQ3, tmQ1, tm1, tm2, tmP, tmOut, tmXo, b1, wqkv, w1, w2, wo, b2, 0ull);
}
```

```cpp
#include <cuda_runtime.h>
#include <cuda_bf16.h>
#include <cuda.h>
#include <stdint.h>

#define PROF(i) do { } while (0)
#define PROFT(i) do { } while (0)
#define PROFH(i) do { } while (0)
#define PROFWT(i) do { } while (0)
#define PROF_WG 0

namespace {

constexpr int SEQ = 2048, DM = 576, FF = 4608, NH = 32, DH = 18;

constexpr int KV_GROUP_BYTES = 5 * 128;
constexpr int KV_HEAD_BYTES = (SEQ / 8) * KV_GROUP_BYTES;
constexpr int Q_OFFSET = NH * KV_HEAD_BYTES;
#define POLY_MASK 0xB6B6
__device__ __align__(1024) uint8_t g_QKV[2 * NH * KV_HEAD_BYTES];
__device__ __align__(1024) float g_kmax[NH * 64];
constexpr int SLAB = 16 * 36 * 256;
__device__ __align__(1024) uint4 g_part[8 * SLAB];
__device__ __align__(1024) uint2 g_ffn[128 * 18 * 128];
__device__ __align__(1024) uint32_t g_O[SEQ * DM / 2];
struct Flags {
    unsigned int qkv_stored[16];
    unsigned int ffn_done[16];
    unsigned int o_done[32];
    unsigned int kv_ready;
    unsigned int exited;
};
__device__ Flags g_flags;
__device__ __align__(1024) uint4 g_Olate[32 * 9 * 128];
constexpr uint32_t O_EMPTY = 0xFFFFFFFFu;
constexpr int WO_TILE_BYTES = DM * 144 * 2;
__device__ __align__(1024) uint8_t g_Wo[4 * WO_TILE_BYTES];

__device__ __forceinline__ uint32_t s2u(const void* p) { return (uint32_t)__cvta_generic_to_shared(p); }
__device__ __forceinline__ void mbar_init(uint32_t b, int c) { asm volatile("mbarrier.init.shared::cta.b64 [%0], %1;" ::"r"(b), "r"(c) : "memory"); }
__device__ __forceinline__ void mbar_expect(uint32_t b, uint32_t bytes) {
    asm volatile("mbarrier.arrive.expect_tx.shared::cta.b64 _, [%0], %1;" ::"r"(b), "r"(bytes) : "memory");
}
__device__ __forceinline__ void mbar_wait(uint32_t b, uint32_t parity) {
    asm volatile(
        "{\n.reg .pred p;\n.reg .u32 c;\n"
        "mov.u32 c, 0;\n"
        "LOOP:\n"
        "mbarrier.try_wait.parity.shared::cta.b64 p, [%0], %1;\n"
        "@p bra DONE;\n"
        "add.u32 c, c, 1;\n"
        "setp.lt.u32 p, c, 4194304;\n"
        "@p bra LOOP;\n"
        "trap;\n"
        "DONE:\n}\n" ::"r"(b), "r"(parity) : "memory");
}
__device__ __forceinline__ void fence_barrier_init() { asm volatile("fence.mbarrier_init.release.cluster;" ::: "memory"); }
__device__ __forceinline__ void fence_proxy_async() { asm volatile("fence.proxy.async.shared::cta;" ::: "memory"); }
__device__ __forceinline__ void cluster_arrive() { asm volatile("barrier.cluster.arrive.relaxed.aligned;" ::: "memory"); }
__device__ __forceinline__ void cluster_wait() { asm volatile("barrier.cluster.wait.aligned;" ::: "memory"); }
__device__ __forceinline__ void named_bar_sync(int id, int n) { asm volatile("bar.sync %0, %1;" ::"r"(id), "r"(n) : "memory"); }

__device__ __forceinline__ void tma3d_mc(uint32_t dst, const CUtensorMap* tm, int c0, int c1, int c2, uint32_t bar, uint16_t mask) {
    asm volatile("cp.async.bulk.tensor.3d.shared::cluster.global.mbarrier::complete_tx::bytes.multicast::cluster [%0], [%1, {%3, %4, %5}], [%2], %6;"
                 ::"r"(dst), "l"(tm), "r"(bar), "r"(c0), "r"(c1), "r"(c2), "h"(mask) : "memory");
}
__device__ __forceinline__ void tma2d_mc(uint32_t dst, const CUtensorMap* tm, int c0, int c1, uint32_t bar, uint16_t mask) {
    asm volatile("cp.async.bulk.tensor.2d.shared::cluster.global.mbarrier::complete_tx::bytes.multicast::cluster [%0], [%1, {%3, %4}], [%2], %5;"
                 ::"r"(dst), "l"(tm), "r"(bar), "r"(c0), "r"(c1), "h"(mask) : "memory");
}
__device__ __forceinline__ void tma4d(uint32_t dst, const CUtensorMap* tm, int c0, int c1, int c2, int c3, uint32_t bar) {
    asm volatile("cp.async.bulk.tensor.4d.shared::cluster.global.mbarrier::complete_tx::bytes [%0], [%1, {%3, %4, %5, %6}], [%2];"
                 ::"r"(dst), "l"(tm), "r"(bar), "r"(c0), "r"(c1), "r"(c2), "r"(c3) : "memory");
}
__device__ __forceinline__ void tma2d(uint32_t dst, const CUtensorMap* tm, int c0, int c1, uint32_t bar) {
    asm volatile("cp.async.bulk.tensor.2d.shared::cluster.global.mbarrier::complete_tx::bytes [%0], [%1, {%3, %4}], [%2];"
                 ::"r"(dst), "l"(tm), "r"(bar), "r"(c0), "r"(c1) : "memory");
}
__device__ __forceinline__ void bulk_load(uint32_t dst, const void* src, uint32_t bytes, uint32_t bar) {
    asm volatile("cp.async.bulk.shared::cluster.global.mbarrier::complete_tx::bytes [%0], [%1], %2, [%3];"
                 ::"r"(dst), "l"(src), "r"(bytes), "r"(bar) : "memory");
}
__device__ __forceinline__ void prefetch_l2(const void* p, uint32_t bytes) {
    asm volatile("cp.async.bulk.prefetch.L2.global [%0], %1;" ::"l"(p), "r"(bytes) : "memory");
}
__device__ __forceinline__ void prefetch_tmap(const CUtensorMap* tm) { asm volatile("prefetch.tensormap [%0];" ::"l"(tm) : "memory"); }

__device__ __forceinline__ void wg_fence() { asm volatile("wgmma.fence.sync.aligned;" ::: "memory"); }
__device__ __forceinline__ void wg_commit() { asm volatile("wgmma.commit_group.sync.aligned;" ::: "memory"); }
template <int N> __device__ __forceinline__ void wg_wait() { asm volatile("wgmma.wait_group.sync.aligned %0;" ::"n"(N) : "memory"); }
template <int N> __device__ __forceinline__ void reg_fence(float (&d)[N]) {
#pragma unroll
    for (int i = 0; i < N; i++) asm volatile("" : "+f"(d[i])::"memory");
}
template <int N> __device__ __forceinline__ void reg_fence(uint32_t (&d)[N]) {
#pragma unroll
    for (int i = 0; i < N; i++) asm volatile("" : "+r"(d[i])::"memory");
}
template <int R> __device__ __forceinline__ void reg_alloc() { asm volatile("setmaxnreg.inc.sync.aligned.u32 %0;" ::"n"(R)); }
template <int R> __device__ __forceinline__ void reg_dealloc() { asm volatile("setmaxnreg.dec.sync.aligned.u32 %0;" ::"n"(R)); }

__device__ __forceinline__ uint64_t mk_desc(uint64_t z, uint32_t addr, uint32_t lbo, uint32_t sbo, uint32_t swz) {
    return z + ((uint64_t)(((addr & 0x3FFFF) >> 4) | ((lbo >> 4) << 16)) | ((uint64_t)((sbo >> 4) | (swz << 30)) << 32));
}
__device__ __forceinline__ uint32_t pack_bf16(float lo, float hi) {
    uint32_t r;
    asm("cvt.rn.bf16x2.f32 %0, %1, %2;" : "=r"(r) : "f"(hi), "f"(lo));
    return r;
}
__device__ __forceinline__ float bf_lo(uint32_t w) { return __uint_as_float(w << 16); }
__device__ __forceinline__ float bf_hi(uint32_t w) { return __uint_as_float(w & 0xFFFF0000u); }
__device__ __forceinline__ float ex2(float x) {
    float r;
    asm("ex2.approx.ftz.f32 %0, %1;" : "=f"(r) : "f"(x));
    return r;
}
__device__ __forceinline__ float tanh_fast(float x) {
    float r;
    asm("tanh.approx.f32 %0, %1;" : "=f"(r) : "f"(x));
    return r;
}
__device__ __forceinline__ uint32_t hfma2_bf16(uint32_t a, uint32_t b, uint32_t c) {
    uint32_t r;
    asm("fma.rn.bf16x2 %0, %1, %2, %3;" : "=r"(r) : "r"(a), "r"(b), "r"(c));
    return r;
}
__device__ __forceinline__ uint32_t hadd2_bf16(uint32_t a, uint32_t b) {
    uint32_t r;
    asm("add.rn.bf16x2 %0, %1, %2;" : "=r"(r) : "r"(a), "r"(b));
    return r;
}
__device__ __forceinline__ void ldsm4(uint32_t (&a)[4], uint32_t addr) {
    asm volatile("ldmatrix.sync.aligned.m8n8.x4.shared.b16 {%0, %1, %2, %3}, [%4];" : "=r"(a[0]), "=r"(a[1]), "=r"(a[2]), "=r"(a[3]) : "r"(addr) : "memory");
}
__device__ __forceinline__ void stsm4(uint32_t addr, const uint32_t (&a)[4]) {
    asm volatile("stmatrix.sync.aligned.m8n8.x4.shared.b16 [%0], {%1, %2, %3, %4};" ::"r"(addr), "r"(a[0]), "r"(a[1]), "r"(a[2]), "r"(a[3]) : "memory");
}
__device__ __forceinline__ void mma16816(float (&c)[4], const uint32_t (&a)[4], uint32_t b0, uint32_t b1) {
    asm("mma.sync.aligned.m16n8k16.row.col.f32.bf16.bf16.f32 {%0, %1, %2, %3}, {%4, %5, %6, %7}, {%8, %9}, {%0, %1, %2, %3};"
        : "+f"(c[0]), "+f"(c[1]), "+f"(c[2]), "+f"(c[3]) : "r"(a[0]), "r"(a[1]), "r"(a[2]), "r"(a[3]), "r"(b0), "r"(b1));
}
__device__ __forceinline__ float gelu2(float u) {
    const float w = fmaf(u * u, 0.0356774081f, 0.7978845608f);
    return fmaf(u, tanh_fast(u * w), u);
}

template<int TB, int AOFF, int BOFF> __device__ __forceinline__ void wgmma_ss_n216(float (&d)[108], uint64_t da, uint64_t db, int sd) {
    asm volatile("{\n.reg .pred p;\n.reg .b64 ta, tb;\nsetp.ne.b32 p, %110, 0;\nadd.s64 ta, %108, %112;\nadd.s64 tb, %109, %113;\n"
      "wgmma.mma_async.sync.aligned.m64n216k16.f32.bf16.bf16 {%0, %1, %2, %3, %4, %5, %6, %7, %8, %9, %10, %11, %12, %13, %14, %15, %16, %17, %18, %19, %20, %21, %22, %23, %24, %25, %26, %27, %28, %29, %30, %31, %32, %33, %34, %35, %36, %37, %38, %39, %40, %41, %42, %43, %44, %45, %46, %47, %48, %49, %50, %51, %52, %53, %54, %55, %56, %57, %58, %59, %60, %61, %62, %63, %64, %65, %66, %67, %68, %69, %70, %71, %72, %73, %74, %75, %76, %77, %78, %79, %80, %81, %82, %83, %84, %85, %86, %87, %88, %89, %90, %91, %92, %93, %94, %95, %96, %97, %98, %99, %100, %101, %102, %103, %104, %105, %106, %107}, ta, tb, p, 1, 1, 0, %111;\n}\n"
      : "+f"(d[0]), "+f"(d[1]), "+f"(d[2]), "+f"(d[3]), "+f"(d[4]), "+f"(d[5]), "+f"(d[6]), "+f"(d[7]), "+f"(d[8]), "+f"(d[9]), "+f"(d[10]), "+f"(d[11]), "+f"(d[12]), "+f"(d[13]), "+f"(d[14]), "+f"(d[15]), "+f"(d[16]), "+f"(d[17]), "+f"(d[18]), "+f"(d[19]), "+f"(d[20]), "+f"(d[21]), "+f"(d[22]), "+f"(d[23]), "+f"(d[24]), "+f"(d[25]), "+f"(d[26]), "+f"(d[27]), "+f"(d[28]), "+f"(d[29]), "+f"(d[30]), "+f"(d[31]), "+f"(d[32]), "+f"(d[33]), "+f"(d[34]), "+f"(d[35]), "+f"(d[36]), "+f"(d[37]), "+f"(d[38]), "+f"(d[39]), "+f"(d[40]), "+f"(d[41]), "+f"(d[42]), "+f"(d[43]), "+f"(d[44]), "+f"(d[45]), "+f"(d[46]), "+f"(d[47]), "+f"(d[48]), "+f"(d[49]), "+f"(d[50]), "+f"(d[51]), "+f"(d[52]), "+f"(d[53]), "+f"(d[54]), "+f"(d[55]), "+f"(d[56]), "+f"(d[57]), "+f"(d[58]), "+f"(d[59]), "+f"(d[60]), "+f"(d[61]), "+f"(d[62]), "+f"(d[63]), "+f"(d[64]), "+f"(d[65]), "+f"(d[66]), "+f"(d[67]), "+f"(d[68]), "+f"(d[69]), "+f"(d[70]), "+f"(d[71]), "+f"(d[72]), "+f"(d[73]), "+f"(d[74]), "+f"(d[75]), "+f"(d[76]), "+f"(d[77]), "+f"(d[78]), "+f"(d[79]), "+f"(d[80]), "+f"(d[81]), "+f"(d[82]), "+f"(d[83]), "+f"(d[84]), "+f"(d[85]), "+f"(d[86]), "+f"(d[87]), "+f"(d[88]), "+f"(d[89]), "+f"(d[90]), "+f"(d[91]), "+f"(d[92]), "+f"(d[93]), "+f"(d[94]), "+f"(d[95]), "+f"(d[96]), "+f"(d[97]), "+f"(d[98]), "+f"(d[99]), "+f"(d[100]), "+f"(d[101]), "+f"(d[102]), "+f"(d[103]), "+f"(d[104]), "+f"(d[105]), "+f"(d[106]), "+f"(d[107])
      : "l"(da), "l"(db), "r"(sd), "n"(TB), "n"(AOFF), "n"(BOFF));
}

template<int TB, int AOFF, int BOFF> __device__ __forceinline__ void wgmma_ss_n128(float (&d)[64], uint64_t da, uint64_t db, int sd) {
    asm volatile("{\n.reg .pred p;\n.reg .b64 ta, tb;\nsetp.ne.b32 p, %66, 0;\nadd.s64 ta, %64, %68;\nadd.s64 tb, %65, %69;\n"
      "wgmma.mma_async.sync.aligned.m64n128k16.f32.bf16.bf16 {%0, %1, %2, %3, %4, %5, %6, %7, %8, %9, %10, %11, %12, %13, %14, %15, %16, %17, %18, %19, %20, %21, %22, %23, %24, %25, %26, %27, %28, %29, %30, %31, %32, %33, %34, %35, %36, %37, %38, %39, %40, %41, %42, %43, %44, %45, %46, %47, %48, %49, %50, %51, %52, %53, %54, %55, %56, %57, %58, %59, %60, %61, %62, %63}, ta, tb, p, 1, 1, 0, %67;\n}\n"
      : "+f"(d[0]), "+f"(d[1]), "+f"(d[2]), "+f"(d[3]), "+f"(d[4]), "+f"(d[5]), "+f"(d[6]), "+f"(d[7]), "+f"(d[8]), "+f"(d[9]), "+f"(d[10]), "+f"(d[11]), "+f"(d[12]), "+f"(d[13]), "+f"(d[14]), "+f"(d[15]), "+f"(d[16]), "+f"(d[17]), "+f"(d[18]), "+f"(d[19]), "+f"(d[20]), "+f"(d[21]), "+f"(d[22]), "+f"(d[23]), "+f"(d[24]), "+f"(d[25]), "+f"(d[26]), "+f"(d[27]), "+f"(d[28]), "+f"(d[29]), "+f"(d[30]), "+f"(d[31]), "+f"(d[32]), "+f"(d[33]), "+f"(d[34]), "+f"(d[35]), "+f"(d[36]), "+f"(d[37]), "+f"(d[38]), "+f"(d[39]), "+f"(d[40]), "+f"(d[41]), "+f"(d[42]), "+f"(d[43]), "+f"(d[44]), "+f"(d[45]), "+f"(d[46]), "+f"(d[47]), "+f"(d[48]), "+f"(d[49]), "+f"(d[50]), "+f"(d[51]), "+f"(d[52]), "+f"(d[53]), "+f"(d[54]), "+f"(d[55]), "+f"(d[56]), "+f"(d[57]), "+f"(d[58]), "+f"(d[59]), "+f"(d[60]), "+f"(d[61]), "+f"(d[62]), "+f"(d[63])
      : "l"(da), "l"(db), "r"(sd), "n"(TB), "n"(AOFF), "n"(BOFF));
}

template<int TB, int AOFF, int BOFF> __device__ __forceinline__ void wgmma_ss_n72(float (&d)[36], uint64_t da, uint64_t db, int sd) {
    asm volatile("{\n.reg .pred p;\n.reg .b64 ta, tb;\nsetp.ne.b32 p, %38, 0;\nadd.s64 ta, %36, %40;\nadd.s64 tb, %37, %41;\n"
      "wgmma.mma_async.sync.aligned.m64n72k16.f32.bf16.bf16 {%0, %1, %2, %3, %4, %5, %6, %7, %8, %9, %10, %11, %12, %13, %14, %15, %16, %17, %18, %19, %20, %21, %22, %23, %24, %25, %26, %27, %28, %29, %30, %31, %32, %33, %34, %35}, ta, tb, p, 1, 1, 0, %39;\n}\n"
      : "+f"(d[0]), "+f"(d[1]), "+f"(d[2]), "+f"(d[3]), "+f"(d[4]), "+f"(d[5]), "+f"(d[6]), "+f"(d[7]), "+f"(d[8]), "+f"(d[9]), "+f"(d[10]), "+f"(d[11]), "+f"(d[12]), "+f"(d[13]), "+f"(d[14]), "+f"(d[15]), "+f"(d[16]), "+f"(d[17]), "+f"(d[18]), "+f"(d[19]), "+f"(d[20]), "+f"(d[21]), "+f"(d[22]), "+f"(d[23]), "+f"(d[24]), "+f"(d[25]), "+f"(d[26]), "+f"(d[27]), "+f"(d[28]), "+f"(d[29]), "+f"(d[30]), "+f"(d[31]), "+f"(d[32]), "+f"(d[33]), "+f"(d[34]), "+f"(d[35])
      : "l"(da), "l"(db), "r"(sd), "n"(TB), "n"(AOFF), "n"(BOFF));
}

template<int TB, int BOFF> __device__ __forceinline__ void wgmma_rs_n24(float (&d)[12], uint32_t a0, uint32_t a1, uint32_t a2, uint32_t a3, uint64_t db, int sd) {
    asm volatile("{\n.reg .pred p;\n.reg .b64 tb;\nsetp.ne.b32 p, %17, 0;\nadd.s64 tb, %16, %19;\n"
      "wgmma.mma_async.sync.aligned.m64n24k16.f32.bf16.bf16 {%0, %1, %2, %3, %4, %5, %6, %7, %8, %9, %10, %11}, {%12, %13, %14, %15}, tb, p, 1, 1, %18;\n}\n"
      : "+f"(d[0]), "+f"(d[1]), "+f"(d[2]), "+f"(d[3]), "+f"(d[4]), "+f"(d[5]), "+f"(d[6]), "+f"(d[7]), "+f"(d[8]), "+f"(d[9]), "+f"(d[10]), "+f"(d[11])
      : "r"(a0), "r"(a1), "r"(a2), "r"(a3), "l"(db), "r"(sd), "n"(TB), "n"(BOFF));
}

template<int TB, int BOFF> __device__ __forceinline__ void wgmma_rs_n72(float (&d)[36], uint32_t a0, uint32_t a1, uint32_t a2, uint32_t a3, uint64_t db, int sd) {
    asm volatile("{\n.reg .pred p;\n.reg .b64 tb;\nsetp.ne.b32 p, %41, 0;\nadd.s64 tb, %40, %43;\n"
      "wgmma.mma_async.sync.aligned.m64n72k16.f32.bf16.bf16 {%0, %1, %2, %3, %4, %5, %6, %7, %8, %9, %10, %11, %12, %13, %14, %15, %16, %17, %18, %19, %20, %21, %22, %23, %24, %25, %26, %27, %28, %29, %30, %31, %32, %33, %34, %35}, {%36, %37, %38, %39}, tb, p, 1, 1, %42;\n}\n"
      : "+f"(d[0]), "+f"(d[1]), "+f"(d[2]), "+f"(d[3]), "+f"(d[4]), "+f"(d[5]), "+f"(d[6]), "+f"(d[7]), "+f"(d[8]), "+f"(d[9]), "+f"(d[10]), "+f"(d[11]), "+f"(d[12]), "+f"(d[13]), "+f"(d[14]), "+f"(d[15]), "+f"(d[16]), "+f"(d[17]), "+f"(d[18]), "+f"(d[19]), "+f"(d[20]), "+f"(d[21]), "+f"(d[22]), "+f"(d[23]), "+f"(d[24]), "+f"(d[25]), "+f"(d[26]), "+f"(d[27]), "+f"(d[28]), "+f"(d[29]), "+f"(d[30]), "+f"(d[31]), "+f"(d[32]), "+f"(d[33]), "+f"(d[34]), "+f"(d[35])
      : "r"(a0), "r"(a1), "r"(a2), "r"(a3), "l"(db), "r"(sd), "n"(TB), "n"(BOFF));
}

template<int TB, int AINC, int BINC> __device__ __forceinline__ void wgmma_ss_n64_pi(float (&d)[32], uint64_t& da, uint64_t& db, int sd) {
    asm volatile("{\n.reg .pred p;\nsetp.ne.b32 p, %34, 0;\n"
      "wgmma.mma_async.sync.aligned.m64n64k16.f32.bf16.bf16 {%0, %1, %2, %3, %4, %5, %6, %7, %8, %9, %10, %11, %12, %13, %14, %15, %16, %17, %18, %19, %20, %21, %22, %23, %24, %25, %26, %27, %28, %29, %30, %31}, %32, %33, p, 1, 1, 0, %35;\n"
      "add.s64 %32, %32, %36;\nadd.s64 %33, %33, %37;\n}\n"
      : "+f"(d[0]), "+f"(d[1]), "+f"(d[2]), "+f"(d[3]), "+f"(d[4]), "+f"(d[5]), "+f"(d[6]), "+f"(d[7]), "+f"(d[8]), "+f"(d[9]), "+f"(d[10]), "+f"(d[11]), "+f"(d[12]), "+f"(d[13]), "+f"(d[14]), "+f"(d[15]), "+f"(d[16]), "+f"(d[17]), "+f"(d[18]), "+f"(d[19]), "+f"(d[20]), "+f"(d[21]), "+f"(d[22]), "+f"(d[23]), "+f"(d[24]), "+f"(d[25]), "+f"(d[26]), "+f"(d[27]), "+f"(d[28]), "+f"(d[29]), "+f"(d[30]), "+f"(d[31]), "+l"(da), "+l"(db)
      : "r"(sd), "n"(TB), "n"(AINC), "n"(BINC));
}

template<int TB, int BINC> __device__ __forceinline__ void wgmma_rs_n64_pi(float (&d)[32], uint32_t a0, uint32_t a1, uint32_t a2, uint32_t a3, uint64_t& db, int sd) {
    asm volatile("{\n.reg .pred p;\nsetp.ne.b32 p, %37, 0;\n"
      "wgmma.mma_async.sync.aligned.m64n64k16.f32.bf16.bf16 {%0, %1, %2, %3, %4, %5, %6, %7, %8, %9, %10, %11, %12, %13, %14, %15, %16, %17, %18, %19, %20, %21, %22, %23, %24, %25, %26, %27, %28, %29, %30, %31}, {%33, %34, %35, %36}, %32, p, 1, 1, %38;\n"
      "add.s64 %32, %32, %39;\n}\n"
      : "+f"(d[0]), "+f"(d[1]), "+f"(d[2]), "+f"(d[3]), "+f"(d[4]), "+f"(d[5]), "+f"(d[6]), "+f"(d[7]), "+f"(d[8]), "+f"(d[9]), "+f"(d[10]), "+f"(d[11]), "+f"(d[12]), "+f"(d[13]), "+f"(d[14]), "+f"(d[15]), "+f"(d[16]), "+f"(d[17]), "+f"(d[18]), "+f"(d[19]), "+f"(d[20]), "+f"(d[21]), "+f"(d[22]), "+f"(d[23]), "+f"(d[24]), "+f"(d[25]), "+f"(d[26]), "+f"(d[27]), "+f"(d[28]), "+f"(d[29]), "+f"(d[30]), "+f"(d[31]), "+l"(db)
      : "r"(a0), "r"(a1), "r"(a2), "r"(a3), "r"(sd), "n"(TB), "n"(BINC));
}

constexpr int K1_XN_BYTES = 16 * 9216;
constexpr int K1_OFF_RING = K1_XN_BYTES;
constexpr int K1_OFF_BIAS = K1_OFF_RING + 10 * 8192;
constexpr int K1_OFF_BAR = K1_OFF_BIAS + 576 * 2;
constexpr int K1_SMEM = K1_OFF_BAR + 800;
constexpr float QSCALE = 0.23570226039551584f * 1.4426950408889634f;

struct K1Ctx {
    uint32_t full0;
    uint32_t rel_addr;
    uint64_t descA, descB;
    uint32_t phase;
    __device__ __forceinline__ void begin_stage(int s) {
        mbar_wait(full0 + s * 8, phase);
        wg_fence();
    }
    __device__ __forceinline__ void release(int s) {
        if (rel_addr) asm volatile("mbarrier.arrive.shared::cluster.b64 _, [%0];" ::"r"(rel_addr + s * 8) : "memory");
    }
    __device__ __forceinline__ void end_stage(int s) {
        wg_commit();
        wg_wait<1>();
        release(s == 0 ? 8 : s - 1);
    }
};

__host__ __device__ constexpr int a_off(int ks) { return ((ks / 12) * 49152 + ((ks >> 2) % 3) * 1024 + (ks & 3) * 32) >> 4; }

template <int V> struct IC { static constexpr int value = V; };
template <int I, int N, class F> __device__ __forceinline__ void static_for(F&& f) {
    if constexpr (I < N) { f(IC<I>{}); static_for<I + 1, N>(f); }
}

template <bool A_RS, bool B_RS, class Epi>
__device__ __forceinline__ void tile_pair(K1Ctx& c, float (&accA)[32], float (&accB)[32], uint32_t (&h)[144], Epi&& epi) {
    static_for<0, 9>([&](auto sc) {
        constexpr int s = decltype(sc)::value;
        c.begin_stage(s);
        static_for<0, 8>([&](auto tc) {
            constexpr int t = decltype(tc)::value, kk = s * 8 + t, ks = kk % 36;
            constexpr int db = ks == 35 ? -35 * 128 : 128, da = a_off((ks + 1) % 36) - a_off(ks);
            if constexpr (kk < 36) {
                if constexpr (A_RS) wgmma_rs_n64_pi<1, db>(accA, h[ks * 4], h[ks * 4 + 1], h[ks * 4 + 2], h[ks * 4 + 3], c.descB, ks != 0);
                else wgmma_ss_n64_pi<1, da, db>(accA, c.descA, c.descB, ks != 0);
            } else {
                if constexpr (B_RS) wgmma_rs_n64_pi<1, db>(accB, h[ks * 4], h[ks * 4 + 1], h[ks * 4 + 2], h[ks * 4 + 3], c.descB, ks != 0);
                else wgmma_ss_n64_pi<1, da, db>(accB, c.descA, c.descB, ks != 0);
            }
            if constexpr (t == 0) {
                c.end_stage(s);
                epi(sc);
                wg_fence();
            }
        });
        wg_commit();
    });
    c.phase ^= 1;
}

template <int B0, int NB, int HOFF>
__device__ __forceinline__ void gelu_blocks(const float (&acc)[32], uint32_t (&h)[144], const uint32_t (&bq)[8], float rs0, float rs1) {
#pragma unroll
    for (int b = B0; b < B0 + NB; b++) {
        const float b0 = bf_lo(bq[b]), b1 = bf_hi(bq[b]);
        h[HOFF + b * 2 + 0] = pack_bf16(gelu2(fmaf(acc[b * 4 + 0], rs0, b0)), gelu2(fmaf(acc[b * 4 + 1], rs0, b1)));
        h[HOFF + b * 2 + 1] = pack_bf16(gelu2(fmaf(acc[b * 4 + 2], rs1, b0)), gelu2(fmaf(acc[b * 4 + 3], rs1, b1)));
    }
#pragma unroll
    for (int i = HOFF + B0 * 2; i < HOFF + (B0 + NB) * 2; i++) asm volatile("" : "+r"(h[i]));
}
__device__ __forceinline__ void load_bias(uint32_t (&bq)[8], uint32_t addr) {
    asm volatile("ld.shared.v4.u32 {%0, %1, %2, %3}, [%4];" : "=r"(bq[0]), "=r"(bq[1]), "=r"(bq[2]), "=r"(bq[3]) : "r"(addr));
    asm volatile("ld.shared.v4.u32 {%0, %1, %2, %3}, [%4 + 16];" : "=r"(bq[4]), "=r"(bq[5]), "=r"(bq[6]), "=r"(bq[7]) : "r"(addr));
}
__device__ __forceinline__ void st_pred2(bool p, void* a, uint32_t x, uint32_t y) {
    asm volatile("{\n.reg .pred p;\nsetp.ne.u32 p, %3, 0;\n@p st.global.v2.u32 [%0], {%1, %2};\n}\n" ::"l"(a), "r"(x), "r"(y), "r"((uint32_t)p) : "memory");
}
__device__ __forceinline__ void st_pred1(bool p, void* a, uint32_t x) {
    asm volatile("{\n.reg .pred p;\nsetp.ne.u32 p, %2, 0;\n@p st.global.u32 [%0], %1;\n}\n" ::"l"(a), "r"(x), "r"((uint32_t)p) : "memory");
}
template <int S> __device__ __forceinline__ void store_part(const float (&o)[32], uint4* p) {
    uint4 v;
    v.x = pack_bf16(o[S * 8 + 0], o[S * 8 + 1]); v.y = pack_bf16(o[S * 8 + 2], o[S * 8 + 3]);
    v.z = pack_bf16(o[S * 8 + 4], o[S * 8 + 5]); v.w = pack_bf16(o[S * 8 + 6], o[S * 8 + 7]);
    p[S * 256] = v;
}

constexpr int NCHUNK = 16;
constexpr int CHUNK_BYTES = KV_HEAD_BYTES / NCHUNK;
constexpr int SM_Q = 0;
constexpr int SM_KV = 32768;
constexpr int PIECE = 19968;
__host__ __device__ constexpr int sm_piece(int p) { return p == 0 ? 209408 : (p == 1 ? 0 : SM_KV + (p - 2) * PIECE); }
__host__ __device__ constexpr int sm_wstep(int k) { return k < 27 ? sm_piece(k / 3) + (k % 3) * 4608 : (k < 35 ? SM_KV + 7 * PIECE + (k - 27) * 4608 : PIECE); }
__host__ __device__ constexpr int sm_ostep(int k) { return sm_piece(k / 3) + 13824 + (k % 3) * 2048; }
constexpr int SM_RED = SM_KV + KV_HEAD_BYTES;

__device__ __forceinline__ float exp2_fixed(float y) {
    const float u = __uint_as_float(__float_as_uint(y) & 0xFF807FFFu) - 512.02545f;
    float t = fmaf(u, 0.019497588f, 0.114550486f);
    t = fmaf(t, u, -0.29839927f);
    return fmaf(t, u, y);
}
__device__ __forceinline__ uint32_t pack_fixed(float lo, float hi) { return __byte_perm(__float_as_uint(lo), __float_as_uint(hi), 0x6521); }

#define QK1_BLK 0
#define QK2_BLK 1
#define PV_SPLIT 0x86420
__host__ __device__ constexpr int pv_first(int g) { return (PV_SPLIT >> (4 * g)) & 15; }
#define PV_GROUP 4
#define POLY_MODE 1
__device__ __forceinline__ uint32_t exp2_packed(float y0, float y1, uint32_t one2) {
    const uint32_t w = pack_fixed(y0, y1);
    uint32_t m;
    asm("lop3.b32 %0, %1, 0x007F007F, %2, 0xEA;" : "=r"(m) : "r"(w), "r"(one2));
    const uint32_t d = hfma2_bf16(m, 0x3EF93EF9u, 0xBF38BF38u);
    const uint32_t e = hfma2_bf16(d, d, 0xBD71BD71u);
    return hfma2_bf16(w, e, w);
}
constexpr int KV_TILE = CHUNK_BYTES / 16;
template <int OFF> __device__ __forceinline__ void issue_qk(float (&s)[64], uint64_t qd, uint64_t kd) {
    wgmma_ss_n128<0, 0, OFF + (8 << 16)>(s, qd, kd, 0);
    wgmma_ss_n128<0, 16, OFF + 32>(s, qd, kd, 1);
}
template <int OFF> __device__ __forceinline__ void issue_pv(float (&o)[12], const uint32_t (&p)[32], uint64_t vd) {
    static_for<0, 8>([&](auto kc) {
        constexpr int k = decltype(kc)::value;
        wgmma_rs_n24<1, OFF + k * (2 * KV_GROUP_BYTES / 16)>(o, p[k * 4], p[k * 4 + 1], p[k * 4 + 2], p[k * 4 + 3], vd, 1);
    });
}
template <int OFF>
__device__ __forceinline__ void softmax_pv(const float (&s)[64], uint32_t (&p)[32], float (&o)[12], uint64_t vd, uint32_t one2) {
    static_for<0, 8 / PV_GROUP>([&](auto gc) {
        constexpr int g0 = decltype(gc)::value * PV_GROUP;
#pragma unroll
        for (int b = g0 * 2; b < (g0 + PV_GROUP) * 2; b++) {
            if ((POLY_MASK >> b) & 1) {
                p[b * 2 + 0] = exp2_packed(s[b * 4 + 0], s[b * 4 + 1], one2);
                p[b * 2 + 1] = exp2_packed(s[b * 4 + 2], s[b * 4 + 3], one2);
            } else {
                p[b * 2 + 0] = pack_bf16(ex2(s[b * 4 + 0]), ex2(s[b * 4 + 1]));
                p[b * 2 + 1] = pack_bf16(ex2(s[b * 4 + 2]), ex2(s[b * 4 + 3]));
            }
        }
#pragma unroll
        for (int i = g0 * 4; i < (g0 + PV_GROUP) * 4; i++) asm volatile("" : "+r"(p[i])::"memory");
        wg_fence();
        static_for<g0, g0 + PV_GROUP>([&](auto kc) {
            constexpr int k = decltype(kc)::value;
            wgmma_rs_n24<1, OFF + k * (2 * KV_GROUP_BYTES / 16)>(o, p[k * 4], p[k * 4 + 1], p[k * 4 + 2], p[k * 4 + 3], vd, 1);
        });
    });
    wg_commit();
}
template <int KOFF>
__device__ __forceinline__ void attn_step(const float (&s)[64], float (&sn)[64], uint32_t (&p)[32], const uint32_t (&pp)[32], float (&o)[12],
                                          uint64_t qd, uint64_t kd, uint64_t vd, uint32_t one2, uint32_t z) {
    static_for<0, 4>([&](auto gc) {
        constexpr int g0 = decltype(gc)::value;
        wg_fence();
        if constexpr (g0 == QK1_BLK) wgmma_ss_n128<0, 0, KOFF + (8 << 16)>(sn, qd, kd, 0);
        if constexpr (g0 == QK2_BLK) wgmma_ss_n128<0, 16, KOFF + 32>(sn, qd, kd, 1);
        static_for<pv_first(g0), pv_first(g0 + 1)>([&](auto kc) {
            constexpr int k = decltype(kc)::value;
            wgmma_rs_n24<1, k * (2 * KV_GROUP_BYTES / 16)>(o, pp[k * 4], pp[k * 4 + 1], pp[k * 4 + 2], pp[k * 4 + 3], vd, 1);
        });
        wg_commit();
#pragma unroll
        for (int b = g0 * 4; b < g0 * 4 + 4; b++) {
            if ((POLY_MASK >> b) & 1) {
                p[b * 2 + 0] = exp2_packed(s[b * 4 + 0], s[b * 4 + 1], one2);
                p[b * 2 + 1] = exp2_packed(s[b * 4 + 2], s[b * 4 + 3], one2);
            } else {
                p[b * 2 + 0] = pack_bf16(ex2(s[b * 4 + 0]), ex2(s[b * 4 + 1]));
                p[b * 2 + 1] = pack_bf16(ex2(s[b * 4 + 2]), ex2(s[b * 4 + 3]));
            }
        }
#pragma unroll
        for (int i = g0 * 8; i < g0 * 8 + 8; i++) asm volatile("" : "+r"(p[i])::"memory");
        if constexpr (g0 < 3) asm volatile("{\n.reg .pred q;\nsetp.eq.u32 q, %0, 0;\n@q bra GO;\ntrap;\nGO:\n}\n" ::"r"(z) : "memory");
    });
}
__device__ __forceinline__ int head_pair(int hh, int i) {
    if (i == 8) return hh == 3 ? 0 : 8;
    const int q = i >> 1, t = (4 - hh) & 3;
    if ((i & 1) == 0) return t + q;
    return (hh == 1 || hh == 2) ? (q >= hh ? q - hh : t + 4 + q) : t + 4 + q;
}
template <bool LATE> __device__ __forceinline__ void store_o(float (&o)[12], int rt, int head, int wq, int lane) {
    const int g = lane >> 2, q = lane & 3;
    const float i0 = __fdividef(1.0f, __shfl_sync(~0u, o[8], lane | 3)), i1 = __fdividef(1.0f, __shfl_sync(~0u, o[10], lane | 3));
#pragma unroll
    for (int i = 0; i < 3; i++) {
        const uint32_t w0 = pack_bf16(o[i * 4] * i0, o[i * 4 + 1] * i0), w1 = pack_bf16(o[i * 4 + 2] * i1, o[i * 4 + 3] * i1);
        if (i < 2 || q == 2) {
            if constexpr (LATE) {
                const int pc = (head & 7) * 9 + head_pair(head & 3, i < 2 ? i * 4 + q : 8);
                uint32_t* op = reinterpret_cast<uint32_t*>(g_Olate) + (((rt * 9 + (pc >> 3)) * 128 + wq * 32 + g * 4 + (pc & 3)) * 4 + ((pc >> 2) & 1) * 2);
                asm volatile("st.relaxed.gpu.global.v2.u32 [%0], {%1, %2};" ::"l"(op), "r"(w0), "r"(w1) : "memory");
            } else {
                const int pc = head * 9 + head_pair(head & 3, i < 2 ? i * 4 + q : 8);
                uint32_t* op = g_O + ((rt * 72 + (pc >> 2)) * 8 + wq * 2) * 32 + g * 4 + (pc & 3);
                op[0] = w0;
                op[32] = w1;
            }
        }
    }
#pragma unroll
    for (int i = 0; i < 12; i++) o[i] = 0.f;
}
__device__ __forceinline__ void mbar_arrive(uint32_t b) { asm volatile("mbarrier.arrive.shared::cta.b64 _, [%0];" ::"r"(b) : "memory"); }
__device__ __forceinline__ void mbar_wait_sleep(uint32_t b, uint32_t ns) {
    uint32_t ok, spins = 0;
    while (true) {
        asm volatile("{\n.reg .pred p;\nmbarrier.try_wait.parity.shared::cta.b64 p, [%1], 0;\nselp.u32 %0, 1, 0, p;\n}\n" : "=r"(ok) : "r"(b) : "memory");
        if (ok) break;
        __nanosleep(ns);
        if (++spins > (1u << 21)) __trap();
    }
}
__device__ __forceinline__ void flag_signal(unsigned int* f) {
    __threadfence();
    atomicAdd(f, 1u);
}
__device__ __forceinline__ void flag_wait(const unsigned int* f, unsigned int target, unsigned int sleep_ns) {
    uint32_t v, spins = 0;
    while (true) {
        asm volatile("ld.acquire.gpu.global.u32 %0, [%1];" : "=r"(v) : "l"(f) : "memory");
        if (v >= target) break;
        if (sleep_ns) __nanosleep(sleep_ns);
        if (++spins > (1u << 21)) __trap();
    }
}
__device__ __forceinline__ uint4 hadd8_bf16(const uint4 a, const uint4 b) {
    return make_uint4(hadd2_bf16(a.x, b.x), hadd2_bf16(a.y, b.y), hadd2_bf16(a.z, b.z), hadd2_bf16(a.w, b.w));
}
__device__ __forceinline__ float sumsq2(uint32_t w) { return fmaf(bf_lo(w), bf_lo(w), bf_hi(w) * bf_hi(w)); }
__device__ __forceinline__ float sumsq8(const uint4 v) { return (sumsq2(v.x) + sumsq2(v.y)) + (sumsq2(v.z) + sumsq2(v.w)); }

enum { B_FULL = 0, B_EMPTY = 9, B_BASE = 18, B_XNDEAD = 19, B_QRDY = 20, B_FFN = 21, B_KV = 22, B_FREE = 38, B_WO = 46, B_RED = 55, B_X = 61, B_EARLY = 85, B_OS = 86, B_LATE = 94, B_BIAS = 95, B_END = 96 };

__global__ void __cluster_dims__(2, 1, 1) __launch_bounds__(384, 1)
fused_kernel(const __grid_constant__ CUtensorMap tmX, const __grid_constant__ CUtensorMap tmQ3, const __grid_constant__ CUtensorMap tmQ1,
          const __grid_constant__ CUtensorMap tm1, const __grid_constant__ CUtensorMap tm2, const __grid_constant__ CUtensorMap tmP,
          const __grid_constant__ CUtensorMap tmOut, const __grid_constant__ CUtensorMap tmXo, const __nv_bfloat16* __restrict__ b1,
          const __nv_bfloat16* __restrict__ wqkv, const __nv_bfloat16* __restrict__ w1, const __nv_bfloat16* __restrict__ w2,
          const __nv_bfloat16* __restrict__ wo, const __nv_bfloat16* __restrict__ b2,
          const uint64_t zero) {
    extern __shared__ __align__(1024) uint8_t smem[];
    const uint32_t sb = s2u(smem);
    const int tid = threadIdx.x, lane = tid & 31;
    const int warp = __shfl_sync(~0u, tid >> 5, 0);
    const uint32_t rank = blockIdx.x & 1;
    const int cl = blockIdx.x >> 1;
    const int rb = (cl & 7) * 2 + rank;
    const int j = cl >> 3;
    const uint32_t bar0 = sb + K1_OFF_BAR;
    const uint32_t full0 = bar0 + B_FULL * 8, empty0 = bar0 + B_EMPTY * 8, xbar0 = bar0 + B_X * 8;
    const int head = blockIdx.x >> 2, quarter = blockIdx.x & 3;
    const int rt = quarter * 8 + (head >> 2), ct = head & 3;
    const int rot = head >> 3;
    const int ks0 = ((((head >> 3) + 2) & 3) * 9);
    volatile uint32_t* slow_flag = reinterpret_cast<volatile uint32_t*>(smem + K1_OFF_BAR + B_END * 8);

    if (__builtin_expect(warp < 8, 1)) {
        PROF(0);
        PROFT(48);
        if (lane == 0) {
#pragma unroll
            for (int i = 0; i < 3; i++) mbar_init(xbar0 + (warp * 3 + i) * 8, 1);
            fence_barrier_init();
#pragma unroll 1
            for (int i = 0; i < 3; i++) {
                const uint32_t xb = xbar0 + (warp * 3 + i) * 8;
                mbar_expect(xb, 6144);
                tma4d(sb + i * 49152 + warp * 6144, &tmX, 0, 0, i * 3, rb * 16 + warp * 2, xb);
            }
        }
        __syncwarp();
        cluster_arrive();
        PROF(22);
        reg_alloc<240>();
        PROF(23);
        float rs0, rs1;
        {
            const uint32_t la = sb + (warp * 2 + ((lane >> 3) & 1)) * 3072 + (lane & 7) * 128;
            uint32_t off[4];
#pragma unroll
            for (int i = 0; i < 4; i++) off[i] = la + (((i * 2 + (lane >> 4)) ^ (lane & 7)) << 4);
            float c1[4] = {0.f, 0.f, 0.f, 0.f}, c2[4] = {0.f, 0.f, 0.f, 0.f}, c3[4] = {0.f, 0.f, 0.f, 0.f};
            uint32_t a[36][4];
#pragma unroll
            for (int t = 0; t < 3; t++) {
                mbar_wait(xbar0 + (warp * 3 + t) * 8, 0);
                PROF(24 + t);
#pragma unroll
                for (int i = 0; i < 12; i++) ldsm4(a[t * 12 + i], off[i & 3] + t * 49152 + (i >> 2) * 1024);
#pragma unroll
                for (int i = t * 12; i < t * 12 + 12; i++) {
                    mma16816(c3, a[i], 0x3F803F80u, 0x3F803F80u);
                    mma16816(c1, a[i], a[i][0], a[i][2]);
                    mma16816(c2, a[i], a[i][1], a[i][3]);
                }
            }
            PROF(27);
            const int gg = lane >> 2, src = (lane & ~3) | (gg >> 1);
            const float m0 = c3[0] * (1.0f / DM), m1 = c3[2] * (1.0f / DM);
            const uint32_t mc0 = pack_bf16(-m0, -m0), mc1 = pack_bf16(-m1, -m1);
#pragma unroll
            for (int i = 0; i < 36; i++) {
#pragma unroll
                for (int k = 0; k < 4; k++) a[i][k] = hadd2_bf16(a[i][k], (k & 1) ? mc1 : mc0);
                stsm4(off[i & 3] + (i / 12) * 49152 + ((i >> 2) % 3) * 1024, a[i]);
            }
            const float q0 = __shfl_sync(~0u, (gg & 1) ? c1[1] : c1[0], src), q1 = __shfl_sync(~0u, (gg & 1) ? c2[3] : c2[2], src);
            rs0 = rsqrtf(fmaxf(fmaf(-m0, m0, q0 * (1.0f / DM)), 0.f) + 1e-5f);
            rs1 = rsqrtf(fmaxf(fmaf(-m1, m1, q1 * (1.0f / DM)), 0.f) + 1e-5f);
            if (__any_sync(~0u, fabsf(m0) * rs0 > 0.25f || fabsf(m1) * rs1 > 0.25f)) {
                const float d0 = -m0 - bf_lo(mc0), d1 = -m1 - bf_lo(mc1);
                const uint32_t md0 = pack_bf16(d0, d0), md1 = pack_bf16(d1, d1);
#pragma unroll 1
                for (int i = 0; i < 9; i++) {
#pragma unroll
                    for (int k4 = 0; k4 < 4; k4++) {
                        const uint32_t ad = off[k4] + (i / 3) * 49152 + (i % 3) * 1024;
                        uint32_t b[4];
                        ldsm4(b, ad);
#pragma unroll
                        for (int k = 0; k < 4; k++) b[k] = hadd2_bf16(b[k], (k & 1) ? md1 : md0);
                        stsm4(ad, b);
                    }
                }
            }
        }
        PROF(28);
        const int wg = warp >> 2, wq = warp & 3;
        fence_proxy_async();
        named_bar_sync(1 + wg, 128);
        cluster_wait();
        PROF(1); PROFT(59);

        const int g = lane >> 2, q = lane & 3;
        K1Ctx c;
        c.full0 = full0;
        c.rel_addr = 0;
        c.descA = mk_desc(zero, sb + wg * 8 * 3072, 16, 3072, 1);
        c.descB = mk_desc(zero, sb + K1_OFF_RING, 2048, 1024, 1);
        c.phase = 0;
        uint32_t biasq = sb + K1_OFF_BIAS + q * 32;
        uint32_t bq[8];

        uint32_t h[144];
        float accA[32], accB[32];
        uint32_t qo[3], qt[3];
        {
            float accQ[108];
            uint32_t rel = 0;
            if (lane == 0 && wq < 2) asm("mapa.shared::cluster.u32 %0, %1, %2;" : "=r"(rel) : "r"(empty0), "r"(wq));
#pragma unroll 1
            for (int r = 0; r < 2; r++) {
                static_for<0, 9>([&](auto sc) {
                    constexpr int s = decltype(sc)::value;
                    c.begin_stage(s);
                    const uint64_t da = c.descA + (r ? a_off(18 + 2 * s) : a_off(2 * s));
                    wgmma_ss_n216<1, 0, ((2 * s) % 9) * 512>(accQ, da, c.descB, (r | s) != 0);
                    wgmma_ss_n216<1, 2, ((2 * s + 1) % 9) * 512>(accQ, da, c.descB, 1);
                    c.end_stage(s);
                    c.rel_addr = rel;
                });
                c.phase ^= 1;
            }
            PROF(2); PROFWT(54);
            mbar_wait(bar0 + B_BIAS * 8, 0);
            wg_wait<0>();
            reg_fence(accQ);
#pragma unroll
            for (int grp = 0; grp < 3; grp++) {
                const int G = 3 * j + grp, type = G >> 3;
                const uint32_t base = (G & 7) * 4 * KV_HEAD_BYTES + (rb * 16 + warp * 2) * KV_GROUP_BYTES + g * 16 + (type == 0 ? Q_OFFSET : (type == 2 ? 256 : 0));
                qo[grp] = base + (q >> 1) * 128 + (q & 1) * 8;
                qt[grp] = base + q * KV_HEAD_BYTES + (type == 0 ? 256 : (type == 2 ? 264 : 512));
#pragma unroll
                for (int hf = 0; hf < 2; hf++) {
                    const float sc = (hf ? rs1 : rs0) * (type == 0 ? QSCALE : ((type == 1 && ((POLY_MASK >> (warp * 2 + hf)) & 1)) ? 2.f : 1.f));
                    uint32_t w[9];
#pragma unroll
                    for (int i = 0; i < 9; i++) w[i] = pack_bf16(accQ[(grp * 9 + i) * 4 + hf * 2] * sc, accQ[(grp * 9 + i) * 4 + hf * 2 + 1] * sc);
                    uint32_t* d = h + 32 + hf * 32 + grp * 8;
                    d[0] = w[0]; d[1] = w[1]; d[2] = w[3]; d[3] = q >= 1 ? w[2] : w[4];
                    d[4] = w[5]; d[5] = q >= 2 ? w[4] : w[6]; d[6] = w[7]; d[7] = w[8];
                    h[32 + hf * 32 + 24 + grp] = q == 0 ? w[2] : (q == 1 ? w[4] : w[6]);
                }
            }
        }
        PROF(3); PROFWT(55); PROFT(60);
#pragma unroll
        for (int i = 32; i < 112; i++)
            if (i >= 96 || (i & 31) >= 27) asm volatile("mov.u32 %0, 0;" : "=r"(h[i]));
#pragma unroll
        for (int i = 0; i < 32; i++) asm volatile("mov.f32 %0, 0f00000000;" : "=f"(accB[i]));
#pragma unroll
        for (int i = 0; i < 8; i++) bq[i] = 0;
#pragma unroll 1
        for (int p = 0; p < 4; p++) {
            uint8_t* const qb = g_QKV + p * KV_GROUP_BYTES;
            tile_pair<false, false>(c, accA, accB, h, [&](auto sc) {
                constexpr int s = decltype(sc)::value;
                if constexpr (s == 0) {
                    reg_fence(accB);
#pragma unroll
                    for (int i = 0; i < 80; i++) h[i] = h[i + 32];
                }
                if constexpr (s >= 1 && s <= 6) {
                    constexpr int grp = (s - 1) >> 1, k = ((s - 1) & 1) * 2;
                    st_pred2(p < 2, qb + qo[grp] + k * KV_HEAD_BYTES, h[grp * 8 + k * 2], h[grp * 8 + k * 2 + 1]);
                    st_pred2(p < 2, qb + qo[grp] + (k + 1) * KV_HEAD_BYTES, h[grp * 8 + k * 2 + 2], h[grp * 8 + k * 2 + 3]);
                    if constexpr (k == 2) st_pred1(p < 2, qb + qt[grp], h[24 + grp]);
                }
                if constexpr (s < 4) gelu_blocks<s * 2, 2, 80>(accB, h, bq, rs0, rs1);
                if constexpr (s == 4) load_bias(bq, biasq);
                if constexpr (s == 5) reg_fence(accA);
                if constexpr (s >= 5) gelu_blocks<(s - 5) * 2, 2, 96>(accA, h, bq, rs0, rs1);
                if constexpr (s == 8) load_bias(bq, biasq + 128);
            });
            if (p == 1) asm volatile("bar.arrive 3, 352;" ::: "memory");
            biasq += 256;
        }
        PROF(4); PROFWT(56); PROFT(61);
        tile_pair<false, true>(c, accA, accB, h, [&](auto sc) {
            constexpr int s = decltype(sc)::value;
            if constexpr (s == 0) reg_fence(accB);
            if constexpr (s < 4) gelu_blocks<s * 2, 2, 112>(accB, h, bq, rs0, rs1);
            if constexpr (s == 4) load_bias(bq, biasq);
            if constexpr (s == 5) { reg_fence(accA); if (tid == wg * 128) mbar_arrive(bar0 + B_XNDEAD * 8); }
            if constexpr (s == 5 || s == 6) gelu_blocks<(s - 5) * 3, 3, 128>(accA, h, bq, rs0, rs1);
            if constexpr (s == 7) gelu_blocks<6, 2, 128>(accA, h, bq, rs0, rs1);
            if constexpr (s == 3 || s == 7) reg_fence(h);
        });
        PROF(5); PROFWT(57); PROFT(62);
        uint4* pout = g_part + j * SLAB + rb * 36 * 256 + tid;
#pragma unroll 1
        for (int p = 0; p < 4; p++) {
            tile_pair<true, true>(c, accA, accB, h, [&](auto sc) {
                constexpr int s = decltype(sc)::value;
                if constexpr (s == 0) reg_fence(accB);
                if constexpr (s < 4) store_part<s>(accB, pout);
                if constexpr (s == 5) reg_fence(accA);
                if constexpr (s >= 5) store_part<s - 5>(accA, pout + 1024);
            });
            pout += 2048;
            PROF(6 + p);
        }
        wg_wait<0>();
        c.release(8);
        reg_fence(accB);
        store_part<0>(accB, pout); store_part<1>(accB, pout); store_part<2>(accB, pout); store_part<3>(accB, pout);
        __syncwarp();
        if (lane == 0) mbar_arrive(bar0 + B_FFN * 8);
        PROF(10); PROFWT(58);
        PROFT(49);

        mbar_wait(bar0 + B_QRDY * 8, 0);
        const uint32_t slow = __any_sync(~0u, *slow_flag != 0);
        const uint64_t kd0 = mk_desc(zero, sb + SM_KV, 0, KV_GROUP_BYTES, 0);
        const uint64_t vd0 = mk_desc(zero, sb + SM_KV + 256, KV_GROUP_BYTES, 128, 0);
        const uint64_t qd0 = mk_desc(zero, sb + SM_Q + wg * 4096, 128, 512, 0);
        const uint32_t kvbar = bar0 + B_KV * 8;
        float o[12];
#pragma unroll
        for (int i = 0; i < 12; i++) o[i] = 0.f;
        PROF(16);
        PROFT(50);
        if (__builtin_expect(!slow, 1)) {
            const uint32_t one2 = 0x3F803F80u + (uint32_t)zero;
            float s0[64], s1[64];
            uint32_t p0[32], p1[32];
            mbar_wait(kvbar, 0);
            reg_fence(o);
            wg_fence();
            issue_qk<0>(s0, qd0, kd0);
            wg_commit();
#pragma unroll
            for (int i = 0; i < 32; i++) asm volatile("mov.u32 %0, 0;" : "=r"(p1[i]));
            uint64_t qd = qd0, vd = vd0;
            const uint32_t fre = (tid == wg * 128) ? bar0 + B_FREE * 8 - 8 : 0;
#pragma unroll 1
            for (int pass = 0; pass < 4; pass++) {
                uint64_t kd = kd0;
                uint32_t bn = kvbar + 8;
#pragma unroll 1
                for (int it = 0; it < 8; it++) {
                    if (pass == 0) {
                        mbar_wait(bn, 0);
                        mbar_wait(it == 7 ? bn : bn + 8, 0);
                    }
                    wg_wait<0>();
                    reg_fence(s0);
                    if (pass == 3 && it > 0 && fre) mbar_arrive(fre + it * 8);
                    attn_step<KV_TILE>(s0, s1, p0, p1, o, qd, kd, vd, one2, (uint32_t)zero);
                    vd = vd0 + it * (2 * KV_TILE);
                    kd += 2 * KV_TILE;
                    if (it == 7) { kd = kd0; qd += 512; }
                    wg_wait<0>();
                    if (it == 0 && pass != 0) {
                        reg_fence(o);
                        store_o<false>(o, quarter * 8 + ((pass - 1 + rot) & 3) * 2 + wg, head, wq, lane);
                        reg_fence(o);
                        __syncwarp();
                        if (lane == 0) mbar_arrive(bar0 + (B_OS + pass * 2 - 2 + wg) * 8);
                    }
                    reg_fence(s1);
                    attn_step<0>(s1, s0, p1, p0, o, qd, kd, vd, one2, (uint32_t)zero);
                    vd += KV_TILE;
                    bn += 16;
                }
                if (pass == 0) PROF(17);
            }
            reg_fence(p1);
            wg_fence();
            issue_pv<0>(o, p1, vd);
            wg_commit();
            wg_wait<0>();
            reg_fence(o);
            reg_fence(s0);
            reg_fence(s1);
            store_o<true>(o, quarter * 8 + ((3 + rot) & 3) * 2 + wg, head, wq, lane);
        } else {
#pragma unroll 1
            for (int pass = 0; pass < 4; pass++) {
                float m0 = -INFINITY, m1 = -INFINITY;
                float s[64];
                uint32_t p[32];
#pragma unroll 1
                for (int t = 0; t < 16; t++) {
                    mbar_wait(kvbar + t * 8, 0);
                    wg_fence();
                    issue_qk<0>(s, qd0 + pass * 512, kd0 + t * KV_TILE);
                    wg_commit();
                    wg_wait<0>();
                    reg_fence(s);
                    float a0 = m0, a1 = m1;
#pragma unroll
                    for (int k = 0; k < 16; k++) {
                        if ((POLY_MASK >> k) & 1) {
#pragma unroll
                            for (int i = 0; i < 4; i++) s[k * 4 + i] *= 0.5f;
                        }
                        a0 = fmaxf(a0, fmaxf(s[k * 4 + 0], s[k * 4 + 1]));
                        a1 = fmaxf(a1, fmaxf(s[k * 4 + 2], s[k * 4 + 3]));
                    }
                    a0 = fmaxf(a0, __shfl_xor_sync(~0u, a0, 1)); a1 = fmaxf(a1, __shfl_xor_sync(~0u, a1, 1));
                    a0 = fmaxf(a0, __shfl_xor_sync(~0u, a0, 2)); a1 = fmaxf(a1, __shfl_xor_sync(~0u, a1, 2));
                    const float r0 = ex2(m0 - a0), r1 = ex2(m1 - a1);
                    m0 = a0; m1 = a1;
#pragma unroll
                    for (int i = 0; i < 3; i++) { o[i * 4] *= r0; o[i * 4 + 1] *= r0; o[i * 4 + 2] *= r1; o[i * 4 + 3] *= r1; }
#pragma unroll
                    for (int k = 0; k < 16; k++) {
                        p[k * 2 + 0] = pack_bf16(ex2(s[k * 4 + 0] - m0), ex2(s[k * 4 + 1] - m0));
                        p[k * 2 + 1] = pack_bf16(ex2(s[k * 4 + 2] - m1), ex2(s[k * 4 + 3] - m1));
                    }
                    reg_fence(p);
                    reg_fence(o);
                    wg_fence();
                    issue_pv<0>(o, p, vd0 + t * KV_TILE);
                    wg_commit();
                    wg_wait<0>();
                    reg_fence(o);
                }
                if (pass < 3) {
                    store_o<false>(o, quarter * 8 + ((pass + rot) & 3) * 2 + wg, head, wq, lane);
                    __syncwarp();
                    if (lane == 0) mbar_arrive(bar0 + (B_OS + pass * 2 + wg) * 8);
                }
            }
            store_o<true>(o, quarter * 8 + ((3 + rot) & 3) * 2 + wg, head, wq, lane);
            if (tid == wg * 128)
                for (int i = 0; i < 7; i++) mbar_arrive(bar0 + (B_FREE + i) * 8);
        }
        PROF(18);
        PROFT(51);

        if (tid == wg * 128) mbar_arrive(bar0 + (B_FREE + 7) * 8);
        const int t128 = tid & 127;
        uint32_t bv[9];
        uint2 fv[9];
        mbar_wait(bar0 + B_BASE * 8, 0);
#pragma unroll
        for (int i = 0; i < 9; i++) {
            bv[i] = __ldg(reinterpret_cast<const uint32_t*>(b2 + ct * 144 + wg * 72 + q * 2) + i * 4);
            fv[i] = __ldcg(g_ffn + (blockIdx.x * 18 + wg * 9 + i) * 128 + t128);
        }
        float acc[36];
        const uint64_t od = mk_desc(zero, sb, 1024, 128, 0), wd = mk_desc(zero, sb + wg * 9 * 128, 2304, 128, 0);
        static_for<0, 9>([&](auto pc) {
            constexpr int p = decltype(pc)::value;
            mbar_wait(bar0 + (B_WO + p) * 8, 0);
            wg_fence();
            wgmma_ss_n72<1, sm_ostep(p * 3) / 16, sm_wstep(p * 3) / 16>(acc, od, wd, p != 0);
            wgmma_ss_n72<1, sm_ostep(p * 3 + 1) / 16, sm_wstep(p * 3 + 1) / 16>(acc, od, wd, 1);
            wgmma_ss_n72<1, sm_ostep(p * 3 + 2) / 16, sm_wstep(p * 3 + 2) / 16>(acc, od, wd, 1);
            wg_commit();
            if constexpr (p == 1) {
                wg_wait<1>();
                if (t128 == 0) mbar_arrive(bar0 + B_EARLY * 8);
            }
        });
        wg_wait<0>();
        reg_fence(acc);
        PROF(29);
        uint4 al[9];
        {
            const uint4* ap = g_Olate + rt * 9 * 128 + t128;
            uint32_t spins = 0;
            bool ok;
            do {
                ok = true;
#pragma unroll
                for (int k = 0; k < 9; k++)
                    asm volatile("ld.relaxed.gpu.global.v4.u32 {%0, %1, %2, %3}, [%4];" : "=r"(al[k].x), "=r"(al[k].y), "=r"(al[k].z), "=r"(al[k].w) : "l"(ap + k * 128) : "memory");
#pragma unroll
                for (int k = 0; k < 9; k++) ok = ok && al[k].x != O_EMPTY && al[k].y != O_EMPTY && al[k].z != O_EMPTY && al[k].w != O_EMPTY;
                if (++spins > (1u << 20)) __trap();
            } while (!__all_sync(~0u, ok));
        }
        PROF(19);
        mbar_wait(bar0 + B_LATE * 8, 0);
        PROF(20);
        wg_fence();
        static_for<27, 36>([&](auto kc) {
            constexpr int k = decltype(kc)::value;
            wgmma_rs_n72<1, sm_wstep(k) / 16>(acc, al[k - 27].x, al[k - 27].y, al[k - 27].z, al[k - 27].w, wd, 1);
        });
        wg_commit();
        PROF(31);
        uint32_t* st = reinterpret_cast<uint32_t*>(smem + sm_piece(0) + wg * 9216) + (wq * 16 + g) * 36 + q;
        float bs[36];
#pragma unroll
        for (int i = 0; i < 9; i++) {
            const uint32_t x0 = st[i * 4], x1 = st[i * 4 + 288];
            bs[i * 4 + 0] = fmaf(bf_lo(fv[i].x), 0.5f, bf_lo(x0) + bf_lo(bv[i]));
            bs[i * 4 + 1] = fmaf(bf_hi(fv[i].x), 0.5f, bf_hi(x0) + bf_hi(bv[i]));
            bs[i * 4 + 2] = fmaf(bf_lo(fv[i].y), 0.5f, bf_lo(x1) + bf_lo(bv[i]));
            bs[i * 4 + 3] = fmaf(bf_hi(fv[i].y), 0.5f, bf_hi(x1) + bf_hi(bv[i]));
        }
        reg_fence(bs);
        wg_wait<0>();
        reg_fence(acc);
        PROF(32);
#pragma unroll
        for (int i = 0; i < 9; i++) {
            st[i * 4] = pack_bf16(acc[i * 4] + bs[i * 4], acc[i * 4 + 1] + bs[i * 4 + 1]);
            st[i * 4 + 288] = pack_bf16(acc[i * 4 + 2] + bs[i * 4 + 2], acc[i * 4 + 3] + bs[i * 4 + 3]);
        }
        fence_proxy_async();
        named_bar_sync(1 + wg, 128);
        if (t128 == 0) {
            asm volatile("cp.async.bulk.tensor.2d.global.shared::cta.bulk_group [%0, {%2, %3}], [%1];"
                         ::"l"(&tmOut), "r"(sb + sm_piece(0) + wg * 9216), "r"(ct * 144 + wg * 72), "r"(rt * 64) : "memory");
            asm volatile("cp.async.bulk.commit_group;" ::: "memory");
            asm volatile("cp.async.bulk.wait_group.read 0;" ::: "memory");
        }
        PROF(21);
        PROFT(52);
    } else {
        reg_dealloc<24>();
        if (warp == 8 && lane == 0) {
            prefetch_tmap(&tmQ3); prefetch_tmap(&tmQ1); prefetch_tmap(&tm1); prefetch_tmap(&tm2);
            #pragma unroll 1
            for (int i = 0; i < 9; i++) { mbar_init(full0 + i * 8, 1); mbar_init(empty0 + i * 8, 4); mbar_init(bar0 + (B_WO + i) * 8, 2); }
            mbar_init(bar0 + B_BASE * 8, 3); mbar_init(bar0 + B_XNDEAD * 8, 2); mbar_init(bar0 + B_QRDY * 8, 3); mbar_init(bar0 + B_FFN * 8, 8); mbar_init(bar0 + B_EARLY * 8, 2); mbar_init(bar0 + B_LATE * 8, 2); mbar_init(bar0 + B_BIAS * 8, 96);
#pragma unroll 1
            for (int i = 0; i < 16; i++) { mbar_init(bar0 + (B_KV + i) * 8, 1); mbar_init(bar0 + (B_FREE + (i & 7)) * 8, 2); if (i < 6) mbar_init(bar0 + (B_RED + i) * 8, 1); if (i < 6) mbar_init(bar0 + (B_OS + i) * 8, 4); }
            *slow_flag = 0;
            fence_barrier_init();
        }
        __syncwarp();
        cluster_arrive();
        cluster_wait();
        const uint8_t* kvsrc = g_QKV + (size_t)head * KV_HEAD_BYTES;
        if (warp == 8) {
            if (lane == 0) {
                int st = 0, u = rank, tile = -4;
                int es = 5;
                uint32_t eph = 1;
#pragma unroll 1
                for (int n = 0; n < 99; n++) {
                    mbar_wait(empty0 + es * 8, eph);
                    const uint32_t fb = full0 + st * 8, dst = sb + K1_OFF_RING + u * 8192;
                    mbar_expect(fb, 16384);
                    if (tile < 0) {
                        tma3d_mc(dst, &tmQ3, j * 216, n * 32 + rank * 16, 0, fb, 3);
                        tma2d_mc(dst + 6144, &tmQ1, j * 216 + 192, n * 32 + rank * 16, fb, 3);
                    } else if (tile < 9) {
                        tma2d_mc(dst, &tm1, j * 576 + tile * 64, u * 64, fb, 3);
                    } else {
                        tma2d_mc(dst, &tm2, (tile - 9) * 64, j * 576 + u * 64, fb, 3);
                    }
                    u += 2;
                    if (u >= 9) { u -= 9; tile++; }
                    if (++st == 9) st = 0;
                    if (++es == 9) { es = 0; eph ^= 1; }
                }
                mbar_wait(empty0 + 8 * 8, 0);
                mbar_wait(bar0 + B_QRDY * 8, 0);
                asm volatile("fence.proxy.async;" ::: "memory");
#pragma unroll 1
                for (int i = 11; i < NCHUNK; i++) {
                    mbar_expect(bar0 + (B_KV + i) * 8, CHUNK_BYTES);
                    bulk_load(sb + SM_KV + i * CHUNK_BYTES, kvsrc + i * CHUNK_BYTES, CHUNK_BYTES, bar0 + (B_KV + i) * 8);
                }
                const uint8_t* wsrc = g_Wo + ct * WO_TILE_BYTES;
                prefetch_tmap(&tmOut);
                mbar_wait_sleep(bar0 + B_BASE * 8, 500);
#pragma unroll 1
                for (int p = 0; p < 9; p++) {
                    if (p > 0) mbar_wait_sleep(bar0 + (B_FREE + p - 1) * 8, p == 1 ? 500 : 40);
                    const int k = ks0 + p * 3 >= 36 ? ks0 + p * 3 - 36 : ks0 + p * 3;
                    mbar_expect(bar0 + (B_WO + p) * 8, 13824);
                    bulk_load(sb + (p == 0 ? sm_piece(0) : (p == 1 ? sm_piece(1) : SM_KV + (p - 2) * PIECE)), wsrc + k * 4608, 13824, bar0 + (B_WO + p) * 8);
                }
                const int kl = ks0 == 0 ? 27 : ks0 - 9;
                mbar_expect(bar0 + B_LATE * 8, 9 * 4608);
                bulk_load(sb + sm_wstep(27), wsrc + kl * 4608, 8 * 4608, bar0 + B_LATE * 8);
                bulk_load(sb + sm_wstep(35), wsrc + (kl + 8) * 4608, 4608, bar0 + B_LATE * 8);
            }
        } else {
            const int ht = tid - 288;
            if (ht == 64) prefetch_l2(wqkv + blockIdx.x * (DM * 3 * DM / 128), DM * 3 * DM / 64);
            if (ht < 72) {
                const uint4 v = __ldg(reinterpret_cast<const uint4*>(b1 + j * 576) + ht);
                uint32_t* sbias = reinterpret_cast<uint32_t*>(smem + K1_OFF_BIAS) + (ht >> 3) * 32 + (ht & 7);
                sbias[0] = v.x; sbias[8] = v.y; sbias[16] = v.z; sbias[24] = v.w;
            }
            mbar_arrive(bar0 + B_BIAS * 8);
            PROFH(37);
#pragma unroll
            for (int i = 0; i < 3; i++) g_Olate[blockIdx.x * 288 + i * 96 + ht] = make_uint4(O_EMPTY, O_EMPTY, O_EMPTY, O_EMPTY);
#pragma unroll 1
            for (int i = ht; i < 512; i += 96) {
                const int key = i & 127;
                uint8_t* p = g_QKV + (size_t)(j * 4 + (i >> 7)) * KV_HEAD_BYTES + (rb * 16 + (key >> 3)) * KV_GROUP_BYTES + 512 + (key & 7) * 16;
                *reinterpret_cast<uint32_t*>(p + 4) = ((POLY_MASK >> (key >> 3)) & 1) ? 0x3F804000u : 0x00003F80u;
                *reinterpret_cast<uint32_t*>(p + 12) = 0x00003F80u;
            }
            if (ht == 32) prefetch_l2(w1 + blockIdx.x * (DM * FF / 128), DM * FF / 64);
#pragma unroll 2
            for (int i = blockIdx.x * 324 + ht; i < blockIdx.x * 324 + 324; i += 96) {
                const int k = i / 72, nc = i - k * 72, c4 = nc / 18;
                *reinterpret_cast<uint4*>(g_Wo + c4 * WO_TILE_BYTES + (k >> 3) * 2304 + (nc - c4 * 18) * 128 + (k & 7) * 16) =
                    __ldg(reinterpret_cast<const uint4*>(wo) + i);
            }
            PROFH(38);
            named_bar_sync(3, 352);
            if (ht == 32) prefetch_l2(w2 + blockIdx.x * (DM * FF / 128), DM * FF / 64);
            if (ht == 0) {
                flag_signal(&g_flags.qkv_stored[rb]);
                flag_wait(&g_flags.qkv_stored[rb], 8, 200);
            }
            named_bar_sync(7, 96);
            PROFH(39);
#pragma unroll 1
            for (int i = warp - 9; i < 16; i += 3) {
                const int hd = j * 4 + (i >> 2), key = (i & 3) * 32 + lane;
                const uint8_t* p = g_QKV + (size_t)hd * KV_HEAD_BYTES + (rb * 16 + (key >> 3)) * KV_GROUP_BYTES + (key & 7) * 16;
                const uint4 a = __ldcg(reinterpret_cast<const uint4*>(p)), b = __ldcg(reinterpret_cast<const uint4*>(p + 128));
                float n = sumsq2(__ldcg(reinterpret_cast<const uint32_t*>(p + 512))) + sumsq8(a) + sumsq8(b);
                if ((POLY_MASK >> (key >> 3)) & 1) n *= 0.25f;
#pragma unroll
                for (int o = 16; o; o >>= 1) n = fmaxf(n, __shfl_xor_sync(~0u, n, o));
                if (lane == 0) g_kmax[hd * 64 + rb * 4 + (i & 3)] = n;
            }
            named_bar_sync(7, 96);
            PROFH(40);
            if (ht == 0) {
                flag_signal(&g_flags.kv_ready);
                flag_wait(&g_flags.kv_ready, 128, 300);
                mbar_wait_sleep(bar0 + B_XNDEAD * 8, 300);
            }
            named_bar_sync(7, 96);
            PROFH(41);
            float kmax2;
            {
                const float2 v = __ldcg(reinterpret_cast<const float2*>(g_kmax + head * 64 + lane * 2));
                kmax2 = fmaxf(v.x, v.y);
#pragma unroll
                for (int o = 16; o; o >>= 1) kmax2 = fmaxf(kmax2, __shfl_xor_sync(~0u, kmax2, o));
            }
            asm volatile("fence.proxy.async;" ::: "memory");
            int chunk = warp - 9;
#pragma unroll 1
            for (int r = ht; r < 512; r += 96) {
                if (lane == 0 && chunk < 11) {
                    mbar_expect(bar0 + (B_KV + chunk) * 8, CHUNK_BYTES);
                    bulk_load(sb + SM_KV + chunk * CHUNK_BYTES, kvsrc + chunk * CHUNK_BYTES, CHUNK_BYTES, bar0 + (B_KV + chunk) * 8);
                }
                chunk += 3;
                const uint8_t* p = kvsrc + Q_OFFSET + (quarter * 64 + (((r >> 3) + rot * 16) & 63)) * KV_GROUP_BYTES + (r & 7) * 16;
                const uint4 a = __ldcg(reinterpret_cast<const uint4*>(p)), b = __ldcg(reinterpret_cast<const uint4*>(p + 128));
                const uint32_t e = __ldcg(reinterpret_cast<const uint32_t*>(p + 256));
                const float cc = sqrtf((sumsq2(e) + sumsq8(a) + sumsq8(b)) * kmax2) * 1.02f;
                if (!(cc <= 58.f)) *slow_flag = 1;
                uint4* dst = reinterpret_cast<uint4*>(smem + SM_Q + (r >> 3) * 512 + (r & 7) * 16);
                dst[0] = a;
                dst[8] = b;
                dst[16] = make_uint4(e, pack_bf16(-cc, 768.f), 0u, 0u);
                dst[24] = make_uint4(0u, POLY_MODE ? 0xBFFF0000u : 0xC0000000u, 0u, 0u);
            }
            named_bar_sync(7, 96);
            if (*slow_flag) {
#pragma unroll 1
                for (int r = ht; r < 512; r += 96) {
                    uint32_t* dst = reinterpret_cast<uint32_t*>(smem + SM_Q + (r >> 3) * 512 + (r & 7) * 16);
                    dst[65] = 0u;
                    dst[97] = 0u;
                }
            }
            fence_proxy_async();
            __syncwarp();
            if (lane == 0) mbar_arrive(bar0 + B_QRDY * 8);
            PROFH(42);
            if (ht == 0) {
                mbar_wait_sleep(bar0 + B_FFN * 8, 300);
                flag_signal(&g_flags.ffn_done[rb]);
                flag_wait(&g_flags.ffn_done[rt >> 1], 8, 300);
            }
            named_bar_sync(7, 96);
            {
                const int w3 = warp - 9;
                const uint32_t rbar = bar0 + (B_RED + w3 * 2) * 8, rbuf = SM_RED + w3 * 8192;
                const int u0 = ((rt >> 1) * 36 + ct * 9) * 256 + (rt & 1) * 128;
                mbar_wait_sleep(bar0 + (B_KV + 15) * 8, 500);
                asm volatile("fence.proxy.async;" ::: "memory");
#pragma unroll 1
                for (int i = -2; i < 12; i++) {
                    if (i >= 0) {
                        __nanosleep(400);
                        mbar_wait(rbar + (i & 1) * 8, (i >> 1) & 1);
                        const uint4* sp = reinterpret_cast<const uint4*>(smem + rbuf + (i & 1) * 4096) + lane;
                        const uint4 v = hadd8_bf16(hadd8_bf16(hadd8_bf16(sp[0], sp[32]), hadd8_bf16(sp[64], sp[96])),
                                                   hadd8_bf16(hadd8_bf16(sp[128], sp[160]), hadd8_bf16(sp[192], sp[224])));
                        const int bx = i * 3 + w3;
                        uint2* fp = g_ffn + (blockIdx.x * 18 + (bx >> 2) * 2) * 128 + (bx & 3) * 32 + lane;
                        fp[0] = make_uint2(v.x, v.y);
                        fp[128] = make_uint2(v.z, v.w);
                    }
                    __syncwarp();
                    if (lane == 0 && i < 10) {
                        const int bx = (i + 2) * 3 + w3;
                        mbar_expect(rbar + (i & 1) * 8, 4096);
                        tma2d(sb + rbuf + (i & 1) * 4096, &tmP, (u0 + (bx >> 2) * 256 + (bx & 3) * 32) * 2, 0, rbar + (i & 1) * 8);
                    }
                }
            }
            __syncwarp();
            if (lane == 0) mbar_arrive(bar0 + B_BASE * 8);
            PROFH(43);
            if (ht == 0) {
#pragma unroll 1
                for (int i = 0; i < 6; i++) {
                    mbar_wait_sleep(bar0 + (B_OS + i) * 8, 200);
                    flag_signal(&g_flags.o_done[quarter * 8 + (((i >> 1) + rot) & 3) * 2 + (i & 1)]);
                }
            } else if (ht == 32) {
                const uint8_t* osrc = reinterpret_cast<const uint8_t*>(g_O) + rt * 73728;
                mbar_wait_sleep(bar0 + B_BASE * 8, 500);
                mbar_wait_sleep(bar0 + B_FREE * 8, 500);
                flag_wait(&g_flags.o_done[rt], 24, 100);
                if (atomicAdd(&g_flags.exited, 1u) == gridDim.x - 1) {
                    unsigned int* f = reinterpret_cast<unsigned int*>(&g_flags);
#pragma unroll 1
                    for (int i = 0; i < (int)(sizeof(Flags) / 4); i++) f[i] = 0;
                }
                prefetch_tmap(&tmXo);
                asm volatile("fence.proxy.async;" ::: "memory");
#pragma unroll 1
                for (int p = 0; p < 9; p++) {
                    if (p > 1) mbar_wait_sleep(bar0 + (B_FREE + p - 1) * 8, 40);
                    const int k = ks0 + p * 3 >= 36 ? ks0 + p * 3 - 36 : ks0 + p * 3;
                    mbar_expect(bar0 + (B_WO + p) * 8, 6144);
                    bulk_load(sb + 13824 + (p == 0 ? sm_piece(0) : (p == 1 ? sm_piece(1) : SM_KV + (p - 2) * PIECE)), osrc + k * 2048, 6144, bar0 + (B_WO + p) * 8);
                }
                mbar_expect(bar0 + B_LATE * 8, 2 * 9216);
                mbar_wait(bar0 + B_EARLY * 8, 0);
                tma2d(sb + sm_piece(0), &tmXo, ct * 144, rt * 64, bar0 + B_LATE * 8);
                tma2d(sb + sm_piece(0) + 9216, &tmXo, ct * 144 + 72, rt * 64, bar0 + B_LATE * 8);
            }
        }
    }
}

typedef CUresult (*EncodeFn)(CUtensorMap*, CUtensorMapDataType, cuuint32_t, void*, const cuuint64_t*, const cuuint64_t*, const cuuint32_t*,
                             const cuuint32_t*, CUtensorMapInterleave, CUtensorMapSwizzle, CUtensorMapL2promotion, CUtensorMapFloatOOBfill);

void make_map(EncodeFn fn, CUtensorMap* m, const void* base, int rank, const cuuint64_t* dims, const cuuint64_t* strides, const cuuint32_t* box) {
    cuuint32_t es[4] = {1, 1, 1, 1};
    fn(m, CU_TENSOR_MAP_DATA_TYPE_BFLOAT16, rank, const_cast<void*>(base), dims, strides, box, es, CU_TENSOR_MAP_INTERLEAVE_NONE,
       CU_TENSOR_MAP_SWIZZLE_128B, CU_TENSOR_MAP_L2_PROMOTION_L2_256B, CU_TENSOR_MAP_FLOAT_OOB_FILL_NONE);
}

}

extern "C" void kernel_launch(void* const* d_in, const int* in_sizes, int n_in, void* d_out, int out_size) {
    const __nv_bfloat16* x = (const __nv_bfloat16*)d_in[0];
    const __nv_bfloat16* wqkv = (const __nv_bfloat16*)d_in[1];
    const __nv_bfloat16* wo = (const __nv_bfloat16*)d_in[2];
    const __nv_bfloat16* w1 = (const __nv_bfloat16*)d_in[4];
    const __nv_bfloat16* b1 = (const __nv_bfloat16*)d_in[5];
    const __nv_bfloat16* w2 = (const __nv_bfloat16*)d_in[6];
    const __nv_bfloat16* b2 = (const __nv_bfloat16*)d_in[7];
    __nv_bfloat16* out = (__nv_bfloat16*)d_out;

    EncodeFn fn = nullptr;
    cudaDriverEntryPointQueryResult qr;
    cudaGetDriverEntryPoint("cuTensorMapEncodeTiled", (void**)&fn, cudaEnableDefault, &qr);
    CUtensorMap tmX, tmQ3, tmQ1, tm1, tm2, tmP, tmOut, tmXo;
    {
        cuuint64_t d[2] = {DM, SEQ}, s[1] = {DM * 2};
        cuuint32_t b[2] = {72, 64}, es[2] = {1, 1};
        fn(&tmOut, CU_TENSOR_MAP_DATA_TYPE_BFLOAT16, 2, out, d, s, b, es, CU_TENSOR_MAP_INTERLEAVE_NONE, CU_TENSOR_MAP_SWIZZLE_NONE,
           CU_TENSOR_MAP_L2_PROMOTION_NONE, CU_TENSOR_MAP_FLOAT_OOB_FILL_NONE);
        fn(&tmXo, CU_TENSOR_MAP_DATA_TYPE_BFLOAT16, 2, const_cast<__nv_bfloat16*>(x), d, s, b, es, CU_TENSOR_MAP_INTERLEAVE_NONE,
           CU_TENSOR_MAP_SWIZZLE_NONE, CU_TENSOR_MAP_L2_PROMOTION_NONE, CU_TENSOR_MAP_FLOAT_OOB_FILL_NONE);
    }
    {
        void* gp = nullptr;
        cudaGetSymbolAddress(&gp, g_part);
        cuuint64_t d[2] = {SLAB * 2, 8}, s[1] = {SLAB * 16};
        cuuint32_t b[2] = {64, 8}, es[2] = {1, 1};
        fn(&tmP, CU_TENSOR_MAP_DATA_TYPE_INT64, 2, gp, d, s, b, es, CU_TENSOR_MAP_INTERLEAVE_NONE, CU_TENSOR_MAP_SWIZZLE_NONE,
           CU_TENSOR_MAP_L2_PROMOTION_NONE, CU_TENSOR_MAP_FLOAT_OOB_FILL_NONE);
    }
    {
        cuuint64_t d[4] = {64, 8, 9, SEQ / 8}, s[3] = {DM * 2, 128, DM * 2 * 8};
        cuuint32_t b[4] = {64, 8, 3, 2};
        make_map(fn, &tmX, x, 4, d, s, b);
    }
    {
        cuuint64_t d[3] = {3 * DM, DM, 3}, s[2] = {3 * DM * 2, 128};
        cuuint32_t b[3] = {64, 16, 3};
        make_map(fn, &tmQ3, wqkv, 3, d, s, b);
        make_map(fn, &tmQ1, wqkv, 2, d, s, b);
    }
    {
        cuuint64_t d[2] = {FF, DM}, s[1] = {FF * 2};
        cuuint32_t b[2] = {64, 64};
        make_map(fn, &tm1, w1, 2, d, s, b);
        cuuint64_t d2[2] = {DM, FF}, s2[1] = {DM * 2};
        make_map(fn, &tm2, w2, 2, d2, s2, b);
    }
    cudaFuncSetAttribute(fused_kernel, cudaFuncAttributeMaxDynamicSharedMemorySize, K1_SMEM);
    fused_kernel<<<128, 384, K1_SMEM, cudaStreamPerThread>>>(tmX, tmQ3, tmQ1, tm1, tm2, tmP, tmOut, tmXo, b1, wqkv, w1, w2, wo, b2, 0ull);
}
```

```cpp
#include <cuda_runtime.h>
#include <cuda_bf16.h>
#include <cuda.h>
#include <stdint.h>

#define PROF(i) do { } while (0)
#define PROFT(i) do { } while (0)
#define PROFH(i) do { } while (0)
#define PROFWT(i) do { } while (0)
#define PROF_WG 0

namespace {

constexpr int SEQ = 2048, DM = 576, FF = 4608, NH = 32, DH = 18;

constexpr int KV_GROUP_BYTES = 5 * 128;
constexpr int KV_HEAD_BYTES = (SEQ / 8) * KV_GROUP_BYTES;
constexpr int Q_OFFSET = NH * KV_HEAD_BYTES;
#define POLY_MASK 0xB6B6
__device__ __align__(1024) uint8_t g_QKV[2 * NH * KV_HEAD_BYTES];
__device__ __align__(1024) float g_kmax[NH * 64];
constexpr int SLAB = 16 * 36 * 256;
__device__ __align__(1024) uint4 g_part[8 * SLAB];
__device__ __align__(1024) uint2 g_ffn[128 * 18 * 128];
__device__ __align__(1024) uint32_t g_O[SEQ * DM / 2];
struct Flags {
    unsigned int qkv_stored[16];
    unsigned int ffn_done[16];
    unsigned int o_done[32];
    unsigned int kv_ready;
    unsigned int exited;
};
__device__ Flags g_flags;
__device__ __align__(1024) uint4 g_Olate[32 * 9 * 128];
constexpr uint32_t O_EMPTY = 0xFFFFFFFFu;
constexpr int WO_TILE_BYTES = DM * 144 * 2;
__device__ __align__(1024) uint8_t g_Wo[4 * WO_TILE_BYTES];

__device__ __forceinline__ uint32_t s2u(const void* p) { return (uint32_t)__cvta_generic_to_shared(p); }
__device__ __forceinline__ void mbar_init(uint32_t b, int c) { asm volatile("mbarrier.init.shared::cta.b64 [%0], %1;" ::"r"(b), "r"(c) : "memory"); }
__device__ __forceinline__ void mbar_expect(uint32_t b, uint32_t bytes) {
    asm volatile("mbarrier.arrive.expect_tx.shared::cta.b64 _, [%0], %1;" ::"r"(b), "r"(bytes) : "memory");
}
__device__ __forceinline__ void mbar_wait(uint32_t b, uint32_t parity) {
    asm volatile(
        "{\n.reg .pred p;\n.reg .u32 c;\n"
        "mov.u32 c, 0;\n"
        "LOOP:\n"
        "mbarrier.try_wait.parity.shared::cta.b64 p, [%0], %1;\n"
        "@p bra DONE;\n"
        "add.u32 c, c, 1;\n"
        "setp.lt.u32 p, c, 4194304;\n"
        "@p bra LOOP;\n"
        "trap;\n"
        "DONE:\n}\n" ::"r"(b), "r"(parity) : "memory");
}
__device__ __forceinline__ void fence_barrier_init() { asm volatile("fence.mbarrier_init.release.cluster;" ::: "memory"); }
__device__ __forceinline__ void fence_proxy_async() { asm volatile("fence.proxy.async.shared::cta;" ::: "memory"); }
__device__ __forceinline__ void cluster_arrive() { asm volatile("barrier.cluster.arrive.relaxed.aligned;" ::: "memory"); }
__device__ __forceinline__ void cluster_wait() { asm volatile("barrier.cluster.wait.aligned;" ::: "memory"); }
__device__ __forceinline__ void named_bar_sync(int id, int n) { asm volatile("bar.sync %0, %1;" ::"r"(id), "r"(n) : "memory"); }

__device__ __forceinline__ void tma3d_mc(uint32_t dst, const CUtensorMap* tm, int c0, int c1, int c2, uint32_t bar, uint16_t mask) {
    asm volatile("cp.async.bulk.tensor.3d.shared::cluster.global.mbarrier::complete_tx::bytes.multicast::cluster [%0], [%1, {%3, %4, %5}], [%2], %6;"
                 ::"r"(dst), "l"(tm), "r"(bar), "r"(c0), "r"(c1), "r"(c2), "h"(mask) : "memory");
}
__device__ __forceinline__ void tma2d_mc(uint32_t dst, const CUtensorMap* tm, int c0, int c1, uint32_t bar, uint16_t mask) {
    asm volatile("cp.async.bulk.tensor.2d.shared::cluster.global.mbarrier::complete_tx::bytes.multicast::cluster [%0], [%1, {%3, %4}], [%2], %5;"
                 ::"r"(dst), "l"(tm), "r"(bar), "r"(c0), "r"(c1), "h"(mask) : "memory");
}
__device__ __forceinline__ void tma4d(uint32_t dst, const CUtensorMap* tm, int c0, int c1, int c2, int c3, uint32_t bar) {
    asm volatile("cp.async.bulk.tensor.4d.shared::cluster.global.mbarrier::complete_tx::bytes [%0], [%1, {%3, %4, %5, %6}], [%2];"
                 ::"r"(dst), "l"(tm), "r"(bar), "r"(c0), "r"(c1), "r"(c2), "r"(c3) : "memory");
}
__device__ __forceinline__ void tma2d(uint32_t dst, const CUtensorMap* tm, int c0, int c1, uint32_t bar) {
    asm volatile("cp.async.bulk.tensor.2d.shared::cluster.global.mbarrier::complete_tx::bytes [%0], [%1, {%3, %4}], [%2];"
                 ::"r"(dst), "l"(tm), "r"(bar), "r"(c0), "r"(c1) : "memory");
}
__device__ __forceinline__ void bulk_load(uint32_t dst, const void* src, uint32_t bytes, uint32_t bar) {
    asm volatile("cp.async.bulk.shared::cluster.global.mbarrier::complete_tx::bytes [%0], [%1], %2, [%3];"
                 ::"r"(dst), "l"(src), "r"(bytes), "r"(bar) : "memory");
}
__device__ __forceinline__ void prefetch_l2(const void* p, uint32_t bytes) {
    asm volatile("cp.async.bulk.prefetch.L2.global [%0], %1;" ::"l"(p), "r"(bytes) : "memory");
}
__device__ __forceinline__ void prefetch_tmap(const CUtensorMap* tm) { asm volatile("prefetch.tensormap [%0];" ::"l"(tm) : "memory"); }

__device__ __forceinline__ void wg_fence() { asm volatile("wgmma.fence.sync.aligned;" ::: "memory"); }
__device__ __forceinline__ void wg_commit() { asm volatile("wgmma.commit_group.sync.aligned;" ::: "memory"); }
template <int N> __device__ __forceinline__ void wg_wait() { asm volatile("wgmma.wait_group.sync.aligned %0;" ::"n"(N) : "memory"); }
template <int N> __device__ __forceinline__ void reg_fence(float (&d)[N]) {
#pragma unroll
    for (int i = 0; i < N; i++) asm volatile("" : "+f"(d[i])::"memory");
}
template <int N> __device__ __forceinline__ void reg_fence(uint32_t (&d)[N]) {
#pragma unroll
    for (int i = 0; i < N; i++) asm volatile("" : "+r"(d[i])::"memory");
}
template <int R> __device__ __forceinline__ void reg_alloc() { asm volatile("setmaxnreg.inc.sync.aligned.u32 %0;" ::"n"(R)); }
template <int R> __device__ __forceinline__ void reg_dealloc() { asm volatile("setmaxnreg.dec.sync.aligned.u32 %0;" ::"n"(R)); }

__device__ __forceinline__ uint64_t mk_desc(uint64_t z, uint32_t addr, uint32_t lbo, uint32_t sbo, uint32_t swz) {
    return z + ((uint64_t)(((addr & 0x3FFFF) >> 4) | ((lbo >> 4) << 16)) | ((uint64_t)((sbo >> 4) | (swz << 30)) << 32));
}
__device__ __forceinline__ uint32_t pack_bf16(float lo, float hi) {
    uint32_t r;
    asm("cvt.rn.bf16x2.f32 %0, %1, %2;" : "=r"(r) : "f"(hi), "f"(lo));
    return r;
}
__device__ __forceinline__ float bf_lo(uint32_t w) { return __uint_as_float(w << 16); }
__device__ __forceinline__ float bf_hi(uint32_t w) { return __uint_as_float(w & 0xFFFF0000u); }
__device__ __forceinline__ float ex2(float x) {
    float r;
    asm("ex2.approx.ftz.f32 %0, %1;" : "=f"(r) : "f"(x));
    return r;
}
__device__ __forceinline__ float tanh_fast(float x) {
    float r;
    asm("tanh.approx.f32 %0, %1;" : "=f"(r) : "f"(x));
    return r;
}
__device__ __forceinline__ uint32_t hfma2_bf16(uint32_t a, uint32_t b, uint32_t c) {
    uint32_t r;
    asm("fma.rn.bf16x2 %0, %1, %2, %3;" : "=r"(r) : "r"(a), "r"(b), "r"(c));
    return r;
}
__device__ __forceinline__ uint32_t hadd2_bf16(uint32_t a, uint32_t b) {
    uint32_t r;
    asm("add.rn.bf16x2 %0, %1, %2;" : "=r"(r) : "r"(a), "r"(b));
    return r;
}
__device__ __forceinline__ void ldsm4(uint32_t (&a)[4], uint32_t addr) {
    asm volatile("ldmatrix.sync.aligned.m8n8.x4.shared.b16 {%0, %1, %2, %3}, [%4];" : "=r"(a[0]), "=r"(a[1]), "=r"(a[2]), "=r"(a[3]) : "r"(addr) : "memory");
}
__device__ __forceinline__ void stsm4(uint32_t addr, const uint32_t (&a)[4]) {
    asm volatile("stmatrix.sync.aligned.m8n8.x4.shared.b16 [%0], {%1, %2, %3, %4};" ::"r"(addr), "r"(a[0]), "r"(a[1]), "r"(a[2]), "r"(a[3]) : "memory");
}
__device__ __forceinline__ void mma16816(float (&c)[4], const uint32_t (&a)[4], uint32_t b0, uint32_t b1) {
    asm("mma.sync.aligned.m16n8k16.row.col.f32.bf16.bf16.f32 {%0, %1, %2, %3}, {%4, %5, %6, %7}, {%8, %9}, {%0, %1, %2, %3};"
        : "+f"(c[0]), "+f"(c[1]), "+f"(c[2]), "+f"(c[3]) : "r"(a[0]), "r"(a[1]), "r"(a[2]), "r"(a[3]), "r"(b0), "r"(b1));
}
__device__ __forceinline__ float gelu2(float u) {
    const float w = fmaf(u * u, 0.0356774081f, 0.7978845608f);
    return fmaf(u, tanh_fast(u * w), u);
}

template<int TB, int AOFF, int BOFF> __device__ __forceinline__ void wgmma_ss_n216(float (&d)[108], uint64_t da, uint64_t db, int sd) {
    asm volatile("{\n.reg .pred p;\n.reg .b64 ta, tb;\nsetp.ne.b32 p, %110, 0;\nadd.s64 ta, %108, %112;\nadd.s64 tb, %109, %113;\n"
      "wgmma.mma_async.sync.aligned.m64n216k16.f32.bf16.bf16 {%0, %1, %2, %3, %4, %5, %6, %7, %8, %9, %10, %11, %12, %13, %14, %15, %16, %17, %18, %19, %20, %21, %22, %23, %24, %25, %26, %27, %28, %29, %30, %31, %32, %33, %34, %35, %36, %37, %38, %39, %40, %41, %42, %43, %44, %45, %46, %47, %48, %49, %50, %51, %52, %53, %54, %55, %56, %57, %58, %59, %60, %61, %62, %63, %64, %65, %66, %67, %68, %69, %70, %71, %72, %73, %74, %75, %76, %77, %78, %79, %80, %81, %82, %83, %84, %85, %86, %87, %88, %89, %90, %91, %92, %93, %94, %95, %96, %97, %98, %99, %100, %101, %102, %103, %104, %105, %106, %107}, ta, tb, p, 1, 1, 0, %111;\n}\n"
      : "+f"(d[0]), "+f"(d[1]), "+f"(d[2]), "+f"(d[3]), "+f"(d[4]), "+f"(d[5]), "+f"(d[6]), "+f"(d[7]), "+f"(d[8]), "+f"(d[9]), "+f"(d[10]), "+f"(d[11]), "+f"(d[12]), "+f"(d[13]), "+f"(d[14]), "+f"(d[15]), "+f"(d[16]), "+f"(d[17]), "+f"(d[18]), "+f"(d[19]), "+f"(d[20]), "+f"(d[21]), "+f"(d[22]), "+f"(d[23]), "+f"(d[24]), "+f"(d[25]), "+f"(d[26]), "+f"(d[27]), "+f"(d[28]), "+f"(d[29]), "+f"(d[30]), "+f"(d[31]), "+f"(d[32]), "+f"(d[33]), "+f"(d[34]), "+f"(d[35]), "+f"(d[36]), "+f"(d[37]), "+f"(d[38]), "+f"(d[39]), "+f"(d[40]), "+f"(d[41]), "+f"(d[42]), "+f"(d[43]), "+f"(d[44]), "+f"(d[45]), "+f"(d[46]), "+f"(d[47]), "+f"(d[48]), "+f"(d[49]), "+f"(d[50]), "+f"(d[51]), "+f"(d[52]), "+f"(d[53]), "+f"(d[54]), "+f"(d[55]), "+f"(d[56]), "+f"(d[57]), "+f"(d[58]), "+f"(d[59]), "+f"(d[60]), "+f"(d[61]), "+f"(d[62]), "+f"(d[63]), "+f"(d[64]), "+f"(d[65]), "+f"(d[66]), "+f"(d[67]), "+f"(d[68]), "+f"(d[69]), "+f"(d[70]), "+f"(d[71]), "+f"(d[72]), "+f"(d[73]), "+f"(d[74]), "+f"(d[75]), "+f"(d[76]), "+f"(d[77]), "+f"(d[78]), "+f"(d[79]), "+f"(d[80]), "+f"(d[81]), "+f"(d[82]), "+f"(d[83]), "+f"(d[84]), "+f"(d[85]), "+f"(d[86]), "+f"(d[87]), "+f"(d[88]), "+f"(d[89]), "+f"(d[90]), "+f"(d[91]), "+f"(d[92]), "+f"(d[93]), "+f"(d[94]), "+f"(d[95]), "+f"(d[96]), "+f"(d[97]), "+f"(d[98]), "+f"(d[99]), "+f"(d[100]), "+f"(d[101]), "+f"(d[102]), "+f"(d[103]), "+f"(d[104]), "+f"(d[105]), "+f"(d[106]), "+f"(d[107])
      : "l"(da), "l"(db), "r"(sd), "n"(TB), "n"(AOFF), "n"(BOFF));
}

template<int TB, int AOFF, int BOFF> __device__ __forceinline__ void wgmma_ss_n128(float (&d)[64], uint64_t da, uint64_t db, int sd) {
    asm volatile("{\n.reg .pred p;\n.reg .b64 ta, tb;\nsetp.ne.b32 p, %66, 0;\nadd.s64 ta, %64, %68;\nadd.s64 tb, %65, %69;\n"
      "wgmma.mma_async.sync.aligned.m64n128k16.f32.bf16.bf16 {%0, %1, %2, %3, %4, %5, %6, %7, %8, %9, %10, %11, %12, %13, %14, %15, %16, %17, %18, %19, %20, %21, %22, %23, %24, %25, %26, %27, %28, %29, %30, %31, %32, %33, %34, %35, %36, %37, %38, %39, %40, %41, %42, %43, %44, %45, %46, %47, %48, %49, %50, %51, %52, %53, %54, %55, %56, %57, %58, %59, %60, %61, %62, %63}, ta, tb, p, 1, 1, 0, %67;\n}\n"
      : "+f"(d[0]), "+f"(d[1]), "+f"(d[2]), "+f"(d[3]), "+f"(d[4]), "+f"(d[5]), "+f"(d[6]), "+f"(d[7]), "+f"(d[8]), "+f"(d[9]), "+f"(d[10]), "+f"(d[11]), "+f"(d[12]), "+f"(d[13]), "+f"(d[14]), "+f"(d[15]), "+f"(d[16]), "+f"(d[17]), "+f"(d[18]), "+f"(d[19]), "+f"(d[20]), "+f"(d[21]), "+f"(d[22]), "+f"(d[23]), "+f"(d[24]), "+f"(d[25]), "+f"(d[26]), "+f"(d[27]), "+f"(d[28]), "+f"(d[29]), "+f"(d[30]), "+f"(d[31]), "+f"(d[32]), "+f"(d[33]), "+f"(d[34]), "+f"(d[35]), "+f"(d[36]), "+f"(d[37]), "+f"(d[38]), "+f"(d[39]), "+f"(d[40]), "+f"(d[41]), "+f"(d[42]), "+f"(d[43]), "+f"(d[44]), "+f"(d[45]), "+f"(d[46]), "+f"(d[47]), "+f"(d[48]), "+f"(d[49]), "+f"(d[50]), "+f"(d[51]), "+f"(d[52]), "+f"(d[53]), "+f"(d[54]), "+f"(d[55]), "+f"(d[56]), "+f"(d[57]), "+f"(d[58]), "+f"(d[59]), "+f"(d[60]), "+f"(d[61]), "+f"(d[62]), "+f"(d[63])
      : "l"(da), "l"(db), "r"(sd), "n"(TB), "n"(AOFF), "n"(BOFF));
}

template<int TB, int AOFF, int BOFF> __device__ __forceinline__ void wgmma_ss_n72(float (&d)[36], uint64_t da, uint64_t db, int sd) {
    asm volatile("{\n.reg .pred p;\n.reg .b64 ta, tb;\nsetp.ne.b32 p, %38, 0;\nadd.s64 ta, %36, %40;\nadd.s64 tb, %37, %41;\n"
      "wgmma.mma_async.sync.aligned.m64n72k16.f32.bf16.bf16 {%0, %1, %2, %3, %4, %5, %6, %7, %8, %9, %10, %11, %12, %13, %14, %15, %16, %17, %18, %19, %20, %21, %22, %23, %24, %25, %26, %27, %28, %29, %30, %31, %32, %33, %34, %35}, ta, tb, p, 1, 1, 0, %39;\n}\n"
      : "+f"(d[0]), "+f"(d[1]), "+f"(d[2]), "+f"(d[3]), "+f"(d[4]), "+f"(d[5]), "+f"(d[6]), "+f"(d[7]), "+f"(d[8]), "+f"(d[9]), "+f"(d[10]), "+f"(d[11]), "+f"(d[12]), "+f"(d[13]), "+f"(d[14]), "+f"(d[15]), "+f"(d[16]), "+f"(d[17]), "+f"(d[18]), "+f"(d[19]), "+f"(d[20]), "+f"(d[21]), "+f"(d[22]), "+f"(d[23]), "+f"(d[24]), "+f"(d[25]), "+f"(d[26]), "+f"(d[27]), "+f"(d[28]), "+f"(d[29]), "+f"(d[30]), "+f"(d[31]), "+f"(d[32]), "+f"(d[33]), "+f"(d[34]), "+f"(d[35])
      : "l"(da), "l"(db), "r"(sd), "n"(TB), "n"(AOFF), "n"(BOFF));
}

template<int TB, int BOFF> __device__ __forceinline__ void wgmma_rs_n24(float (&d)[12], uint32_t a0, uint32_t a1, uint32_t a2, uint32_t a3, uint64_t db, int sd) {
    asm volatile("{\n.reg .pred p;\n.reg .b64 tb;\nsetp.ne.b32 p, %17, 0;\nadd.s64 tb, %16, %19;\n"
      "wgmma.mma_async.sync.aligned.m64n24k16.f32.bf16.bf16 {%0, %1, %2, %3, %4, %5, %6, %7, %8, %9, %10, %11}, {%12, %13, %14, %15}, tb, p, 1, 1, %18;\n}\n"
      : "+f"(d[0]), "+f"(d[1]), "+f"(d[2]), "+f"(d[3]), "+f"(d[4]), "+f"(d[5]), "+f"(d[6]), "+f"(d[7]), "+f"(d[8]), "+f"(d[9]), "+f"(d[10]), "+f"(d[11])
      : "r"(a0), "r"(a1), "r"(a2), "r"(a3), "l"(db), "r"(sd), "n"(TB), "n"(BOFF));
}

template<int TB, int BOFF> __device__ __forceinline__ void wgmma_rs_n72(float (&d)[36], uint32_t a0, uint32_t a1, uint32_t a2, uint32_t a3, uint64_t db, int sd) {
    asm volatile("{\n.reg .pred p;\n.reg .b64 tb;\nsetp.ne.b32 p, %41, 0;\nadd.s64 tb, %40, %43;\n"
      "wgmma.mma_async.sync.aligned.m64n72k16.f32.bf16.bf16 {%0, %1, %2, %3, %4, %5, %6, %7, %8, %9, %10, %11, %12, %13, %14, %15, %16, %17, %18, %19, %20, %21, %22, %23, %24, %25, %26, %27, %28, %29, %30, %31, %32, %33, %34, %35}, {%36, %37, %38, %39}, tb, p, 1, 1, %42;\n}\n"
      : "+f"(d[0]), "+f"(d[1]), "+f"(d[2]), "+f"(d[3]), "+f"(d[4]), "+f"(d[5]), "+f"(d[6]), "+f"(d[7]), "+f"(d[8]), "+f"(d[9]), "+f"(d[10]), "+f"(d[11]), "+f"(d[12]), "+f"(d[13]), "+f"(d[14]), "+f"(d[15]), "+f"(d[16]), "+f"(d[17]), "+f"(d[18]), "+f"(d[19]), "+f"(d[20]), "+f"(d[21]), "+f"(d[22]), "+f"(d[23]), "+f"(d[24]), "+f"(d[25]), "+f"(d[26]), "+f"(d[27]), "+f"(d[28]), "+f"(d[29]), "+f"(d[30]), "+f"(d[31]), "+f"(d[32]), "+f"(d[33]), "+f"(d[34]), "+f"(d[35])
      : "r"(a0), "r"(a1), "r"(a2), "r"(a3), "l"(db), "r"(sd), "n"(TB), "n"(BOFF));
}

template<int TB, int AINC, int BINC> __device__ __forceinline__ void wgmma_ss_n64_pi(float (&d)[32], uint64_t& da, uint64_t& db, int sd) {
    asm volatile("{\n.reg .pred p;\nsetp.ne.b32 p, %34, 0;\n"
      "wgmma.mma_async.sync.aligned.m64n64k16.f32.bf16.bf16 {%0, %1, %2, %3, %4, %5, %6, %7, %8, %9, %10, %11, %12, %13, %14, %15, %16, %17, %18, %19, %20, %21, %22, %23, %24, %25, %26, %27, %28, %29, %30, %31}, %32, %33, p, 1, 1, 0, %35;\n"
      "add.s64 %32, %32, %36;\nadd.s64 %33, %33, %37;\n}\n"
      : "+f"(d[0]), "+f"(d[1]), "+f"(d[2]), "+f"(d[3]), "+f"(d[4]), "+f"(d[5]), "+f"(d[6]), "+f"(d[7]), "+f"(d[8]), "+f"(d[9]), "+f"(d[10]), "+f"(d[11]), "+f"(d[12]), "+f"(d[13]), "+f"(d[14]), "+f"(d[15]), "+f"(d[16]), "+f"(d[17]), "+f"(d[18]), "+f"(d[19]), "+f"(d[20]), "+f"(d[21]), "+f"(d[22]), "+f"(d[23]), "+f"(d[24]), "+f"(d[25]), "+f"(d[26]), "+f"(d[27]), "+f"(d[28]), "+f"(d[29]), "+f"(d[30]), "+f"(d[31]), "+l"(da), "+l"(db)
      : "r"(sd), "n"(TB), "n"(AINC), "n"(BINC));
}

template<int TB, int BINC> __device__ __forceinline__ void wgmma_rs_n64_pi(float (&d)[32], uint32_t a0, uint32_t a1, uint32_t a2, uint32_t a3, uint64_t& db, int sd) {
    asm volatile("{\n.reg .pred p;\nsetp.ne.b32 p, %37, 0;\n"
      "wgmma.mma_async.sync.aligned.m64n64k16.f32.bf16.bf16 {%0, %1, %2, %3, %4, %5, %6, %7, %8, %9, %10, %11, %12, %13, %14, %15, %16, %17, %18, %19, %20, %21, %22, %23, %24, %25, %26, %27, %28, %29, %30, %31}, {%33, %34, %35, %36}, %32, p, 1, 1, %38;\n"
      "add.s64 %32, %32, %39;\n}\n"
      : "+f"(d[0]), "+f"(d[1]), "+f"(d[2]), "+f"(d[3]), "+f"(d[4]), "+f"(d[5]), "+f"(d[6]), "+f"(d[7]), "+f"(d[8]), "+f"(d[9]), "+f"(d[10]), "+f"(d[11]), "+f"(d[12]), "+f"(d[13]), "+f"(d[14]), "+f"(d[15]), "+f"(d[16]), "+f"(d[17]), "+f"(d[18]), "+f"(d[19]), "+f"(d[20]), "+f"(d[21]), "+f"(d[22]), "+f"(d[23]), "+f"(d[24]), "+f"(d[25]), "+f"(d[26]), "+f"(d[27]), "+f"(d[28]), "+f"(d[29]), "+f"(d[30]), "+f"(d[31]), "+l"(db)
      : "r"(a0), "r"(a1), "r"(a2), "r"(a3), "r"(sd), "n"(TB), "n"(BINC));
}

constexpr int K1_XN_BYTES = 16 * 9216;
constexpr int K1_OFF_RING = K1_XN_BYTES;
constexpr int K1_OFF_BIAS = K1_OFF_RING + 10 * 8192;
constexpr int K1_OFF_BAR = K1_OFF_BIAS + 576 * 2;
constexpr int K1_SMEM = K1_OFF_BAR + 800;
constexpr float QSCALE = 0.23570226039551584f * 1.4426950408889634f;

struct K1Ctx {
    uint32_t full0;
    uint32_t rel_addr;
    uint64_t descA, descB;
    uint32_t phase;
    uint32_t ak[8][4];
    __device__ __forceinline__ void begin_stage(int s) {
        mbar_wait(full0 + s * 8, phase);
        wg_fence();
    }
    __device__ __forceinline__ void release(int s) {
        if (rel_addr) asm volatile("mbarrier.arrive.shared::cluster.b64 _, [%0];" ::"r"(rel_addr + s * 8) : "memory");
    }
    __device__ __forceinline__ void end_stage(int s) {
        wg_commit();
        wg_wait<1>();
        release(s == 0 ? 8 : s - 1);
    }
};

__host__ __device__ constexpr int a_off(int ks) { return ((ks / 12) * 49152 + ((ks >> 2) % 3) * 1024 + (ks & 3) * 32) >> 4; }

#define NKEEP 4
__host__ __device__ constexpr int keep_idx(int ks) { return NKEEP > 0 && (ks % (36 / (NKEEP > 0 ? NKEEP : 1))) == 36 / (NKEEP > 0 ? NKEEP : 1) - 1 ? ks / (36 / (NKEEP > 0 ? NKEEP : 1)) : -1; }
template <int V> struct IC { static constexpr int value = V; };
template <int I, int N, class F> __device__ __forceinline__ void static_for(F&& f) {
    if constexpr (I < N) { f(IC<I>{}); static_for<I + 1, N>(f); }
}

template <bool A_RS, bool B_RS, class Epi>
__device__ __forceinline__ void tile_pair(K1Ctx& c, float (&accA)[32], float (&accB)[32], uint32_t (&h)[144], Epi&& epi) {
    static_for<0, 9>([&](auto sc) {
        constexpr int s = decltype(sc)::value;
        c.begin_stage(s);
        static_for<0, 8>([&](auto tc) {
            constexpr int t = decltype(tc)::value, kk = s * 8 + t, ks = kk % 36;
            constexpr int db = ks == 35 ? -35 * 128 : 128, da = a_off((ks + 1) % 36) - a_off(ks);
            constexpr int ki = keep_idx(ks);
            constexpr bool rs = kk < 36 ? A_RS : B_RS;
            float (&acc)[32] = kk < 36 ? accA : accB;
            if constexpr (rs) {
                wgmma_rs_n64_pi<1, db>(acc, h[ks * 4], h[ks * 4 + 1], h[ks * 4 + 2], h[ks * 4 + 3], c.descB, ks != 0);
            } else if constexpr (ki >= 0 && !B_RS) {
                wgmma_rs_n64_pi<1, db>(acc, c.ak[ki][0], c.ak[ki][1], c.ak[ki][2], c.ak[ki][3], c.descB, ks != 0);
                c.descA += da;
            } else {
                wgmma_ss_n64_pi<1, da, db>(acc, c.descA, c.descB, ks != 0);
            }
            if constexpr (t == 0) {
                c.end_stage(s);
                epi(sc);
                wg_fence();
            }
        });
        wg_commit();
    });
    c.phase ^= 1;
}

template <int B0, int NB, int HOFF>
__device__ __forceinline__ void gelu_blocks(const float (&acc)[32], uint32_t (&h)[144], const uint32_t (&bq)[8], float rs0, float rs1) {
#pragma unroll
    for (int b = B0; b < B0 + NB; b++) {
        const float b0 = bf_lo(bq[b]), b1 = bf_hi(bq[b]);
        h[HOFF + b * 2 + 0] = pack_bf16(gelu2(fmaf(acc[b * 4 + 0], rs0, b0)), gelu2(fmaf(acc[b * 4 + 1], rs0, b1)));
        h[HOFF + b * 2 + 1] = pack_bf16(gelu2(fmaf(acc[b * 4 + 2], rs1, b0)), gelu2(fmaf(acc[b * 4 + 3], rs1, b1)));
    }
#pragma unroll
    for (int i = HOFF + B0 * 2; i < HOFF + (B0 + NB) * 2; i++) asm volatile("" : "+r"(h[i]));
}
__device__ __forceinline__ void load_bias(uint32_t (&bq)[8], uint32_t addr) {
    asm volatile("ld.shared.v4.u32 {%0, %1, %2, %3}, [%4];" : "=r"(bq[0]), "=r"(bq[1]), "=r"(bq[2]), "=r"(bq[3]) : "r"(addr));
    asm volatile("ld.shared.v4.u32 {%0, %1, %2, %3}, [%4 + 16];" : "=r"(bq[4]), "=r"(bq[5]), "=r"(bq[6]), "=r"(bq[7]) : "r"(addr));
}
__device__ __forceinline__ void st_pred2(bool p, void* a, uint32_t x, uint32_t y) {
    asm volatile("{\n.reg .pred p;\nsetp.ne.u32 p, %3, 0;\n@p st.global.v2.u32 [%0], {%1, %2};\n}\n" ::"l"(a), "r"(x), "r"(y), "r"((uint32_t)p) : "memory");
}
__device__ __forceinline__ void st_pred1(bool p, void* a, uint32_t x) {
    asm volatile("{\n.reg .pred p;\nsetp.ne.u32 p, %2, 0;\n@p st.global.u32 [%0], %1;\n}\n" ::"l"(a), "r"(x), "r"((uint32_t)p) : "memory");
}
template <int S> __device__ __forceinline__ void store_part(const float (&o)[32], uint4* p) {
    uint4 v;
    v.x = pack_bf16(o[S * 8 + 0], o[S * 8 + 1]); v.y = pack_bf16(o[S * 8 + 2], o[S * 8 + 3]);
    v.z = pack_bf16(o[S * 8 + 4], o[S * 8 + 5]); v.w = pack_bf16(o[S * 8 + 6], o[S * 8 + 7]);
    p[S * 256] = v;
}

constexpr int NCHUNK = 16;
constexpr int CHUNK_BYTES = KV_HEAD_BYTES / NCHUNK;
constexpr int SM_Q = 0;
constexpr int SM_KV = 32768;
constexpr int PIECE = 19968;
__host__ __device__ constexpr int sm_piece(int p) { return p == 0 ? 209408 : (p == 1 ? 0 : SM_KV + (p - 2) * PIECE); }
__host__ __device__ constexpr int sm_wstep(int k) { return k < 27 ? sm_piece(k / 3) + (k % 3) * 4608 : (k < 35 ? SM_KV + 7 * PIECE + (k - 27) * 4608 : PIECE); }
__host__ __device__ constexpr int sm_ostep(int k) { return sm_piece(k / 3) + 13824 + (k % 3) * 2048; }
constexpr int SM_RED = SM_KV + KV_HEAD_BYTES;

__device__ __forceinline__ float exp2_fixed(float y) {
    const float u = __uint_as_float(__float_as_uint(y) & 0xFF807FFFu) - 512.02545f;
    float t = fmaf(u, 0.019497588f, 0.114550486f);
    t = fmaf(t, u, -0.29839927f);
    return fmaf(t, u, y);
}
__device__ __forceinline__ uint32_t pack_fixed(float lo, float hi) { return __byte_perm(__float_as_uint(lo), __float_as_uint(hi), 0x6521); }

#define PV_GROUP 4
#define POLY_MODE 1
__device__ __forceinline__ uint32_t exp2_packed(float y0, float y1, uint32_t one2) {
    const uint32_t w = pack_fixed(y0, y1);
    uint32_t m;
    asm("lop3.b32 %0, %1, 0x007F007F, %2, 0xEA;" : "=r"(m) : "r"(w), "r"(one2));
    const uint32_t d = hfma2_bf16(m, 0x3EF93EF9u, 0xBF38BF38u);
    const uint32_t e = hfma2_bf16(d, d, 0xBD71BD71u);
    return hfma2_bf16(w, e, w);
}
constexpr int KV_TILE = CHUNK_BYTES / 16;
template <int OFF> __device__ __forceinline__ void issue_qk(float (&s)[64], uint64_t qd, uint64_t kd) {
    wgmma_ss_n128<0, 0, OFF + (8 << 16)>(s, qd, kd, 0);
    wgmma_ss_n128<0, 16, OFF + 32>(s, qd, kd, 1);
}
template <int OFF> __device__ __forceinline__ void issue_pv(float (&o)[12], const uint32_t (&p)[32], uint64_t vd) {
    static_for<0, 8>([&](auto kc) {
        constexpr int k = decltype(kc)::value;
        wgmma_rs_n24<1, OFF + k * (2 * KV_GROUP_BYTES / 16)>(o, p[k * 4], p[k * 4 + 1], p[k * 4 + 2], p[k * 4 + 3], vd, 1);
    });
}
template <int OFF>
__device__ __forceinline__ void softmax_pv(const float (&s)[64], uint32_t (&p)[32], float (&o)[12], uint64_t vd, uint32_t one2) {
    static_for<0, 8 / PV_GROUP>([&](auto gc) {
        constexpr int g0 = decltype(gc)::value * PV_GROUP;
#pragma unroll
        for (int b = g0 * 2; b < (g0 + PV_GROUP) * 2; b++) {
            if ((POLY_MASK >> b) & 1) {
                p[b * 2 + 0] = exp2_packed(s[b * 4 + 0], s[b * 4 + 1], one2);
                p[b * 2 + 1] = exp2_packed(s[b * 4 + 2], s[b * 4 + 3], one2);
            } else {
                p[b * 2 + 0] = pack_bf16(ex2(s[b * 4 + 0]), ex2(s[b * 4 + 1]));
                p[b * 2 + 1] = pack_bf16(ex2(s[b * 4 + 2]), ex2(s[b * 4 + 3]));
            }
        }
#pragma unroll
        for (int i = g0 * 4; i < (g0 + PV_GROUP) * 4; i++) asm volatile("" : "+r"(p[i])::"memory");
        wg_fence();
        static_for<g0, g0 + PV_GROUP>([&](auto kc) {
            constexpr int k = decltype(kc)::value;
            wgmma_rs_n24<1, OFF + k * (2 * KV_GROUP_BYTES / 16)>(o, p[k * 4], p[k * 4 + 1], p[k * 4 + 2], p[k * 4 + 3], vd, 1);
        });
    });
    wg_commit();
}
__device__ __forceinline__ int head_pair(int hh, int i) {
    if (i == 8) return hh == 3 ? 0 : 8;
    const int q = i >> 1, t = (4 - hh) & 3;
    if ((i & 1) == 0) return t + q;
    return (hh == 1 || hh == 2) ? (q >= hh ? q - hh : t + 4 + q) : t + 4 + q;
}
template <bool LATE> __device__ __forceinline__ void store_o(float (&o)[12], int rt, int head, int wq, int lane) {
    const int g = lane >> 2, q = lane & 3;
    const float i0 = __fdividef(1.0f, __shfl_sync(~0u, o[8], lane | 3)), i1 = __fdividef(1.0f, __shfl_sync(~0u, o[10], lane | 3));
#pragma unroll
    for (int i = 0; i < 3; i++) {
        const uint32_t w0 = pack_bf16(o[i * 4] * i0, o[i * 4 + 1] * i0), w1 = pack_bf16(o[i * 4 + 2] * i1, o[i * 4 + 3] * i1);
        if (i < 2 || q == 2) {
            if constexpr (LATE) {
                const int pc = (head & 7) * 9 + head_pair(head & 3, i < 2 ? i * 4 + q : 8);
                uint32_t* op = reinterpret_cast<uint32_t*>(g_Olate) + (((rt * 9 + (pc >> 3)) * 128 + wq * 32 + g * 4 + (pc & 3)) * 4 + ((pc >> 2) & 1) * 2);
                asm volatile("st.relaxed.gpu.global.v2.u32 [%0], {%1, %2};" ::"l"(op), "r"(w0), "r"(w1) : "memory");
            } else {
                const int pc = head * 9 + head_pair(head & 3, i < 2 ? i * 4 + q : 8);
                uint32_t* op = g_O + ((rt * 72 + (pc >> 2)) * 8 + wq * 2) * 32 + g * 4 + (pc & 3);
                op[0] = w0;
                op[32] = w1;
            }
        }
    }
#pragma unroll
    for (int i = 0; i < 12; i++) o[i] = 0.f;
}
__device__ __forceinline__ void mbar_arrive(uint32_t b) { asm volatile("mbarrier.arrive.shared::cta.b64 _, [%0];" ::"r"(b) : "memory"); }
__device__ __forceinline__ void mbar_wait_sleep(uint32_t b, uint32_t ns) {
    uint32_t ok, spins = 0;
    while (true) {
        asm volatile("{\n.reg .pred p;\nmbarrier.try_wait.parity.shared::cta.b64 p, [%1], 0;\nselp.u32 %0, 1, 0, p;\n}\n" : "=r"(ok) : "r"(b) : "memory");
        if (ok) break;
        __nanosleep(ns);
        if (++spins > (1u << 21)) __trap();
    }
}
__device__ __forceinline__ void flag_signal(unsigned int* f) {
    __threadfence();
    atomicAdd(f, 1u);
}
__device__ __forceinline__ void flag_wait(const unsigned int* f, unsigned int target, unsigned int sleep_ns) {
    uint32_t v, spins = 0;
    while (true) {
        asm volatile("ld.acquire.gpu.global.u32 %0, [%1];" : "=r"(v) : "l"(f) : "memory");
        if (v >= target) break;
        if (sleep_ns) __nanosleep(sleep_ns);
        if (++spins > (1u << 21)) __trap();
    }
}
__device__ __forceinline__ uint4 hadd8_bf16(const uint4 a, const uint4 b) {
    return make_uint4(hadd2_bf16(a.x, b.x), hadd2_bf16(a.y, b.y), hadd2_bf16(a.z, b.z), hadd2_bf16(a.w, b.w));
}
__device__ __forceinline__ float sumsq2(uint32_t w) { return fmaf(bf_lo(w), bf_lo(w), bf_hi(w) * bf_hi(w)); }
__device__ __forceinline__ float sumsq8(const uint4 v) { return (sumsq2(v.x) + sumsq2(v.y)) + (sumsq2(v.z) + sumsq2(v.w)); }

enum { B_FULL = 0, B_EMPTY = 9, B_BASE = 18, B_XNDEAD = 19, B_QRDY = 20, B_FFN = 21, B_KV = 22, B_FREE = 38, B_WO = 46, B_RED = 55, B_X = 61, B_EARLY = 85, B_OS = 86, B_LATE = 94, B_BIAS = 95, B_END = 96 };

__global__ void __cluster_dims__(2, 1, 1) __launch_bounds__(384, 1)
fused_kernel(const __grid_constant__ CUtensorMap tmX, const __grid_constant__ CUtensorMap tmQ3, const __grid_constant__ CUtensorMap tmQ1,
          const __grid_constant__ CUtensorMap tm1, const __grid_constant__ CUtensorMap tm2, const __grid_constant__ CUtensorMap tmP,
          const __grid_constant__ CUtensorMap tmOut, const __grid_constant__ CUtensorMap tmXo, const __nv_bfloat16* __restrict__ b1,
          const __nv_bfloat16* __restrict__ wqkv, const __nv_bfloat16* __restrict__ w1, const __nv_bfloat16* __restrict__ w2,
          const __nv_bfloat16* __restrict__ wo, const __nv_bfloat16* __restrict__ b2,
          const uint64_t zero) {
    extern __shared__ __align__(1024) uint8_t smem[];
    const uint32_t sb = s2u(smem);
    const int tid = threadIdx.x, lane = tid & 31;
    const int warp = __shfl_sync(~0u, tid >> 5, 0);
    const uint32_t rank = blockIdx.x & 1;
    const int cl = blockIdx.x >> 1;
    const int rb = (cl & 7) * 2 + rank;
    const int j = cl >> 3;
    const uint32_t bar0 = sb + K1_OFF_BAR;
    const uint32_t full0 = bar0 + B_FULL * 8, empty0 = bar0 + B_EMPTY * 8, xbar0 = bar0 + B_X * 8;
    const int head = blockIdx.x >> 2, quarter = blockIdx.x & 3;
    const int rt = quarter * 8 + (head >> 2), ct = head & 3;
    const int rot = head >> 3;
    const int ks0 = ((((head >> 3) + 2) & 3) * 9);
    volatile uint32_t* slow_flag = reinterpret_cast<volatile uint32_t*>(smem + K1_OFF_BAR + B_END * 8);

    if (__builtin_expect(warp < 8, 1)) {
        PROF(0);
        PROFT(48);
        if (lane == 0) {
#pragma unroll
            for (int i = 0; i < 3; i++) mbar_init(xbar0 + (warp * 3 + i) * 8, 1);
            fence_barrier_init();
#pragma unroll 1
            for (int i = 0; i < 3; i++) {
                const uint32_t xb = xbar0 + (warp * 3 + i) * 8;
                mbar_expect(xb, 6144);
                tma4d(sb + i * 49152 + warp * 6144, &tmX, 0, 0, i * 3, rb * 16 + warp * 2, xb);
            }
        }
        __syncwarp();
        cluster_arrive();
        PROF(22);
        reg_alloc<240>();
        PROF(23);
        float rs0, rs1;
        K1Ctx c;
        {
            const uint32_t la = sb + (warp * 2 + ((lane >> 3) & 1)) * 3072 + (lane & 7) * 128;
            uint32_t off[4];
#pragma unroll
            for (int i = 0; i < 4; i++) off[i] = la + (((i * 2 + (lane >> 4)) ^ (lane & 7)) << 4);
            float c1[4] = {0.f, 0.f, 0.f, 0.f}, c2[4] = {0.f, 0.f, 0.f, 0.f}, c3[4] = {0.f, 0.f, 0.f, 0.f};
            uint32_t a[36][4];
#pragma unroll
            for (int t = 0; t < 3; t++) {
                mbar_wait(xbar0 + (warp * 3 + t) * 8, 0);
                PROF(24 + t);
#pragma unroll
                for (int i = 0; i < 12; i++) ldsm4(a[t * 12 + i], off[i & 3] + t * 49152 + (i >> 2) * 1024);
#pragma unroll
                for (int i = t * 12; i < t * 12 + 12; i++) {
                    mma16816(c3, a[i], 0x3F803F80u, 0x3F803F80u);
                    mma16816(c1, a[i], a[i][0], a[i][2]);
                    mma16816(c2, a[i], a[i][1], a[i][3]);
                }
            }
            PROF(27);
            const int gg = lane >> 2, src = (lane & ~3) | (gg >> 1);
            const float m0 = c3[0] * (1.0f / DM), m1 = c3[2] * (1.0f / DM);
            const uint32_t mc0 = pack_bf16(-m0, -m0), mc1 = pack_bf16(-m1, -m1);
#pragma unroll
            for (int i = 0; i < 36; i++) {
#pragma unroll
                for (int k = 0; k < 4; k++) a[i][k] = hadd2_bf16(a[i][k], (k & 1) ? mc1 : mc0);
                stsm4(off[i & 3] + (i / 12) * 49152 + ((i >> 2) % 3) * 1024, a[i]);
                if (keep_idx(i) >= 0) {
#pragma unroll
                    for (int k = 0; k < 4; k++) c.ak[keep_idx(i) >= 0 ? keep_idx(i) : 0][k] = a[i][k];
                }
            }
            const float q0 = __shfl_sync(~0u, (gg & 1) ? c1[1] : c1[0], src), q1 = __shfl_sync(~0u, (gg & 1) ? c2[3] : c2[2], src);
            rs0 = rsqrtf(fmaxf(fmaf(-m0, m0, q0 * (1.0f / DM)), 0.f) + 1e-5f);
            rs1 = rsqrtf(fmaxf(fmaf(-m1, m1, q1 * (1.0f / DM)), 0.f) + 1e-5f);
            if (__any_sync(~0u, fabsf(m0) * rs0 > 0.25f || fabsf(m1) * rs1 > 0.25f)) {
                const float d0 = -m0 - bf_lo(mc0), d1 = -m1 - bf_lo(mc1);
                const uint32_t md0 = pack_bf16(d0, d0), md1 = pack_bf16(d1, d1);
#pragma unroll 1
                for (int i = 0; i < 9; i++) {
#pragma unroll
                    for (int k4 = 0; k4 < 4; k4++) {
                        const uint32_t ad = off[k4] + (i / 3) * 49152 + (i % 3) * 1024;
                        uint32_t b[4];
                        ldsm4(b, ad);
#pragma unroll
                        for (int k = 0; k < 4; k++) b[k] = hadd2_bf16(b[k], (k & 1) ? md1 : md0);
                        stsm4(ad, b);
                    }
                }
#pragma unroll
                for (int i = 0; i < NKEEP; i++)
#pragma unroll
                    for (int k = 0; k < 4; k++) c.ak[i][k] = hadd2_bf16(c.ak[i][k], (k & 1) ? md1 : md0);
            }
        }
        PROF(28);
        const int wg = warp >> 2, wq = warp & 3;
        fence_proxy_async();
        named_bar_sync(1 + wg, 128);
        cluster_wait();
        PROF(1); PROFT(59);

        const int g = lane >> 2, q = lane & 3;
        c.full0 = full0;
        c.rel_addr = 0;
        c.descA = mk_desc(zero, sb + wg * 8 * 3072, 16, 3072, 1);
        c.descB = mk_desc(zero, sb + K1_OFF_RING, 2048, 1024, 1);
        c.phase = 0;
        uint32_t biasq = sb + K1_OFF_BIAS + q * 32;
        uint32_t bq[8];

        uint32_t h[144];
        float accA[32], accB[32];
        uint32_t qo[3], qt[3];
        {
            float accQ[108];
            uint32_t rel = 0;
            if (lane == 0 && wq < 2) asm("mapa.shared::cluster.u32 %0, %1, %2;" : "=r"(rel) : "r"(empty0), "r"(wq));
#pragma unroll 1
            for (int r = 0; r < 2; r++) {
                static_for<0, 9>([&](auto sc) {
                    constexpr int s = decltype(sc)::value;
                    c.begin_stage(s);
                    const uint64_t da = c.descA + (r ? a_off(18 + 2 * s) : a_off(2 * s));
                    wgmma_ss_n216<1, 0, ((2 * s) % 9) * 512>(accQ, da, c.descB, (r | s) != 0);
                    wgmma_ss_n216<1, 2, ((2 * s + 1) % 9) * 512>(accQ, da, c.descB, 1);
                    c.end_stage(s);
                    c.rel_addr = rel;
                });
                c.phase ^= 1;
            }
            PROF(2); PROFWT(54);
            mbar_wait(bar0 + B_BIAS * 8, 0);
            wg_wait<0>();
            reg_fence(accQ);
#pragma unroll
            for (int grp = 0; grp < 3; grp++) {
                const int G = 3 * j + grp, type = G >> 3;
                const uint32_t base = (G & 7) * 4 * KV_HEAD_BYTES + (rb * 16 + warp * 2) * KV_GROUP_BYTES + g * 16 + (type == 0 ? Q_OFFSET : (type == 2 ? 256 : 0));
                qo[grp] = base + (q >> 1) * 128 + (q & 1) * 8;
                qt[grp] = base + q * KV_HEAD_BYTES + (type == 0 ? 256 : (type == 2 ? 264 : 512));
#pragma unroll
                for (int hf = 0; hf < 2; hf++) {
                    const float sc = (hf ? rs1 : rs0) * (type == 0 ? QSCALE : ((type == 1 && ((POLY_MASK >> (warp * 2 + hf)) & 1)) ? 2.f : 1.f));
                    uint32_t w[9];
#pragma unroll
                    for (int i = 0; i < 9; i++) w[i] = pack_bf16(accQ[(grp * 9 + i) * 4 + hf * 2] * sc, accQ[(grp * 9 + i) * 4 + hf * 2 + 1] * sc);
                    uint32_t* d = h + 32 + hf * 32 + grp * 8;
                    d[0] = w[0]; d[1] = w[1]; d[2] = w[3]; d[3] = q >= 1 ? w[2] : w[4];
                    d[4] = w[5]; d[5] = q >= 2 ? w[4] : w[6]; d[6] = w[7]; d[7] = w[8];
                    h[32 + hf * 32 + 24 + grp] = q == 0 ? w[2] : (q == 1 ? w[4] : w[6]);
                }
            }
        }
        PROF(3); PROFWT(55); PROFT(60);
#pragma unroll
        for (int i = 32; i < 112; i++)
            if (i >= 96 || (i & 31) >= 27) asm volatile("mov.u32 %0, 0;" : "=r"(h[i]));
#pragma unroll
        for (int i = 0; i < 32; i++) asm volatile("mov.f32 %0, 0f00000000;" : "=f"(accB[i]));
#pragma unroll
        for (int i = 0; i < 8; i++) bq[i] = 0;
#pragma unroll 1
        for (int p = 0; p < 4; p++) {
            uint8_t* const qb = g_QKV + p * KV_GROUP_BYTES;
            tile_pair<false, false>(c, accA, accB, h, [&](auto sc) {
                constexpr int s = decltype(sc)::value;
                if constexpr (s == 0) {
                    reg_fence(accB);
#pragma unroll
                    for (int i = 0; i < 80; i++) h[i] = h[i + 32];
                }
                if constexpr (s >= 1 && s <= 6) {
                    constexpr int grp = (s - 1) >> 1, k = ((s - 1) & 1) * 2;
                    st_pred2(p < 2, qb + qo[grp] + k * KV_HEAD_BYTES, h[grp * 8 + k * 2], h[grp * 8 + k * 2 + 1]);
                    st_pred2(p < 2, qb + qo[grp] + (k + 1) * KV_HEAD_BYTES, h[grp * 8 + k * 2 + 2], h[grp * 8 + k * 2 + 3]);
                    if constexpr (k == 2) st_pred1(p < 2, qb + qt[grp], h[24 + grp]);
                }
                if constexpr (s < 4) gelu_blocks<s * 2, 2, 80>(accB, h, bq, rs0, rs1);
                if constexpr (s == 4) load_bias(bq, biasq);
                if constexpr (s == 5) reg_fence(accA);
                if constexpr (s >= 5) gelu_blocks<(s - 5) * 2, 2, 96>(accA, h, bq, rs0, rs1);
                if constexpr (s == 8) load_bias(bq, biasq + 128);
            });
            if (p == 1) asm volatile("bar.arrive 3, 352;" ::: "memory");
            biasq += 256;
        }
        PROF(4); PROFWT(56); PROFT(61);
        tile_pair<false, true>(c, accA, accB, h, [&](auto sc) {
            constexpr int s = decltype(sc)::value;
            if constexpr (s == 0) reg_fence(accB);
            if constexpr (s < 4) gelu_blocks<s * 2, 2, 112>(accB, h, bq, rs0, rs1);
            if constexpr (s == 4) load_bias(bq, biasq);
            if constexpr (s == 5) { reg_fence(accA); if (tid == wg * 128) mbar_arrive(bar0 + B_XNDEAD * 8); }
            if constexpr (s == 5 || s == 6) gelu_blocks<(s - 5) * 3, 3, 128>(accA, h, bq, rs0, rs1);
            if constexpr (s == 7) gelu_blocks<6, 2, 128>(accA, h, bq, rs0, rs1);
            if constexpr (s == 3 || s == 7) reg_fence(h);
        });
        PROF(5); PROFWT(57); PROFT(62);
        uint4* pout = g_part + j * SLAB + rb * 36 * 256 + tid;
#pragma unroll 1
        for (int p = 0; p < 4; p++) {
            tile_pair<true, true>(c, accA, accB, h, [&](auto sc) {
                constexpr int s = decltype(sc)::value;
                if constexpr (s == 0) reg_fence(accB);
                if constexpr (s < 4) store_part<s>(accB, pout);
                if constexpr (s == 5) reg_fence(accA);
                if constexpr (s >= 5) store_part<s - 5>(accA, pout + 1024);
            });
            pout += 2048;
            PROF(6 + p);
        }
        wg_wait<0>();
        c.release(8);
        reg_fence(accB);
        store_part<0>(accB, pout); store_part<1>(accB, pout); store_part<2>(accB, pout); store_part<3>(accB, pout);
        __syncwarp();
        if (lane == 0) mbar_arrive(bar0 + B_FFN * 8);
        PROF(10); PROFWT(58);
        PROFT(49);

        mbar_wait(bar0 + B_QRDY * 8, 0);
        const uint32_t slow = __any_sync(~0u, *slow_flag != 0);
        const uint64_t kd0 = mk_desc(zero, sb + SM_KV, 0, KV_GROUP_BYTES, 0);
        const uint64_t vd0 = mk_desc(zero, sb + SM_KV + 256, KV_GROUP_BYTES, 128, 0);
        const uint64_t qd0 = mk_desc(zero, sb + SM_Q + wg * 4096, 128, 512, 0);
        const uint32_t kvbar = bar0 + B_KV * 8;
        float o[12];
#pragma unroll
        for (int i = 0; i < 12; i++) o[i] = 0.f;
        PROF(16);
        PROFT(50);
        if (__builtin_expect(!slow, 1)) {
            const uint32_t one2 = 0x3F803F80u + (uint32_t)zero;
            float s0[64], s1[64];
            uint32_t p0[32], p1[32];
            mbar_wait(kvbar, 0);
            reg_fence(o);
            wg_fence();
            issue_qk<0>(s0, qd0, kd0);
            wg_commit();
            wg_commit();
            uint64_t qd = qd0;
            const uint32_t fre = (tid == wg * 128) ? bar0 + B_FREE * 8 - 8 : 0;
#pragma unroll 1
            for (int pass = 0; pass < 4; pass++) {
                uint64_t vd = vd0, kd = kd0;
                uint32_t bn = kvbar + 8;
#pragma unroll 1
                for (int it = 0; it < 8; it++) {
                    if (pass == 0) {
                        mbar_wait(bn, 0);
                        mbar_wait(it == 7 ? bn : bn + 8, 0);
                    }
                    if (it == 0 && pass != 0) {
                        wg_wait<0>();
                        reg_fence(o);
                        store_o<false>(o, quarter * 8 + ((pass - 1 + rot) & 3) * 2 + wg, head, wq, lane);
                        reg_fence(o);
                        __syncwarp();
                        if (lane == 0) mbar_arrive(bar0 + (B_OS + pass * 2 - 2 + wg) * 8);
                    }
                    wg_wait<1>();
                    reg_fence(s0);
                    wg_fence();
                    issue_qk<KV_TILE>(s1, qd, kd);
                    wg_commit();
                    if (pass == 3 && it > 0 && fre) mbar_arrive(fre + it * 8);
                    softmax_pv<0>(s0, p0, o, vd, one2);
                    kd += 2 * KV_TILE;
                    if (it == 7) { kd = kd0; qd += 512; }
                    wg_wait<1>();
                    reg_fence(s1);
                    wg_fence();
                    issue_qk<0>(s0, qd, kd);
                    wg_commit();
                    softmax_pv<KV_TILE>(s1, p1, o, vd, one2);
                    vd += 2 * KV_TILE; bn += 16;
                }
                if (pass == 0) PROF(17);
            }
            wg_wait<0>();
            reg_fence(o);
            reg_fence(s0);
            reg_fence(s1);
            store_o<true>(o, quarter * 8 + ((3 + rot) & 3) * 2 + wg, head, wq, lane);
        } else {
#pragma unroll 1
            for (int pass = 0; pass < 4; pass++) {
                float m0 = -INFINITY, m1 = -INFINITY;
                float s[64];
                uint32_t p[32];
#pragma unroll 1
                for (int t = 0; t < 16; t++) {
                    mbar_wait(kvbar + t * 8, 0);
                    wg_fence();
                    issue_qk<0>(s, qd0 + pass * 512, kd0 + t * KV_TILE);
                    wg_commit();
                    wg_wait<0>();
                    reg_fence(s);
                    float a0 = m0, a1 = m1;
#pragma unroll
                    for (int k = 0; k < 16; k++) {
                        if ((POLY_MASK >> k) & 1) {
#pragma unroll
                            for (int i = 0; i < 4; i++) s[k * 4 + i] *= 0.5f;
                        }
                        a0 = fmaxf(a0, fmaxf(s[k * 4 + 0], s[k * 4 + 1]));
                        a1 = fmaxf(a1, fmaxf(s[k * 4 + 2], s[k * 4 + 3]));
                    }
                    a0 = fmaxf(a0, __shfl_xor_sync(~0u, a0, 1)); a1 = fmaxf(a1, __shfl_xor_sync(~0u, a1, 1));
                    a0 = fmaxf(a0, __shfl_xor_sync(~0u, a0, 2)); a1 = fmaxf(a1, __shfl_xor_sync(~0u, a1, 2));
                    const float r0 = ex2(m0 - a0), r1 = ex2(m1 - a1);
                    m0 = a0; m1 = a1;
#pragma unroll
                    for (int i = 0; i < 3; i++) { o[i * 4] *= r0; o[i * 4 + 1] *= r0; o[i * 4 + 2] *= r1; o[i * 4 + 3] *= r1; }
#pragma unroll
                    for (int k = 0; k < 16; k++) {
                        p[k * 2 + 0] = pack_bf16(ex2(s[k * 4 + 0] - m0), ex2(s[k * 4 + 1] - m0));
                        p[k * 2 + 1] = pack_bf16(ex2(s[k * 4 + 2] - m1), ex2(s[k * 4 + 3] - m1));
                    }
                    reg_fence(p);
                    reg_fence(o);
                    wg_fence();
                    issue_pv<0>(o, p, vd0 + t * KV_TILE);
                    wg_commit();
                    wg_wait<0>();
                    reg_fence(o);
                }
                if (pass < 3) {
                    store_o<false>(o, quarter * 8 + ((pass + rot) & 3) * 2 + wg, head, wq, lane);
                    __syncwarp();
                    if (lane == 0) mbar_arrive(bar0 + (B_OS + pass * 2 + wg) * 8);
                }
            }
            store_o<true>(o, quarter * 8 + ((3 + rot) & 3) * 2 + wg, head, wq, lane);
            if (tid == wg * 128)
                for (int i = 0; i < 7; i++) mbar_arrive(bar0 + (B_FREE + i) * 8);
        }
        PROF(18);
        PROFT(51);

        if (tid == wg * 128) mbar_arrive(bar0 + (B_FREE + 7) * 8);
        const int t128 = tid & 127;
        uint32_t bv[9];
        uint2 fv[9];
        mbar_wait(bar0 + B_BASE * 8, 0);
#pragma unroll
        for (int i = 0; i < 9; i++) {
            bv[i] = __ldg(reinterpret_cast<const uint32_t*>(b2 + ct * 144 + wg * 72 + q * 2) + i * 4);
            fv[i] = __ldcg(g_ffn + (blockIdx.x * 18 + wg * 9 + i) * 128 + t128);
        }
        float acc[36];
        const uint64_t od = mk_desc(zero, sb, 1024, 128, 0), wd = mk_desc(zero, sb + wg * 9 * 128, 2304, 128, 0);
        static_for<0, 9>([&](auto pc) {
            constexpr int p = decltype(pc)::value;
            mbar_wait(bar0 + (B_WO + p) * 8, 0);
            wg_fence();
            wgmma_ss_n72<1, sm_ostep(p * 3) / 16, sm_wstep(p * 3) / 16>(acc, od, wd, p != 0);
            wgmma_ss_n72<1, sm_ostep(p * 3 + 1) / 16, sm_wstep(p * 3 + 1) / 16>(acc, od, wd, 1);
            wgmma_ss_n72<1, sm_ostep(p * 3 + 2) / 16, sm_wstep(p * 3 + 2) / 16>(acc, od, wd, 1);
            wg_commit();
            if constexpr (p == 1) {
                wg_wait<1>();
                if (t128 == 0) mbar_arrive(bar0 + B_EARLY * 8);
            }
        });
        wg_wait<0>();
        reg_fence(acc);
        PROF(29);
        uint4 al[9];
        {
            const uint4* ap = g_Olate + rt * 9 * 128 + t128;
            uint32_t spins = 0;
            bool ok;
            do {
                ok = true;
#pragma unroll
                for (int k = 0; k < 9; k++)
                    asm volatile("ld.relaxed.gpu.global.v4.u32 {%0, %1, %2, %3}, [%4];" : "=r"(al[k].x), "=r"(al[k].y), "=r"(al[k].z), "=r"(al[k].w) : "l"(ap + k * 128) : "memory");
#pragma unroll
                for (int k = 0; k < 9; k++) ok = ok && al[k].x != O_EMPTY && al[k].y != O_EMPTY && al[k].z != O_EMPTY && al[k].w != O_EMPTY;
                if (++spins > (1u << 20)) __trap();
            } while (!__all_sync(~0u, ok));
        }
        PROF(19);
        mbar_wait(bar0 + B_LATE * 8, 0);
        PROF(20);
        wg_fence();
        static_for<27, 36>([&](auto kc) {
            constexpr int k = decltype(kc)::value;
            wgmma_rs_n72<1, sm_wstep(k) / 16>(acc, al[k - 27].x, al[k - 27].y, al[k - 27].z, al[k - 27].w, wd, 1);
        });
        wg_commit();
        PROF(31);
        uint32_t* st = reinterpret_cast<uint32_t*>(smem + sm_piece(0) + wg * 9216) + (wq * 16 + g) * 36 + q;
        float bs[36];
#pragma unroll
        for (int i = 0; i < 9; i++) {
            const uint32_t x0 = st[i * 4], x1 = st[i * 4 + 288];
            bs[i * 4 + 0] = fmaf(bf_lo(fv[i].x), 0.5f, bf_lo(x0) + bf_lo(bv[i]));
            bs[i * 4 + 1] = fmaf(bf_hi(fv[i].x), 0.5f, bf_hi(x0) + bf_hi(bv[i]));
            bs[i * 4 + 2] = fmaf(bf_lo(fv[i].y), 0.5f, bf_lo(x1) + bf_lo(bv[i]));
            bs[i * 4 + 3] = fmaf(bf_hi(fv[i].y), 0.5f, bf_hi(x1) + bf_hi(bv[i]));
        }
        reg_fence(bs);
        wg_wait<0>();
        reg_fence(acc);
        PROF(32);
#pragma unroll
        for (int i = 0; i < 9; i++) {
            st[i * 4] = pack_bf16(acc[i * 4] + bs[i * 4], acc[i * 4 + 1] + bs[i * 4 + 1]);
            st[i * 4 + 288] = pack_bf16(acc[i * 4 + 2] + bs[i * 4 + 2], acc[i * 4 + 3] + bs[i * 4 + 3]);
        }
        fence_proxy_async();
        named_bar_sync(1 + wg, 128);
        if (t128 == 0) {
            asm volatile("cp.async.bulk.tensor.2d.global.shared::cta.bulk_group [%0, {%2, %3}], [%1];"
                         ::"l"(&tmOut), "r"(sb + sm_piece(0) + wg * 9216), "r"(ct * 144 + wg * 72), "r"(rt * 64) : "memory");
            asm volatile("cp.async.bulk.commit_group;" ::: "memory");
            asm volatile("cp.async.bulk.wait_group.read 0;" ::: "memory");
        }
        PROF(21);
        PROFT(52);
    } else {
        reg_dealloc<24>();
        if (warp == 8 && lane == 0) {
            prefetch_tmap(&tmQ3); prefetch_tmap(&tmQ1); prefetch_tmap(&tm1); prefetch_tmap(&tm2);
            #pragma unroll 1
            for (int i = 0; i < 9; i++) { mbar_init(full0 + i * 8, 1); mbar_init(empty0 + i * 8, 4); mbar_init(bar0 + (B_WO + i) * 8, 2); }
            mbar_init(bar0 + B_BASE * 8, 3); mbar_init(bar0 + B_XNDEAD * 8, 2); mbar_init(bar0 + B_QRDY * 8, 3); mbar_init(bar0 + B_FFN * 8, 8); mbar_init(bar0 + B_EARLY * 8, 2); mbar_init(bar0 + B_LATE * 8, 2); mbar_init(bar0 + B_BIAS * 8, 96);
#pragma unroll 1
            for (int i = 0; i < 16; i++) { mbar_init(bar0 + (B_KV + i) * 8, 1); mbar_init(bar0 + (B_FREE + (i & 7)) * 8, 2); if (i < 6) mbar_init(bar0 + (B_RED + i) * 8, 1); if (i < 6) mbar_init(bar0 + (B_OS + i) * 8, 4); }
            *slow_flag = 0;
            fence_barrier_init();
        }
        __syncwarp();
        cluster_arrive();
        cluster_wait();
        const uint8_t* kvsrc = g_QKV + (size_t)head * KV_HEAD_BYTES;
        if (warp == 8) {
            if (lane == 0) {
                int st = 0, u = rank, tile = -4;
                int es = 5;
                uint32_t eph = 1;
#pragma unroll 1
                for (int n = 0; n < 99; n++) {
                    mbar_wait(empty0 + es * 8, eph);
                    const uint32_t fb = full0 + st * 8, dst = sb + K1_OFF_RING + u * 8192;
                    mbar_expect(fb, 16384);
                    if (tile < 0) {
                        tma3d_mc(dst, &tmQ3, j * 216, n * 32 + rank * 16, 0, fb, 3);
                        tma2d_mc(dst + 6144, &tmQ1, j * 216 + 192, n * 32 + rank * 16, fb, 3);
                    } else if (tile < 9) {
                        tma2d_mc(dst, &tm1, j * 576 + tile * 64, u * 64, fb, 3);
                    } else {
                        tma2d_mc(dst, &tm2, (tile - 9) * 64, j * 576 + u * 64, fb, 3);
                    }
                    u += 2;
                    if (u >= 9) { u -= 9; tile++; }
                    if (++st == 9) st = 0;
                    if (++es == 9) { es = 0; eph ^= 1; }
                }
                mbar_wait(empty0 + 8 * 8, 0);
                mbar_wait(bar0 + B_QRDY * 8, 0);
                asm volatile("fence.proxy.async;" ::: "memory");
#pragma unroll 1
                for (int i = 11; i < NCHUNK; i++) {
                    mbar_expect(bar0 + (B_KV + i) * 8, CHUNK_BYTES);
                    bulk_load(sb + SM_KV + i * CHUNK_BYTES, kvsrc + i * CHUNK_BYTES, CHUNK_BYTES, bar0 + (B_KV + i) * 8);
                }
                const uint8_t* wsrc = g_Wo + ct * WO_TILE_BYTES;
                prefetch_tmap(&tmOut);
                mbar_wait_sleep(bar0 + B_BASE * 8, 500);
#pragma unroll 1
                for (int p = 0; p < 9; p++) {
                    if (p > 0) mbar_wait_sleep(bar0 + (B_FREE + p - 1) * 8, p == 1 ? 500 : 40);
                    const int k = ks0 + p * 3 >= 36 ? ks0 + p * 3 - 36 : ks0 + p * 3;
                    mbar_expect(bar0 + (B_WO + p) * 8, 13824);
                    bulk_load(sb + (p == 0 ? sm_piece(0) : (p == 1 ? sm_piece(1) : SM_KV + (p - 2) * PIECE)), wsrc + k * 4608, 13824, bar0 + (B_WO + p) * 8);
                }
                const int kl = ks0 == 0 ? 27 : ks0 - 9;
                mbar_expect(bar0 + B_LATE * 8, 9 * 4608);
                bulk_load(sb + sm_wstep(27), wsrc + kl * 4608, 8 * 4608, bar0 + B_LATE * 8);
                bulk_load(sb + sm_wstep(35), wsrc + (kl + 8) * 4608, 4608, bar0 + B_LATE * 8);
            }
        } else {
            const int ht = tid - 288;
            if (ht == 64) prefetch_l2(wqkv + blockIdx.x * (DM * 3 * DM / 128), DM * 3 * DM / 64);
            if (ht < 72) {
                const uint4 v = __ldg(reinterpret_cast<const uint4*>(b1 + j * 576) + ht);
                uint32_t* sbias = reinterpret_cast<uint32_t*>(smem + K1_OFF_BIAS) + (ht >> 3) * 32 + (ht & 7);
                sbias[0] = v.x; sbias[8] = v.y; sbias[16] = v.z; sbias[24] = v.w;
            }
            mbar_arrive(bar0 + B_BIAS * 8);
            PROFH(37);
#pragma unroll
            for (int i = 0; i < 3; i++) g_Olate[blockIdx.x * 288 + i * 96 + ht] = make_uint4(O_EMPTY, O_EMPTY, O_EMPTY, O_EMPTY);
#pragma unroll 1
            for (int i = ht; i < 512; i += 96) {
                const int key = i & 127;
                uint8_t* p = g_QKV + (size_t)(j * 4 + (i >> 7)) * KV_HEAD_BYTES + (rb * 16 + (key >> 3)) * KV_GROUP_BYTES + 512 + (key & 7) * 16;
                *reinterpret_cast<uint32_t*>(p + 4) = ((POLY_MASK >> (key >> 3)) & 1) ? 0x3F804000u : 0x00003F80u;
                *reinterpret_cast<uint32_t*>(p + 12) = 0x00003F80u;
            }
            if (ht == 32) prefetch_l2(w1 + blockIdx.x * (DM * FF / 128), DM * FF / 64);
#pragma unroll 2
            for (int i = blockIdx.x * 324 + ht; i < blockIdx.x * 324 + 324; i += 96) {
                const int k = i / 72, nc = i - k * 72, c4 = nc / 18;
                *reinterpret_cast<uint4*>(g_Wo + c4 * WO_TILE_BYTES + (k >> 3) * 2304 + (nc - c4 * 18) * 128 + (k & 7) * 16) =
                    __ldg(reinterpret_cast<const uint4*>(wo) + i);
            }
            PROFH(38);
            named_bar_sync(3, 352);
            if (ht == 32) prefetch_l2(w2 + blockIdx.x * (DM * FF / 128), DM * FF / 64);
            if (ht == 0) {
                flag_signal(&g_flags.qkv_stored[rb]);
                flag_wait(&g_flags.qkv_stored[rb], 8, 200);
            }
            named_bar_sync(7, 96);
            PROFH(39);
#pragma unroll 1
            for (int i = warp - 9; i < 16; i += 3) {
                const int hd = j * 4 + (i >> 2), key = (i & 3) * 32 + lane;
                const uint8_t* p = g_QKV + (size_t)hd * KV_HEAD_BYTES + (rb * 16 + (key >> 3)) * KV_GROUP_BYTES + (key & 7) * 16;
                const uint4 a = __ldcg(reinterpret_cast<const uint4*>(p)), b = __ldcg(reinterpret_cast<const uint4*>(p + 128));
                float n = sumsq2(__ldcg(reinterpret_cast<const uint32_t*>(p + 512))) + sumsq8(a) + sumsq8(b);
                if ((POLY_MASK >> (key >> 3)) & 1) n *= 0.25f;
#pragma unroll
                for (int o = 16; o; o >>= 1) n = fmaxf(n, __shfl_xor_sync(~0u, n, o));
                if (lane == 0) g_kmax[hd * 64 + rb * 4 + (i & 3)] = n;
            }
            named_bar_sync(7, 96);
            PROFH(40);
            if (ht == 0) {
                flag_signal(&g_flags.kv_ready);
                flag_wait(&g_flags.kv_ready, 128, 300);
                mbar_wait_sleep(bar0 + B_XNDEAD * 8, 300);
            }
            named_bar_sync(7, 96);
            PROFH(41);
            float kmax2;
            {
                const float2 v = __ldcg(reinterpret_cast<const float2*>(g_kmax + head * 64 + lane * 2));
                kmax2 = fmaxf(v.x, v.y);
#pragma unroll
                for (int o = 16; o; o >>= 1) kmax2 = fmaxf(kmax2, __shfl_xor_sync(~0u, kmax2, o));
            }
            asm volatile("fence.proxy.async;" ::: "memory");
            int chunk = warp - 9;
#pragma unroll 1
            for (int r = ht; r < 512; r += 96) {
                if (lane == 0 && chunk < 11) {
                    mbar_expect(bar0 + (B_KV + chunk) * 8, CHUNK_BYTES);
                    bulk_load(sb + SM_KV + chunk * CHUNK_BYTES, kvsrc + chunk * CHUNK_BYTES, CHUNK_BYTES, bar0 + (B_KV + chunk) * 8);
                }
                chunk += 3;
                const uint8_t* p = kvsrc + Q_OFFSET + (quarter * 64 + (((r >> 3) + rot * 16) & 63)) * KV_GROUP_BYTES + (r & 7) * 16;
                const uint4 a = __ldcg(reinterpret_cast<const uint4*>(p)), b = __ldcg(reinterpret_cast<const uint4*>(p + 128));
                const uint32_t e = __ldcg(reinterpret_cast<const uint32_t*>(p + 256));
                const float cc = sqrtf((sumsq2(e) + sumsq8(a) + sumsq8(b)) * kmax2) * 1.02f;
                if (!(cc <= 58.f)) *slow_flag = 1;
                uint4* dst = reinterpret_cast<uint4*>(smem + SM_Q + (r >> 3) * 512 + (r & 7) * 16);
                dst[0] = a;
                dst[8] = b;
                dst[16] = make_uint4(e, pack_bf16(-cc, 768.f), 0u, 0u);
                dst[24] = make_uint4(0u, POLY_MODE ? 0xBFFF0000u : 0xC0000000u, 0u, 0u);
            }
            named_bar_sync(7, 96);
            if (*slow_flag) {
#pragma unroll 1
                for (int r = ht; r < 512; r += 96) {
                    uint32_t* dst = reinterpret_cast<uint32_t*>(smem + SM_Q + (r >> 3) * 512 + (r & 7) * 16);
                    dst[65] = 0u;
                    dst[97] = 0u;
                }
            }
            fence_proxy_async();
            __syncwarp();
            if (lane == 0) mbar_arrive(bar0 + B_QRDY * 8);
            PROFH(42);
            if (ht == 0) {
                mbar_wait_sleep(bar0 + B_FFN * 8, 300);
                flag_signal(&g_flags.ffn_done[rb]);
                flag_wait(&g_flags.ffn_done[rt >> 1], 8, 300);
            }
            named_bar_sync(7, 96);
            {
                const int w3 = warp - 9;
                const uint32_t rbar = bar0 + (B_RED + w3 * 2) * 8, rbuf = SM_RED + w3 * 8192;
                const int u0 = ((rt >> 1) * 36 + ct * 9) * 256 + (rt & 1) * 128;
                mbar_wait_sleep(bar0 + (B_KV + 15) * 8, 500);
                asm volatile("fence.proxy.async;" ::: "memory");
#pragma unroll 1
                for (int i = -2; i < 12; i++) {
                    if (i >= 0) {
                        __nanosleep(400);
                        mbar_wait(rbar + (i & 1) * 8, (i >> 1) & 1);
                        const uint4* sp = reinterpret_cast<const uint4*>(smem + rbuf + (i & 1) * 4096) + lane;
                        const uint4 v = hadd8_bf16(hadd8_bf16(hadd8_bf16(sp[0], sp[32]), hadd8_bf16(sp[64], sp[96])),
                                                   hadd8_bf16(hadd8_bf16(sp[128], sp[160]), hadd8_bf16(sp[192], sp[224])));
                        const int bx = i * 3 + w3;
                        uint2* fp = g_ffn + (blockIdx.x * 18 + (bx >> 2) * 2) * 128 + (bx & 3) * 32 + lane;
                        fp[0] = make_uint2(v.x, v.y);
                        fp[128] = make_uint2(v.z, v.w);
                    }
                    __syncwarp();
                    if (lane == 0 && i < 10) {
                        const int bx = (i + 2) * 3 + w3;
                        mbar_expect(rbar + (i & 1) * 8, 4096);
                        tma2d(sb + rbuf + (i & 1) * 4096, &tmP, (u0 + (bx >> 2) * 256 + (bx & 3) * 32) * 2, 0, rbar + (i & 1) * 8);
                    }
                }
            }
            __syncwarp();
            if (lane == 0) mbar_arrive(bar0 + B_BASE * 8);
            PROFH(43);
            if (ht == 0) {
#pragma unroll 1
                for (int i = 0; i < 6; i++) {
                    mbar_wait_sleep(bar0 + (B_OS + i) * 8, 200);
                    flag_signal(&g_flags.o_done[quarter * 8 + (((i >> 1) + rot) & 3) * 2 + (i & 1)]);
                }
            } else if (ht == 32) {
                const uint8_t* osrc = reinterpret_cast<const uint8_t*>(g_O) + rt * 73728;
                mbar_wait_sleep(bar0 + B_BASE * 8, 500);
                mbar_wait_sleep(bar0 + B_FREE * 8, 500);
                flag_wait(&g_flags.o_done[rt], 24, 100);
                if (atomicAdd(&g_flags.exited, 1u) == gridDim.x - 1) {
                    unsigned int* f = reinterpret_cast<unsigned int*>(&g_flags);
#pragma unroll 1
                    for (int i = 0; i < (int)(sizeof(Flags) / 4); i++) f[i] = 0;
                }
                prefetch_tmap(&tmXo);
                asm volatile("fence.proxy.async;" ::: "memory");
#pragma unroll 1
                for (int p = 0; p < 9; p++) {
                    if (p > 1) mbar_wait_sleep(bar0 + (B_FREE + p - 1) * 8, 40);
                    const int k = ks0 + p * 3 >= 36 ? ks0 + p * 3 - 36 : ks0 + p * 3;
                    mbar_expect(bar0 + (B_WO + p) * 8, 6144);
                    bulk_load(sb + 13824 + (p == 0 ? sm_piece(0) : (p == 1 ? sm_piece(1) : SM_KV + (p - 2) * PIECE)), osrc + k * 2048, 6144, bar0 + (B_WO + p) * 8);
                }
                mbar_expect(bar0 + B_LATE * 8, 2 * 9216);
                mbar_wait(bar0 + B_EARLY * 8, 0);
                tma2d(sb + sm_piece(0), &tmXo, ct * 144, rt * 64, bar0 + B_LATE * 8);
                tma2d(sb + sm_piece(0) + 9216, &tmXo, ct * 144 + 72, rt * 64, bar0 + B_LATE * 8);
            }
        }
    }
}

typedef CUresult (*EncodeFn)(CUtensorMap*, CUtensorMapDataType, cuuint32_t, void*, const cuuint64_t*, const cuuint64_t*, const cuuint32_t*,
                             const cuuint32_t*, CUtensorMapInterleave, CUtensorMapSwizzle, CUtensorMapL2promotion, CUtensorMapFloatOOBfill);

void make_map(EncodeFn fn, CUtensorMap* m, const void* base, int rank, const cuuint64_t* dims, const cuuint64_t* strides, const cuuint32_t* box) {
    cuuint32_t es[4] = {1, 1, 1, 1};
    fn(m, CU_TENSOR_MAP_DATA_TYPE_BFLOAT16, rank, const_cast<void*>(base), dims, strides, box, es, CU_TENSOR_MAP_INTERLEAVE_NONE,
       CU_TENSOR_MAP_SWIZZLE_128B, CU_TENSOR_MAP_L2_PROMOTION_L2_256B, CU_TENSOR_MAP_FLOAT_OOB_FILL_NONE);
}

}

extern "C" void kernel_launch(void* const* d_in, const int* in_sizes, int n_in, void* d_out, int out_size) {
    const __nv_bfloat16* x = (const __nv_bfloat16*)d_in[0];
    const __nv_bfloat16* wqkv = (const __nv_bfloat16*)d_in[1];
    const __nv_bfloat16* wo = (const __nv_bfloat16*)d_in[2];
    const __nv_bfloat16* w1 = (const __nv_bfloat16*)d_in[4];
    const __nv_bfloat16* b1 = (const __nv_bfloat16*)d_in[5];
    const __nv_bfloat16* w2 = (const __nv_bfloat16*)d_in[6];
    const __nv_bfloat16* b2 = (const __nv_bfloat16*)d_in[7];
    __nv_bfloat16* out = (__nv_bfloat16*)d_out;

    EncodeFn fn = nullptr;
    cudaDriverEntryPointQueryResult qr;
    cudaGetDriverEntryPoint("cuTensorMapEncodeTiled", (void**)&fn, cudaEnableDefault, &qr);
    CUtensorMap tmX, tmQ3, tmQ1, tm1, tm2, tmP, tmOut, tmXo;
    {
        cuuint64_t d[2] = {DM, SEQ}, s[1] = {DM * 2};
        cuuint32_t b[2] = {72, 64}, es[2] = {1, 1};
        fn(&tmOut, CU_TENSOR_MAP_DATA_TYPE_BFLOAT16, 2, out, d, s, b, es, CU_TENSOR_MAP_INTERLEAVE_NONE, CU_TENSOR_MAP_SWIZZLE_NONE,
           CU_TENSOR_MAP_L2_PROMOTION_NONE, CU_TENSOR_MAP_FLOAT_OOB_FILL_NONE);
        fn(&tmXo, CU_TENSOR_MAP_DATA_TYPE_BFLOAT16, 2, const_cast<__nv_bfloat16*>(x), d, s, b, es, CU_TENSOR_MAP_INTERLEAVE_NONE,
           CU_TENSOR_MAP_SWIZZLE_NONE, CU_TENSOR_MAP_L2_PROMOTION_NONE, CU_TENSOR_MAP_FLOAT_OOB_FILL_NONE);
    }
    {
        void* gp = nullptr;
        cudaGetSymbolAddress(&gp, g_part);
        cuuint64_t d[2] = {SLAB * 2, 8}, s[1] = {SLAB * 16};
        cuuint32_t b[2] = {64, 8}, es[2] = {1, 1};
        fn(&tmP, CU_TENSOR_MAP_DATA_TYPE_INT64, 2, gp, d, s, b, es, CU_TENSOR_MAP_INTERLEAVE_NONE, CU_TENSOR_MAP_SWIZZLE_NONE,
           CU_TENSOR_MAP_L2_PROMOTION_NONE, CU_TENSOR_MAP_FLOAT_OOB_FILL_NONE);
    }
    {
        cuuint64_t d[4] = {64, 8, 9, SEQ / 8}, s[3] = {DM * 2, 128, DM * 2 * 8};
        cuuint32_t b[4] = {64, 8, 3, 2};
        make_map(fn, &tmX, x, 4, d, s, b);
    }
    {
        cuuint64_t d[3] = {3 * DM, DM, 3}, s[2] = {3 * DM * 2, 128};
        cuuint32_t b[3] = {64, 16, 3};
        make_map(fn, &tmQ3, wqkv, 3, d, s, b);
        make_map(fn, &tmQ1, wqkv, 2, d, s, b);
    }
    {
        cuuint64_t d[2] = {FF, DM}, s[1] = {FF * 2};
        cuuint32_t b[2] = {64, 64};
        make_map(fn, &tm1, w1, 2, d, s, b);
        cuuint64_t d2[2] = {DM, FF}, s2[1] = {DM * 2};
        make_map(fn, &tm2, w2, 2, d2, s2, b);
    }
    cudaFuncSetAttribute(fused_kernel, cudaFuncAttributeMaxDynamicSharedMemorySize, K1_SMEM);
    fused_kernel<<<128, 384, K1_SMEM, cudaStreamPerThread>>>(tmX, tmQ3, tmQ1, tm1, tm2, tmP, tmOut, tmXo, b1, wqkv, w1, w2, wo, b2, 0ull);
}
```

```cpp
#include <cuda_runtime.h>
#include <cuda_bf16.h>
#include <cuda.h>
#include <stdint.h>

#define PROF(i) do { } while (0)
#define PROFT(i) do { } while (0)
#define PROFH(i) do { } while (0)
#define PROFWT(i) do { } while (0)
#define PROF_WG 0

namespace {

constexpr int SEQ = 2048, DM = 576, FF = 4608, NH = 32, DH = 18;

constexpr int KV_GROUP_BYTES = 5 * 128;
constexpr int KV_HEAD_BYTES = (SEQ / 8) * KV_GROUP_BYTES;
constexpr int Q_OFFSET = NH * KV_HEAD_BYTES;
#define POLY_MASK 0xB6B6
__device__ __align__(1024) uint8_t g_QKV[2 * NH * KV_HEAD_BYTES];
__device__ __align__(1024) float g_kmax[NH * 64];
constexpr int SLAB = 16 * 36 * 256;
__device__ __align__(1024) uint4 g_part[8 * SLAB];
__device__ __align__(1024) uint2 g_ffn[128 * 18 * 128];
__device__ __align__(1024) uint32_t g_O[SEQ * DM / 2];
struct Flags {
    unsigned int qkv_stored[16];
    unsigned int ffn_done[16];
    unsigned int o_done[32];
    unsigned int kv_ready;
    unsigned int exited;
};
__device__ Flags g_flags;
__device__ __align__(1024) uint4 g_Olate[32 * 9 * 128];
constexpr uint32_t O_EMPTY = 0xFFFFFFFFu;
constexpr int WO_TILE_BYTES = DM * 144 * 2;
__device__ __align__(1024) uint8_t g_Wo[4 * WO_TILE_BYTES];

__device__ __forceinline__ uint32_t s2u(const void* p) { return (uint32_t)__cvta_generic_to_shared(p); }
__device__ __forceinline__ void mbar_init(uint32_t b, int c) { asm volatile("mbarrier.init.shared::cta.b64 [%0], %1;" ::"r"(b), "r"(c) : "memory"); }
__device__ __forceinline__ void mbar_expect(uint32_t b, uint32_t bytes) {
    asm volatile("mbarrier.arrive.expect_tx.shared::cta.b64 _, [%0], %1;" ::"r"(b), "r"(bytes) : "memory");
}
__device__ __forceinline__ void mbar_wait(uint32_t b, uint32_t parity) {
    asm volatile(
        "{\n.reg .pred p;\n.reg .u32 c;\n"
        "mov.u32 c, 0;\n"
        "LOOP:\n"
        "mbarrier.try_wait.parity.shared::cta.b64 p, [%0], %1;\n"
        "@p bra DONE;\n"
        "add.u32 c, c, 1;\n"
        "setp.lt.u32 p, c, 4194304;\n"
        "@p bra LOOP;\n"
        "trap;\n"
        "DONE:\n}\n" ::"r"(b), "r"(parity) : "memory");
}
__device__ __forceinline__ uint32_t mbar_test(uint32_t b, uint32_t parity) {
    uint32_t ok;
    asm volatile("{\n.reg .pred p;\nmbarrier.try_wait.parity.shared::cta.b64 p, [%1], %2;\nselp.u32 %0, 1, 0, p;\n}\n" : "=r"(ok) : "r"(b), "r"(parity) : "memory");
    return ok;
}
__device__ __forceinline__ void mbar_wait_if(uint32_t ok, uint32_t b, uint32_t parity) {
    asm volatile(
        "{\n.reg .pred p;\n.reg .u32 c;\n"
        "setp.ne.u32 p, %2, 0;\n"
        "@p bra DONE;\n"
        "mov.u32 c, 0;\n"
        "LOOP:\n"
        "mbarrier.try_wait.parity.shared::cta.b64 p, [%0], %1;\n"
        "@p bra DONE;\n"
        "add.u32 c, c, 1;\n"
        "setp.lt.u32 p, c, 4194304;\n"
        "@p bra LOOP;\n"
        "trap;\n"
        "DONE:\n}\n" ::"r"(b), "r"(parity), "r"(ok) : "memory");
}
__device__ __forceinline__ void fence_barrier_init() { asm volatile("fence.mbarrier_init.release.cluster;" ::: "memory"); }
__device__ __forceinline__ void fence_proxy_async() { asm volatile("fence.proxy.async.shared::cta;" ::: "memory"); }
__device__ __forceinline__ void cluster_arrive() { asm volatile("barrier.cluster.arrive.relaxed.aligned;" ::: "memory"); }
__device__ __forceinline__ void cluster_wait() { asm volatile("barrier.cluster.wait.aligned;" ::: "memory"); }
__device__ __forceinline__ void named_bar_sync(int id, int n) { asm volatile("bar.sync %0, %1;" ::"r"(id), "r"(n) : "memory"); }

__device__ __forceinline__ void tma3d_mc(uint32_t dst, const CUtensorMap* tm, int c0, int c1, int c2, uint32_t bar, uint16_t mask) {
    asm volatile("cp.async.bulk.tensor.3d.shared::cluster.global.mbarrier::complete_tx::bytes.multicast::cluster [%0], [%1, {%3, %4, %5}], [%2], %6;"
                 ::"r"(dst), "l"(tm), "r"(bar), "r"(c0), "r"(c1), "r"(c2), "h"(mask) : "memory");
}
__device__ __forceinline__ void tma2d_mc(uint32_t dst, const CUtensorMap* tm, int c0, int c1, uint32_t bar, uint16_t mask) {
    asm volatile("cp.async.bulk.tensor.2d.shared::cluster.global.mbarrier::complete_tx::bytes.multicast::cluster [%0], [%1, {%3, %4}], [%2], %5;"
                 ::"r"(dst), "l"(tm), "r"(bar), "r"(c0), "r"(c1), "h"(mask) : "memory");
}
__device__ __forceinline__ void tma4d(uint32_t dst, const CUtensorMap* tm, int c0, int c1, int c2, int c3, uint32_t bar) {
    asm volatile("cp.async.bulk.tensor.4d.shared::cluster.global.mbarrier::complete_tx::bytes [%0], [%1, {%3, %4, %5, %6}], [%2];"
                 ::"r"(dst), "l"(tm), "r"(bar), "r"(c0), "r"(c1), "r"(c2), "r"(c3) : "memory");
}
__device__ __forceinline__ void tma2d(uint32_t dst, const CUtensorMap* tm, int c0, int c1, uint32_t bar) {
    asm volatile("cp.async.bulk.tensor.2d.shared::cluster.global.mbarrier::complete_tx::bytes [%0], [%1, {%3, %4}], [%2];"
                 ::"r"(dst), "l"(tm), "r"(bar), "r"(c0), "r"(c1) : "memory");
}
__device__ __forceinline__ void bulk_load(uint32_t dst, const void* src, uint32_t bytes, uint32_t bar) {
    asm volatile("cp.async.bulk.shared::cluster.global.mbarrier::complete_tx::bytes [%0], [%1], %2, [%3];"
                 ::"r"(dst), "l"(src), "r"(bytes), "r"(bar) : "memory");
}
__device__ __forceinline__ void prefetch_l2(const void* p, uint32_t bytes) {
    asm volatile("cp.async.bulk.prefetch.L2.global [%0], %1;" ::"l"(p), "r"(bytes) : "memory");
}
__device__ __forceinline__ void prefetch_tmap(const CUtensorMap* tm) { asm volatile("prefetch.tensormap [%0];" ::"l"(tm) : "memory"); }

__device__ __forceinline__ void wg_fence() { asm volatile("wgmma.fence.sync.aligned;" ::: "memory"); }
__device__ __forceinline__ void wg_commit() { asm volatile("wgmma.commit_group.sync.aligned;" ::: "memory"); }
template <int N> __device__ __forceinline__ void wg_wait() { asm volatile("wgmma.wait_group.sync.aligned %0;" ::"n"(N) : "memory"); }
template <int N> __device__ __forceinline__ void reg_fence(float (&d)[N]) {
#pragma unroll
    for (int i = 0; i < N; i++) asm volatile("" : "+f"(d[i])::"memory");
}
template <int N> __device__ __forceinline__ void reg_fence(uint32_t (&d)[N]) {
#pragma unroll
    for (int i = 0; i < N; i++) asm volatile("" : "+r"(d[i])::"memory");
}
template <int R> __device__ __forceinline__ void reg_alloc() { asm volatile("setmaxnreg.inc.sync.aligned.u32 %0;" ::"n"(R)); }
template <int R> __device__ __forceinline__ void reg_dealloc() { asm volatile("setmaxnreg.dec.sync.aligned.u32 %0;" ::"n"(R)); }

__device__ __forceinline__ uint64_t mk_desc(uint64_t z, uint32_t addr, uint32_t lbo, uint32_t sbo, uint32_t swz) {
    return z + ((uint64_t)(((addr & 0x3FFFF) >> 4) | ((lbo >> 4) << 16)) | ((uint64_t)((sbo >> 4) | (swz << 30)) << 32));
}
__device__ __forceinline__ uint32_t pack_bf16(float lo, float hi) {
    uint32_t r;
    asm("cvt.rn.bf16x2.f32 %0, %1, %2;" : "=r"(r) : "f"(hi), "f"(lo));
    return r;
}
__device__ __forceinline__ float bf_lo(uint32_t w) { return __uint_as_float(w << 16); }
__device__ __forceinline__ float bf_hi(uint32_t w) { return __uint_as_float(w & 0xFFFF0000u); }
__device__ __forceinline__ float ex2(float x) {
    float r;
    asm("ex2.approx.ftz.f32 %0, %1;" : "=f"(r) : "f"(x));
    return r;
}
__device__ __forceinline__ float tanh_fast(float x) {
    float r;
    asm("tanh.approx.f32 %0, %1;" : "=f"(r) : "f"(x));
    return r;
}
__device__ __forceinline__ uint32_t hfma2_bf16(uint32_t a, uint32_t b, uint32_t c) {
    uint32_t r;
    asm("fma.rn.bf16x2 %0, %1, %2, %3;" : "=r"(r) : "r"(a), "r"(b), "r"(c));
    return r;
}
__device__ __forceinline__ uint32_t hadd2_bf16(uint32_t a, uint32_t b) {
    uint32_t r;
    asm("add.rn.bf16x2 %0, %1, %2;" : "=r"(r) : "r"(a), "r"(b));
    return r;
}
__device__ __forceinline__ void ldsm4(uint32_t (&a)[4], uint32_t addr) {
    asm volatile("ldmatrix.sync.aligned.m8n8.x4.shared.b16 {%0, %1, %2, %3}, [%4];" : "=r"(a[0]), "=r"(a[1]), "=r"(a[2]), "=r"(a[3]) : "r"(addr) : "memory");
}
__device__ __forceinline__ void stsm4(uint32_t addr, const uint32_t (&a)[4]) {
    asm volatile("stmatrix.sync.aligned.m8n8.x4.shared.b16 [%0], {%1, %2, %3, %4};" ::"r"(addr), "r"(a[0]), "r"(a[1]), "r"(a[2]), "r"(a[3]) : "memory");
}
__device__ __forceinline__ void mma16816(float (&c)[4], const uint32_t (&a)[4], uint32_t b0, uint32_t b1) {
    asm("mma.sync.aligned.m16n8k16.row.col.f32.bf16.bf16.f32 {%0, %1, %2, %3}, {%4, %5, %6, %7}, {%8, %9}, {%0, %1, %2, %3};"
        : "+f"(c[0]), "+f"(c[1]), "+f"(c[2]), "+f"(c[3]) : "r"(a[0]), "r"(a[1]), "r"(a[2]), "r"(a[3]), "r"(b0), "r"(b1));
}
__device__ __forceinline__ float gelu2(float u) {
    const float w = fmaf(u * u, 0.0356774081f, 0.7978845608f);
    return fmaf(u, tanh_fast(u * w), u);
}

template<int TB, int AOFF, int BOFF> __device__ __forceinline__ void wgmma_ss_n216(float (&d)[108], uint64_t da, uint64_t db, int sd) {
    asm volatile("{\n.reg .pred p;\n.reg .b64 ta, tb;\nsetp.ne.b32 p, %110, 0;\nadd.s64 ta, %108, %112;\nadd.s64 tb, %109, %113;\n"
      "wgmma.mma_async.sync.aligned.m64n216k16.f32.bf16.bf16 {%0, %1, %2, %3, %4, %5, %6, %7, %8, %9, %10, %11, %12, %13, %14, %15, %16, %17, %18, %19, %20, %21, %22, %23, %24, %25, %26, %27, %28, %29, %30, %31, %32, %33, %34, %35, %36, %37, %38, %39, %40, %41, %42, %43, %44, %45, %46, %47, %48, %49, %50, %51, %52, %53, %54, %55, %56, %57, %58, %59, %60, %61, %62, %63, %64, %65, %66, %67, %68, %69, %70, %71, %72, %73, %74, %75, %76, %77, %78, %79, %80, %81, %82, %83, %84, %85, %86, %87, %88, %89, %90, %91, %92, %93, %94, %95, %96, %97, %98, %99, %100, %101, %102, %103, %104, %105, %106, %107}, ta, tb, p, 1, 1, 0, %111;\n}\n"
      : "+f"(d[0]), "+f"(d[1]), "+f"(d[2]), "+f"(d[3]), "+f"(d[4]), "+f"(d[5]), "+f"(d[6]), "+f"(d[7]), "+f"(d[8]), "+f"(d[9]), "+f"(d[10]), "+f"(d[11]), "+f"(d[12]), "+f"(d[13]), "+f"(d[14]), "+f"(d[15]), "+f"(d[16]), "+f"(d[17]), "+f"(d[18]), "+f"(d[19]), "+f"(d[20]), "+f"(d[21]), "+f"(d[22]), "+f"(d[23]), "+f"(d[24]), "+f"(d[25]), "+f"(d[26]), "+f"(d[27]), "+f"(d[28]), "+f"(d[29]), "+f"(d[30]), "+f"(d[31]), "+f"(d[32]), "+f"(d[33]), "+f"(d[34]), "+f"(d[35]), "+f"(d[36]), "+f"(d[37]), "+f"(d[38]), "+f"(d[39]), "+f"(d[40]), "+f"(d[41]), "+f"(d[42]), "+f"(d[43]), "+f"(d[44]), "+f"(d[45]), "+f"(d[46]), "+f"(d[47]), "+f"(d[48]), "+f"(d[49]), "+f"(d[50]), "+f"(d[51]), "+f"(d[52]), "+f"(d[53]), "+f"(d[54]), "+f"(d[55]), "+f"(d[56]), "+f"(d[57]), "+f"(d[58]), "+f"(d[59]), "+f"(d[60]), "+f"(d[61]), "+f"(d[62]), "+f"(d[63]), "+f"(d[64]), "+f"(d[65]), "+f"(d[66]), "+f"(d[67]), "+f"(d[68]), "+f"(d[69]), "+f"(d[70]), "+f"(d[71]), "+f"(d[72]), "+f"(d[73]), "+f"(d[74]), "+f"(d[75]), "+f"(d[76]), "+f"(d[77]), "+f"(d[78]), "+f"(d[79]), "+f"(d[80]), "+f"(d[81]), "+f"(d[82]), "+f"(d[83]), "+f"(d[84]), "+f"(d[85]), "+f"(d[86]), "+f"(d[87]), "+f"(d[88]), "+f"(d[89]), "+f"(d[90]), "+f"(d[91]), "+f"(d[92]), "+f"(d[93]), "+f"(d[94]), "+f"(d[95]), "+f"(d[96]), "+f"(d[97]), "+f"(d[98]), "+f"(d[99]), "+f"(d[100]), "+f"(d[101]), "+f"(d[102]), "+f"(d[103]), "+f"(d[104]), "+f"(d[105]), "+f"(d[106]), "+f"(d[107])
      : "l"(da), "l"(db), "r"(sd), "n"(TB), "n"(AOFF), "n"(BOFF));
}

template<int TB, int AOFF, int BOFF> __device__ __forceinline__ void wgmma_ss_n128(float (&d)[64], uint64_t da, uint64_t db, int sd) {
    asm volatile("{\n.reg .pred p;\n.reg .b64 ta, tb;\nsetp.ne.b32 p, %66, 0;\nadd.s64 ta, %64, %68;\nadd.s64 tb, %65, %69;\n"
      "wgmma.mma_async.sync.aligned.m64n128k16.f32.bf16.bf16 {%0, %1, %2, %3, %4, %5, %6, %7, %8, %9, %10, %11, %12, %13, %14, %15, %16, %17, %18, %19, %20, %21, %22, %23, %24, %25, %26, %27, %28, %29, %30, %31, %32, %33, %34, %35, %36, %37, %38, %39, %40, %41, %42, %43, %44, %45, %46, %47, %48, %49, %50, %51, %52, %53, %54, %55, %56, %57, %58, %59, %60, %61, %62, %63}, ta, tb, p, 1, 1, 0, %67;\n}\n"
      : "+f"(d[0]), "+f"(d[1]), "+f"(d[2]), "+f"(d[3]), "+f"(d[4]), "+f"(d[5]), "+f"(d[6]), "+f"(d[7]), "+f"(d[8]), "+f"(d[9]), "+f"(d[10]), "+f"(d[11]), "+f"(d[12]), "+f"(d[13]), "+f"(d[14]), "+f"(d[15]), "+f"(d[16]), "+f"(d[17]), "+f"(d[18]), "+f"(d[19]), "+f"(d[20]), "+f"(d[21]), "+f"(d[22]), "+f"(d[23]), "+f"(d[24]), "+f"(d[25]), "+f"(d[26]), "+f"(d[27]), "+f"(d[28]), "+f"(d[29]), "+f"(d[30]), "+f"(d[31]), "+f"(d[32]), "+f"(d[33]), "+f"(d[34]), "+f"(d[35]), "+f"(d[36]), "+f"(d[37]), "+f"(d[38]), "+f"(d[39]), "+f"(d[40]), "+f"(d[41]), "+f"(d[42]), "+f"(d[43]), "+f"(d[44]), "+f"(d[45]), "+f"(d[46]), "+f"(d[47]), "+f"(d[48]), "+f"(d[49]), "+f"(d[50]), "+f"(d[51]), "+f"(d[52]), "+f"(d[53]), "+f"(d[54]), "+f"(d[55]), "+f"(d[56]), "+f"(d[57]), "+f"(d[58]), "+f"(d[59]), "+f"(d[60]), "+f"(d[61]), "+f"(d[62]), "+f"(d[63])
      : "l"(da), "l"(db), "r"(sd), "n"(TB), "n"(AOFF), "n"(BOFF));
}

template<int TB, int AOFF, int BOFF> __device__ __forceinline__ void wgmma_ss_n72(float (&d)[36], uint64_t da, uint64_t db, int sd) {
    asm volatile("{\n.reg .pred p;\n.reg .b64 ta, tb;\nsetp.ne.b32 p, %38, 0;\nadd.s64 ta, %36, %40;\nadd.s64 tb, %37, %41;\n"
      "wgmma.mma_async.sync.aligned.m64n72k16.f32.bf16.bf16 {%0, %1, %2, %3, %4, %5, %6, %7, %8, %9, %10, %11, %12, %13, %14, %15, %16, %17, %18, %19, %20, %21, %22, %23, %24, %25, %26, %27, %28, %29, %30, %31, %32, %33, %34, %35}, ta, tb, p, 1, 1, 0, %39;\n}\n"
      : "+f"(d[0]), "+f"(d[1]), "+f"(d[2]), "+f"(d[3]), "+f"(d[4]), "+f"(d[5]), "+f"(d[6]), "+f"(d[7]), "+f"(d[8]), "+f"(d[9]), "+f"(d[10]), "+f"(d[11]), "+f"(d[12]), "+f"(d[13]), "+f"(d[14]), "+f"(d[15]), "+f"(d[16]), "+f"(d[17]), "+f"(d[18]), "+f"(d[19]), "+f"(d[20]), "+f"(d[21]), "+f"(d[22]), "+f"(d[23]), "+f"(d[24]), "+f"(d[25]), "+f"(d[26]), "+f"(d[27]), "+f"(d[28]), "+f"(d[29]), "+f"(d[30]), "+f"(d[31]), "+f"(d[32]), "+f"(d[33]), "+f"(d[34]), "+f"(d[35])
      : "l"(da), "l"(db), "r"(sd), "n"(TB), "n"(AOFF), "n"(BOFF));
}

template<int TB, int BOFF> __device__ __forceinline__ void wgmma_rs_n24(float (&d)[12], uint32_t a0, uint32_t a1, uint32_t a2, uint32_t a3, uint64_t db, int sd) {
    asm volatile("{\n.reg .pred p;\n.reg .b64 tb;\nsetp.ne.b32 p, %17, 0;\nadd.s64 tb, %16, %19;\n"
      "wgmma.mma_async.sync.aligned.m64n24k16.f32.bf16.bf16 {%0, %1, %2, %3, %4, %5, %6, %7, %8, %9, %10, %11}, {%12, %13, %14, %15}, tb, p, 1, 1, %18;\n}\n"
      : "+f"(d[0]), "+f"(d[1]), "+f"(d[2]), "+f"(d[3]), "+f"(d[4]), "+f"(d[5]), "+f"(d[6]), "+f"(d[7]), "+f"(d[8]), "+f"(d[9]), "+f"(d[10]), "+f"(d[11])
      : "r"(a0), "r"(a1), "r"(a2), "r"(a3), "l"(db), "r"(sd), "n"(TB), "n"(BOFF));
}

template<int TB, int BOFF> __device__ __forceinline__ void wgmma_rs_n72(float (&d)[36], uint32_t a0, uint32_t a1, uint32_t a2, uint32_t a3, uint64_t db, int sd) {
    asm volatile("{\n.reg .pred p;\n.reg .b64 tb;\nsetp.ne.b32 p, %41, 0;\nadd.s64 tb, %40, %43;\n"
      "wgmma.mma_async.sync.aligned.m64n72k16.f32.bf16.bf16 {%0, %1, %2, %3, %4, %5, %6, %7, %8, %9, %10, %11, %12, %13, %14, %15, %16, %17, %18, %19, %20, %21, %22, %23, %24, %25, %26, %27, %28, %29, %30, %31, %32, %33, %34, %35}, {%36, %37, %38, %39}, tb, p, 1, 1, %42;\n}\n"
      : "+f"(d[0]), "+f"(d[1]), "+f"(d[2]), "+f"(d[3]), "+f"(d[4]), "+f"(d[5]), "+f"(d[6]), "+f"(d[7]), "+f"(d[8]), "+f"(d[9]), "+f"(d[10]), "+f"(d[11]), "+f"(d[12]), "+f"(d[13]), "+f"(d[14]), "+f"(d[15]), "+f"(d[16]), "+f"(d[17]), "+f"(d[18]), "+f"(d[19]), "+f"(d[20]), "+f"(d[21]), "+f"(d[22]), "+f"(d[23]), "+f"(d[24]), "+f"(d[25]), "+f"(d[26]), "+f"(d[27]), "+f"(d[28]), "+f"(d[29]), "+f"(d[30]), "+f"(d[31]), "+f"(d[32]), "+f"(d[33]), "+f"(d[34]), "+f"(d[35])
      : "r"(a0), "r"(a1), "r"(a2), "r"(a3), "l"(db), "r"(sd), "n"(TB), "n"(BOFF));
}

template<int TB, int AINC, int BINC> __device__ __forceinline__ void wgmma_ss_n64_pi(float (&d)[32], uint64_t& da, uint64_t& db, int sd) {
    asm volatile("{\n.reg .pred p;\nsetp.ne.b32 p, %34, 0;\n"
      "wgmma.mma_async.sync.aligned.m64n64k16.f32.bf16.bf16 {%0, %1, %2, %3, %4, %5, %6, %7, %8, %9, %10, %11, %12, %13, %14, %15, %16, %17, %18, %19, %20, %21, %22, %23, %24, %25, %26, %27, %28, %29, %30, %31}, %32, %33, p, 1, 1, 0, %35;\n"
      "add.s64 %32, %32, %36;\nadd.s64 %33, %33, %37;\n}\n"
      : "+f"(d[0]), "+f"(d[1]), "+f"(d[2]), "+f"(d[3]), "+f"(d[4]), "+f"(d[5]), "+f"(d[6]), "+f"(d[7]), "+f"(d[8]), "+f"(d[9]), "+f"(d[10]), "+f"(d[11]), "+f"(d[12]), "+f"(d[13]), "+f"(d[14]), "+f"(d[15]), "+f"(d[16]), "+f"(d[17]), "+f"(d[18]), "+f"(d[19]), "+f"(d[20]), "+f"(d[21]), "+f"(d[22]), "+f"(d[23]), "+f"(d[24]), "+f"(d[25]), "+f"(d[26]), "+f"(d[27]), "+f"(d[28]), "+f"(d[29]), "+f"(d[30]), "+f"(d[31]), "+l"(da), "+l"(db)
      : "r"(sd), "n"(TB), "n"(AINC), "n"(BINC));
}

template<int TB, int BINC> __device__ __forceinline__ void wgmma_rs_n64_pi(float (&d)[32], uint32_t a0, uint32_t a1, uint32_t a2, uint32_t a3, uint64_t& db, int sd) {
    asm volatile("{\n.reg .pred p;\nsetp.ne.b32 p, %37, 0;\n"
      "wgmma.mma_async.sync.aligned.m64n64k16.f32.bf16.bf16 {%0, %1, %2, %3, %4, %5, %6, %7, %8, %9, %10, %11, %12, %13, %14, %15, %16, %17, %18, %19, %20, %21, %22, %23, %24, %25, %26, %27, %28, %29, %30, %31}, {%33, %34, %35, %36}, %32, p, 1, 1, %38;\n"
      "add.s64 %32, %32, %39;\n}\n"
      : "+f"(d[0]), "+f"(d[1]), "+f"(d[2]), "+f"(d[3]), "+f"(d[4]), "+f"(d[5]), "+f"(d[6]), "+f"(d[7]), "+f"(d[8]), "+f"(d[9]), "+f"(d[10]), "+f"(d[11]), "+f"(d[12]), "+f"(d[13]), "+f"(d[14]), "+f"(d[15]), "+f"(d[16]), "+f"(d[17]), "+f"(d[18]), "+f"(d[19]), "+f"(d[20]), "+f"(d[21]), "+f"(d[22]), "+f"(d[23]), "+f"(d[24]), "+f"(d[25]), "+f"(d[26]), "+f"(d[27]), "+f"(d[28]), "+f"(d[29]), "+f"(d[30]), "+f"(d[31]), "+l"(db)
      : "r"(a0), "r"(a1), "r"(a2), "r"(a3), "r"(sd), "n"(TB), "n"(BINC));
}

constexpr int K1_XN_BYTES = 16 * 9216;
constexpr int K1_OFF_RING = K1_XN_BYTES;
constexpr int K1_OFF_BIAS = K1_OFF_RING + 10 * 8192;
constexpr int K1_OFF_BAR = K1_OFF_BIAS + 576 * 2;
constexpr int K1_SMEM = K1_OFF_BAR + 800;
constexpr float QSCALE = 0.23570226039551584f * 1.4426950408889634f;

struct K1Ctx {
    uint32_t full0;
    uint32_t rel_addr;
    uint64_t descA, descB;
    uint32_t phase;
    uint32_t rdy;
    __device__ __forceinline__ void begin_stage(int s) {
        mbar_wait_if(rdy, full0 + s * 8, phase);
        wg_fence();
    }
    __device__ __forceinline__ void probe_next(int s) { rdy = mbar_test(full0 + (s == 8 ? 0 : s + 1) * 8, s == 8 ? phase ^ 1 : phase); }
    __device__ __forceinline__ void release(int s) {
        if (rel_addr) asm volatile("mbarrier.arrive.shared::cluster.b64 _, [%0];" ::"r"(rel_addr + s * 8) : "memory");
    }
    __device__ __forceinline__ void end_stage(int s) {
        wg_commit();
        wg_wait<1>();
        release(s == 0 ? 8 : s - 1);
    }
};

__host__ __device__ constexpr int a_off(int ks) { return ((ks / 12) * 49152 + ((ks >> 2) % 3) * 1024 + (ks & 3) * 32) >> 4; }

#define PROBE_T 3
template <int V> struct IC { static constexpr int value = V; };
template <int I, int N, class F> __device__ __forceinline__ void static_for(F&& f) {
    if constexpr (I < N) { f(IC<I>{}); static_for<I + 1, N>(f); }
}

template <bool A_RS, bool B_RS, class Epi>
__device__ __forceinline__ void tile_pair(K1Ctx& c, float (&accA)[32], float (&accB)[32], uint32_t (&h)[144], Epi&& epi) {
    static_for<0, 9>([&](auto sc) {
        constexpr int s = decltype(sc)::value;
        c.begin_stage(s);
        static_for<0, 8>([&](auto tc) {
            constexpr int t = decltype(tc)::value, kk = s * 8 + t, ks = kk % 36;
            constexpr int db = ks == 35 ? -35 * 128 : 128, da = a_off((ks + 1) % 36) - a_off(ks);
            if constexpr (kk < 36) {
                if constexpr (A_RS) wgmma_rs_n64_pi<1, db>(accA, h[ks * 4], h[ks * 4 + 1], h[ks * 4 + 2], h[ks * 4 + 3], c.descB, ks != 0);
                else wgmma_ss_n64_pi<1, da, db>(accA, c.descA, c.descB, ks != 0);
            } else {
                if constexpr (B_RS) wgmma_rs_n64_pi<1, db>(accB, h[ks * 4], h[ks * 4 + 1], h[ks * 4 + 2], h[ks * 4 + 3], c.descB, ks != 0);
                else wgmma_ss_n64_pi<1, da, db>(accB, c.descA, c.descB, ks != 0);
            }
            if constexpr (t == 0) {
                c.end_stage(s);
                epi(sc);
                wg_fence();
            }
            if constexpr (t == PROBE_T) c.probe_next(s);
        });
        wg_commit();
    });
    c.phase ^= 1;
}

template <int B0, int NB, int HOFF>
__device__ __forceinline__ void gelu_blocks(const float (&acc)[32], uint32_t (&h)[144], const uint32_t (&bq)[8], float rs0, float rs1) {
#pragma unroll
    for (int b = B0; b < B0 + NB; b++) {
        const float b0 = bf_lo(bq[b]), b1 = bf_hi(bq[b]);
        h[HOFF + b * 2 + 0] = pack_bf16(gelu2(fmaf(acc[b * 4 + 0], rs0, b0)), gelu2(fmaf(acc[b * 4 + 1], rs0, b1)));
        h[HOFF + b * 2 + 1] = pack_bf16(gelu2(fmaf(acc[b * 4 + 2], rs1, b0)), gelu2(fmaf(acc[b * 4 + 3], rs1, b1)));
    }
#pragma unroll
    for (int i = HOFF + B0 * 2; i < HOFF + (B0 + NB) * 2; i++) asm volatile("" : "+r"(h[i]));
}
__device__ __forceinline__ void load_bias(uint32_t (&bq)[8], uint32_t addr) {
    asm volatile("ld.shared.v4.u32 {%0, %1, %2, %3}, [%4];" : "=r"(bq[0]), "=r"(bq[1]), "=r"(bq[2]), "=r"(bq[3]) : "r"(addr));
    asm volatile("ld.shared.v4.u32 {%0, %1, %2, %3}, [%4 + 16];" : "=r"(bq[4]), "=r"(bq[5]), "=r"(bq[6]), "=r"(bq[7]) : "r"(addr));
}
__device__ __forceinline__ void st_pred2(bool p, void* a, uint32_t x, uint32_t y) {
    asm volatile("{\n.reg .pred p;\nsetp.ne.u32 p, %3, 0;\n@p st.global.v2.u32 [%0], {%1, %2};\n}\n" ::"l"(a), "r"(x), "r"(y), "r"((uint32_t)p) : "memory");
}
__device__ __forceinline__ void st_pred1(bool p, void* a, uint32_t x) {
    asm volatile("{\n.reg .pred p;\nsetp.ne.u32 p, %2, 0;\n@p st.global.u32 [%0], %1;\n}\n" ::"l"(a), "r"(x), "r"((uint32_t)p) : "memory");
}
template <int S> __device__ __forceinline__ void store_part(const float (&o)[32], uint4* p) {
    uint4 v;
    v.x = pack_bf16(o[S * 8 + 0], o[S * 8 + 1]); v.y = pack_bf16(o[S * 8 + 2], o[S * 8 + 3]);
    v.z = pack_bf16(o[S * 8 + 4], o[S * 8 + 5]); v.w = pack_bf16(o[S * 8 + 6], o[S * 8 + 7]);
    p[S * 256] = v;
}

constexpr int NCHUNK = 16;
constexpr int CHUNK_BYTES = KV_HEAD_BYTES / NCHUNK;
constexpr int SM_Q = 0;
constexpr int SM_KV = 32768;
constexpr int PIECE = 19968;
__host__ __device__ constexpr int sm_piece(int p) { return p == 0 ? 209408 : (p == 1 ? 0 : SM_KV + (p - 2) * PIECE); }
__host__ __device__ constexpr int sm_wstep(int k) { return k < 27 ? sm_piece(k / 3) + (k % 3) * 4608 : (k < 35 ? SM_KV + 7 * PIECE + (k - 27) * 4608 : PIECE); }
__host__ __device__ constexpr int sm_ostep(int k) { return sm_piece(k / 3) + 13824 + (k % 3) * 2048; }
constexpr int SM_RED = SM_KV + KV_HEAD_BYTES;

__device__ __forceinline__ float exp2_fixed(float y) {
    const float u = __uint_as_float(__float_as_uint(y) & 0xFF807FFFu) - 512.02545f;
    float t = fmaf(u, 0.019497588f, 0.114550486f);
    t = fmaf(t, u, -0.29839927f);
    return fmaf(t, u, y);
}
__device__ __forceinline__ uint32_t pack_fixed(float lo, float hi) { return __byte_perm(__float_as_uint(lo), __float_as_uint(hi), 0x6521); }

#define PV_GROUP 4
#define POLY_MODE 1
__device__ __forceinline__ uint32_t exp2_packed(float y0, float y1, uint32_t one2) {
    const uint32_t w = pack_fixed(y0, y1);
    uint32_t m;
    asm("lop3.b32 %0, %1, 0x007F007F, %2, 0xEA;" : "=r"(m) : "r"(w), "r"(one2));
    const uint32_t d = hfma2_bf16(m, 0x3EF93EF9u, 0xBF38BF38u);
    const uint32_t e = hfma2_bf16(d, d, 0xBD71BD71u);
    return hfma2_bf16(w, e, w);
}
constexpr int KV_TILE = CHUNK_BYTES / 16;
template <int OFF> __device__ __forceinline__ void issue_qk(float (&s)[64], uint64_t qd, uint64_t kd) {
    wgmma_ss_n128<0, 0, OFF + (8 << 16)>(s, qd, kd, 0);
    wgmma_ss_n128<0, 16, OFF + 32>(s, qd, kd, 1);
}
template <int OFF> __device__ __forceinline__ void issue_pv(float (&o)[12], const uint32_t (&p)[32], uint64_t vd) {
    static_for<0, 8>([&](auto kc) {
        constexpr int k = decltype(kc)::value;
        wgmma_rs_n24<1, OFF + k * (2 * KV_GROUP_BYTES / 16)>(o, p[k * 4], p[k * 4 + 1], p[k * 4 + 2], p[k * 4 + 3], vd, 1);
    });
}
template <int OFF>
__device__ __forceinline__ void softmax_pv(const float (&s)[64], uint32_t (&p)[32], float (&o)[12], uint64_t vd, uint32_t one2) {
    static_for<0, 8 / PV_GROUP>([&](auto gc) {
        constexpr int g0 = decltype(gc)::value * PV_GROUP;
#pragma unroll
        for (int b = g0 * 2; b < (g0 + PV_GROUP) * 2; b++) {
            if ((POLY_MASK >> b) & 1) {
                p[b * 2 + 0] = exp2_packed(s[b * 4 + 0], s[b * 4 + 1], one2);
                p[b * 2 + 1] = exp2_packed(s[b * 4 + 2], s[b * 4 + 3], one2);
            } else {
                p[b * 2 + 0] = pack_bf16(ex2(s[b * 4 + 0]), ex2(s[b * 4 + 1]));
                p[b * 2 + 1] = pack_bf16(ex2(s[b * 4 + 2]), ex2(s[b * 4 + 3]));
            }
        }
#pragma unroll
        for (int i = g0 * 4; i < (g0 + PV_GROUP) * 4; i++) asm volatile("" : "+r"(p[i])::"memory");
        wg_fence();
        static_for<g0, g0 + PV_GROUP>([&](auto kc) {
            constexpr int k = decltype(kc)::value;
            wgmma_rs_n24<1, OFF + k * (2 * KV_GROUP_BYTES / 16)>(o, p[k * 4], p[k * 4 + 1], p[k * 4 + 2], p[k * 4 + 3], vd, 1);
        });
    });
    wg_commit();
}
__device__ __forceinline__ int head_pair(int hh, int i) {
    if (i == 8) return hh == 3 ? 0 : 8;
    const int q = i >> 1, t = (4 - hh) & 3;
    if ((i & 1) == 0) return t + q;
    return (hh == 1 || hh == 2) ? (q >= hh ? q - hh : t + 4 + q) : t + 4 + q;
}
template <bool LATE> __device__ __forceinline__ void store_o(float (&o)[12], int rt, int head, int wq, int lane) {
    const int g = lane >> 2, q = lane & 3;
    const float i0 = __fdividef(1.0f, __shfl_sync(~0u, o[8], lane | 3)), i1 = __fdividef(1.0f, __shfl_sync(~0u, o[10], lane | 3));
#pragma unroll
    for (int i = 0; i < 3; i++) {
        const uint32_t w0 = pack_bf16(o[i * 4] * i0, o[i * 4 + 1] * i0), w1 = pack_bf16(o[i * 4 + 2] * i1, o[i * 4 + 3] * i1);
        if (i < 2 || q == 2) {
            if constexpr (LATE) {
                const int pc = (head & 7) * 9 + head_pair(head & 3, i < 2 ? i * 4 + q : 8);
                uint32_t* op = reinterpret_cast<uint32_t*>(g_Olate) + (((rt * 9 + (pc >> 3)) * 128 + wq * 32 + g * 4 + (pc & 3)) * 4 + ((pc >> 2) & 1) * 2);
                asm volatile("st.relaxed.gpu.global.v2.u32 [%0], {%1, %2};" ::"l"(op), "r"(w0), "r"(w1) : "memory");
            } else {
                const int pc = head * 9 + head_pair(head & 3, i < 2 ? i * 4 + q : 8);
                uint32_t* op = g_O + ((rt * 72 + (pc >> 2)) * 8 + wq * 2) * 32 + g * 4 + (pc & 3);
                op[0] = w0;
                op[32] = w1;
            }
        }
    }
#pragma unroll
    for (int i = 0; i < 12; i++) o[i] = 0.f;
}
__device__ __forceinline__ void mbar_arrive(uint32_t b) { asm volatile("mbarrier.arrive.shared::cta.b64 _, [%0];" ::"r"(b) : "memory"); }
__device__ __forceinline__ void mbar_wait_sleep(uint32_t b, uint32_t ns) {
    uint32_t ok, spins = 0;
    while (true) {
        asm volatile("{\n.reg .pred p;\nmbarrier.try_wait.parity.shared::cta.b64 p, [%1], 0;\nselp.u32 %0, 1, 0, p;\n}\n" : "=r"(ok) : "r"(b) : "memory");
        if (ok) break;
        __nanosleep(ns);
        if (++spins > (1u << 21)) __trap();
    }
}
__device__ __forceinline__ void flag_signal(unsigned int* f) {
    __threadfence();
    atomicAdd(f, 1u);
}
__device__ __forceinline__ void flag_wait(const unsigned int* f, unsigned int target, unsigned int sleep_ns) {
    uint32_t v, spins = 0;
    while (true) {
        asm volatile("ld.acquire.gpu.global.u32 %0, [%1];" : "=r"(v) : "l"(f) : "memory");
        if (v >= target) break;
        if (sleep_ns) __nanosleep(sleep_ns);
        if (++spins > (1u << 21)) __trap();
    }
}
__device__ __forceinline__ uint4 hadd8_bf16(const uint4 a, const uint4 b) {
    return make_uint4(hadd2_bf16(a.x, b.x), hadd2_bf16(a.y, b.y), hadd2_bf16(a.z, b.z), hadd2_bf16(a.w, b.w));
}
__device__ __forceinline__ float sumsq2(uint32_t w) { return fmaf(bf_lo(w), bf_lo(w), bf_hi(w) * bf_hi(w)); }
__device__ __forceinline__ float sumsq8(const uint4 v) { return (sumsq2(v.x) + sumsq2(v.y)) + (sumsq2(v.z) + sumsq2(v.w)); }

enum { B_FULL = 0, B_EMPTY = 9, B_BASE = 18, B_XNDEAD = 19, B_QRDY = 20, B_FFN = 21, B_KV = 22, B_FREE = 38, B_WO = 46, B_RED = 55, B_X = 61, B_EARLY = 85, B_OS = 86, B_LATE = 94, B_BIAS = 95, B_END = 96 };

__global__ void __cluster_dims__(2, 1, 1) __launch_bounds__(384, 1)
fused_kernel(const __grid_constant__ CUtensorMap tmX, const __grid_constant__ CUtensorMap tmQ3, const __grid_constant__ CUtensorMap tmQ1,
          const __grid_constant__ CUtensorMap tm1, const __grid_constant__ CUtensorMap tm2, const __grid_constant__ CUtensorMap tmP,
          const __grid_constant__ CUtensorMap tmOut, const __grid_constant__ CUtensorMap tmXo, const __nv_bfloat16* __restrict__ b1,
          const __nv_bfloat16* __restrict__ wqkv, const __nv_bfloat16* __restrict__ w1, const __nv_bfloat16* __restrict__ w2,
          const __nv_bfloat16* __restrict__ wo, const __nv_bfloat16* __restrict__ b2,
          const uint64_t zero) {
    extern __shared__ __align__(1024) uint8_t smem[];
    const uint32_t sb = s2u(smem);
    const int tid = threadIdx.x, lane = tid & 31;
    const int warp = __shfl_sync(~0u, tid >> 5, 0);
    const uint32_t rank = blockIdx.x & 1;
    const int cl = blockIdx.x >> 1;
    const int rb = (cl & 7) * 2 + rank;
    const int j = cl >> 3;
    const uint32_t bar0 = sb + K1_OFF_BAR;
    const uint32_t full0 = bar0 + B_FULL * 8, empty0 = bar0 + B_EMPTY * 8, xbar0 = bar0 + B_X * 8;
    const int head = blockIdx.x >> 2, quarter = blockIdx.x & 3;
    const int rt = quarter * 8 + (head >> 2), ct = head & 3;
    const int rot = head >> 3;
    const int ks0 = ((((head >> 3) + 2) & 3) * 9);
    volatile uint32_t* slow_flag = reinterpret_cast<volatile uint32_t*>(smem + K1_OFF_BAR + B_END * 8);

    if (__builtin_expect(warp < 8, 1)) {
        PROF(0);
        PROFT(48);
        if (lane == 0) {
#pragma unroll
            for (int i = 0; i < 3; i++) mbar_init(xbar0 + (warp * 3 + i) * 8, 1);
            fence_barrier_init();
#pragma unroll 1
            for (int i = 0; i < 3; i++) {
                const uint32_t xb = xbar0 + (warp * 3 + i) * 8;
                mbar_expect(xb, 6144);
                tma4d(sb + i * 49152 + warp * 6144, &tmX, 0, 0, i * 3, rb * 16 + warp * 2, xb);
            }
        }
        __syncwarp();
        cluster_arrive();
        PROF(22);
        reg_alloc<240>();
        PROF(23);
        float rs0, rs1;
        {
            const uint32_t la = sb + (warp * 2 + ((lane >> 3) & 1)) * 3072 + (lane & 7) * 128;
            uint32_t off[4];
#pragma unroll
            for (int i = 0; i < 4; i++) off[i] = la + (((i * 2 + (lane >> 4)) ^ (lane & 7)) << 4);
            float c1[4] = {0.f, 0.f, 0.f, 0.f}, c2[4] = {0.f, 0.f, 0.f, 0.f}, c3[4] = {0.f, 0.f, 0.f, 0.f};
            uint32_t a[36][4];
#pragma unroll
            for (int t = 0; t < 3; t++) {
                mbar_wait(xbar0 + (warp * 3 + t) * 8, 0);
                PROF(24 + t);
#pragma unroll
                for (int i = 0; i < 12; i++) ldsm4(a[t * 12 + i], off[i & 3] + t * 49152 + (i >> 2) * 1024);
#pragma unroll
                for (int i = t * 12; i < t * 12 + 12; i++) {
                    mma16816(c3, a[i], 0x3F803F80u, 0x3F803F80u);
                    mma16816(c1, a[i], a[i][0], a[i][2]);
                    mma16816(c2, a[i], a[i][1], a[i][3]);
                }
            }
            PROF(27);
            const int gg = lane >> 2, src = (lane & ~3) | (gg >> 1);
            const float m0 = c3[0] * (1.0f / DM), m1 = c3[2] * (1.0f / DM);
            const uint32_t mc0 = pack_bf16(-m0, -m0), mc1 = pack_bf16(-m1, -m1);
#pragma unroll
            for (int i = 0; i < 36; i++) {
#pragma unroll
                for (int k = 0; k < 4; k++) a[i][k] = hadd2_bf16(a[i][k], (k & 1) ? mc1 : mc0);
                stsm4(off[i & 3] + (i / 12) * 49152 + ((i >> 2) % 3) * 1024, a[i]);
            }
            const float q0 = __shfl_sync(~0u, (gg & 1) ? c1[1] : c1[0], src), q1 = __shfl_sync(~0u, (gg & 1) ? c2[3] : c2[2], src);
            rs0 = rsqrtf(fmaxf(fmaf(-m0, m0, q0 * (1.0f / DM)), 0.f) + 1e-5f);
            rs1 = rsqrtf(fmaxf(fmaf(-m1, m1, q1 * (1.0f / DM)), 0.f) + 1e-5f);
            if (__any_sync(~0u, fabsf(m0) * rs0 > 0.25f || fabsf(m1) * rs1 > 0.25f)) {
                const float d0 = -m0 - bf_lo(mc0), d1 = -m1 - bf_lo(mc1);
                const uint32_t md0 = pack_bf16(d0, d0), md1 = pack_bf16(d1, d1);
#pragma unroll 1
                for (int i = 0; i < 9; i++) {
#pragma unroll
                    for (int k4 = 0; k4 < 4; k4++) {
                        const uint32_t ad = off[k4] + (i / 3) * 49152 + (i % 3) * 1024;
                        uint32_t b[4];
                        ldsm4(b, ad);
#pragma unroll
                        for (int k = 0; k < 4; k++) b[k] = hadd2_bf16(b[k], (k & 1) ? md1 : md0);
                        stsm4(ad, b);
                    }
                }
            }
        }
        PROF(28);
        const int wg = warp >> 2, wq = warp & 3;
        fence_proxy_async();
        named_bar_sync(1 + wg, 128);
        cluster_wait();
        PROF(1); PROFT(59);

        const int g = lane >> 2, q = lane & 3;
        K1Ctx c;
        c.full0 = full0;
        c.rel_addr = 0;
        c.descA = mk_desc(zero, sb + wg * 8 * 3072, 16, 3072, 1);
        c.descB = mk_desc(zero, sb + K1_OFF_RING, 2048, 1024, 1);
        c.phase = 0;
        c.rdy = 0;
        uint32_t biasq = sb + K1_OFF_BIAS + q * 32;
        uint32_t bq[8];

        uint32_t h[144];
        float accA[32], accB[32];
        uint32_t qo[3], qt[3];
        {
            float accQ[108];
            uint32_t rel = 0;
            if (lane == 0 && wq < 2) asm("mapa.shared::cluster.u32 %0, %1, %2;" : "=r"(rel) : "r"(empty0), "r"(wq));
#pragma unroll 1
            for (int r = 0; r < 2; r++) {
                static_for<0, 9>([&](auto sc) {
                    constexpr int s = decltype(sc)::value;
                    c.begin_stage(s);
                    const uint64_t da = c.descA + (r ? a_off(18 + 2 * s) : a_off(2 * s));
                    wgmma_ss_n216<1, 0, ((2 * s) % 9) * 512>(accQ, da, c.descB, (r | s) != 0);
                    wgmma_ss_n216<1, 2, ((2 * s + 1) % 9) * 512>(accQ, da, c.descB, 1);
                    c.probe_next(s);
                    c.end_stage(s);
                    c.rel_addr = rel;
                });
                c.phase ^= 1;
            }
            PROF(2); PROFWT(54);
            mbar_wait(bar0 + B_BIAS * 8, 0);
            wg_wait<0>();
            reg_fence(accQ);
#pragma unroll
            for (int grp = 0; grp < 3; grp++) {
                const int G = 3 * j + grp, type = G >> 3;
                const uint32_t base = (G & 7) * 4 * KV_HEAD_BYTES + (rb * 16 + warp * 2) * KV_GROUP_BYTES + g * 16 + (type == 0 ? Q_OFFSET : (type == 2 ? 256 : 0));
                qo[grp] = base + (q >> 1) * 128 + (q & 1) * 8;
                qt[grp] = base + q * KV_HEAD_BYTES + (type == 0 ? 256 : (type == 2 ? 264 : 512));
#pragma unroll
                for (int hf = 0; hf < 2; hf++) {
                    const float sc = (hf ? rs1 : rs0) * (type == 0 ? QSCALE : ((type == 1 && ((POLY_MASK >> (warp * 2 + hf)) & 1)) ? 2.f : 1.f));
                    uint32_t w[9];
#pragma unroll
                    for (int i = 0; i < 9; i++) w[i] = pack_bf16(accQ[(grp * 9 + i) * 4 + hf * 2] * sc, accQ[(grp * 9 + i) * 4 + hf * 2 + 1] * sc);
                    uint32_t* d = h + 32 + hf * 32 + grp * 8;
                    d[0] = w[0]; d[1] = w[1]; d[2] = w[3]; d[3] = q >= 1 ? w[2] : w[4];
                    d[4] = w[5]; d[5] = q >= 2 ? w[4] : w[6]; d[6] = w[7]; d[7] = w[8];
                    h[32 + hf * 32 + 24 + grp] = q == 0 ? w[2] : (q == 1 ? w[4] : w[6]);
                }
            }
        }
        PROF(3); PROFWT(55); PROFT(60);
#pragma unroll
        for (int i = 32; i < 112; i++)
            if (i >= 96 || (i & 31) >= 27) asm volatile("mov.u32 %0, 0;" : "=r"(h[i]));
#pragma unroll
        for (int i = 0; i < 32; i++) asm volatile("mov.f32 %0, 0f00000000;" : "=f"(accB[i]));
#pragma unroll
        for (int i = 0; i < 8; i++) bq[i] = 0;
#pragma unroll 1
        for (int p = 0; p < 4; p++) {
            uint8_t* const qb = g_QKV + p * KV_GROUP_BYTES;
            tile_pair<false, false>(c, accA, accB, h, [&](auto sc) {
                constexpr int s = decltype(sc)::value;
                if constexpr (s == 0) {
                    reg_fence(accB);
#pragma unroll
                    for (int i = 0; i < 80; i++) h[i] = h[i + 32];
                }
                if constexpr (s >= 1 && s <= 6) {
                    constexpr int grp = (s - 1) >> 1, k = ((s - 1) & 1) * 2;
                    st_pred2(p < 2, qb + qo[grp] + k * KV_HEAD_BYTES, h[grp * 8 + k * 2], h[grp * 8 + k * 2 + 1]);
                    st_pred2(p < 2, qb + qo[grp] + (k + 1) * KV_HEAD_BYTES, h[grp * 8 + k * 2 + 2], h[grp * 8 + k * 2 + 3]);
                    if constexpr (k == 2) st_pred1(p < 2, qb + qt[grp], h[24 + grp]);
                }
                if constexpr (s < 4) gelu_blocks<s * 2, 2, 80>(accB, h, bq, rs0, rs1);
                if constexpr (s == 4) load_bias(bq, biasq);
                if constexpr (s == 5) reg_fence(accA);
                if constexpr (s >= 5) gelu_blocks<(s - 5) * 2, 2, 96>(accA, h, bq, rs0, rs1);
                if constexpr (s == 8) load_bias(bq, biasq + 128);
            });
            if (p == 1) asm volatile("bar.arrive 3, 352;" ::: "memory");
            biasq += 256;
            PROF(33 + p);
        }
        PROF(4); PROFWT(56); PROFT(61);
        tile_pair<false, true>(c, accA, accB, h, [&](auto sc) {
            constexpr int s = decltype(sc)::value;
            if constexpr (s == 0) reg_fence(accB);
            if constexpr (s < 4) gelu_blocks<s * 2, 2, 112>(accB, h, bq, rs0, rs1);
            if constexpr (s == 4) load_bias(bq, biasq);
            if constexpr (s == 5) { reg_fence(accA); if (tid == wg * 128) mbar_arrive(bar0 + B_XNDEAD * 8); }
            if constexpr (s == 5 || s == 6) gelu_blocks<(s - 5) * 3, 3, 128>(accA, h, bq, rs0, rs1);
            if constexpr (s == 7) gelu_blocks<6, 2, 128>(accA, h, bq, rs0, rs1);
            if constexpr (s == 3 || s == 7) reg_fence(h);
        });
        PROF(5); PROFWT(57); PROFT(62);
        uint4* pout = g_part + j * SLAB + rb * 36 * 256 + tid;
#pragma unroll 1
        for (int p = 0; p < 4; p++) {
            tile_pair<true, true>(c, accA, accB, h, [&](auto sc) {
                constexpr int s = decltype(sc)::value;
                if constexpr (s == 0) reg_fence(accB);
                if constexpr (s < 4) store_part<s>(accB, pout);
                if constexpr (s == 5) reg_fence(accA);
                if constexpr (s >= 5) store_part<s - 5>(accA, pout + 1024);
            });
            pout += 2048;
            PROF(6 + p);
        }
        wg_wait<0>();
        c.release(8);
        reg_fence(accB);
        store_part<0>(accB, pout); store_part<1>(accB, pout); store_part<2>(accB, pout); store_part<3>(accB, pout);
        __syncwarp();
        if (lane == 0) mbar_arrive(bar0 + B_FFN * 8);
        PROF(10); PROFWT(58);
        PROFT(49);

        mbar_wait(bar0 + B_QRDY * 8, 0);
        const uint32_t slow = __any_sync(~0u, *slow_flag != 0);
        const uint64_t kd0 = mk_desc(zero, sb + SM_KV, 0, KV_GROUP_BYTES, 0);
        const uint64_t vd0 = mk_desc(zero, sb + SM_KV + 256, KV_GROUP_BYTES, 128, 0);
        const uint64_t qd0 = mk_desc(zero, sb + SM_Q + wg * 4096, 128, 512, 0);
        const uint32_t kvbar = bar0 + B_KV * 8;
        float o[12];
#pragma unroll
        for (int i = 0; i < 12; i++) o[i] = 0.f;
        PROF(16);
        PROFT(50);
        if (__builtin_expect(!slow, 1)) {
            const uint32_t one2 = 0x3F803F80u + (uint32_t)zero;
            float s0[64], s1[64];
            uint32_t p0[32], p1[32];
            mbar_wait(kvbar, 0);
            reg_fence(o);
            wg_fence();
            issue_qk<0>(s0, qd0, kd0);
            wg_commit();
            wg_commit();
            uint64_t qd = qd0;
            const uint32_t fre = (tid == wg * 128) ? bar0 + B_FREE * 8 - 8 : 0;
#pragma unroll 1
            for (int pass = 0; pass < 4; pass++) {
                uint64_t vd = vd0, kd = kd0;
                uint32_t bn = kvbar + 8;
#pragma unroll 1
                for (int it = 0; it < 8; it++) {
                    if (pass == 0) {
                        mbar_wait(bn, 0);
                        mbar_wait(it == 7 ? bn : bn + 8, 0);
                    }
                    if (it == 0 && pass != 0) {
                        wg_wait<0>();
                        reg_fence(o);
                        store_o<false>(o, quarter * 8 + ((pass - 1 + rot) & 3) * 2 + wg, head, wq, lane);
                        reg_fence(o);
                        __syncwarp();
                        if (lane == 0) mbar_arrive(bar0 + (B_OS + pass * 2 - 2 + wg) * 8);
                    }
                    wg_wait<1>();
                    reg_fence(s0);
                    wg_fence();
                    issue_qk<KV_TILE>(s1, qd, kd);
                    wg_commit();
                    if (pass == 3 && it > 0 && fre) mbar_arrive(fre + it * 8);
                    softmax_pv<0>(s0, p0, o, vd, one2);
                    kd += 2 * KV_TILE;
                    if (it == 7) { kd = kd0; qd += 512; }
                    wg_wait<1>();
                    reg_fence(s1);
                    wg_fence();
                    issue_qk<0>(s0, qd, kd);
                    wg_commit();
                    softmax_pv<KV_TILE>(s1, p1, o, vd, one2);
                    vd += 2 * KV_TILE; bn += 16;
                }
                if (pass == 0) PROF(17);
            }
            wg_wait<0>();
            reg_fence(o);
            reg_fence(s0);
            reg_fence(s1);
            store_o<true>(o, quarter * 8 + ((3 + rot) & 3) * 2 + wg, head, wq, lane);
        } else {
#pragma unroll 1
            for (int pass = 0; pass < 4; pass++) {
                float m0 = -INFINITY, m1 = -INFINITY;
                float s[64];
                uint32_t p[32];
#pragma unroll 1
                for (int t = 0; t < 16; t++) {
                    mbar_wait(kvbar + t * 8, 0);
                    wg_fence();
                    issue_qk<0>(s, qd0 + pass * 512, kd0 + t * KV_TILE);
                    wg_commit();
                    wg_wait<0>();
                    reg_fence(s);
                    float a0 = m0, a1 = m1;
#pragma unroll
                    for (int k = 0; k < 16; k++) {
                        if ((POLY_MASK >> k) & 1) {
#pragma unroll
                            for (int i = 0; i < 4; i++) s[k * 4 + i] *= 0.5f;
                        }
                        a0 = fmaxf(a0, fmaxf(s[k * 4 + 0], s[k * 4 + 1]));
                        a1 = fmaxf(a1, fmaxf(s[k * 4 + 2], s[k * 4 + 3]));
                    }
                    a0 = fmaxf(a0, __shfl_xor_sync(~0u, a0, 1)); a1 = fmaxf(a1, __shfl_xor_sync(~0u, a1, 1));
                    a0 = fmaxf(a0, __shfl_xor_sync(~0u, a0, 2)); a1 = fmaxf(a1, __shfl_xor_sync(~0u, a1, 2));
                    const float r0 = ex2(m0 - a0), r1 = ex2(m1 - a1);
                    m0 = a0; m1 = a1;
#pragma unroll
                    for (int i = 0; i < 3; i++) { o[i * 4] *= r0; o[i * 4 + 1] *= r0; o[i * 4 + 2] *= r1; o[i * 4 + 3] *= r1; }
#pragma unroll
                    for (int k = 0; k < 16; k++) {
                        p[k * 2 + 0] = pack_bf16(ex2(s[k * 4 + 0] - m0), ex2(s[k * 4 + 1] - m0));
                        p[k * 2 + 1] = pack_bf16(ex2(s[k * 4 + 2] - m1), ex2(s[k * 4 + 3] - m1));
                    }
                    reg_fence(p);
                    reg_fence(o);
                    wg_fence();
                    issue_pv<0>(o, p, vd0 + t * KV_TILE);
                    wg_commit();
                    wg_wait<0>();
                    reg_fence(o);
                }
                if (pass < 3) {
                    store_o<false>(o, quarter * 8 + ((pass + rot) & 3) * 2 + wg, head, wq, lane);
                    __syncwarp();
                    if (lane == 0) mbar_arrive(bar0 + (B_OS + pass * 2 + wg) * 8);
                }
            }
            store_o<true>(o, quarter * 8 + ((3 + rot) & 3) * 2 + wg, head, wq, lane);
            if (tid == wg * 128)
                for (int i = 0; i < 7; i++) mbar_arrive(bar0 + (B_FREE + i) * 8);
        }
        PROF(18);
        PROFT(51);

        if (tid == wg * 128) mbar_arrive(bar0 + (B_FREE + 7) * 8);
        const int t128 = tid & 127;
        uint32_t bv[9];
        uint2 fv[9];
        mbar_wait(bar0 + B_BASE * 8, 0);
#pragma unroll
        for (int i = 0; i < 9; i++) {
            bv[i] = __ldg(reinterpret_cast<const uint32_t*>(b2 + ct * 144 + wg * 72 + q * 2) + i * 4);
            fv[i] = __ldcg(g_ffn + (blockIdx.x * 18 + wg * 9 + i) * 128 + t128);
        }
        float acc[36];
        const uint64_t od = mk_desc(zero, sb, 1024, 128, 0), wd = mk_desc(zero, sb + wg * 9 * 128, 2304, 128, 0);
        static_for<0, 9>([&](auto pc) {
            constexpr int p = decltype(pc)::value;
            mbar_wait(bar0 + (B_WO + p) * 8, 0);
            wg_fence();
            wgmma_ss_n72<1, sm_ostep(p * 3) / 16, sm_wstep(p * 3) / 16>(acc, od, wd, p != 0);
            wgmma_ss_n72<1, sm_ostep(p * 3 + 1) / 16, sm_wstep(p * 3 + 1) / 16>(acc, od, wd, 1);
            wgmma_ss_n72<1, sm_ostep(p * 3 + 2) / 16, sm_wstep(p * 3 + 2) / 16>(acc, od, wd, 1);
            wg_commit();
            if constexpr (p == 1) {
                wg_wait<1>();
                if (t128 == 0) mbar_arrive(bar0 + B_EARLY * 8);
            }
        });
        wg_wait<0>();
        reg_fence(acc);
        PROF(29);
        uint4 al[9];
        {
            const uint4* ap = g_Olate + rt * 9 * 128 + t128;
            uint32_t spins = 0;
            bool ok;
            do {
                ok = true;
#pragma unroll
                for (int k = 0; k < 9; k++)
                    asm volatile("ld.relaxed.gpu.global.v4.u32 {%0, %1, %2, %3}, [%4];" : "=r"(al[k].x), "=r"(al[k].y), "=r"(al[k].z), "=r"(al[k].w) : "l"(ap + k * 128) : "memory");
#pragma unroll
                for (int k = 0; k < 9; k++) ok = ok && al[k].x != O_EMPTY && al[k].y != O_EMPTY && al[k].z != O_EMPTY && al[k].w != O_EMPTY;
                if (++spins > (1u << 20)) __trap();
            } while (!__all_sync(~0u, ok));
        }
        PROF(19);
        mbar_wait(bar0 + B_LATE * 8, 0);
        PROF(20);
        wg_fence();
        static_for<27, 36>([&](auto kc) {
            constexpr int k = decltype(kc)::value;
            wgmma_rs_n72<1, sm_wstep(k) / 16>(acc, al[k - 27].x, al[k - 27].y, al[k - 27].z, al[k - 27].w, wd, 1);
        });
        wg_commit();
        PROF(31);
        uint32_t* st = reinterpret_cast<uint32_t*>(smem + sm_piece(0) + wg * 9216) + (wq * 16 + g) * 36 + q;
        float bs[36];
#pragma unroll
        for (int i = 0; i < 9; i++) {
            const uint32_t x0 = st[i * 4], x1 = st[i * 4 + 288];
            bs[i * 4 + 0] = fmaf(bf_lo(fv[i].x), 0.5f, bf_lo(x0) + bf_lo(bv[i]));
            bs[i * 4 + 1] = fmaf(bf_hi(fv[i].x), 0.5f, bf_hi(x0) + bf_hi(bv[i]));
            bs[i * 4 + 2] = fmaf(bf_lo(fv[i].y), 0.5f, bf_lo(x1) + bf_lo(bv[i]));
            bs[i * 4 + 3] = fmaf(bf_hi(fv[i].y), 0.5f, bf_hi(x1) + bf_hi(bv[i]));
        }
        reg_fence(bs);
        wg_wait<0>();
        reg_fence(acc);
        PROF(32);
#pragma unroll
        for (int i = 0; i < 9; i++) {
            st[i * 4] = pack_bf16(acc[i * 4] + bs[i * 4], acc[i * 4 + 1] + bs[i * 4 + 1]);
            st[i * 4 + 288] = pack_bf16(acc[i * 4 + 2] + bs[i * 4 + 2], acc[i * 4 + 3] + bs[i * 4 + 3]);
        }
        fence_proxy_async();
        named_bar_sync(1 + wg, 128);
        if (t128 == 0) {
            asm volatile("cp.async.bulk.tensor.2d.global.shared::cta.bulk_group [%0, {%2, %3}], [%1];"
                         ::"l"(&tmOut), "r"(sb + sm_piece(0) + wg * 9216), "r"(ct * 144 + wg * 72), "r"(rt * 64) : "memory");
            asm volatile("cp.async.bulk.commit_group;" ::: "memory");
            asm volatile("cp.async.bulk.wait_group.read 0;" ::: "memory");
        }
        PROF(21);
        PROFT(52);
    } else {
        reg_dealloc<24>();
        if (warp == 8 && lane == 0) {
            prefetch_tmap(&tmQ3); prefetch_tmap(&tmQ1); prefetch_tmap(&tm1); prefetch_tmap(&tm2);
            #pragma unroll 1
            for (int i = 0; i < 9; i++) { mbar_init(full0 + i * 8, 1); mbar_init(empty0 + i * 8, 4); mbar_init(bar0 + (B_WO + i) * 8, 2); }
            mbar_init(bar0 + B_BASE * 8, 3); mbar_init(bar0 + B_XNDEAD * 8, 2); mbar_init(bar0 + B_QRDY * 8, 3); mbar_init(bar0 + B_FFN * 8, 8); mbar_init(bar0 + B_EARLY * 8, 2); mbar_init(bar0 + B_LATE * 8, 2); mbar_init(bar0 + B_BIAS * 8, 96);
#pragma unroll 1
            for (int i = 0; i < 16; i++) { mbar_init(bar0 + (B_KV + i) * 8, 1); mbar_init(bar0 + (B_FREE + (i & 7)) * 8, 2); if (i < 6) mbar_init(bar0 + (B_RED + i) * 8, 1); if (i < 6) mbar_init(bar0 + (B_OS + i) * 8, 4); }
            *slow_flag = 0;
            fence_barrier_init();
        }
        __syncwarp();
        cluster_arrive();
        cluster_wait();
        const uint8_t* kvsrc = g_QKV + (size_t)head * KV_HEAD_BYTES;
        if (warp == 8) {
            if (lane == 0) {
                int st = 0, u = rank, tile = -4;
                int es = 5;
                uint32_t eph = 1;
#pragma unroll 1
                for (int n = 0; n < 99; n++) {
                    mbar_wait(empty0 + es * 8, eph);
                    const uint32_t fb = full0 + st * 8, dst = sb + K1_OFF_RING + u * 8192;
                    mbar_expect(fb, 16384);
                    if (tile < 0) {
                        tma3d_mc(dst, &tmQ3, j * 216, n * 32 + rank * 16, 0, fb, 3);
                        tma2d_mc(dst + 6144, &tmQ1, j * 216 + 192, n * 32 + rank * 16, fb, 3);
                    } else if (tile < 9) {
                        tma2d_mc(dst, &tm1, j * 576 + tile * 64, u * 64, fb, 3);
                    } else {
                        tma2d_mc(dst, &tm2, (tile - 9) * 64, j * 576 + u * 64, fb, 3);
                    }
                    u += 2;
                    if (u >= 9) { u -= 9; tile++; }
                    if (++st == 9) st = 0;
                    if (++es == 9) { es = 0; eph ^= 1; }
                }
                mbar_wait(empty0 + 8 * 8, 0);
                mbar_wait(bar0 + B_QRDY * 8, 0);
                asm volatile("fence.proxy.async;" ::: "memory");
#pragma unroll 1
                for (int i = 11; i < NCHUNK; i++) {
                    mbar_expect(bar0 + (B_KV + i) * 8, CHUNK_BYTES);
                    bulk_load(sb + SM_KV + i * CHUNK_BYTES, kvsrc + i * CHUNK_BYTES, CHUNK_BYTES, bar0 + (B_KV + i) * 8);
                }
                const uint8_t* wsrc = g_Wo + ct * WO_TILE_BYTES;
                prefetch_tmap(&tmOut);
                mbar_wait_sleep(bar0 + B_BASE * 8, 500);
#pragma unroll 1
                for (int p = 0; p < 9; p++) {
                    if (p > 0) mbar_wait_sleep(bar0 + (B_FREE + p - 1) * 8, p == 1 ? 500 : 40);
                    const int k = ks0 + p * 3 >= 36 ? ks0 + p * 3 - 36 : ks0 + p * 3;
                    mbar_expect(bar0 + (B_WO + p) * 8, 13824);
                    bulk_load(sb + (p == 0 ? sm_piece(0) : (p == 1 ? sm_piece(1) : SM_KV + (p - 2) * PIECE)), wsrc + k * 4608, 13824, bar0 + (B_WO + p) * 8);
                }
                const int kl = ks0 == 0 ? 27 : ks0 - 9;
                mbar_expect(bar0 + B_LATE * 8, 9 * 4608);
                bulk_load(sb + sm_wstep(27), wsrc + kl * 4608, 8 * 4608, bar0 + B_LATE * 8);
                bulk_load(sb + sm_wstep(35), wsrc + (kl + 8) * 4608, 4608, bar0 + B_LATE * 8);
            }
        } else {
            const int ht = tid - 288;
            if (ht == 64) prefetch_l2(wqkv + blockIdx.x * (DM * 3 * DM / 128), DM * 3 * DM / 64);
            if (ht < 72) {
                const uint4 v = __ldg(reinterpret_cast<const uint4*>(b1 + j * 576) + ht);
                uint32_t* sbias = reinterpret_cast<uint32_t*>(smem + K1_OFF_BIAS) + (ht >> 3) * 32 + (ht & 7);
                sbias[0] = v.x; sbias[8] = v.y; sbias[16] = v.z; sbias[24] = v.w;
            }
            mbar_arrive(bar0 + B_BIAS * 8);
            PROFH(37);
#pragma unroll
            for (int i = 0; i < 3; i++) g_Olate[blockIdx.x * 288 + i * 96 + ht] = make_uint4(O_EMPTY, O_EMPTY, O_EMPTY, O_EMPTY);
#pragma unroll 1
            for (int i = ht; i < 512; i += 96) {
                const int key = i & 127;
                uint8_t* p = g_QKV + (size_t)(j * 4 + (i >> 7)) * KV_HEAD_BYTES + (rb * 16 + (key >> 3)) * KV_GROUP_BYTES + 512 + (key & 7) * 16;
                *reinterpret_cast<uint32_t*>(p + 4) = ((POLY_MASK >> (key >> 3)) & 1) ? 0x3F804000u : 0x00003F80u;
                *reinterpret_cast<uint32_t*>(p + 12) = 0x00003F80u;
            }
            if (ht == 32) prefetch_l2(w1 + blockIdx.x * (DM * FF / 128), DM * FF / 64);
#pragma unroll 2
            for (int i = blockIdx.x * 324 + ht; i < blockIdx.x * 324 + 324; i += 96) {
                const int k = i / 72, nc = i - k * 72, c4 = nc / 18;
                *reinterpret_cast<uint4*>(g_Wo + c4 * WO_TILE_BYTES + (k >> 3) * 2304 + (nc - c4 * 18) * 128 + (k & 7) * 16) =
                    __ldg(reinterpret_cast<const uint4*>(wo) + i);
            }
            PROFH(38);
            named_bar_sync(3, 352);
            if (ht == 32) prefetch_l2(w2 + blockIdx.x * (DM * FF / 128), DM * FF / 64);
            if (ht == 0) {
                flag_signal(&g_flags.qkv_stored[rb]);
                flag_wait(&g_flags.qkv_stored[rb], 8, 200);
            }
            named_bar_sync(7, 96);
            PROFH(39);
#pragma unroll 1
            for (int i = warp - 9; i < 16; i += 3) {
                const int hd = j * 4 + (i >> 2), key = (i & 3) * 32 + lane;
                const uint8_t* p = g_QKV + (size_t)hd * KV_HEAD_BYTES + (rb * 16 + (key >> 3)) * KV_GROUP_BYTES + (key & 7) * 16;
                const uint4 a = __ldcg(reinterpret_cast<const uint4*>(p)), b = __ldcg(reinterpret_cast<const uint4*>(p + 128));
                float n = sumsq2(__ldcg(reinterpret_cast<const uint32_t*>(p + 512))) + sumsq8(a) + sumsq8(b);
                if ((POLY_MASK >> (key >> 3)) & 1) n *= 0.25f;
#pragma unroll
                for (int o = 16; o; o >>= 1) n = fmaxf(n, __shfl_xor_sync(~0u, n, o));
                if (lane == 0) g_kmax[hd * 64 + rb * 4 + (i & 3)] = n;
            }
            named_bar_sync(7, 96);
            PROFH(40);
            if (ht == 0) {
                flag_signal(&g_flags.kv_ready);
                flag_wait(&g_flags.kv_ready, 128, 300);
                mbar_wait_sleep(bar0 + B_XNDEAD * 8, 300);
            }
            named_bar_sync(7, 96);
            PROFH(41);
            float kmax2;
            {
                const float2 v = __ldcg(reinterpret_cast<const float2*>(g_kmax + head * 64 + lane * 2));
                kmax2 = fmaxf(v.x, v.y);
#pragma unroll
                for (int o = 16; o; o >>= 1) kmax2 = fmaxf(kmax2, __shfl_xor_sync(~0u, kmax2, o));
            }
            asm volatile("fence.proxy.async;" ::: "memory");
            int chunk = warp - 9;
#pragma unroll 1
            for (int r = ht; r < 512; r += 96) {
                if (lane == 0 && chunk < 11) {
                    mbar_expect(bar0 + (B_KV + chunk) * 8, CHUNK_BYTES);
                    bulk_load(sb + SM_KV + chunk * CHUNK_BYTES, kvsrc + chunk * CHUNK_BYTES, CHUNK_BYTES, bar0 + (B_KV + chunk) * 8);
                }
                chunk += 3;
                const uint8_t* p = kvsrc + Q_OFFSET + (quarter * 64 + (((r >> 3) + rot * 16) & 63)) * KV_GROUP_BYTES + (r & 7) * 16;
                const uint4 a = __ldcg(reinterpret_cast<const uint4*>(p)), b = __ldcg(reinterpret_cast<const uint4*>(p + 128));
                const uint32_t e = __ldcg(reinterpret_cast<const uint32_t*>(p + 256));
                const float cc = sqrtf((sumsq2(e) + sumsq8(a) + sumsq8(b)) * kmax2) * 1.02f;
                if (!(cc <= 58.f)) *slow_flag = 1;
                uint4* dst = reinterpret_cast<uint4*>(smem + SM_Q + (r >> 3) * 512 + (r & 7) * 16);
                dst[0] = a;
                dst[8] = b;
                dst[16] = make_uint4(e, pack_bf16(-cc, 768.f), 0u, 0u);
                dst[24] = make_uint4(0u, POLY_MODE ? 0xBFFF0000u : 0xC0000000u, 0u, 0u);
            }
            named_bar_sync(7, 96);
            if (*slow_flag) {
#pragma unroll 1
                for (int r = ht; r < 512; r += 96) {
                    uint32_t* dst = reinterpret_cast<uint32_t*>(smem + SM_Q + (r >> 3) * 512 + (r & 7) * 16);
                    dst[65] = 0u;
                    dst[97] = 0u;
                }
            }
            fence_proxy_async();
            __syncwarp();
            if (lane == 0) mbar_arrive(bar0 + B_QRDY * 8);
            PROFH(42);
            if (ht == 0) {
                mbar_wait_sleep(bar0 + B_FFN * 8, 300);
                flag_signal(&g_flags.ffn_done[rb]);
                flag_wait(&g_flags.ffn_done[rt >> 1], 8, 300);
            }
            named_bar_sync(7, 96);
            {
                const int w3 = warp - 9;
                const uint32_t rbar = bar0 + (B_RED + w3 * 2) * 8, rbuf = SM_RED + w3 * 8192;
                const int u0 = ((rt >> 1) * 36 + ct * 9) * 256 + (rt & 1) * 128;
                mbar_wait_sleep(bar0 + (B_KV + 15) * 8, 500);
                asm volatile("fence.proxy.async;" ::: "memory");
#pragma unroll 1
                for (int i = -2; i < 12; i++) {
                    if (i >= 0) {
                        __nanosleep(400);
                        mbar_wait(rbar + (i & 1) * 8, (i >> 1) & 1);
                        const uint4* sp = reinterpret_cast<const uint4*>(smem + rbuf + (i & 1) * 4096) + lane;
                        const uint4 v = hadd8_bf16(hadd8_bf16(hadd8_bf16(sp[0], sp[32]), hadd8_bf16(sp[64], sp[96])),
                                                   hadd8_bf16(hadd8_bf16(sp[128], sp[160]), hadd8_bf16(sp[192], sp[224])));
                        const int bx = i * 3 + w3;
                        uint2* fp = g_ffn + (blockIdx.x * 18 + (bx >> 2) * 2) * 128 + (bx & 3) * 32 + lane;
                        fp[0] = make_uint2(v.x, v.y);
                        fp[128] = make_uint2(v.z, v.w);
                    }
                    __syncwarp();
                    if (lane == 0 && i < 10) {
                        const int bx = (i + 2) * 3 + w3;
                        mbar_expect(rbar + (i & 1) * 8, 4096);
                        tma2d(sb + rbuf + (i & 1) * 4096, &tmP, (u0 + (bx >> 2) * 256 + (bx & 3) * 32) * 2, 0, rbar + (i & 1) * 8);
                    }
                }
            }
            __syncwarp();
            if (lane == 0) mbar_arrive(bar0 + B_BASE * 8);
            PROFH(43);
            if (ht == 0) {
#pragma unroll 1
                for (int i = 0; i < 6; i++) {
                    mbar_wait_sleep(bar0 + (B_OS + i) * 8, 200);
                    flag_signal(&g_flags.o_done[quarter * 8 + (((i >> 1) + rot) & 3) * 2 + (i & 1)]);
                }
            } else if (ht == 32) {
                const uint8_t* osrc = reinterpret_cast<const uint8_t*>(g_O) + rt * 73728;
                mbar_wait_sleep(bar0 + B_BASE * 8, 500);
                mbar_wait_sleep(bar0 + B_FREE * 8, 500);
                flag_wait(&g_flags.o_done[rt], 24, 100);
                if (atomicAdd(&g_flags.exited, 1u) == gridDim.x - 1) {
                    unsigned int* f = reinterpret_cast<unsigned int*>(&g_flags);
#pragma unroll 1
                    for (int i = 0; i < (int)(sizeof(Flags) / 4); i++) f[i] = 0;
                }
                prefetch_tmap(&tmXo);
                asm volatile("fence.proxy.async;" ::: "memory");
#pragma unroll 1
                for (int p = 0; p < 9; p++) {
                    if (p > 1) mbar_wait_sleep(bar0 + (B_FREE + p - 1) * 8, 40);
                    const int k = ks0 + p * 3 >= 36 ? ks0 + p * 3 - 36 : ks0 + p * 3;
                    mbar_expect(bar0 + (B_WO + p) * 8, 6144);
                    bulk_load(sb + 13824 + (p == 0 ? sm_piece(0) : (p == 1 ? sm_piece(1) : SM_KV + (p - 2) * PIECE)), osrc + k * 2048, 6144, bar0 + (B_WO + p) * 8);
                }
                mbar_expect(bar0 + B_LATE * 8, 2 * 9216);
                mbar_wait(bar0 + B_EARLY * 8, 0);
                tma2d(sb + sm_piece(0), &tmXo, ct * 144, rt * 64, bar0 + B_LATE * 8);
                tma2d(sb + sm_piece(0) + 9216, &tmXo, ct * 144 + 72, rt * 64, bar0 + B_LATE * 8);
            }
        }
    }
}

typedef CUresult (*EncodeFn)(CUtensorMap*, CUtensorMapDataType, cuuint32_t, void*, const cuuint64_t*, const cuuint64_t*, const cuuint32_t*,
                             const cuuint32_t*, CUtensorMapInterleave, CUtensorMapSwizzle, CUtensorMapL2promotion, CUtensorMapFloatOOBfill);

void make_map(EncodeFn fn, CUtensorMap* m, const void* base, int rank, const cuuint64_t* dims, const cuuint64_t* strides, const cuuint32_t* box) {
    cuuint32_t es[4] = {1, 1, 1, 1};
    fn(m, CU_TENSOR_MAP_DATA_TYPE_BFLOAT16, rank, const_cast<void*>(base), dims, strides, box, es, CU_TENSOR_MAP_INTERLEAVE_NONE,
       CU_TENSOR_MAP_SWIZZLE_128B, CU_TENSOR_MAP_L2_PROMOTION_L2_256B, CU_TENSOR_MAP_FLOAT_OOB_FILL_NONE);
}

}

extern "C" void kernel_launch(void* const* d_in, const int* in_sizes, int n_in, void* d_out, int out_size) {
    const __nv_bfloat16* x = (const __nv_bfloat16*)d_in[0];
    const __nv_bfloat16* wqkv = (const __nv_bfloat16*)d_in[1];
    const __nv_bfloat16* wo = (const __nv_bfloat16*)d_in[2];
    const __nv_bfloat16* w1 = (const __nv_bfloat16*)d_in[4];
    const __nv_bfloat16* b1 = (const __nv_bfloat16*)d_in[5];
    const __nv_bfloat16* w2 = (const __nv_bfloat16*)d_in[6];
    const __nv_bfloat16* b2 = (const __nv_bfloat16*)d_in[7];
    __nv_bfloat16* out = (__nv_bfloat16*)d_out;

    EncodeFn fn = nullptr;
    cudaDriverEntryPointQueryResult qr;
    cudaGetDriverEntryPoint("cuTensorMapEncodeTiled", (void**)&fn, cudaEnableDefault, &qr);
    CUtensorMap tmX, tmQ3, tmQ1, tm1, tm2, tmP, tmOut, tmXo;
    {
        cuuint64_t d[2] = {DM, SEQ}, s[1] = {DM * 2};
        cuuint32_t b[2] = {72, 64}, es[2] = {1, 1};
        fn(&tmOut, CU_TENSOR_MAP_DATA_TYPE_BFLOAT16, 2, out, d, s, b, es, CU_TENSOR_MAP_INTERLEAVE_NONE, CU_TENSOR_MAP_SWIZZLE_NONE,
           CU_TENSOR_MAP_L2_PROMOTION_NONE, CU_TENSOR_MAP_FLOAT_OOB_FILL_NONE);
        fn(&tmXo, CU_TENSOR_MAP_DATA_TYPE_BFLOAT16, 2, const_cast<__nv_bfloat16*>(x), d, s, b, es, CU_TENSOR_MAP_INTERLEAVE_NONE,
           CU_TENSOR_MAP_SWIZZLE_NONE, CU_TENSOR_MAP_L2_PROMOTION_NONE, CU_TENSOR_MAP_FLOAT_OOB_FILL_NONE);
    }
    {
        void* gp = nullptr;
        cudaGetSymbolAddress(&gp, g_part);
        cuuint64_t d[2] = {SLAB * 2, 8}, s[1] = {SLAB * 16};
        cuuint32_t b[2] = {64, 8}, es[2] = {1, 1};
        fn(&tmP, CU_TENSOR_MAP_DATA_TYPE_INT64, 2, gp, d, s, b, es, CU_TENSOR_MAP_INTERLEAVE_NONE, CU_TENSOR_MAP_SWIZZLE_NONE,
           CU_TENSOR_MAP_L2_PROMOTION_NONE, CU_TENSOR_MAP_FLOAT_OOB_FILL_NONE);
    }
    {
        cuuint64_t d[4] = {64, 8, 9, SEQ / 8}, s[3] = {DM * 2, 128, DM * 2 * 8};
        cuuint32_t b[4] = {64, 8, 3, 2};
        make_map(fn, &tmX, x, 4, d, s, b);
    }
    {
        cuuint64_t d[3] = {3 * DM, DM, 3}, s[2] = {3 * DM * 2, 128};
        cuuint32_t b[3] = {64, 16, 3};
        make_map(fn, &tmQ3, wqkv, 3, d, s, b);
        make_map(fn, &tmQ1, wqkv, 2, d, s, b);
    }
    {
        cuuint64_t d[2] = {FF, DM}, s[1] = {FF * 2};
        cuuint32_t b[2] = {64, 64};
        make_map(fn, &tm1, w1, 2, d, s, b);
        cuuint64_t d2[2] = {DM, FF}, s2[1] = {DM * 2};
        make_map(fn, &tm2, w2, 2, d2, s2, b);
    }
    cudaFuncSetAttribute(fused_kernel, cudaFuncAttributeMaxDynamicSharedMemorySize, K1_SMEM);
    fused_kernel<<<128, 384, K1_SMEM, cudaStreamPerThread>>>(tmX, tmQ3, tmQ1, tm1, tm2, tmP, tmOut, tmXo, b1, wqkv, w1, w2, wo, b2, 0ull);
}
```

```cpp
#include <cuda_runtime.h>
#include <cuda_bf16.h>
#include <cuda.h>
#include <stdint.h>

namespace {

constexpr int SEQ = 2048, DM = 576, FF = 4608, NH = 32;

constexpr int KV_GROUP_BYTES = 5 * 128;
constexpr int KV_HEAD_BYTES = (SEQ / 8) * KV_GROUP_BYTES;
constexpr int Q_OFFSET = NH * KV_HEAD_BYTES;
#define POLY_MASK 0xDADA
__device__ __align__(1024) uint8_t g_QKV[2 * NH * KV_HEAD_BYTES];
__device__ __align__(1024) float g_kmax[NH * 64];
constexpr int SLAB = 16 * 36 * 256;
__device__ __align__(1024) uint4 g_part[8 * SLAB];
__device__ __align__(1024) uint2 g_ffn[128 * 18 * 128];
__device__ __align__(1024) uint32_t g_O[SEQ * DM / 2];
struct Flags {
    unsigned int qkv_stored[16];
    unsigned int ffn_done[16];
    unsigned int o_done[32];
    unsigned int kv_ready;
    unsigned int exited;
};
__device__ Flags g_flags;
__device__ __align__(1024) uint4 g_Olate[32 * 9 * 128];
constexpr uint32_t O_EMPTY = 0xFFFFFFFFu;
constexpr int WO_TILE_BYTES = DM * 144 * 2;
__device__ __align__(1024) uint8_t g_Wo[4 * WO_TILE_BYTES];

__device__ __forceinline__ uint32_t s2u(const void* p) { return (uint32_t)__cvta_generic_to_shared(p); }
__device__ __forceinline__ void mbar_init(uint32_t b, int c) { asm volatile("mbarrier.init.shared::cta.b64 [%0], %1;" ::"r"(b), "r"(c) : "memory"); }
__device__ __forceinline__ void mbar_expect(uint32_t b, uint32_t bytes) {
    asm volatile("mbarrier.arrive.expect_tx.shared::cta.b64 _, [%0], %1;" ::"r"(b), "r"(bytes) : "memory");
}
__device__ __forceinline__ void mbar_wait(uint32_t b, uint32_t parity) {
    asm volatile(
        "{\n.reg .pred p;\n.reg .u32 c;\n"
        "mov.u32 c, 0;\n"
        "LOOP:\n"
        "mbarrier.try_wait.parity.shared::cta.b64 p, [%0], %1;\n"
        "@p bra DONE;\n"
        "add.u32 c, c, 1;\n"
        "setp.lt.u32 p, c, 4194304;\n"
        "@p bra LOOP;\n"
        "trap;\n"
        "DONE:\n}\n" ::"r"(b), "r"(parity) : "memory");
}
__device__ __forceinline__ uint32_t mbar_test(uint32_t b, uint32_t parity) {
    uint32_t ok;
    asm volatile("{\n.reg .pred p;\nmbarrier.test_wait.parity.shared::cta.b64 p, [%1], %2;\nselp.u32 %0, 1, 0, p;\n}\n" : "=r"(ok) : "r"(b), "r"(parity) : "memory");
    return ok;
}
__device__ __forceinline__ void mbar_wait_if(uint32_t ok, uint32_t b, uint32_t parity) {
    asm volatile(
        "{\n.reg .pred p;\n.reg .u32 c;\n"
        "setp.ne.u32 p, %2, 0;\n"
        "@p bra DONE;\n"
        "mov.u32 c, 0;\n"
        "LOOP:\n"
        "mbarrier.try_wait.parity.shared::cta.b64 p, [%0], %1;\n"
        "@p bra DONE;\n"
        "add.u32 c, c, 1;\n"
        "setp.lt.u32 p, c, 4194304;\n"
        "@p bra LOOP;\n"
        "trap;\n"
        "DONE:\n}\n" ::"r"(b), "r"(parity), "r"(ok) : "memory");
}
__device__ __forceinline__ void fence_barrier_init() { asm volatile("fence.mbarrier_init.release.cluster;" ::: "memory"); }
__device__ __forceinline__ void fence_proxy_async() { asm volatile("fence.proxy.async.shared::cta;" ::: "memory"); }
__device__ __forceinline__ void cluster_arrive() { asm volatile("barrier.cluster.arrive.relaxed.aligned;" ::: "memory"); }
__device__ __forceinline__ void cluster_wait() { asm volatile("barrier.cluster.wait.aligned;" ::: "memory"); }
__device__ __forceinline__ void named_bar_sync(int id, int n) { asm volatile("bar.sync %0, %1;" ::"r"(id), "r"(n) : "memory"); }

__device__ __forceinline__ void tma3d_mc(uint32_t dst, const CUtensorMap* tm, int c0, int c1, int c2, uint32_t bar, uint16_t mask) {
    asm volatile("cp.async.bulk.tensor.3d.shared::cluster.global.mbarrier::complete_tx::bytes.multicast::cluster [%0], [%1, {%3, %4, %5}], [%2], %6;"
                 ::"r"(dst), "l"(tm), "r"(bar), "r"(c0), "r"(c1), "r"(c2), "h"(mask) : "memory");
}
__device__ __forceinline__ void tma2d_mc(uint32_t dst, const CUtensorMap* tm, int c0, int c1, uint32_t bar, uint16_t mask) {
    asm volatile("cp.async.bulk.tensor.2d.shared::cluster.global.mbarrier::complete_tx::bytes.multicast::cluster [%0], [%1, {%3, %4}], [%2], %5;"
                 ::"r"(dst), "l"(tm), "r"(bar), "r"(c0), "r"(c1), "h"(mask) : "memory");
}
__device__ __forceinline__ void tma4d(uint32_t dst, const CUtensorMap* tm, int c0, int c1, int c2, int c3, uint32_t bar) {
    asm volatile("cp.async.bulk.tensor.4d.shared::cluster.global.mbarrier::complete_tx::bytes [%0], [%1, {%3, %4, %5, %6}], [%2];"
                 ::"r"(dst), "l"(tm), "r"(bar), "r"(c0), "r"(c1), "r"(c2), "r"(c3) : "memory");
}
__device__ __forceinline__ void tma2d(uint32_t dst, const CUtensorMap* tm, int c0, int c1, uint32_t bar) {
    asm volatile("cp.async.bulk.tensor.2d.shared::cluster.global.mbarrier::complete_tx::bytes [%0], [%1, {%3, %4}], [%2];"
                 ::"r"(dst), "l"(tm), "r"(bar), "r"(c0), "r"(c1) : "memory");
}
__device__ __forceinline__ void bulk_load(uint32_t dst, const void* src, uint32_t bytes, uint32_t bar) {
    asm volatile("cp.async.bulk.shared::cluster.global.mbarrier::complete_tx::bytes [%0], [%1], %2, [%3];"
                 ::"r"(dst), "l"(src), "r"(bytes), "r"(bar) : "memory");
}
__device__ __forceinline__ void prefetch_l2(const void* p, uint32_t bytes) {
    asm volatile("cp.async.bulk.prefetch.L2.global [%0], %1;" ::"l"(p), "r"(bytes) : "memory");
}
__device__ __forceinline__ void prefetch_tmap(const CUtensorMap* tm) { asm volatile("prefetch.tensormap [%0];" ::"l"(tm) : "memory"); }

__device__ __forceinline__ void wg_fence() { asm volatile("wgmma.fence.sync.aligned;" ::: "memory"); }
__device__ __forceinline__ void wg_commit() { asm volatile("wgmma.commit_group.sync.aligned;" ::: "memory"); }
template <int N> __device__ __forceinline__ void wg_wait() { asm volatile("wgmma.wait_group.sync.aligned %0;" ::"n"(N) : "memory"); }
template <int N> __device__ __forceinline__ void reg_fence(float (&d)[N]) {
#pragma unroll
    for (int i = 0; i < N; i++) asm volatile("" : "+f"(d[i])::"memory");
}
template <int N> __device__ __forceinline__ void reg_fence(uint32_t (&d)[N]) {
#pragma unroll
    for (int i = 0; i < N; i++) asm volatile("" : "+r"(d[i])::"memory");
}
template <int R> __device__ __forceinline__ void reg_alloc() { asm volatile("setmaxnreg.inc.sync.aligned.u32 %0;" ::"n"(R)); }
template <int R> __device__ __forceinline__ void reg_dealloc() { asm volatile("setmaxnreg.dec.sync.aligned.u32 %0;" ::"n"(R)); }

__device__ __forceinline__ uint64_t mk_desc(uint64_t z, uint32_t addr, uint32_t lbo, uint32_t sbo, uint32_t swz) {
    return z + ((uint64_t)(((addr & 0x3FFFF) >> 4) | ((lbo >> 4) << 16)) | ((uint64_t)((sbo >> 4) | (swz << 30)) << 32));
}
__device__ __forceinline__ uint32_t pack_bf16(float lo, float hi) {
    uint32_t r;
    asm("cvt.rn.bf16x2.f32 %0, %1, %2;" : "=r"(r) : "f"(hi), "f"(lo));
    return r;
}
__device__ __forceinline__ float bf_lo(uint32_t w) { return __uint_as_float(w << 16); }
__device__ __forceinline__ float bf_hi(uint32_t w) { return __uint_as_float(w & 0xFFFF0000u); }
__device__ __forceinline__ float ex2(float x) {
    float r;
    asm("ex2.approx.ftz.f32 %0, %1;" : "=f"(r) : "f"(x));
    return r;
}
__device__ __forceinline__ float tanh_fast(float x) {
    float r;
    asm("tanh.approx.f32 %0, %1;" : "=f"(r) : "f"(x));
    return r;
}
__device__ __forceinline__ uint32_t hfma2_bf16(uint32_t a, uint32_t b, uint32_t c) {
    uint32_t r;
    asm("fma.rn.bf16x2 %0, %1, %2, %3;" : "=r"(r) : "r"(a), "r"(b), "r"(c));
    return r;
}
__device__ __forceinline__ uint32_t hadd2_bf16(uint32_t a, uint32_t b) {
    uint32_t r;
    asm("add.rn.bf16x2 %0, %1, %2;" : "=r"(r) : "r"(a), "r"(b));
    return r;
}
__device__ __forceinline__ void ldsm4(uint32_t (&a)[4], uint32_t addr) {
    asm volatile("ldmatrix.sync.aligned.m8n8.x4.shared.b16 {%0, %1, %2, %3}, [%4];" : "=r"(a[0]), "=r"(a[1]), "=r"(a[2]), "=r"(a[3]) : "r"(addr) : "memory");
}
__device__ __forceinline__ void stsm4(uint32_t addr, const uint32_t (&a)[4]) {
    asm volatile("stmatrix.sync.aligned.m8n8.x4.shared.b16 [%0], {%1, %2, %3, %4};" ::"r"(addr), "r"(a[0]), "r"(a[1]), "r"(a[2]), "r"(a[3]) : "memory");
}
__device__ __forceinline__ void mma16816(float (&c)[4], const uint32_t (&a)[4], uint32_t b0, uint32_t b1) {
    asm("mma.sync.aligned.m16n8k16.row.col.f32.bf16.bf16.f32 {%0, %1, %2, %3}, {%4, %5, %6, %7}, {%8, %9}, {%0, %1, %2, %3};"
        : "+f"(c[0]), "+f"(c[1]), "+f"(c[2]), "+f"(c[3]) : "r"(a[0]), "r"(a[1]), "r"(a[2]), "r"(a[3]), "r"(b0), "r"(b1));
}
constexpr float GELU_IA = 0.329203491f, GELU_OUT = 1.518817429f;
__device__ __forceinline__ float gelu2(float y) { return fmaf(y, tanh_fast(y * fmaf(y, y, 2.423681954f)), y); }

template<int TB, int AOFF, int BOFF> __device__ __forceinline__ void wgmma_ss_n216(float (&d)[108], uint64_t da, uint64_t db, int sd) {
    asm volatile("{\n.reg .pred p;\n.reg .b64 ta, tb;\nsetp.ne.b32 p, %110, 0;\nadd.s64 ta, %108, %112;\nadd.s64 tb, %109, %113;\n"
      "wgmma.mma_async.sync.aligned.m64n216k16.f32.bf16.bf16 {%0, %1, %2, %3, %4, %5, %6, %7, %8, %9, %10, %11, %12, %13, %14, %15, %16, %17, %18, %19, %20, %21, %22, %23, %24, %25, %26, %27, %28, %29, %30, %31, %32, %33, %34, %35, %36, %37, %38, %39, %40, %41, %42, %43, %44, %45, %46, %47, %48, %49, %50, %51, %52, %53, %54, %55, %56, %57, %58, %59, %60, %61, %62, %63, %64, %65, %66, %67, %68, %69, %70, %71, %72, %73, %74, %75, %76, %77, %78, %79, %80, %81, %82, %83, %84, %85, %86, %87, %88, %89, %90, %91, %92, %93, %94, %95, %96, %97, %98, %99, %100, %101, %102, %103, %104, %105, %106, %107}, ta, tb, p, 1, 1, 0, %111;\n}\n"
      : "+f"(d[0]), "+f"(d[1]), "+f"(d[2]), "+f"(d[3]), "+f"(d[4]), "+f"(d[5]), "+f"(d[6]), "+f"(d[7]), "+f"(d[8]), "+f"(d[9]), "+f"(d[10]), "+f"(d[11]), "+f"(d[12]), "+f"(d[13]), "+f"(d[14]), "+f"(d[15]), "+f"(d[16]), "+f"(d[17]), "+f"(d[18]), "+f"(d[19]), "+f"(d[20]), "+f"(d[21]), "+f"(d[22]), "+f"(d[23]), "+f"(d[24]), "+f"(d[25]), "+f"(d[26]), "+f"(d[27]), "+f"(d[28]), "+f"(d[29]), "+f"(d[30]), "+f"(d[31]), "+f"(d[32]), "+f"(d[33]), "+f"(d[34]), "+f"(d[35]), "+f"(d[36]), "+f"(d[37]), "+f"(d[38]), "+f"(d[39]), "+f"(d[40]), "+f"(d[41]), "+f"(d[42]), "+f"(d[43]), "+f"(d[44]), "+f"(d[45]), "+f"(d[46]), "+f"(d[47]), "+f"(d[48]), "+f"(d[49]), "+f"(d[50]), "+f"(d[51]), "+f"(d[52]), "+f"(d[53]), "+f"(d[54]), "+f"(d[55]), "+f"(d[56]), "+f"(d[57]), "+f"(d[58]), "+f"(d[59]), "+f"(d[60]), "+f"(d[61]), "+f"(d[62]), "+f"(d[63]), "+f"(d[64]), "+f"(d[65]), "+f"(d[66]), "+f"(d[67]), "+f"(d[68]), "+f"(d[69]), "+f"(d[70]), "+f"(d[71]), "+f"(d[72]), "+f"(d[73]), "+f"(d[74]), "+f"(d[75]), "+f"(d[76]), "+f"(d[77]), "+f"(d[78]), "+f"(d[79]), "+f"(d[80]), "+f"(d[81]), "+f"(d[82]), "+f"(d[83]), "+f"(d[84]), "+f"(d[85]), "+f"(d[86]), "+f"(d[87]), "+f"(d[88]), "+f"(d[89]), "+f"(d[90]), "+f"(d[91]), "+f"(d[92]), "+f"(d[93]), "+f"(d[94]), "+f"(d[95]), "+f"(d[96]), "+f"(d[97]), "+f"(d[98]), "+f"(d[99]), "+f"(d[100]), "+f"(d[101]), "+f"(d[102]), "+f"(d[103]), "+f"(d[104]), "+f"(d[105]), "+f"(d[106]), "+f"(d[107])
      : "l"(da), "l"(db), "r"(sd), "n"(TB), "n"(AOFF), "n"(BOFF));
}

template<int TB, int AOFF, int BOFF> __device__ __forceinline__ void wgmma_ss_n128(float (&d)[64], uint64_t da, uint64_t db, int sd) {
    asm volatile("{\n.reg .pred p;\n.reg .b64 ta, tb;\nsetp.ne.b32 p, %66, 0;\nadd.s64 ta, %64, %68;\nadd.s64 tb, %65, %69;\n"
      "wgmma.mma_async.sync.aligned.m64n128k16.f32.bf16.bf16 {%0, %1, %2, %3, %4, %5, %6, %7, %8, %9, %10, %11, %12, %13, %14, %15, %16, %17, %18, %19, %20, %21, %22, %23, %24, %25, %26, %27, %28, %29, %30, %31, %32, %33, %34, %35, %36, %37, %38, %39, %40, %41, %42, %43, %44, %45, %46, %47, %48, %49, %50, %51, %52, %53, %54, %55, %56, %57, %58, %59, %60, %61, %62, %63}, ta, tb, p, 1, 1, 0, %67;\n}\n"
      : "+f"(d[0]), "+f"(d[1]), "+f"(d[2]), "+f"(d[3]), "+f"(d[4]), "+f"(d[5]), "+f"(d[6]), "+f"(d[7]), "+f"(d[8]), "+f"(d[9]), "+f"(d[10]), "+f"(d[11]), "+f"(d[12]), "+f"(d[13]), "+f"(d[14]), "+f"(d[15]), "+f"(d[16]), "+f"(d[17]), "+f"(d[18]), "+f"(d[19]), "+f"(d[20]), "+f"(d[21]), "+f"(d[22]), "+f"(d[23]), "+f"(d[24]), "+f"(d[25]), "+f"(d[26]), "+f"(d[27]), "+f"(d[28]), "+f"(d[29]), "+f"(d[30]), "+f"(d[31]), "+f"(d[32]), "+f"(d[33]), "+f"(d[34]), "+f"(d[35]), "+f"(d[36]), "+f"(d[37]), "+f"(d[38]), "+f"(d[39]), "+f"(d[40]), "+f"(d[41]), "+f"(d[42]), "+f"(d[43]), "+f"(d[44]), "+f"(d[45]), "+f"(d[46]), "+f"(d[47]), "+f"(d[48]), "+f"(d[49]), "+f"(d[50]), "+f"(d[51]), "+f"(d[52]), "+f"(d[53]), "+f"(d[54]), "+f"(d[55]), "+f"(d[56]), "+f"(d[57]), "+f"(d[58]), "+f"(d[59]), "+f"(d[60]), "+f"(d[61]), "+f"(d[62]), "+f"(d[63])
      : "l"(da), "l"(db), "r"(sd), "n"(TB), "n"(AOFF), "n"(BOFF));
}

template<int TB, int AOFF, int BOFF> __device__ __forceinline__ void wgmma_ss_n72(float (&d)[36], uint64_t da, uint64_t db, int sd) {
    asm volatile("{\n.reg .pred p;\n.reg .b64 ta, tb;\nsetp.ne.b32 p, %38, 0;\nadd.s64 ta, %36, %40;\nadd.s64 tb, %37, %41;\n"
      "wgmma.mma_async.sync.aligned.m64n72k16.f32.bf16.bf16 {%0, %1, %2, %3, %4, %5, %6, %7, %8, %9, %10, %11, %12, %13, %14, %15, %16, %17, %18, %19, %20, %21, %22, %23, %24, %25, %26, %27, %28, %29, %30, %31, %32, %33, %34, %35}, ta, tb, p, 1, 1, 0, %39;\n}\n"
      : "+f"(d[0]), "+f"(d[1]), "+f"(d[2]), "+f"(d[3]), "+f"(d[4]), "+f"(d[5]), "+f"(d[6]), "+f"(d[7]), "+f"(d[8]), "+f"(d[9]), "+f"(d[10]), "+f"(d[11]), "+f"(d[12]), "+f"(d[13]), "+f"(d[14]), "+f"(d[15]), "+f"(d[16]), "+f"(d[17]), "+f"(d[18]), "+f"(d[19]), "+f"(d[20]), "+f"(d[21]), "+f"(d[22]), "+f"(d[23]), "+f"(d[24]), "+f"(d[25]), "+f"(d[26]), "+f"(d[27]), "+f"(d[28]), "+f"(d[29]), "+f"(d[30]), "+f"(d[31]), "+f"(d[32]), "+f"(d[33]), "+f"(d[34]), "+f"(d[35])
      : "l"(da), "l"(db), "r"(sd), "n"(TB), "n"(AOFF), "n"(BOFF));
}

template<int TB, int BOFF> __device__ __forceinline__ void wgmma_rs_n24(float (&d)[12], uint32_t a0, uint32_t a1, uint32_t a2, uint32_t a3, uint64_t db, int sd) {
    asm volatile("{\n.reg .pred p;\n.reg .b64 tb;\nsetp.ne.b32 p, %17, 0;\nadd.s64 tb, %16, %19;\n"
      "wgmma.mma_async.sync.aligned.m64n24k16.f32.bf16.bf16 {%0, %1, %2, %3, %4, %5, %6, %7, %8, %9, %10, %11}, {%12, %13, %14, %15}, tb, p, 1, 1, %18;\n}\n"
      : "+f"(d[0]), "+f"(d[1]), "+f"(d[2]), "+f"(d[3]), "+f"(d[4]), "+f"(d[5]), "+f"(d[6]), "+f"(d[7]), "+f"(d[8]), "+f"(d[9]), "+f"(d[10]), "+f"(d[11])
      : "r"(a0), "r"(a1), "r"(a2), "r"(a3), "l"(db), "r"(sd), "n"(TB), "n"(BOFF));
}

template<int TB, int BOFF> __device__ __forceinline__ void wgmma_rs_n72(float (&d)[36], uint32_t a0, uint32_t a1, uint32_t a2, uint32_t a3, uint64_t db, int sd) {
    asm volatile("{\n.reg .pred p;\n.reg .b64 tb;\nsetp.ne.b32 p, %41, 0;\nadd.s64 tb, %40, %43;\n"
      "wgmma.mma_async.sync.aligned.m64n72k16.f32.bf16.bf16 {%0, %1, %2, %3, %4, %5, %6, %7, %8, %9, %10, %11, %12, %13, %14, %15, %16, %17, %18, %19, %20, %21, %22, %23, %24, %25, %26, %27, %28, %29, %30, %31, %32, %33, %34, %35}, {%36, %37, %38, %39}, tb, p, 1, 1, %42;\n}\n"
      : "+f"(d[0]), "+f"(d[1]), "+f"(d[2]), "+f"(d[3]), "+f"(d[4]), "+f"(d[5]), "+f"(d[6]), "+f"(d[7]), "+f"(d[8]), "+f"(d[9]), "+f"(d[10]), "+f"(d[11]), "+f"(d[12]), "+f"(d[13]), "+f"(d[14]), "+f"(d[15]), "+f"(d[16]), "+f"(d[17]), "+f"(d[18]), "+f"(d[19]), "+f"(d[20]), "+f"(d[21]), "+f"(d[22]), "+f"(d[23]), "+f"(d[24]), "+f"(d[25]), "+f"(d[26]), "+f"(d[27]), "+f"(d[28]), "+f"(d[29]), "+f"(d[30]), "+f"(d[31]), "+f"(d[32]), "+f"(d[33]), "+f"(d[34]), "+f"(d[35])
      : "r"(a0), "r"(a1), "r"(a2), "r"(a3), "l"(db), "r"(sd), "n"(TB), "n"(BOFF));
}

template<int TB, int AINC, int BINC> __device__ __forceinline__ void wgmma_ss_n64_pi(float (&d)[32], uint32_t& al, uint32_t ah, uint32_t& bl, uint32_t bh, int sd) {
    asm volatile("{\n.reg .pred p;\n.reg .b64 da, db;\nsetp.ne.b32 p, %34, 0;\nmov.b64 da, {%32, %38};\nmov.b64 db, {%33, %39};\n"
      "wgmma.mma_async.sync.aligned.m64n64k16.f32.bf16.bf16 {%0, %1, %2, %3, %4, %5, %6, %7, %8, %9, %10, %11, %12, %13, %14, %15, %16, %17, %18, %19, %20, %21, %22, %23, %24, %25, %26, %27, %28, %29, %30, %31}, da, db, p, 1, 1, 0, %35;\n"
      "add.s32 %32, %32, %36;\nadd.s32 %33, %33, %37;\n}\n"
      : "+f"(d[0]), "+f"(d[1]), "+f"(d[2]), "+f"(d[3]), "+f"(d[4]), "+f"(d[5]), "+f"(d[6]), "+f"(d[7]), "+f"(d[8]), "+f"(d[9]), "+f"(d[10]), "+f"(d[11]), "+f"(d[12]), "+f"(d[13]), "+f"(d[14]), "+f"(d[15]), "+f"(d[16]), "+f"(d[17]), "+f"(d[18]), "+f"(d[19]), "+f"(d[20]), "+f"(d[21]), "+f"(d[22]), "+f"(d[23]), "+f"(d[24]), "+f"(d[25]), "+f"(d[26]), "+f"(d[27]), "+f"(d[28]), "+f"(d[29]), "+f"(d[30]), "+f"(d[31]), "+r"(al), "+r"(bl)
      : "r"(sd), "n"(TB), "n"(AINC), "n"(BINC), "r"(ah), "r"(bh));
}

template<int TB, int BINC> __device__ __forceinline__ void wgmma_rs_n64_pi(float (&d)[32], uint32_t a0, uint32_t a1, uint32_t a2, uint32_t a3, uint32_t& bl, uint32_t bh, int sd) {
    asm volatile("{\n.reg .pred p;\n.reg .b64 db;\nsetp.ne.b32 p, %37, 0;\nmov.b64 db, {%32, %40};\n"
      "wgmma.mma_async.sync.aligned.m64n64k16.f32.bf16.bf16 {%0, %1, %2, %3, %4, %5, %6, %7, %8, %9, %10, %11, %12, %13, %14, %15, %16, %17, %18, %19, %20, %21, %22, %23, %24, %25, %26, %27, %28, %29, %30, %31}, {%33, %34, %35, %36}, db, p, 1, 1, %38;\n"
      "add.s32 %32, %32, %39;\n}\n"
      : "+f"(d[0]), "+f"(d[1]), "+f"(d[2]), "+f"(d[3]), "+f"(d[4]), "+f"(d[5]), "+f"(d[6]), "+f"(d[7]), "+f"(d[8]), "+f"(d[9]), "+f"(d[10]), "+f"(d[11]), "+f"(d[12]), "+f"(d[13]), "+f"(d[14]), "+f"(d[15]), "+f"(d[16]), "+f"(d[17]), "+f"(d[18]), "+f"(d[19]), "+f"(d[20]), "+f"(d[21]), "+f"(d[22]), "+f"(d[23]), "+f"(d[24]), "+f"(d[25]), "+f"(d[26]), "+f"(d[27]), "+f"(d[28]), "+f"(d[29]), "+f"(d[30]), "+f"(d[31]), "+r"(bl)
      : "r"(a0), "r"(a1), "r"(a2), "r"(a3), "r"(sd), "n"(TB), "n"(BINC), "r"(bh));
}

constexpr int K1_XN_BYTES = 16 * 9216;
constexpr int K1_OFF_RING = K1_XN_BYTES;
constexpr int K1_OFF_BIAS = K1_OFF_RING + 10 * 8192;
constexpr int K1_OFF_BAR = K1_OFF_BIAS + 576 * 2;
constexpr int K1_SMEM = K1_OFF_BAR + 800;
constexpr float QSCALE = 0.23570226039551584f * 1.4426950408889634f;

struct K1Ctx {
    uint32_t full0;
    uint32_t rel_addr;
    uint64_t descA, descB;
    uint32_t al, ah, bl, bh;
    uint32_t phase;
    uint32_t rdy;
    __device__ __forceinline__ void begin_stage(int s) {
        mbar_wait_if(rdy, full0 + s * 8, phase);
        wg_fence();
    }
    __device__ __forceinline__ void probe_next(int s) { rdy = mbar_test(full0 + (s == 8 ? 0 : s + 1) * 8, s == 8 ? phase ^ 1 : phase); }
    __device__ __forceinline__ void release(int s) {
        if (rel_addr) asm volatile("mbarrier.arrive.shared::cluster.b64 _, [%0];" ::"r"(rel_addr + s * 8) : "memory");
    }
    __device__ __forceinline__ void end_stage(int s) {
        wg_commit();
        wg_wait<1>();
        release(s == 0 ? 8 : s - 1);
    }
};

__host__ __device__ constexpr int a_off(int ks) { return ((ks / 12) * 49152 + ((ks >> 2) % 3) * 1024 + (ks & 3) * 32) >> 4; }

template <int V> struct IC { static constexpr int value = V; };
template <int I, int N, class F> __device__ __forceinline__ void static_for(F&& f) {
    if constexpr (I < N) { f(IC<I>{}); static_for<I + 1, N>(f); }
}

template <bool A_RS, bool B_RS, class Epi>
__device__ __forceinline__ void tile_pair(K1Ctx& c, float (&accA)[32], float (&accB)[32], uint32_t (&h)[144], Epi&& epi) {
    static_for<0, 9>([&](auto sc) {
        constexpr int s = decltype(sc)::value;
        c.begin_stage(s);
        static_for<0, 8>([&](auto tc) {
            constexpr int t = decltype(tc)::value, kk = s * 8 + t, ks = kk % 36;
            constexpr int db = ks == 35 ? -35 * 128 : 128, da = a_off((ks + 1) % 36) - a_off(ks);
            if constexpr (kk < 36) {
                if constexpr (A_RS) wgmma_rs_n64_pi<1, db>(accA, h[ks * 4], h[ks * 4 + 1], h[ks * 4 + 2], h[ks * 4 + 3], c.bl, c.bh, ks != 0);
                else wgmma_ss_n64_pi<1, da, db>(accA, c.al, c.ah, c.bl, c.bh, ks != 0);
            } else {
                if constexpr (B_RS) wgmma_rs_n64_pi<1, db>(accB, h[ks * 4], h[ks * 4 + 1], h[ks * 4 + 2], h[ks * 4 + 3], c.bl, c.bh, ks != 0);
                else wgmma_ss_n64_pi<1, da, db>(accB, c.al, c.ah, c.bl, c.bh, ks != 0);
            }
            if constexpr (t == 0) {
                c.end_stage(s);
                epi(sc);
                wg_fence();
            }
            if constexpr (t == 3) c.probe_next(s);
        });
        wg_commit();
    });
    c.phase ^= 1;
}

template <int B0, int NB, int HOFF>
__device__ __forceinline__ void gelu_blocks(const float (&acc)[32], uint32_t (&h)[144], const uint32_t (&bq)[8], float rs0, float rs1) {
#pragma unroll
    for (int b = B0; b < B0 + NB; b++) {
        const float b0 = bf_lo(bq[b]), b1 = __uint_as_float(bq[b]);
        h[HOFF + b * 2 + 0] = pack_bf16(gelu2(fmaf(acc[b * 4 + 0], rs0, b0)), gelu2(fmaf(acc[b * 4 + 1], rs0, b1)));
        h[HOFF + b * 2 + 1] = pack_bf16(gelu2(fmaf(acc[b * 4 + 2], rs1, b0)), gelu2(fmaf(acc[b * 4 + 3], rs1, b1)));
    }
#pragma unroll
    for (int i = HOFF + B0 * 2; i < HOFF + (B0 + NB) * 2; i++) asm volatile("" : "+r"(h[i]));
}
__device__ __forceinline__ uint32_t pack_bias(uint32_t w) {
    const uint32_t lo = pack_bf16(bf_lo(w) * GELU_IA, 0.f) & 0xFFFFu;
    const uint32_t hb = __float_as_uint(bf_hi(w) * GELU_IA), mag = hb & 0x7FFFFFFFu;
    const uint32_t top = mag >= lo ? (mag - lo + 0x8000u) & 0xFFFF0000u : 0u;
    return (hb & 0x80000000u) | top | lo;
}
__device__ __forceinline__ void load_bias(uint32_t (&bq)[8], uint32_t addr) {
    asm volatile("ld.shared.v4.u32 {%0, %1, %2, %3}, [%4];" : "=r"(bq[0]), "=r"(bq[1]), "=r"(bq[2]), "=r"(bq[3]) : "r"(addr));
    asm volatile("ld.shared.v4.u32 {%0, %1, %2, %3}, [%4 + 16];" : "=r"(bq[4]), "=r"(bq[5]), "=r"(bq[6]), "=r"(bq[7]) : "r"(addr));
}
template <int S> __device__ __forceinline__ void store_part(const float (&o)[32], uint4* p) {
    uint4 v;
    v.x = pack_bf16(o[S * 8 + 0], o[S * 8 + 1]); v.y = pack_bf16(o[S * 8 + 2], o[S * 8 + 3]);
    v.z = pack_bf16(o[S * 8 + 4], o[S * 8 + 5]); v.w = pack_bf16(o[S * 8 + 6], o[S * 8 + 7]);
    p[S * 256] = v;
}

constexpr int NCHUNK = 16;
constexpr int CHUNK_BYTES = KV_HEAD_BYTES / NCHUNK;
constexpr int SM_Q = 0;
constexpr int SM_KV = 32768;
constexpr int PIECE = 19968;
__host__ __device__ constexpr int sm_piece(int p) { return p == 0 ? 209408 : (p == 1 ? 0 : SM_KV + (p - 2) * PIECE); }
__host__ __device__ constexpr int sm_wstep(int k) { return k < 27 ? sm_piece(k / 3) + (k % 3) * 4608 : (k < 35 ? SM_KV + 7 * PIECE + (k - 27) * 4608 : PIECE); }
__host__ __device__ constexpr int sm_ostep(int k) { return sm_piece(k / 3) + 13824 + (k % 3) * 2048; }
constexpr int SM_RED = SM_KV + KV_HEAD_BYTES;

#define PV_GROUP 4
__device__ __forceinline__ uint32_t exp2_packed(float y0, float y1, uint32_t one2) {
    const uint32_t w = __byte_perm(__float_as_uint(y0), __float_as_uint(y1), 0x6521);
    uint32_t m;
    asm("lop3.b32 %0, %1, 0x007F007F, %2, 0xEA;" : "=r"(m) : "r"(w), "r"(one2));
    const uint32_t d = hfma2_bf16(m, 0x3EF73EF7u, 0xBF37BF37u);
    const uint32_t e = hfma2_bf16(d, d, 0xBD6FBD6Fu);
    return hfma2_bf16(w, e, w);
}
constexpr int KV_TILE = CHUNK_BYTES / 16;
template <int OFF> __device__ __forceinline__ void issue_qk(float (&s)[64], uint64_t qd, uint64_t kd) {
    wgmma_ss_n128<0, 0, OFF + (8 << 16)>(s, qd, kd, 0);
    wgmma_ss_n128<0, 16, OFF + 32>(s, qd, kd, 1);
}
template <int OFF> __device__ __forceinline__ void issue_pv(float (&o)[12], const uint32_t (&p)[32], uint64_t vd) {
    static_for<0, 8>([&](auto kc) {
        constexpr int k = decltype(kc)::value;
        wgmma_rs_n24<1, OFF + k * (2 * KV_GROUP_BYTES / 16)>(o, p[k * 4], p[k * 4 + 1], p[k * 4 + 2], p[k * 4 + 3], vd, 1);
    });
}
template <int OFF>
__device__ __forceinline__ void softmax_pv(const float (&s)[64], uint32_t (&p)[32], float (&o)[12], uint64_t vd, uint32_t one2) {
    static_for<0, 2>([&](auto gc) {
        constexpr int g0 = decltype(gc)::value ? PV_GROUP : 0, g1 = decltype(gc)::value ? 8 : PV_GROUP;
#pragma unroll
        for (int b = g0 * 2; b < g1 * 2; b++) {
            if ((POLY_MASK >> b) & 1) {
                p[b * 2 + 0] = exp2_packed(s[b * 4 + 0], s[b * 4 + 1], one2);
                p[b * 2 + 1] = exp2_packed(s[b * 4 + 2], s[b * 4 + 3], one2);
            } else {
                p[b * 2 + 0] = pack_bf16(ex2(s[b * 4 + 0]), ex2(s[b * 4 + 1]));
                p[b * 2 + 1] = pack_bf16(ex2(s[b * 4 + 2]), ex2(s[b * 4 + 3]));
            }
        }
#pragma unroll
        for (int i = g0 * 4; i < g1 * 4; i++) asm volatile("" : "+r"(p[i])::"memory");
        wg_fence();
        static_for<g0, g1>([&](auto kc) {
            constexpr int k = decltype(kc)::value;
            wgmma_rs_n24<1, OFF + k * (2 * KV_GROUP_BYTES / 16)>(o, p[k * 4], p[k * 4 + 1], p[k * 4 + 2], p[k * 4 + 3], vd, 1);
        });
    });
    wg_commit();
}
__device__ __forceinline__ int head_pair(int hh, int i) {
    if (i == 8) return hh == 3 ? 0 : 8;
    const int q = i >> 1, t = (4 - hh) & 3;
    if ((i & 1) == 0) return t + q;
    return (hh == 1 || hh == 2) ? (q >= hh ? q - hh : t + 4 + q) : t + 4 + q;
}
template <bool LATE> __device__ __forceinline__ void store_o(float (&o)[12], int rt, int head, int wq, int lane) {
    const int g = lane >> 2, q = lane & 3;
    const float i0 = __fdividef(1.0f, __shfl_sync(~0u, o[8], lane | 3)), i1 = __fdividef(1.0f, __shfl_sync(~0u, o[10], lane | 3));
#pragma unroll
    for (int i = 0; i < 3; i++) {
        const uint32_t w0 = pack_bf16(o[i * 4] * i0, o[i * 4 + 1] * i0), w1 = pack_bf16(o[i * 4 + 2] * i1, o[i * 4 + 3] * i1);
        if (i < 2 || q == 2) {
            if constexpr (LATE) {
                const int pc = (head & 7) * 9 + head_pair(head & 3, i < 2 ? i * 4 + q : 8);
                uint32_t* op = reinterpret_cast<uint32_t*>(g_Olate) + (((rt * 9 + (pc >> 3)) * 128 + wq * 32 + g * 4 + (pc & 3)) * 4 + ((pc >> 2) & 1) * 2);
                asm volatile("st.relaxed.gpu.global.v2.u32 [%0], {%1, %2};" ::"l"(op), "r"(w0), "r"(w1) : "memory");
            } else {
                const int pc = head * 9 + head_pair(head & 3, i < 2 ? i * 4 + q : 8);
                uint32_t* op = g_O + ((rt * 72 + (pc >> 2)) * 8 + wq * 2) * 32 + g * 4 + (pc & 3);
                op[0] = w0;
                op[32] = w1;
            }
        }
    }
#pragma unroll
    for (int i = 0; i < 12; i++) o[i] = 0.f;
}
__device__ __forceinline__ void mbar_arrive(uint32_t b) { asm volatile("mbarrier.arrive.shared::cta.b64 _, [%0];" ::"r"(b) : "memory"); }
__device__ __forceinline__ void mbar_wait_sleep(uint32_t b, uint32_t ns) {
    uint32_t ok, spins = 0;
    while (true) {
        asm volatile("{\n.reg .pred p;\nmbarrier.try_wait.parity.shared::cta.b64 p, [%1], 0;\nselp.u32 %0, 1, 0, p;\n}\n" : "=r"(ok) : "r"(b) : "memory");
        if (ok) break;
        __nanosleep(ns);
        if (++spins > (1u << 21)) __trap();
    }
}
__device__ __forceinline__ void flag_signal(unsigned int* f) {
    __threadfence();
    atomicAdd(f, 1u);
}
__device__ __forceinline__ void flag_wait(const unsigned int* f, unsigned int target, unsigned int sleep_ns) {
    uint32_t v, spins = 0;
    while (true) {
        asm volatile("ld.acquire.gpu.global.u32 %0, [%1];" : "=r"(v) : "l"(f) : "memory");
        if (v >= target) break;
        if (sleep_ns) __nanosleep(sleep_ns);
        if (++spins > (1u << 21)) __trap();
    }
}
__device__ __forceinline__ uint4 hadd8_bf16(const uint4 a, const uint4 b) {
    return make_uint4(hadd2_bf16(a.x, b.x), hadd2_bf16(a.y, b.y), hadd2_bf16(a.z, b.z), hadd2_bf16(a.w, b.w));
}
__device__ __forceinline__ float sumsq2(uint32_t w) { return fmaf(bf_lo(w), bf_lo(w), bf_hi(w) * bf_hi(w)); }
__device__ __forceinline__ float sumsq8(const uint4 v) { return (sumsq2(v.x) + sumsq2(v.y)) + (sumsq2(v.z) + sumsq2(v.w)); }

enum { B_FULL = 0, B_EMPTY = 9, B_BASE = 18, B_XNDEAD = 19, B_QRDY = 20, B_FFN = 21, B_KV = 22, B_FREE = 38, B_WO = 46, B_RED = 55, B_X = 61, B_EARLY = 85, B_OS = 86, B_LATE = 94, B_BIAS = 95, B_END = 96 };

__global__ void __cluster_dims__(2, 1, 1) __launch_bounds__(384, 1)
fused_kernel(const __grid_constant__ CUtensorMap tmX, const __grid_constant__ CUtensorMap tmQ3, const __grid_constant__ CUtensorMap tmQ1,
          const __grid_constant__ CUtensorMap tm1, const __grid_constant__ CUtensorMap tm2, const __grid_constant__ CUtensorMap tmP,
          const __grid_constant__ CUtensorMap tmOut, const __grid_constant__ CUtensorMap tmXo, const __nv_bfloat16* __restrict__ b1,
          const __nv_bfloat16* __restrict__ wqkv, const __nv_bfloat16* __restrict__ w1, const __nv_bfloat16* __restrict__ w2,
          const __nv_bfloat16* __restrict__ wo, const __nv_bfloat16* __restrict__ b2,
          const uint64_t zero) {
    extern __shared__ __align__(1024) uint8_t smem[];
    const uint32_t sb = s2u(smem);
    const int tid = threadIdx.x, lane = tid & 31;
    const int warp = __shfl_sync(~0u, tid >> 5, 0);
    const uint32_t rank = blockIdx.x & 1;
    const int cl = blockIdx.x >> 1;
    const int rb = (cl & 7) * 2 + rank;
    const int j = cl >> 3;
    const uint32_t bar0 = sb + K1_OFF_BAR;
    const uint32_t full0 = bar0 + B_FULL * 8, empty0 = bar0 + B_EMPTY * 8, xbar0 = bar0 + B_X * 8;
    const int head = blockIdx.x >> 2, quarter = blockIdx.x & 3;
    const int rt = quarter * 8 + (head >> 2), ct = head & 3;
    const int rot = head >> 3;
    const int ks0 = ((((head >> 3) + 2) & 3) * 9);
    volatile uint32_t* slow_flag = reinterpret_cast<volatile uint32_t*>(smem + K1_OFF_BAR + B_END * 8);

    if (__builtin_expect(warp < 8, 1)) {
        if (lane == 0) {
#pragma unroll
            for (int i = 0; i < 3; i++) mbar_init(xbar0 + (warp * 3 + i) * 8, 1);
            fence_barrier_init();
#pragma unroll 1
            for (int i = 0; i < 3; i++) {
                const uint32_t xb = xbar0 + (warp * 3 + i) * 8;
                mbar_expect(xb, 6144);
                tma4d(sb + i * 49152 + warp * 6144, &tmX, 0, 0, i * 3, rb * 16 + warp * 2, xb);
            }
        }
        __syncwarp();
        cluster_arrive();
        reg_alloc<240>();
        float rs0, rs1;
        {
            const uint32_t la = sb + (warp * 2 + ((lane >> 3) & 1)) * 3072 + (lane & 7) * 128;
            uint32_t off[4];
#pragma unroll
            for (int i = 0; i < 4; i++) off[i] = la + (((i * 2 + (lane >> 4)) ^ (lane & 7)) << 4);
            float c1[4] = {0.f, 0.f, 0.f, 0.f}, c2[4] = {0.f, 0.f, 0.f, 0.f}, c3[4] = {0.f, 0.f, 0.f, 0.f};
            uint32_t a[36][4];
#pragma unroll
            for (int t = 0; t < 3; t++) {
                mbar_wait(xbar0 + (warp * 3 + t) * 8, 0);
#pragma unroll
                for (int i = 0; i < 12; i++) ldsm4(a[t * 12 + i], off[i & 3] + t * 49152 + (i >> 2) * 1024);
#pragma unroll
                for (int i = t * 12; i < t * 12 + 12; i++) mma16816(c3, a[i], 0x3F803F80u, 0x3F803F80u);
                if (t < 2) {
#pragma unroll
                    for (int i = t * 12; i < t * 12 + 12; i++) {
                        mma16816(c1, a[i], a[i][0], a[i][2]);
                        mma16816(c2, a[i], a[i][1], a[i][3]);
                    }
                }
            }
            const int gg = lane >> 2, src = (lane & ~3) | (gg >> 1);
            const float m0 = c3[0] * (1.0f / DM), m1 = c3[2] * (1.0f / DM);
            const uint32_t mc0 = pack_bf16(-m0, -m0), mc1 = pack_bf16(-m1, -m1);
#pragma unroll
            for (int i = 0; i < 36; i++) {
                uint32_t d[4];
#pragma unroll
                for (int k = 0; k < 4; k++) d[k] = hadd2_bf16(a[i][k], (k & 1) ? mc1 : mc0);
                stsm4(off[i & 3] + (i / 12) * 49152 + ((i >> 2) % 3) * 1024, d);
                if (i >= 24) {
                    asm volatile("" : "+r"(a[i][0]), "+r"(a[i][1]), "+r"(a[i][2]), "+r"(a[i][3])::"memory");
                    mma16816(c1, a[i], a[i][0], a[i][2]);
                    mma16816(c2, a[i], a[i][1], a[i][3]);
                }
            }
            const float q0 = __shfl_sync(~0u, (gg & 1) ? c1[1] : c1[0], src), q1 = __shfl_sync(~0u, (gg & 1) ? c2[3] : c2[2], src);
            rs0 = rsqrtf(fmaxf(fmaf(-m0, m0, q0 * (1.0f / DM)), 0.f) + 1e-5f);
            rs1 = rsqrtf(fmaxf(fmaf(-m1, m1, q1 * (1.0f / DM)), 0.f) + 1e-5f);
            if (__any_sync(~0u, fabsf(m0) * rs0 > 0.25f || fabsf(m1) * rs1 > 0.25f)) {
#pragma unroll
                for (int k = 0; k < 4; k++) { c1[k] = 0.f; c2[k] = 0.f; }
                const float d0 = -m0 - bf_lo(mc0), d1 = -m1 - bf_lo(mc1);
                const uint32_t md0 = pack_bf16(d0, d0), md1 = pack_bf16(d1, d1);
#pragma unroll 1
                for (int i = 0; i < 9; i++) {
#pragma unroll
                    for (int k4 = 0; k4 < 4; k4++) {
                        const uint32_t ad = off[k4] + (i / 3) * 49152 + (i % 3) * 1024;
                        uint32_t b[4];
                        ldsm4(b, ad);
#pragma unroll
                        for (int k = 0; k < 4; k++) b[k] = hadd2_bf16(b[k], (k & 1) ? md1 : md0);
                        stsm4(ad, b);
                        mma16816(c1, b, b[0], b[2]);
                        mma16816(c2, b, b[1], b[3]);
                    }
                }
                rs0 = rsqrtf(__shfl_sync(~0u, (gg & 1) ? c1[1] : c1[0], src) * (1.0f / DM) + 1e-5f);
                rs1 = rsqrtf(__shfl_sync(~0u, (gg & 1) ? c2[3] : c2[2], src) * (1.0f / DM) + 1e-5f);
            }
        }
        const int wg = warp >> 2, wq = warp & 3;
        uint32_t h[144];
        float accA[32], accB[32];
        uint32_t bq[8];
#pragma unroll
        for (int i = 0; i < 32; i++) asm volatile("mov.f32 %0, 0f00000000;" : "=f"(accB[i]));
#pragma unroll
        for (int i = 112; i < 128; i++) asm volatile("mov.u32 %0, 0;" : "=r"(h[i]));
        fence_proxy_async();
        named_bar_sync(1 + wg, 128);
        cluster_wait();

        const int g = lane >> 2, q = lane & 3;
        K1Ctx c;
        c.full0 = full0;
        c.rel_addr = 0;
        c.descA = mk_desc(zero, sb + wg * 8 * 3072, 16, 3072, 1);
        c.descB = mk_desc(zero, sb + K1_OFF_RING, 2048, 1024, 1);
        c.al = (uint32_t)c.descA; c.ah = (uint32_t)(c.descA >> 32); c.bl = (uint32_t)c.descB; c.bh = (uint32_t)(c.descB >> 32);
        c.phase = 0;
        c.rdy = 0;
        uint32_t biasq = sb + K1_OFF_BIAS + q * 32;

        uint32_t qo[3], qt[3];
        {
            float accQ[108];
            uint32_t rel = 0;
            if (lane == 0 && wq < 2) asm("mapa.shared::cluster.u32 %0, %1, %2;" : "=r"(rel) : "r"(empty0), "r"(wq));
#pragma unroll 1
            for (int r = 0; r < 2; r++) {
                static_for<0, 9>([&](auto sc) {
                    constexpr int s = decltype(sc)::value;
                    c.begin_stage(s);
                    const uint64_t da = c.descA + (r ? a_off(18 + 2 * s) : a_off(2 * s));
                    wgmma_ss_n216<1, 0, ((2 * s) % 9) * 512>(accQ, da, c.descB, (r | s) != 0);
                    wgmma_ss_n216<1, 2, ((2 * s + 1) % 9) * 512>(accQ, da, c.descB, 1);
                    c.probe_next(s);
                    c.end_stage(s);
                    c.rel_addr = rel;
                });
                c.phase ^= 1;
            }
            mbar_wait(bar0 + B_BIAS * 8, 0);
            wg_wait<0>();
            reg_fence(accQ);
#pragma unroll
            for (int grp = 0; grp < 3; grp++) {
                const int G = 3 * j + grp, type = G >> 3;
                const uint32_t base = (G & 7) * 4 * KV_HEAD_BYTES + (rb * 16 + warp * 2) * KV_GROUP_BYTES + g * 16 + (type == 0 ? Q_OFFSET : (type == 2 ? 256 : 0));
                qo[grp] = base + (q >> 1) * 128 + (q & 1) * 8;
                qt[grp] = base + q * KV_HEAD_BYTES + (type == 0 ? 256 : (type == 2 ? 264 : 512));
#pragma unroll
                for (int hf = 0; hf < 2; hf++) {
                    const float sc = (hf ? rs1 : rs0) * (type == 0 ? QSCALE : ((type == 1 && ((POLY_MASK >> (warp * 2 + hf)) & 1)) ? 2.f : 1.f));
                    uint32_t w[9];
#pragma unroll
                    for (int i = 0; i < 9; i++) w[i] = pack_bf16(accQ[(grp * 9 + i) * 4 + hf * 2] * sc, accQ[(grp * 9 + i) * 4 + hf * 2 + 1] * sc);
                    uint32_t* d = h + hf * 32 + grp * 8;
                    d[0] = w[0]; d[1] = w[1]; d[2] = w[3]; d[3] = q >= 1 ? w[2] : w[4];
                    d[4] = w[5]; d[5] = q >= 2 ? w[4] : w[6]; d[6] = w[7]; d[7] = w[8];
                    h[hf * 32 + 24 + grp] = q == 0 ? w[2] : (q == 1 ? w[4] : w[6]);
                }
            }
        }
        rs0 *= GELU_IA; rs1 *= GELU_IA;
#pragma unroll
        for (int i = 59; i < 112; i++) asm volatile("mov.u32 %0, 0;" : "=r"(h[i]));
#pragma unroll
        for (int i = 0; i < 8; i++) bq[i] = 0;
#pragma unroll 1
        for (int p = 0; p < 4; p++) {
            uint8_t* const qb = g_QKV + p * KV_GROUP_BYTES;
            tile_pair<false, false>(c, accA, accB, h, [&](auto sc) {
                constexpr int s = decltype(sc)::value;
                if constexpr (s == 0) reg_fence(accB);
                if constexpr (s < 3) {
                    if (p < 2) {
#pragma unroll
                        for (int k = 0; k < 4; k++)
                            *reinterpret_cast<uint2*>(qb + qo[s] + k * KV_HEAD_BYTES) = make_uint2(h[s * 8 + k * 2], h[s * 8 + k * 2 + 1]);
                        *reinterpret_cast<uint32_t*>(qb + qt[s]) = h[24 + s];
                        if (s == 2 && p == 1) asm volatile("bar.arrive 3, 352;" ::: "memory");
                    }
                }
                if constexpr (s < 4) { if (p > 0) gelu_blocks<s * 2, 2, 112>(accB, h, bq, rs0, rs1); }
                if constexpr (s == 4) {
                    load_bias(bq, biasq);
#pragma unroll
                    for (int i = 0; i < 96; i++) asm volatile("mov.b32 %0, %1;" : "=r"(h[i]) : "r"(h[i + 32]));
                }
                if constexpr (s == 5) reg_fence(accA);
                if constexpr (s >= 5) gelu_blocks<(s - 5) * 2, 2, 96>(accA, h, bq, rs0, rs1);
                if constexpr (s == 8) load_bias(bq, biasq + 128);
            });
            biasq += 256;
        }
        tile_pair<false, true>(c, accA, accB, h, [&](auto sc) {
            constexpr int s = decltype(sc)::value;
            if constexpr (s == 0) reg_fence(accB);
            if constexpr (s < 4) gelu_blocks<s * 2, 2, 112>(accB, h, bq, rs0, rs1);
            if constexpr (s == 4) load_bias(bq, biasq);
            if constexpr (s == 5) { reg_fence(accA); if (tid == wg * 128) mbar_arrive(bar0 + B_XNDEAD * 8); }
            if constexpr (s == 5 || s == 6) gelu_blocks<(s - 5) * 3, 3, 128>(accA, h, bq, rs0, rs1);
            if constexpr (s == 7) gelu_blocks<6, 2, 128>(accA, h, bq, rs0, rs1);
            if constexpr (s == 3 || s == 7) reg_fence(h);
        });
        uint4* pout = g_part + j * SLAB + rb * 36 * 256 + tid;
#pragma unroll 1
        for (int p = 0; p < 4; p++) {
            tile_pair<true, true>(c, accA, accB, h, [&](auto sc) {
                constexpr int s = decltype(sc)::value;
                if constexpr (s == 0) reg_fence(accB);
                if constexpr (s < 4) store_part<s>(accB, pout);
                if constexpr (s == 5) reg_fence(accA);
                if constexpr (s >= 5) store_part<s - 5>(accA, pout + 1024);
            });
            pout += 2048;
        }
        wg_wait<0>();
        c.release(8);
        reg_fence(accB);
        store_part<0>(accB, pout); store_part<1>(accB, pout); store_part<2>(accB, pout); store_part<3>(accB, pout);
        __syncwarp();
        if (lane == 0) mbar_arrive(bar0 + B_FFN * 8);

        mbar_wait(bar0 + B_QRDY * 8, 0);
        const uint32_t slow = __any_sync(~0u, *slow_flag != 0);
        const uint64_t kd0 = mk_desc(zero, sb + SM_KV, 0, KV_GROUP_BYTES, 0);
        const uint64_t vd0 = mk_desc(zero, sb + SM_KV + 256, KV_GROUP_BYTES, 128, 0);
        const uint64_t qd0 = mk_desc(zero, sb + SM_Q + wg * 4096, 128, 512, 0);
        const uint32_t kvbar = bar0 + B_KV * 8;
        float o[12];
#pragma unroll
        for (int i = 0; i < 12; i++) o[i] = 0.f;
        if (__builtin_expect(!slow, 1)) {
            const uint32_t one2 = 0x3F803F80u + (uint32_t)zero;
            float s0[64], s1[64];
            uint32_t p0[32], p1[32];
            reg_fence(o);
            wg_fence();
            issue_qk<0>(s0, qd0, kd0);
            wg_commit();
            wg_commit();
            uint64_t qd = qd0;
            const uint32_t fre = (tid == wg * 128) ? bar0 + B_FREE * 8 - 8 : 0;
#pragma unroll 1
            for (int pass = 0; pass < 4; pass++) {
                uint64_t vd = vd0, kd = kd0;
                const uint32_t ev = pass == 0 ? 0x60u : 0x01u;
#pragma unroll 1
                for (int it = 0; it < 8; it++) {
                    if ((ev >> it) & 1) {
                        if (pass == 0) {
                            mbar_wait(kvbar + (it + 6) * 8, 0);
                        } else {
                            wg_wait<0>();
                            reg_fence(o);
                            store_o<false>(o, quarter * 8 + ((pass - 1 + rot) & 3) * 2 + wg, head, wq, lane);
                            reg_fence(o);
                            __syncwarp();
                            if (lane == 0) mbar_arrive(bar0 + (B_OS + pass * 2 - 2 + wg) * 8);
                        }
                    }
                    wg_wait<1>();
                    reg_fence(s0);
                    wg_fence();
                    issue_qk<KV_TILE>(s1, qd, kd);
                    wg_commit();
                    if (pass == 3 && it > 0 && fre) mbar_arrive(fre + it * 8);
                    softmax_pv<0>(s0, p0, o, vd, one2);
                    kd += 2 * KV_TILE;
                    if (it == 7) { kd = kd0; qd += 512; }
                    wg_wait<1>();
                    reg_fence(s1);
                    wg_fence();
                    issue_qk<0>(s0, qd, kd);
                    wg_commit();
                    softmax_pv<KV_TILE>(s1, p1, o, vd, one2);
                    vd += 2 * KV_TILE;
                }
            }
            wg_wait<0>();
            reg_fence(o);
            reg_fence(s0);
            reg_fence(s1);
            store_o<true>(o, quarter * 8 + ((3 + rot) & 3) * 2 + wg, head, wq, lane);
        } else {
#pragma unroll 1
            for (int pass = 0; pass < 4; pass++) {
                float m0 = -INFINITY, m1 = -INFINITY;
                float s[64];
                uint32_t p[32];
#pragma unroll 1
                for (int t = 0; t < 16; t++) {
                    if (t >= 11) mbar_wait(kvbar + (t < 13 ? 11 : 12) * 8, 0);
                    wg_fence();
                    issue_qk<0>(s, qd0 + pass * 512, kd0 + t * KV_TILE);
                    wg_commit();
                    wg_wait<0>();
                    reg_fence(s);
                    float a0 = m0, a1 = m1;
#pragma unroll
                    for (int k = 0; k < 16; k++) {
                        if ((POLY_MASK >> k) & 1) {
#pragma unroll
                            for (int i = 0; i < 4; i++) s[k * 4 + i] *= 0.5f;
                        }
                        a0 = fmaxf(a0, fmaxf(s[k * 4 + 0], s[k * 4 + 1]));
                        a1 = fmaxf(a1, fmaxf(s[k * 4 + 2], s[k * 4 + 3]));
                    }
                    a0 = fmaxf(a0, __shfl_xor_sync(~0u, a0, 1)); a1 = fmaxf(a1, __shfl_xor_sync(~0u, a1, 1));
                    a0 = fmaxf(a0, __shfl_xor_sync(~0u, a0, 2)); a1 = fmaxf(a1, __shfl_xor_sync(~0u, a1, 2));
                    const float r0 = ex2(m0 - a0), r1 = ex2(m1 - a1);
                    m0 = a0; m1 = a1;
#pragma unroll
                    for (int i = 0; i < 3; i++) { o[i * 4] *= r0; o[i * 4 + 1] *= r0; o[i * 4 + 2] *= r1; o[i * 4 + 3] *= r1; }
#pragma unroll
                    for (int k = 0; k < 16; k++) {
                        p[k * 2 + 0] = pack_bf16(ex2(s[k * 4 + 0] - m0), ex2(s[k * 4 + 1] - m0));
                        p[k * 2 + 1] = pack_bf16(ex2(s[k * 4 + 2] - m1), ex2(s[k * 4 + 3] - m1));
                    }
                    reg_fence(p);
                    reg_fence(o);
                    wg_fence();
                    issue_pv<0>(o, p, vd0 + t * KV_TILE);
                    wg_commit();
                    wg_wait<0>();
                    reg_fence(o);
                }
                if (pass < 3) {
                    store_o<false>(o, quarter * 8 + ((pass + rot) & 3) * 2 + wg, head, wq, lane);
                    __syncwarp();
                    if (lane == 0) mbar_arrive(bar0 + (B_OS + pass * 2 + wg) * 8);
                }
            }
            store_o<true>(o, quarter * 8 + ((3 + rot) & 3) * 2 + wg, head, wq, lane);
            if (tid == wg * 128)
                for (int i = 0; i < 7; i++) mbar_arrive(bar0 + (B_FREE + i) * 8);
        }

        if (tid == wg * 128) mbar_arrive(bar0 + (B_FREE + 7) * 8);
        const int t128 = tid & 127;
        uint32_t bv[9];
        uint2 fv[9];
        mbar_wait(bar0 + B_BASE * 8, 0);
#pragma unroll
        for (int i = 0; i < 9; i++) {
            bv[i] = __ldg(reinterpret_cast<const uint32_t*>(b2 + ct * 144 + wg * 72 + q * 2) + i * 4);
            fv[i] = __ldcg(g_ffn + (blockIdx.x * 18 + wg * 9 + i) * 128 + t128);
        }
        float acc[36];
        const uint64_t od = mk_desc(zero, sb, 1024, 128, 0), wd = mk_desc(zero, sb + wg * 9 * 128, 2304, 128, 0);
        static_for<0, 9>([&](auto pc) {
            constexpr int p = decltype(pc)::value;
            mbar_wait(bar0 + (B_WO + p) * 8, 0);
            wg_fence();
            wgmma_ss_n72<1, sm_ostep(p * 3) / 16, sm_wstep(p * 3) / 16>(acc, od, wd, p != 0);
            wgmma_ss_n72<1, sm_ostep(p * 3 + 1) / 16, sm_wstep(p * 3 + 1) / 16>(acc, od, wd, 1);
            wgmma_ss_n72<1, sm_ostep(p * 3 + 2) / 16, sm_wstep(p * 3 + 2) / 16>(acc, od, wd, 1);
            wg_commit();
            if constexpr (p == 1) {
                wg_wait<1>();
                if (t128 == 0) mbar_arrive(bar0 + B_EARLY * 8);
            }
        });
        wg_wait<0>();
        reg_fence(acc);
        uint4 al[9];
        {
            const uint4* ap = g_Olate + rt * 9 * 128 + t128;
            uint32_t spins = 0;
            bool ok;
            do {
                ok = true;
#pragma unroll
                for (int k = 0; k < 9; k++)
                    asm volatile("ld.relaxed.gpu.global.v4.u32 {%0, %1, %2, %3}, [%4];" : "=r"(al[k].x), "=r"(al[k].y), "=r"(al[k].z), "=r"(al[k].w) : "l"(ap + k * 128) : "memory");
#pragma unroll
                for (int k = 0; k < 9; k++) ok = ok && al[k].x != O_EMPTY && al[k].y != O_EMPTY && al[k].z != O_EMPTY && al[k].w != O_EMPTY;
                if (++spins > (1u << 20)) __trap();
            } while (!__all_sync(~0u, ok));
        }
        mbar_wait(bar0 + B_LATE * 8, 0);
        wg_fence();
        static_for<27, 36>([&](auto kc) {
            constexpr int k = decltype(kc)::value;
            wgmma_rs_n72<1, sm_wstep(k) / 16>(acc, al[k - 27].x, al[k - 27].y, al[k - 27].z, al[k - 27].w, wd, 1);
        });
        wg_commit();
        uint32_t* st = reinterpret_cast<uint32_t*>(smem + sm_piece(0) + wg * 9216) + (wq * 16 + g) * 36 + q;
        float bs[36];
#pragma unroll
        for (int i = 0; i < 9; i++) {
            const uint32_t x0 = st[i * 4], x1 = st[i * 4 + 288];
            bs[i * 4 + 0] = fmaf(bf_lo(fv[i].x), GELU_OUT, bf_lo(x0) + bf_lo(bv[i]));
            bs[i * 4 + 1] = fmaf(bf_hi(fv[i].x), GELU_OUT, bf_hi(x0) + bf_hi(bv[i]));
            bs[i * 4 + 2] = fmaf(bf_lo(fv[i].y), GELU_OUT, bf_lo(x1) + bf_lo(bv[i]));
            bs[i * 4 + 3] = fmaf(bf_hi(fv[i].y), GELU_OUT, bf_hi(x1) + bf_hi(bv[i]));
        }
        reg_fence(bs);
        wg_wait<0>();
        reg_fence(acc);
#pragma unroll
        for (int i = 0; i < 9; i++) {
            st[i * 4] = pack_bf16(acc[i * 4] + bs[i * 4], acc[i * 4 + 1] + bs[i * 4 + 1]);
            st[i * 4 + 288] = pack_bf16(acc[i * 4 + 2] + bs[i * 4 + 2], acc[i * 4 + 3] + bs[i * 4 + 3]);
        }
        fence_proxy_async();
        named_bar_sync(1 + wg, 128);
        if (t128 == 0) {
            asm volatile("cp.async.bulk.tensor.2d.global.shared::cta.bulk_group [%0, {%2, %3}], [%1];"
                         ::"l"(&tmOut), "r"(sb + sm_piece(0) + wg * 9216), "r"(ct * 144 + wg * 72), "r"(rt * 64) : "memory");
            asm volatile("cp.async.bulk.commit_group;" ::: "memory");
            asm volatile("cp.async.bulk.wait_group.read 0;" ::: "memory");
        }
    } else {
        reg_dealloc<24>();
        if (warp == 8 && lane == 0) {
            prefetch_tmap(&tmQ3); prefetch_tmap(&tmQ1); prefetch_tmap(&tm1); prefetch_tmap(&tm2);
            #pragma unroll 1
            for (int i = 0; i < 9; i++) { mbar_init(full0 + i * 8, 1); mbar_init(empty0 + i * 8, 4); mbar_init(bar0 + (B_WO + i) * 8, 2); }
            mbar_init(bar0 + B_BASE * 8, 3); mbar_init(bar0 + B_XNDEAD * 8, 2); mbar_init(bar0 + B_QRDY * 8, 3); mbar_init(bar0 + B_FFN * 8, 8); mbar_init(bar0 + B_EARLY * 8, 2); mbar_init(bar0 + B_LATE * 8, 2); mbar_init(bar0 + B_BIAS * 8, 96);
#pragma unroll 1
            for (int i = 0; i < 16; i++) { mbar_init(bar0 + (B_KV + i) * 8, 1); mbar_init(bar0 + (B_FREE + (i & 7)) * 8, 2); if (i < 6) mbar_init(bar0 + (B_RED + i) * 8, 1); if (i < 6) mbar_init(bar0 + (B_OS + i) * 8, 4); }
            *slow_flag = 0;
            fence_barrier_init();
        }
        __syncwarp();
        cluster_arrive();
        cluster_wait();
        const uint8_t* kvsrc = g_QKV + (size_t)head * KV_HEAD_BYTES;
        if (warp == 8) {
            if (lane == 0) {
                int st = 0, u = rank, tile = -4;
                int es = 4 + rank;
                uint32_t eph = 1;
#pragma unroll 1
                for (int n = 0; n < 99; n++) {
                    mbar_wait(empty0 + es * 8, eph);
                    const uint32_t fb = full0 + st * 8, dst = sb + K1_OFF_RING + u * 8192;
                    mbar_expect(fb, 16384);
                    if (tile < 0) {
                        tma3d_mc(dst, &tmQ3, j * 216, n * 32 + rank * 16, 0, fb, 3);
                        tma2d_mc(dst + 6144, &tmQ1, j * 216 + 192, n * 32 + rank * 16, fb, 3);
                    } else if (tile < 9) {
                        tma2d_mc(dst, &tm1, j * 576 + tile * 64, u * 64, fb, 3);
                    } else {
                        tma2d_mc(dst, &tm2, (tile - 9) * 64, j * 576 + u * 64, fb, 3);
                    }
                    u += 2;
                    if (u >= 9) { u -= 9; tile++; }
                    if (++st == 9) st = 0;
                    if (++es == 9) { es = 0; eph ^= 1; }
                }
                mbar_wait(empty0 + 8 * 8, 0);
                mbar_wait(bar0 + B_QRDY * 8, 0);
                asm volatile("fence.proxy.async;" ::: "memory");
                mbar_expect(bar0 + (B_KV + 11) * 8, 2 * CHUNK_BYTES);
                bulk_load(sb + SM_KV + 11 * CHUNK_BYTES, kvsrc + 11 * CHUNK_BYTES, 2 * CHUNK_BYTES, bar0 + (B_KV + 11) * 8);
                mbar_expect(bar0 + (B_KV + 12) * 8, 3 * CHUNK_BYTES);
                bulk_load(sb + SM_KV + 13 * CHUNK_BYTES, kvsrc + 13 * CHUNK_BYTES, 3 * CHUNK_BYTES, bar0 + (B_KV + 12) * 8);
                const uint8_t* wsrc = g_Wo + ct * WO_TILE_BYTES;
                prefetch_tmap(&tmOut);
                mbar_wait_sleep(bar0 + B_BASE * 8, 500);
#pragma unroll 1
                for (int p = 0; p < 9; p++) {
                    if (p > 0) mbar_wait_sleep(bar0 + (B_FREE + p - 1) * 8, p == 1 ? 500 : 40);
                    const int k = ks0 + p * 3 >= 36 ? ks0 + p * 3 - 36 : ks0 + p * 3;
                    mbar_expect(bar0 + (B_WO + p) * 8, 13824);
                    bulk_load(sb + (p == 0 ? sm_piece(0) : (p == 1 ? sm_piece(1) : SM_KV + (p - 2) * PIECE)), wsrc + k * 4608, 13824, bar0 + (B_WO + p) * 8);
                }
                const int kl = ks0 == 0 ? 27 : ks0 - 9;
                mbar_expect(bar0 + B_LATE * 8, 9 * 4608);
                bulk_load(sb + sm_wstep(27), wsrc + kl * 4608, 8 * 4608, bar0 + B_LATE * 8);
                bulk_load(sb + sm_wstep(35), wsrc + (kl + 8) * 4608, 4608, bar0 + B_LATE * 8);
            }
        } else {
            const int ht = tid - 288;
            if (ht == 64) prefetch_l2(wqkv + blockIdx.x * (DM * 3 * DM / 128), DM * 3 * DM / 64);
            if (ht < 72) {
                const uint4 v = __ldg(reinterpret_cast<const uint4*>(b1 + j * 576) + ht);
                uint32_t* sbias = reinterpret_cast<uint32_t*>(smem + K1_OFF_BIAS) + (ht >> 3) * 32 + (ht & 7);
                sbias[0] = pack_bias(v.x); sbias[8] = pack_bias(v.y); sbias[16] = pack_bias(v.z); sbias[24] = pack_bias(v.w);
            }
            mbar_arrive(bar0 + B_BIAS * 8);
#pragma unroll
            for (int i = 0; i < 3; i++) g_Olate[blockIdx.x * 288 + i * 96 + ht] = make_uint4(O_EMPTY, O_EMPTY, O_EMPTY, O_EMPTY);
#pragma unroll 1
            for (int i = ht; i < 512; i += 96) {
                const int key = i & 127;
                uint8_t* p = g_QKV + (size_t)(j * 4 + (i >> 7)) * KV_HEAD_BYTES + (rb * 16 + (key >> 3)) * KV_GROUP_BYTES + 512 + (key & 7) * 16;
                *reinterpret_cast<uint32_t*>(p + 4) = ((POLY_MASK >> (key >> 3)) & 1) ? 0x3F804000u : 0x00003F80u;
                *reinterpret_cast<uint32_t*>(p + 12) = 0x00003F80u;
            }
            if (ht == 32) prefetch_l2(w1 + blockIdx.x * (DM * FF / 128), DM * FF / 64);
#pragma unroll 2
            for (int i = blockIdx.x * 324 + ht; i < blockIdx.x * 324 + 324; i += 96) {
                const int k = i / 72, nc = i - k * 72, c4 = nc / 18;
                *reinterpret_cast<uint4*>(g_Wo + c4 * WO_TILE_BYTES + (k >> 3) * 2304 + (nc - c4 * 18) * 128 + (k & 7) * 16) =
                    __ldg(reinterpret_cast<const uint4*>(wo) + i);
            }
            named_bar_sync(3, 352);
            if (ht == 32) prefetch_l2(w2 + blockIdx.x * (DM * FF / 128), DM * FF / 64);
            if (ht == 0) {
                flag_signal(&g_flags.qkv_stored[rb]);
                flag_wait(&g_flags.qkv_stored[rb], 8, 200);
            }
            named_bar_sync(7, 96);
#pragma unroll 1
            for (int i = warp - 9; i < 16; i += 3) {
                const int hd = j * 4 + (i >> 2), key = (i & 3) * 32 + lane;
                const uint8_t* p = g_QKV + (size_t)hd * KV_HEAD_BYTES + (rb * 16 + (key >> 3)) * KV_GROUP_BYTES + (key & 7) * 16;
                const uint4 a = __ldcg(reinterpret_cast<const uint4*>(p)), b = __ldcg(reinterpret_cast<const uint4*>(p + 128));
                float n = sumsq2(__ldcg(reinterpret_cast<const uint32_t*>(p + 512))) + sumsq8(a) + sumsq8(b);
                if ((POLY_MASK >> (key >> 3)) & 1) n *= 0.25f;
#pragma unroll
                for (int o = 16; o; o >>= 1) n = fmaxf(n, __shfl_xor_sync(~0u, n, o));
                if (lane == 0) g_kmax[hd * 64 + rb * 4 + (i & 3)] = n;
            }
            named_bar_sync(7, 96);
            if (ht == 0) {
                flag_signal(&g_flags.kv_ready);
                flag_wait(&g_flags.kv_ready, 128, 300);
                mbar_wait_sleep(bar0 + B_XNDEAD * 8, 300);
            }
            named_bar_sync(7, 96);
            float kmax2;
            {
                const float2 v = __ldcg(reinterpret_cast<const float2*>(g_kmax + head * 64 + lane * 2));
                kmax2 = fmaxf(v.x, v.y);
#pragma unroll
                for (int o = 16; o; o >>= 1) kmax2 = fmaxf(kmax2, __shfl_xor_sync(~0u, kmax2, o));
            }
            asm volatile("fence.proxy.async;" ::: "memory");
            int chunk = warp - 9;
#pragma unroll 1
            for (int r = ht; r < 512; r += 96) {
                if (lane == 0 && chunk < 11) {
                    mbar_expect(bar0 + (B_KV + chunk) * 8, CHUNK_BYTES);
                    bulk_load(sb + SM_KV + chunk * CHUNK_BYTES, kvsrc + chunk * CHUNK_BYTES, CHUNK_BYTES, bar0 + (B_KV + chunk) * 8);
                }
                chunk += 3;
                const uint8_t* p = kvsrc + Q_OFFSET + (quarter * 64 + (((r >> 3) + rot * 16) & 63)) * KV_GROUP_BYTES + (r & 7) * 16;
                const uint4 a = __ldcg(reinterpret_cast<const uint4*>(p)), b = __ldcg(reinterpret_cast<const uint4*>(p + 128));
                const uint32_t e = __ldcg(reinterpret_cast<const uint32_t*>(p + 256));
                const float cc = sqrtf((sumsq2(e) + sumsq8(a) + sumsq8(b)) * kmax2) * 1.02f;
                if (!(cc <= 48.f)) *slow_flag = 1;
                uint4* dst = reinterpret_cast<uint4*>(smem + SM_Q + (r >> 3) * 512 + (r & 7) * 16);
                dst[0] = a;
                dst[8] = b;
                dst[16] = make_uint4(e, pack_bf16(-cc, 768.f), 0u, 0u);
                dst[24] = make_uint4(0u, 0xBFFF0000u, 0u, 0u);
            }
            named_bar_sync(7, 96);
            if (*slow_flag) {
#pragma unroll 1
                for (int r = ht; r < 512; r += 96) {
                    uint32_t* dst = reinterpret_cast<uint32_t*>(smem + SM_Q + (r >> 3) * 512 + (r & 7) * 16);
                    dst[65] = 0u;
                    dst[97] = 0u;
                }
            }
            fence_proxy_async();
#pragma unroll 1
            for (int i = warp - 9; i < 11; i += 3) mbar_wait(bar0 + (B_KV + i) * 8, 0);
            __syncwarp();
            if (lane == 0) mbar_arrive(bar0 + B_QRDY * 8);
            if (ht == 0) {
                mbar_wait_sleep(bar0 + B_FFN * 8, 300);
                flag_signal(&g_flags.ffn_done[rb]);
                flag_wait(&g_flags.ffn_done[rt >> 1], 8, 300);
            }
            named_bar_sync(7, 96);
            {
                const int w3 = warp - 9;
                const uint32_t rbar = bar0 + (B_RED + w3 * 2) * 8, rbuf = SM_RED + w3 * 8192;
                const int u0 = ((rt >> 1) * 36 + ct * 9) * 256 + (rt & 1) * 128;
                mbar_wait_sleep(bar0 + (B_KV + 12) * 8, 500);
                asm volatile("fence.proxy.async;" ::: "memory");
#pragma unroll 1
                for (int i = -2; i < 12; i++) {
                    if (i >= 0) {
                        __nanosleep(400);
                        mbar_wait(rbar + (i & 1) * 8, (i >> 1) & 1);
                        const uint4* sp = reinterpret_cast<const uint4*>(smem + rbuf + (i & 1) * 4096) + lane;
                        const uint4 v = hadd8_bf16(hadd8_bf16(hadd8_bf16(sp[0], sp[32]), hadd8_bf16(sp[64], sp[96])),
                                                   hadd8_bf16(hadd8_bf16(sp[128], sp[160]), hadd8_bf16(sp[192], sp[224])));
                        const int bx = i * 3 + w3;
                        uint2* fp = g_ffn + (blockIdx.x * 18 + (bx >> 2) * 2) * 128 + (bx & 3) * 32 + lane;
                        fp[0] = make_uint2(v.x, v.y);
                        fp[128] = make_uint2(v.z, v.w);
                    }
                    __syncwarp();
                    if (lane == 0 && i < 10) {
                        const int bx = (i + 2) * 3 + w3;
                        mbar_expect(rbar + (i & 1) * 8, 4096);
                        tma2d(sb + rbuf + (i & 1) * 4096, &tmP, (u0 + (bx >> 2) * 256 + (bx & 3) * 32) * 2, 0, rbar + (i & 1) * 8);
                    }
                }
            }
            __syncwarp();
            if (lane == 0) mbar_arrive(bar0 + B_BASE * 8);
            if (ht == 0) {
#pragma unroll 1
                for (int i = 0; i < 6; i++) {
                    mbar_wait_sleep(bar0 + (B_OS + i) * 8, 200);
                    flag_signal(&g_flags.o_done[quarter * 8 + (((i >> 1) + rot) & 3) * 2 + (i & 1)]);
                }
            } else if (ht == 32) {
                const uint8_t* osrc = reinterpret_cast<const uint8_t*>(g_O) + rt * 73728;
                mbar_wait_sleep(bar0 + B_BASE * 8, 500);
                mbar_wait_sleep(bar0 + B_FREE * 8, 500);
                flag_wait(&g_flags.o_done[rt], 24, 100);
                if (atomicAdd(&g_flags.exited, 1u) == gridDim.x - 1) {
                    unsigned int* f = reinterpret_cast<unsigned int*>(&g_flags);
#pragma unroll 1
                    for (int i = 0; i < (int)(sizeof(Flags) / 4); i++) f[i] = 0;
                }
                prefetch_tmap(&tmXo);
                asm volatile("fence.proxy.async;" ::: "memory");
#pragma unroll 1
                for (int p = 0; p < 9; p++) {
                    if (p > 1) mbar_wait_sleep(bar0 + (B_FREE + p - 1) * 8, 40);
                    const int k = ks0 + p * 3 >= 36 ? ks0 + p * 3 - 36 : ks0 + p * 3;
                    mbar_expect(bar0 + (B_WO + p) * 8, 6144);
                    bulk_load(sb + 13824 + (p == 0 ? sm_piece(0) : (p == 1 ? sm_piece(1) : SM_KV + (p - 2) * PIECE)), osrc + k * 2048, 6144, bar0 + (B_WO + p) * 8);
                }
                mbar_expect(bar0 + B_LATE * 8, 2 * 9216);
                mbar_wait(bar0 + B_EARLY * 8, 0);
                tma2d(sb + sm_piece(0), &tmXo, ct * 144, rt * 64, bar0 + B_LATE * 8);
                tma2d(sb + sm_piece(0) + 9216, &tmXo, ct * 144 + 72, rt * 64, bar0 + B_LATE * 8);
            }
        }
    }
}

typedef CUresult (*EncodeFn)(CUtensorMap*, CUtensorMapDataType, cuuint32_t, void*, const cuuint64_t*, const cuuint64_t*, const cuuint32_t*,
                             const cuuint32_t*, CUtensorMapInterleave, CUtensorMapSwizzle, CUtensorMapL2promotion, CUtensorMapFloatOOBfill);

void make_map(EncodeFn fn, CUtensorMap* m, const void* base, int rank, const cuuint64_t* dims, const cuuint64_t* strides, const cuuint32_t* box) {
    cuuint32_t es[4] = {1, 1, 1, 1};
    fn(m, CU_TENSOR_MAP_DATA_TYPE_BFLOAT16, rank, const_cast<void*>(base), dims, strides, box, es, CU_TENSOR_MAP_INTERLEAVE_NONE,
       CU_TENSOR_MAP_SWIZZLE_128B, CU_TENSOR_MAP_L2_PROMOTION_L2_256B, CU_TENSOR_MAP_FLOAT_OOB_FILL_NONE);
}

}

extern "C" void kernel_launch(void* const* d_in, const int* in_sizes, int n_in, void* d_out, int out_size) {
    const __nv_bfloat16* x = (const __nv_bfloat16*)d_in[0];
    const __nv_bfloat16* wqkv = (const __nv_bfloat16*)d_in[1];
    const __nv_bfloat16* wo = (const __nv_bfloat16*)d_in[2];
    const __nv_bfloat16* w1 = (const __nv_bfloat16*)d_in[4];
    const __nv_bfloat16* b1 = (const __nv_bfloat16*)d_in[5];
    const __nv_bfloat16* w2 = (const __nv_bfloat16*)d_in[6];
    const __nv_bfloat16* b2 = (const __nv_bfloat16*)d_in[7];
    __nv_bfloat16* out = (__nv_bfloat16*)d_out;

    EncodeFn fn = nullptr;
    cudaDriverEntryPointQueryResult qr;
    cudaGetDriverEntryPoint("cuTensorMapEncodeTiled", (void**)&fn, cudaEnableDefault, &qr);
    CUtensorMap tmX, tmQ3, tmQ1, tm1, tm2, tmP, tmOut, tmXo;
    {
        cuuint64_t d[2] = {DM, SEQ}, s[1] = {DM * 2};
        cuuint32_t b[2] = {72, 64}, es[2] = {1, 1};
        fn(&tmOut, CU_TENSOR_MAP_DATA_TYPE_BFLOAT16, 2, out, d, s, b, es, CU_TENSOR_MAP_INTERLEAVE_NONE, CU_TENSOR_MAP_SWIZZLE_NONE,
           CU_TENSOR_MAP_L2_PROMOTION_NONE, CU_TENSOR_MAP_FLOAT_OOB_FILL_NONE);
        fn(&tmXo, CU_TENSOR_MAP_DATA_TYPE_BFLOAT16, 2, const_cast<__nv_bfloat16*>(x), d, s, b, es, CU_TENSOR_MAP_INTERLEAVE_NONE,
           CU_TENSOR_MAP_SWIZZLE_NONE, CU_TENSOR_MAP_L2_PROMOTION_NONE, CU_TENSOR_MAP_FLOAT_OOB_FILL_NONE);
    }
    {
        void* gp = nullptr;
        cudaGetSymbolAddress(&gp, g_part);
        cuuint64_t d[2] = {SLAB * 2, 8}, s[1] = {SLAB * 16};
        cuuint32_t b[2] = {64, 8}, es[2] = {1, 1};
        fn(&tmP, CU_TENSOR_MAP_DATA_TYPE_INT64, 2, gp, d, s, b, es, CU_TENSOR_MAP_INTERLEAVE_NONE, CU_TENSOR_MAP_SWIZZLE_NONE,
           CU_TENSOR_MAP_L2_PROMOTION_NONE, CU_TENSOR_MAP_FLOAT_OOB_FILL_NONE);
    }
    {
        cuuint64_t d[4] = {64, 8, 9, SEQ / 8}, s[3] = {DM * 2, 128, DM * 2 * 8};
        cuuint32_t b[4] = {64, 8, 3, 2};
        make_map(fn, &tmX, x, 4, d, s, b);
    }
    {
        cuuint64_t d[3] = {3 * DM, DM, 3}, s[2] = {3 * DM * 2, 128};
        cuuint32_t b[3] = {64, 16, 3};
        make_map(fn, &tmQ3, wqkv, 3, d, s, b);
        make_map(fn, &tmQ1, wqkv, 2, d, s, b);
    }
    {
        cuuint64_t d[2] = {FF, DM}, s[1] = {FF * 2};
        cuuint32_t b[2] = {64, 64};
        make_map(fn, &tm1, w1, 2, d, s, b);
        cuuint64_t d2[2] = {DM, FF}, s2[1] = {DM * 2};
        make_map(fn, &tm2, w2, 2, d2, s2, b);
    }
    cudaFuncSetAttribute(fused_kernel, cudaFuncAttributeMaxDynamicSharedMemorySize, K1_SMEM);
    fused_kernel<<<128, 384, K1_SMEM, cudaStreamPerThread>>>(tmX, tmQ3, tmQ1, tm1, tm2, tmP, tmOut, tmXo, b1, wqkv, w1, w2, wo, b2, 0ull);
}
```
